```python
import torch

def _softmax(x, axis=-1):
    return torch.softmax(x, dim=axis)
def _gelu(x):
    return torch.nn.functional.gelu(x, approximate="tanh")
def _silu(x):
    return torch.nn.functional.silu(x)
def _sigmoid(x):
    return torch.sigmoid(x)
def _layernorm(x, axis=-1, eps=1e-5):
    m = x.mean(dim=axis, keepdim=True)
    v = x.var(dim=axis, keepdim=True, unbiased=False)
    return (x - m) / torch.sqrt(v + eps)
def _scatter_add(tgt, idx, src, axis=0):
    return tgt.clone().index_add_(axis, idx, src)
def _segment_sum(src, seg, n):
    out = torch.zeros((n,) + src.shape[1:], dtype=src.dtype)
    return out.index_add_(0, seg, src)
def _pad(x, pw):
    flat = tuple(v for pair in reversed(pw) for v in pair)
    return torch.nn.functional.pad(x, flat)

kernel_name = 'standalone__convnext_block__vision'

def setup_inputs():

    _w = (lambda a: (lambda t: t.to(torch.bfloat16) if t.is_floating_point() else t)(torch.as_tensor(a)))
    H = W = 512
    C = 96
    return {
        "x": _w((lambda *s: torch.randn(*s, dtype=torch.bfloat16) * 0.05)(1, H, W, C)),
        "dw": _w((lambda *s: torch.randn(*s, dtype=torch.bfloat16) * 0.05)(7, 7, C)),
        "w1": _w((lambda *s: torch.randn(*s, dtype=torch.bfloat16) * 0.05)(C, 4 * C)),
        "w2": _w((lambda *s: torch.randn(*s, dtype=torch.bfloat16) * 0.05)(4 * C, C)),
    }

def reference(x, dw, w1, w2):
    B, H, W, C = x.shape
    pad = 3
    xp = _pad(x, ((0,0),(pad,pad),(pad,pad),(0,0)))
    out = torch.zeros_like(x)
    for i in range(7):
        for j in range(7):
            out = out + xp[:, i:i+H, j:j+W, :] * dw[i, j][None, None, None, :]
    h = _layernorm(out, axis=-1)
    return x + _gelu(h @ w1) @ w2
```

```cpp
#include <cuda_runtime.h>
#include <cuda_bf16.h>
#include <cuda.h>
#include <stdint.h>

template<int SCALE_D> __device__ __forceinline__ void wgmma_n48_f16(uint32_t* d, const uint32_t* a, uint64_t desc) {
  if (SCALE_D == 0) asm volatile("wgmma.mma_async.sync.aligned.m64n48k16.f16.f16.f16 {%0,%1,%2,%3,%4,%5,%6,%7,%8,%9,%10,%11}, {%12,%13,%14,%15}, %16, 0, 1, 1, 1;"
    : "=r"(d[0]),"=r"(d[1]),"=r"(d[2]),"=r"(d[3]),"=r"(d[4]),"=r"(d[5]),"=r"(d[6]),"=r"(d[7]),"=r"(d[8]),"=r"(d[9]),"=r"(d[10]),"=r"(d[11])
    : "r"(a[0]),"r"(a[1]),"r"(a[2]),"r"(a[3]),"l"(desc));
  if (SCALE_D == 1) asm volatile("wgmma.mma_async.sync.aligned.m64n48k16.f16.f16.f16 {%0,%1,%2,%3,%4,%5,%6,%7,%8,%9,%10,%11}, {%12,%13,%14,%15}, %16, 1, 1, 1, 1;"
    : "+r"(d[0]),"+r"(d[1]),"+r"(d[2]),"+r"(d[3]),"+r"(d[4]),"+r"(d[5]),"+r"(d[6]),"+r"(d[7]),"+r"(d[8]),"+r"(d[9]),"+r"(d[10]),"+r"(d[11])
    : "r"(a[0]),"r"(a[1]),"r"(a[2]),"r"(a[3]),"l"(desc));
}

template<int SCALE_D> __device__ __forceinline__ void wgmma_n96_f32(float* d, const uint32_t* a, uint64_t desc) {
  if (SCALE_D == 0) asm volatile("wgmma.mma_async.sync.aligned.m64n96k16.f32.f16.f16 {%0,%1,%2,%3,%4,%5,%6,%7,%8,%9,%10,%11,%12,%13,%14,%15,%16,%17,%18,%19,%20,%21,%22,%23,%24,%25,%26,%27,%28,%29,%30,%31,%32,%33,%34,%35,%36,%37,%38,%39,%40,%41,%42,%43,%44,%45,%46,%47}, {%48,%49,%50,%51}, %52, 0, 1, 1, 1;"
    : "=f"(d[0]),"=f"(d[1]),"=f"(d[2]),"=f"(d[3]),"=f"(d[4]),"=f"(d[5]),"=f"(d[6]),"=f"(d[7]),"=f"(d[8]),"=f"(d[9]),"=f"(d[10]),"=f"(d[11]),"=f"(d[12]),"=f"(d[13]),"=f"(d[14]),"=f"(d[15]),"=f"(d[16]),"=f"(d[17]),"=f"(d[18]),"=f"(d[19]),"=f"(d[20]),"=f"(d[21]),"=f"(d[22]),"=f"(d[23]),"=f"(d[24]),"=f"(d[25]),"=f"(d[26]),"=f"(d[27]),"=f"(d[28]),"=f"(d[29]),"=f"(d[30]),"=f"(d[31]),"=f"(d[32]),"=f"(d[33]),"=f"(d[34]),"=f"(d[35]),"=f"(d[36]),"=f"(d[37]),"=f"(d[38]),"=f"(d[39]),"=f"(d[40]),"=f"(d[41]),"=f"(d[42]),"=f"(d[43]),"=f"(d[44]),"=f"(d[45]),"=f"(d[46]),"=f"(d[47])
    : "r"(a[0]),"r"(a[1]),"r"(a[2]),"r"(a[3]),"l"(desc));
  if (SCALE_D == 1) asm volatile("wgmma.mma_async.sync.aligned.m64n96k16.f32.f16.f16 {%0,%1,%2,%3,%4,%5,%6,%7,%8,%9,%10,%11,%12,%13,%14,%15,%16,%17,%18,%19,%20,%21,%22,%23,%24,%25,%26,%27,%28,%29,%30,%31,%32,%33,%34,%35,%36,%37,%38,%39,%40,%41,%42,%43,%44,%45,%46,%47}, {%48,%49,%50,%51}, %52, 1, 1, 1, 1;"
    : "+f"(d[0]),"+f"(d[1]),"+f"(d[2]),"+f"(d[3]),"+f"(d[4]),"+f"(d[5]),"+f"(d[6]),"+f"(d[7]),"+f"(d[8]),"+f"(d[9]),"+f"(d[10]),"+f"(d[11]),"+f"(d[12]),"+f"(d[13]),"+f"(d[14]),"+f"(d[15]),"+f"(d[16]),"+f"(d[17]),"+f"(d[18]),"+f"(d[19]),"+f"(d[20]),"+f"(d[21]),"+f"(d[22]),"+f"(d[23]),"+f"(d[24]),"+f"(d[25]),"+f"(d[26]),"+f"(d[27]),"+f"(d[28]),"+f"(d[29]),"+f"(d[30]),"+f"(d[31]),"+f"(d[32]),"+f"(d[33]),"+f"(d[34]),"+f"(d[35]),"+f"(d[36]),"+f"(d[37]),"+f"(d[38]),"+f"(d[39]),"+f"(d[40]),"+f"(d[41]),"+f"(d[42]),"+f"(d[43]),"+f"(d[44]),"+f"(d[45]),"+f"(d[46]),"+f"(d[47])
    : "r"(a[0]),"r"(a[1]),"r"(a[2]),"r"(a[3]),"l"(desc));
}

#define NG 9
#define RING 32
#define NSLOT 6
#define RPS 2
#define CFETCH 5
#define TRIG 2
constexpr int NCONV = 3 * NG;
constexpr int RBASE = 2048 / NG, RREM = 2048 % NG;
constexpr int TILEB = 12288;
constexpr int CV_ROWB = 136 * 64;
constexpr int SLOTB = RPS * CV_ROWB;
constexpr int W1S = 0, W2S = 73728, ABUF = 147456, MISC = ABUF + 16 * 3072;
constexpr int SMEM_BYTES = MISC + 512;
static_assert(NSLOT * SLOTB <= MISC, "input ring too large");

__device__ __align__(1024) unsigned char g_scratch[(RING * NG + 1) * 2 * TILEB];
__device__ uint32_t g_ready[2048];
__device__ uint32_t g_cons[2048 + 32];
__device__ unsigned long long g_start;

#define GELU_C3 0.32920349f
#define GELU_A2 0x40d940d9u
#define SPIN_LIMIT 0x1000000

__device__ __forceinline__ uint32_t smem_u32(const void* p) { return (uint32_t)__cvta_generic_to_shared(p); }
__device__ __forceinline__ void wg_fence() { asm volatile("wgmma.fence.sync.aligned;" ::: "memory"); }
__device__ __forceinline__ void wg_commit() { asm volatile("wgmma.commit_group.sync.aligned;" ::: "memory"); }
template <int N> __device__ __forceinline__ void wg_wait() { asm volatile("wgmma.wait_group.sync.aligned %0;" ::"n"(N) : "memory"); }
__device__ __forceinline__ void mbar_init(uint32_t bar, uint32_t cnt) { asm volatile("mbarrier.init.shared::cta.b64 [%0], %1;" ::"r"(bar), "r"(cnt) : "memory"); }
__device__ __forceinline__ void mbar_expect_tx(uint32_t bar, uint32_t bytes) { asm volatile("mbarrier.arrive.expect_tx.shared::cta.b64 _, [%0], %1;" ::"r"(bar), "r"(bytes) : "memory"); }
__device__ __forceinline__ void mbar_arrive(uint32_t bar) { asm volatile("mbarrier.arrive.shared::cta.b64 _, [%0];" ::"r"(bar) : "memory"); }
__device__ __forceinline__ void mbar_wait(uint32_t bar, uint32_t parity) {
  asm volatile("{\n.reg .pred p;\n.reg .u32 c;\nmbarrier.try_wait.parity.shared::cta.b64 p, [%0], %1;\n@p bra DONE_%=;\nmov.u32 c, 0;\nWAIT_%=:\nmbarrier.try_wait.parity.shared::cta.b64 p, [%0], %1;\n@p bra DONE_%=;\n"
               "add.u32 c, c, 1;\nsetp.lt.u32 p, c, 0x1000000;\n@p bra WAIT_%=;\ntrap;\nDONE_%=:\n}" ::"r"(bar), "r"(parity) : "memory");
}
__device__ __forceinline__ void bulk_g2s(uint32_t dst, const void* src, uint32_t bytes, uint32_t bar) {
  asm volatile("cp.async.bulk.shared::cluster.global.mbarrier::complete_tx::bytes [%0], [%1], %2, [%3];" ::"r"(dst), "l"(src), "r"(bytes), "r"(bar) : "memory");
}
__device__ __forceinline__ void tma_load3d(uint32_t dst, const CUtensorMap* tm, int c0, int c1, int c2, uint32_t bar) {
  asm volatile("cp.async.bulk.tensor.3d.shared::cluster.global.mbarrier::complete_tx::bytes [%0], [%1, {%3, %4, %5}], [%2];" ::"r"(dst), "l"(tm), "r"(bar), "r"(c0), "r"(c1), "r"(c2) : "memory");
}
__device__ __forceinline__ uint32_t ld_relaxed(const uint32_t* p) { uint32_t v; asm volatile("ld.relaxed.gpu.global.u32 %0, [%1];" : "=r"(v) : "l"(p) : "memory"); return v; }
__device__ __forceinline__ void red_add(uint32_t* p) { asm volatile("red.relaxed.gpu.global.add.u32 [%0], 1;" ::"l"(p) : "memory"); }
__device__ __forceinline__ void lds128(uint32_t* r, uint32_t a) { asm volatile("ld.shared.v4.b32 {%0,%1,%2,%3}, [%4];" : "=r"(r[0]), "=r"(r[1]), "=r"(r[2]), "=r"(r[3]) : "r"(a) : "memory"); }
__device__ __forceinline__ uint2 lds64(uint32_t a) { uint2 v; asm volatile("ld.shared.v2.b32 {%0,%1}, [%2];" : "=r"(v.x), "=r"(v.y) : "r"(a) : "memory"); return v; }
__device__ __forceinline__ uint32_t lds32(uint32_t a) { uint32_t v; asm volatile("ld.shared.b32 %0, [%1];" : "=r"(v) : "r"(a) : "memory"); return v; }
__device__ __forceinline__ void sts32(uint32_t a, uint32_t v) { asm volatile("st.shared.b32 [%0], %1;" ::"r"(a), "r"(v) : "memory"); }
__device__ __forceinline__ void sts128(uint32_t a, uint4 v) { asm volatile("st.shared.v4.b32 [%0], {%1,%2,%3,%4};" ::"r"(a), "r"(v.x), "r"(v.y), "r"(v.z), "r"(v.w) : "memory"); }
__device__ __forceinline__ uint4 ldg128v(const void* p) { uint4 v; asm volatile("ld.global.nc.v4.b32 {%0,%1,%2,%3}, [%4];" : "=r"(v.x), "=r"(v.y), "=r"(v.z), "=r"(v.w) : "l"(p) : "memory"); return v; }
__device__ __forceinline__ void stg128(void* p, uint4 v) { asm volatile("st.global.v4.b32 [%0], {%1,%2,%3,%4};" ::"l"(p), "r"(v.x), "r"(v.y), "r"(v.z), "r"(v.w) : "memory"); }
__device__ __forceinline__ float bf_lo(uint32_t w) { return __uint_as_float(w << 16); }
__device__ __forceinline__ float bf_hi(uint32_t w) { return __uint_as_float(w & 0xffff0000u); }
__device__ __forceinline__ uint32_t pack_f16(float lo, float hi) { uint32_t d; asm("cvt.rn.f16x2.f32 %0, %1, %2;" : "=r"(d) : "f"(hi), "f"(lo)); return d; }
__device__ __forceinline__ uint32_t pack_f16_sat(float lo, float hi) { uint32_t d; asm("cvt.rn.satfinite.f16x2.f32 %0, %1, %2;" : "=r"(d) : "f"(hi), "f"(lo)); return d; }
__device__ __forceinline__ uint32_t pack_bf16(float lo, float hi) { uint32_t d; asm("cvt.rn.bf16x2.f32 %0, %1, %2;" : "=r"(d) : "f"(hi), "f"(lo)); return d; }
__device__ __forceinline__ uint32_t hadd2_bf16(uint32_t a, uint32_t b) { uint32_t d; asm("add.rn.bf16x2 %0, %1, %2;" : "=r"(d) : "r"(a), "r"(b)); return d; }
__device__ __forceinline__ uint32_t h2add(uint32_t a, uint32_t b) { uint32_t d; asm("add.rn.f16x2 %0, %1, %2;" : "=r"(d) : "r"(a), "r"(b)); return d; }
__device__ __forceinline__ uint32_t h2mul(uint32_t a, uint32_t b) { uint32_t d; asm("mul.rn.f16x2 %0, %1, %2;" : "=r"(d) : "r"(a), "r"(b)); return d; }
__device__ __forceinline__ uint32_t h2fma(uint32_t a, uint32_t b, uint32_t c) { uint32_t d; asm("fma.rn.f16x2 %0, %1, %2, %3;" : "=r"(d) : "r"(a), "r"(b), "r"(c)); return d; }
__device__ __forceinline__ uint32_t h2lo(uint32_t a) { uint32_t d; asm("{.reg .f16 l,h; mov.b32 {l,h}, %1; mov.b32 %0, {l,l};}" : "=r"(d) : "r"(a)); return d; }
__device__ __forceinline__ uint32_t h2hi(uint32_t a) { uint32_t d; asm("{.reg .f16 l,h; mov.b32 {l,h}, %1; mov.b32 %0, {h,h};}" : "=r"(d) : "r"(a)); return d; }
__device__ __forceinline__ float h_lo(uint32_t a) { float d; asm("{.reg .f16 l,h; mov.b32 {l,h}, %1; cvt.f32.f16 %0, l;}" : "=f"(d) : "r"(a)); return d; }
__device__ __forceinline__ float h_hi(uint32_t a) { float d; asm("{.reg .f16 l,h; mov.b32 {l,h}, %1; cvt.f32.f16 %0, h;}" : "=f"(d) : "r"(a)); return d; }
__device__ __forceinline__ uint32_t prmt(uint32_t a, uint32_t b, uint32_t s) { uint32_t d; asm("prmt.b32 %0, %1, %2, %3;" : "=r"(d) : "r"(a), "r"(b), "r"(s)); return d; }
__device__ __forceinline__ uint32_t opaque(uint32_t v) { asm volatile("" : "+r"(v)); return v; }
__device__ __forceinline__ void hmma_bf16(float* d, const uint32_t* a, const uint32_t* b, const float* c) {
  asm("mma.sync.aligned.m16n8k16.row.col.f32.bf16.bf16.f32 {%0,%1,%2,%3}, {%4,%5,%6,%7}, {%8,%9}, {%10,%11,%12,%13};"
      : "=f"(d[0]), "=f"(d[1]), "=f"(d[2]), "=f"(d[3])
      : "r"(a[0]), "r"(a[1]), "r"(a[2]), "r"(a[3]), "r"(b[0]), "r"(b[1]), "f"(c[0]), "f"(c[1]), "f"(c[2]), "f"(c[3]));
}
__device__ __forceinline__ uint32_t bf2_to_h2(uint32_t w, float s) { return pack_f16(bf_lo(w) * s, bf_hi(w) * s); }
__device__ __forceinline__ uint32_t bf2_to_h2(uint32_t w) { return pack_f16(bf_lo(w), bf_hi(w)); }

__device__ __forceinline__ uint32_t gelu_h2(uint32_t y) {
  uint32_t t, u, th, g;
  asm volatile("fma.rn.f16x2 %0, %1, %1, %2;" : "=r"(t) : "r"(y), "r"(GELU_A2));
  asm volatile("mul.rn.f16x2 %0, %1, %2;" : "=r"(u) : "r"(y), "r"(t));
  asm volatile("tanh.approx.f16x2 %0, %1;" : "=r"(th) : "r"(u));
  asm volatile("fma.rn.f16x2 %0, %1, %2, %1;" : "=r"(g) : "r"(y), "r"(th));
  return g;
}

__device__ __forceinline__ void prep_weights(uint32_t sb, const __nv_bfloat16* __restrict__ w1, const __nv_bfloat16* __restrict__ w2, int warp, int lane) {
  const int k0 = lane & 7, lq = lane >> 3;
  uint4 v[9], u[3][4];
#pragma unroll
  for (int i = 0; i < 9; i++) {
    int it = warp * 9 + i, nbq = it % 12, skh = it / 12, kh = skh & 1, s = skh >> 1;
    int ch = 16 * s + 4 * (k0 >> 1) + 2 * kh + (k0 & 1);
    v[i] = __ldg((const uint4*)(w1 + ch * 384 + (nbq * 4 + lq) * 8));
  }
#pragma unroll
  for (int i = 0; i < 3; i++) {
    int it = warp + 16 * i;
    if (it < 36) {
      int un = it * 4 + lq, j = un % 3, h8 = un / 3;
      const uint4* p = (const uint4*)(w2 + (h8 * 8 + k0) * 96 + j * 32);
#pragma unroll
      for (int q = 0; q < 4; q++) u[i][q] = __ldg(p + q);
    }
  }
#pragma unroll
  for (int i = 0; i < 9; i++) {
    int it = warp * 9 + i, nbq = it % 12, skh = it / 12, kh = skh & 1, s = skh >> 1;
    sts128(sb + W1S + s * 12288 + (nbq * 4 + lq) * 256 + kh * 128 + k0 * 16, make_uint4(bf2_to_h2(v[i].x), bf2_to_h2(v[i].y), bf2_to_h2(v[i].z), bf2_to_h2(v[i].w)));
  }
  const float sc = 0.5f / GELU_C3;
#pragma unroll
  for (int i = 0; i < 3; i++) {
    int it = warp + 16 * i;
    if (it < 36) {
      int un = it * 4 + lq, j = un % 3, h8 = un / 3;
      uint32_t base = sb + W2S + (h8 >> 1) * 3072 + (j * 4) * 256 + (h8 & 1) * 128 + k0 * 16;
      sts128(base, make_uint4(bf2_to_h2(u[i][0].x, sc), bf2_to_h2(u[i][1].x, sc), bf2_to_h2(u[i][2].x, sc), bf2_to_h2(u[i][3].x, sc)));
      sts128(base + 256, make_uint4(bf2_to_h2(u[i][0].y, sc), bf2_to_h2(u[i][1].y, sc), bf2_to_h2(u[i][2].y, sc), bf2_to_h2(u[i][3].y, sc)));
      sts128(base + 512, make_uint4(bf2_to_h2(u[i][0].z, sc), bf2_to_h2(u[i][1].z, sc), bf2_to_h2(u[i][2].z, sc), bf2_to_h2(u[i][3].z, sc)));
      sts128(base + 768, make_uint4(bf2_to_h2(u[i][0].w, sc), bf2_to_h2(u[i][1].w, sc), bf2_to_h2(u[i][2].w, sc), bf2_to_h2(u[i][3].w, sc)));
    }
  }
}

__device__ __noinline__ void ln_wide(uint32_t ad) {
  float m[2], r[2];
#pragma unroll
  for (int hi = 0; hi < 2; hi++) {
    float sm = 0.f;
    for (int s = 0; s < 6; s++) { uint2 w = lds64(ad + s * 512 + hi * 8); sm += (h_lo(w.x) + h_hi(w.x)) + (h_lo(w.y) + h_hi(w.y)); }
    sm += __shfl_xor_sync(0xffffffffu, sm, 1); sm += __shfl_xor_sync(0xffffffffu, sm, 2);
    m[hi] = sm * (1.f / 96.f);
    float q = 0.f;
    for (int s = 0; s < 6; s++) {
      uint2 w = lds64(ad + s * 512 + hi * 8);
      float d0 = h_lo(w.x) - m[hi], d1 = h_hi(w.x) - m[hi], d2 = h_lo(w.y) - m[hi], d3 = h_hi(w.y) - m[hi];
      q += (d0 * d0 + d1 * d1) + (d2 * d2 + d3 * d3);
    }
    q += __shfl_xor_sync(0xffffffffu, q, 1); q += __shfl_xor_sync(0xffffffffu, q, 2);
    r[hi] = rsqrtf(fmaf(q, 1.f / 96.f, 1e-5f)) * GELU_C3;
  }
  for (int s = 0; s < 6; s++) {
    uint32_t w[4]; lds128(w, ad + s * 512);
    sts128(ad + s * 512, make_uint4(pack_f16((h_lo(w[0]) - m[0]) * r[0], (h_hi(w[0]) - m[0]) * r[0]), pack_f16((h_lo(w[2]) - m[1]) * r[1], (h_hi(w[2]) - m[1]) * r[1]),
                                    pack_f16((h_lo(w[1]) - m[0]) * r[0], (h_hi(w[1]) - m[0]) * r[0]), pack_f16((h_lo(w[3]) - m[1]) * r[1], (h_hi(w[3]) - m[1]) * r[1])));
  }
  asm volatile("fence.proxy.async.shared::cta;" ::: "memory");
}

__device__ __forceinline__ void load_ln(uint32_t ad, uint32_t* a) {
  uint32_t raw[6][4];
#pragma unroll
  for (int s = 0; s < 6; s++) lds128(raw[s], ad + s * 512);
  uint32_t sm[2];
#pragma unroll
  for (int hi = 0; hi < 2; hi++) {
    uint32_t s0 = h2add(raw[0][2 * hi], raw[1][2 * hi]), s1 = h2add(raw[0][2 * hi + 1], raw[1][2 * hi + 1]);
    uint32_t s2 = h2add(raw[2][2 * hi], raw[3][2 * hi]), s3 = h2add(raw[2][2 * hi + 1], raw[3][2 * hi + 1]);
    uint32_t s4 = h2add(raw[4][2 * hi], raw[5][2 * hi]), s5 = h2add(raw[4][2 * hi + 1], raw[5][2 * hi + 1]);
    sm[hi] = h2add(h2add(h2add(s0, s1), h2add(s2, s3)), h2add(s4, s5));
  }
  uint32_t s = h2add(prmt(sm[0], sm[1], 0x5410), prmt(sm[0], sm[1], 0x7632));
  s = h2add(s, __shfl_xor_sync(0xffffffffu, s, 1));
  s = h2add(s, __shfl_xor_sync(0xffffffffu, s, 2));
  const uint32_t nm = h2mul(s, 0xA155A155u);
  uint32_t qq[2];
#pragma unroll
  for (int hi = 0; hi < 2; hi++) {
    const uint32_t m = hi ? h2hi(nm) : h2lo(nm);
    uint32_t q0 = 0, q1 = 0;
#pragma unroll
    for (int k = 0; k < 6; k++) {
      uint32_t d0 = h2add(raw[k][2 * hi], m), d1 = h2add(raw[k][2 * hi + 1], m);
      raw[k][2 * hi] = d0; raw[k][2 * hi + 1] = d1;
      q0 = k ? h2fma(d0, d0, q0) : h2mul(d0, d0);
      q1 = k ? h2fma(d1, d1, q1) : h2mul(d1, d1);
    }
    qq[hi] = h2add(q0, q1);
  }
  uint32_t q = h2add(prmt(qq[0], qq[1], 0x5410), prmt(qq[0], qq[1], 0x7632));
  q = h2add(q, __shfl_xor_sync(0xffffffffu, q, 1));
  q = h2add(q, __shfl_xor_sync(0xffffffffu, q, 2));
  const float r0 = rsqrtf(fmaf(h_lo(q), 1.f / 96.f, 1e-5f)) * GELU_C3, r1 = rsqrtf(fmaf(h_hi(q), 1.f / 96.f, 1e-5f)) * GELU_C3;
  const uint32_t r = pack_f16(r0, r1);
#pragma unroll
  for (int k = 0; k < 6; k++) {
    a[4 * k] = h2mul(raw[k][0], h2lo(r)); a[4 * k + 2] = h2mul(raw[k][1], h2lo(r));
    a[4 * k + 1] = h2mul(raw[k][2], h2hi(r)); a[4 * k + 3] = h2mul(raw[k][3], h2hi(r));
  }
  const bool bad = (((q & 0x7c007c00u) + 0x04000400u) & 0x80008000u) != 0;
  if (__any_sync(0xffffffffu, bad)) {
    ln_wide(ad);
#pragma unroll
    for (int k = 0; k < 6; k++) lds128(a + 4 * k, ad + k * 512);
  }
}

__device__ __forceinline__ void gemm1(uint32_t* p, const uint32_t* a, uint64_t d1, int c) {
  wgmma_n48_f16<0>(p, a, d1 + c * (1536 >> 4));
#pragma unroll
  for (int s = 1; s < 6; s++) wgmma_n48_f16<1>(p, a + 4 * s, d1 + c * (1536 >> 4) + s * (12288 >> 4));
}

struct TileInfo { int L; uint32_t sofs; };
__device__ __forceinline__ TileInfo decode_tile(int n) {
  const int r = n >> 1, j = r / NG, gm = r - j * NG;
  TileInfo ti;
  ti.L = gm * RBASE + min(gm, RREM) + j;
  ti.sofs = (((j & (RING - 1)) * NG + gm) * 2 + (n & 1)) * TILEB;
  return ti;
}
__device__ __forceinline__ void fetch_slice(uint32_t abuf, uint32_t bar, uint32_t sofs, int lane) {
  if (lane == 0) {
    asm volatile("fence.acquire.gpu;" ::: "memory");
    asm volatile("fence.proxy.async.global;" ::: "memory");
    mbar_expect_tx(bar, 3072);
    bulk_g2s(abuf, g_scratch + sofs, 3072, bar);
  }
}
__device__ __forceinline__ void wait_ready(int L, uint32_t target) {
  int spins = 0;
  while (ld_relaxed(&g_ready[L]) != target) { __nanosleep(64); if (++spins > SPIN_LIMIT) __trap(); }
}

__device__ __forceinline__ void mlp_role(uint32_t sb, const __nv_bfloat16* __restrict__ x, const __nv_bfloat16* __restrict__ w1, const __nv_bfloat16* __restrict__ w2,
                                         __nv_bfloat16* __restrict__ out, int warp, int lane) {
  const int wg = warp >> 2, g = lane >> 2, t = lane & 3;
  const uint32_t abuf = sb + ABUF + warp * 3072;
  const uint32_t bar = sb + MISC + warp * 8;
  const int nm = gridDim.x - NCONV;
  if (lane == 0) { mbar_init(bar, 1); asm volatile("fence.mbarrier_init.release.cluster;" ::: "memory"); }
  if (threadIdx.x == 0) sts32(sb + MISC + 256, (uint32_t)(atomicAdd(&g_start, 1ULL) / gridDim.x) + 1);
  prep_weights(sb, w1, w2, warp, lane);
  asm volatile("fence.proxy.async.shared::cta;" ::: "memory");
  __syncthreads();
  const uint32_t rtarget = 3 * lds32(sb + MISC + 256);
  const uint64_t dbase = ((uint64_t)(128 >> 4) << 16) | ((uint64_t)(256 >> 4) << 32);
  const uint64_t d1 = dbase | (uint64_t)(((sb + W1S) >> 4) & 0x3fff);
  const uint64_t d2 = dbase | (uint64_t)(((sb + W2S) >> 4) & 0x3fff);
  const uint32_t ad = abuf + t * 128 + ((g ^ (2 * t)) << 4);
  const int pofs = (16 * (2 * (warp & 3) + (g >> 2)) + 2 * (g & 3)) * 192 + t * 16;
  const int mybar = 1 + wg, nxtbar = 1 + ((wg + 1) & 3);
  int n = wg * nm + (blockIdx.x - NCONV);
  uint32_t ph = 0;
  bool pending = true;
  for (; n < 4096; n += 4 * nm) {
    const TileInfo ti = decode_tile(n);
    if (pending) { wait_ready(ti.L, rtarget); fetch_slice(abuf, bar, ti.sofs + (warp & 3) * 3072, lane); }
    uint32_t a[24], p[8][12], gg[8][12];
    float acc[48];
    mbar_wait(bar, ph); ph ^= 1;
    if (lane == 0) red_add(&g_cons[ti.L]);
    load_ln(ad, a);
    const size_t gofs = (size_t)((ti.L & 511) * 512 + (ti.L >> 9) * 128 + (n & 1) * 8) * 192 + pofs;
    const int nn = n + 4 * nm;
    uint32_t rdy = 0;
    uint4 xr[2][3];
    if (n >= nm) asm volatile("bar.sync %0, 256;" ::"r"(mybar) : "memory");
    wg_fence();
    gemm1(p[0], a, d1, 0); wg_commit();
#pragma unroll
    for (int c = 0; c < 8; c++) {
      wg_wait<0>();
      if (c == TRIG) asm volatile("{.reg .pred p; setp.lt.s32 p, %1, 4096; @p bar.arrive %0, 256;}" ::"r"(nxtbar), "r"(n + nm) : "memory");
      if (c == CFETCH - 1) rdy = ld_relaxed(&g_ready[decode_tile(min(nn, 4095)).L]);
      if (c == CFETCH) {
        pending = (rdy != rtarget);
        if (!pending && nn < 4096) fetch_slice(abuf, bar, decode_tile(nn).sofs + (warp & 3) * 3072, lane);
      }
      if (c == 7) {
#pragma unroll
        for (int hi = 0; hi < 2; hi++)
#pragma unroll
          for (int j = 0; j < 3; j++) xr[hi][j] = ldg128v((const char*)x + gofs + hi * 192 + j * 64);
      }
#pragma unroll
      for (int s = 0; s < 3; s++) {
#pragma unroll
        for (int i = 0; i < 4; i++) gg[c][4 * s + i] = gelu_h2(p[c][4 * s + i]);
        wg_fence();
        if (c == 0 && s == 0) wgmma_n96_f32<0>(acc, gg[c], d2); else wgmma_n96_f32<1>(acc, &gg[c][4 * s], d2 + (c * 3 + s) * (3072 >> 4));
      }
      if (c + 1 < 8) gemm1(p[c + 1], a, d1, c + 1);
      wg_commit();
    }
    wg_wait<0>();
#pragma unroll
    for (int hi = 0; hi < 2; hi++)
#pragma unroll
      for (int j = 0; j < 3; j++) {
        uint4 o;
        o.x = hadd2_bf16(xr[hi][j].x, pack_bf16(acc[(4 * j + 0) * 4 + 2 * hi], acc[(4 * j + 0) * 4 + 2 * hi + 1]));
        o.y = hadd2_bf16(xr[hi][j].y, pack_bf16(acc[(4 * j + 1) * 4 + 2 * hi], acc[(4 * j + 1) * 4 + 2 * hi + 1]));
        o.z = hadd2_bf16(xr[hi][j].z, pack_bf16(acc[(4 * j + 2) * 4 + 2 * hi], acc[(4 * j + 2) * 4 + 2 * hi + 1]));
        o.w = hadd2_bf16(xr[hi][j].w, pack_bf16(acc[(4 * j + 3) * 4 + 2 * hi], acc[(4 * j + 3) * 4 + 2 * hi + 1]));
        stg128((char*)out + gofs + hi * 192 + j * 64, o);
      }
  }
}

struct ConvPlan { int L0, len, vs, iA, iG, iE, nit; };
__device__ __forceinline__ ConvPlan make_plan(int gm) {
  ConvPlan c;
  c.L0 = gm * RBASE + min(gm, RREM);
  c.len = RBASE + (gm < RREM ? 1 : 0);
  const int L1 = c.L0 + c.len - 1;
  const int v0 = c.L0 + 3 * (c.L0 >> 9), v1 = L1 + 3 * (L1 >> 9);
  c.vs = (c.L0 & 511) ? v0 - 3 : v0;
  c.iA = v0 - c.vs + 4;
  c.iE = v1 - c.vs + 4;
  c.iG = (c.L0 >> 9) * 515 + 512 - c.vs + 4;
  c.nit = (c.iE + RPS) / RPS;
  return c;
}
__device__ __forceinline__ int rows_after(const ConvPlan& c, int i) {
  const int e = min(i, c.iE + 1);
  return max(e - c.iA, 0) - min(max(e - c.iG, 0), 3);
}

__device__ __forceinline__ void conv_compute(uint32_t sb, const __nv_bfloat16* __restrict__ dw, int third, int nit, int warp, int lane) {
  const int g = lane >> 2, t = lane & 3;
  const uint32_t full = sb + MISC;
  uint32_t B[4][7][2];
#pragma unroll
  for (int i = 0; i < 7; i++) {
    uint2 w[4];
#pragma unroll
    for (int u = 0; u < 4; u++) {
      const int j = t + 4 * u - g;
      w[u] = make_uint2(0u, 0u);
      if (j >= 0 && j < 7) w[u] = __ldg((const uint2*)(dw + (i * 7 + j) * 96 + third * 32 + warp * 4));
    }
    B[0][i][0] = prmt(w[0].x, w[1].x, 0x5410); B[0][i][1] = prmt(w[2].x, w[3].x, 0x5410);
    B[1][i][0] = prmt(w[0].x, w[1].x, 0x7632); B[1][i][1] = prmt(w[2].x, w[3].x, 0x7632);
    B[2][i][0] = prmt(w[0].y, w[1].y, 0x5410); B[2][i][1] = prmt(w[2].y, w[3].y, 0x5410);
    B[3][i][0] = prmt(w[0].y, w[1].y, 0x7632); B[3][i][1] = prmt(w[2].y, w[3].y, 0x7632);
  }
  float S[4][6][4];
  uint32_t A[4][4];
#pragma unroll
  for (int c = 0; c < 4; c++) {
#pragma unroll
    for (int k = 0; k < 4; k++) A[c][k] = 0;
#pragma unroll
    for (int i = 0; i < 6; i++)
#pragma unroll
      for (int k = 0; k < 4; k++) S[c][i][k] = 0.f;
  }
  const int pU = t + 4 * (g & 1), pV = t + 4 * (1 - (g & 1));
  const uint32_t aU = opaque(sb + (16 * g + pU) * 64 + (((warp >> 1) ^ (pU >> 1)) << 4) + (warp & 1) * 8);
  const uint32_t aV = opaque(sb + (16 * g + pV) * 64 + (((warp >> 1) ^ (pV >> 1)) << 4) + (warp & 1) * 8);
  const uint32_t selL = opaque((g & 1) ? 0x1054u : 0x5410u), selH = opaque((g & 1) ? 0x3276u : 0x7632u);
  const uint32_t selL2 = opaque((g & 1) ? 0x5410u : 0x1054u), selH2 = opaque((g & 1) ? 0x7632u : 0x3276u);
  const int Q = third * 8 + warp;
  unsigned char* const obase = g_scratch + (g >> 1) * 3072 + Q * 128 + (((4 * (g & 1) + t) ^ (2 * (Q & 3))) << 4);
  const float zero4[4] = {0.f, 0.f, 0.f, 0.f};
  uint32_t sofs = 0, bar = full, ph = 0;
  for (int it = 0; it < nit; it++) {
    mbar_wait(bar, ph);
#pragma unroll
    for (int k = 0; k < RPS; k++) {
      uint2 U[3], V[3];
#pragma unroll
      for (int j = 0; j < 3; j++) { U[j] = lds64(aU + sofs + k * CV_ROWB + j * 512); V[j] = lds64(aV + sofs + k * CV_ROWB + j * 512); }
      const uint32_t oo = lds32(bar + 128 + k * 64);
      float T[4][4];
      uint32_t An[4][4];
#pragma unroll
      for (int c = 0; c < 4; c++) hmma_bf16(T[c], A[c], B[c][6], S[c][5]);
#pragma unroll
      for (int c = 0; c < 4; c++) {
#pragma unroll
        for (int i = 5; i >= 1; i--) hmma_bf16(S[c][i], A[c], B[c][i], S[c][i - 1]);
        hmma_bf16(S[c][0], A[c], B[c][0], zero4);
        if (c == 0) {
          stg128(obase + oo, make_uint4(pack_f16_sat(T[0][0], T[1][0]), pack_f16_sat(T[2][0], T[3][0]), pack_f16_sat(T[0][1], T[1][1]), pack_f16_sat(T[2][1], T[3][1])));
          stg128(obase + oo + TILEB, make_uint4(pack_f16_sat(T[0][2], T[1][2]), pack_f16_sat(T[2][2], T[3][2]), pack_f16_sat(T[0][3], T[1][3]), pack_f16_sat(T[2][3], T[3][3])));
        }
        const uint32_t sel = (c & 1) ? selH : selL;
        An[c][0] = prmt(c < 2 ? U[0].x : U[0].y, c < 2 ? V[0].x : V[0].y, sel);
        An[c][1] = prmt(c < 2 ? U[1].x : U[1].y, c < 2 ? V[1].x : V[1].y, sel);
        An[c][2] = prmt(c < 2 ? V[1].x : V[1].y, c < 2 ? U[1].x : U[1].y, (c & 1) ? selH2 : selL2);
        An[c][3] = prmt(c < 2 ? U[2].x : U[2].y, c < 2 ? V[2].x : V[2].y, sel);
      }
#pragma unroll
      for (int c = 0; c < 4; c++)
#pragma unroll
        for (int q = 0; q < 4; q++) A[c][q] = An[c][q];
    }
    __syncwarp();
    if (lane == 0) mbar_arrive(bar + 64);
    sofs += SLOTB; bar += 8;
    if (sofs == NSLOT * SLOTB) { sofs = 0; bar = full; ph ^= 1; }
  }
}

__device__ __forceinline__ void conv_loader(uint32_t sb, const CUtensorMap* tmx, const ConvPlan& c, int gm, int third, int lane) {
  const uint32_t full = sb + MISC;
  uint32_t ctarget = 0;
  int credit = RING, s = 0;
  uint32_t ph = 0;
  for (int it = 0; it < c.nit + NSLOT; it++) {
    if (it >= NSLOT) {
      mbar_wait(full + 64 + s * 8, ph ^ 1);
      if (lane == 0) asm volatile("st.release.cta.shared.u32 [%0], %1;" ::"r"(full + 448), "r"(rows_after(c, (it - NSLOT + 1) * RPS)) : "memory");
    }
    if (it == NSLOT - 1) {
      if (lane == 0) ctarget = 8 * ((uint32_t)(atomicAdd(&g_start, 1ULL) / gridDim.x) + 1);
      ctarget = __shfl_sync(0xffffffffu, ctarget, 0);
    }
    if (it < c.nit) {
      const int need = rows_after(c, (it + 1) * RPS);
      int spins = 0;
      while (need > credit) {
        const uint32_t ok = __ballot_sync(0xffffffffu, ld_relaxed(&g_cons[c.L0 + credit - RING + lane]) == ctarget);
        const int got = __ffs(~ok) - 1;
        credit += got < 0 ? 32 : got;
        if (need > credit) { __nanosleep(64); if (++spins > SPIN_LIMIT) __trap(); }
      }
      if (lane == 0) {
        asm volatile("fence.acquire.gpu;" ::: "memory");
#pragma unroll
        for (int k = 0; k < RPS; k++) {
          const int i = it * RPS + k, j = rows_after(c, i);
          sts32(full + 128 + k * 64 + s * 8, (rows_after(c, i + 1) > j ? (j & (RING - 1)) * NG + gm : RING * NG) * (2 * TILEB));
        }
        mbar_expect_tx(full + s * 8, SLOTB);
#pragma unroll
        for (int k = 0; k < RPS; k++) {
          const int v = c.vs + it * RPS + k, st = v / 515;
          tma_load3d(sb + s * SLOTB + k * CV_ROWB, tmx, third * 32, st * 128 - 3, v - st * 515, full + s * 8);
        }
      }
      __syncwarp();
    }
    if (++s == NSLOT) { s = 0; ph ^= 1; }
  }
}

__device__ __forceinline__ void conv_publisher(uint32_t sb, const ConvPlan& c, int lane) {
  int last = 0, spins = 0;
  while (last < c.len) {
    int d;
    asm volatile("ld.acquire.cta.shared.u32 %0, [%1];" : "=r"(d) : "r"(sb + MISC + 448) : "memory");
    d = min(d, last + 32);
    if (d > last) {
      asm volatile("fence.acq_rel.gpu;" ::: "memory");
      if (last + lane < d) red_add(&g_ready[c.L0 + last + lane]);
      last = d; spins = 0;
    } else { __nanosleep(40); if (++spins > SPIN_LIMIT) __trap(); }
  }
}

__global__ void __launch_bounds__(512, 1) convnext_kernel(const __grid_constant__ CUtensorMap tmx, const __nv_bfloat16* __restrict__ x, const __nv_bfloat16* __restrict__ dw,
                                                          const __nv_bfloat16* __restrict__ w1, const __nv_bfloat16* __restrict__ w2, __nv_bfloat16* __restrict__ out) {
  extern __shared__ __align__(1024) unsigned char smem[];
  const uint32_t sb = smem_u32(smem);
  const int warp = __shfl_sync(0xffffffffu, threadIdx.x >> 5, 0), lane = threadIdx.x & 31;
  if (blockIdx.x >= NCONV) {
    mlp_role(sb, x, w1, w2, out, warp, lane);
  } else {
    const int gm = blockIdx.x / 3, third = blockIdx.x % 3;
    if (threadIdx.x == 0) {
      for (int s = 0; s < NSLOT; s++) { mbar_init(sb + MISC + s * 8, 1); mbar_init(sb + MISC + 64 + s * 8, 8); }
      sts32(sb + MISC + 448, 0);
      asm volatile("fence.mbarrier_init.release.cluster;" ::: "memory");
    }
    __syncthreads();
    const ConvPlan c = make_plan(gm);
    if (warp < 8) {
      asm volatile("setmaxnreg.inc.sync.aligned.u32 216;");
      conv_compute(sb, dw, third, c.nit, warp, lane);
    } else {
      asm volatile("setmaxnreg.dec.sync.aligned.u32 40;");
      if (warp == 8) conv_loader(sb, &tmx, c, gm, third, lane);
      else if (warp == 9) conv_publisher(sb, c, lane);
    }
  }
}

typedef CUresult (*PFN_encodeTiled)(CUtensorMap*, CUtensorMapDataType, cuuint32_t, void*, const cuuint64_t*, const cuuint64_t*, const cuuint32_t*, const cuuint32_t*,
                                    CUtensorMapInterleave, CUtensorMapSwizzle, CUtensorMapL2promotion, CUtensorMapFloatOOBfill);

extern "C" void kernel_launch(void* const* d_in, const int* in_sizes, int n_in, void* d_out, int out_size) {
  const __nv_bfloat16* x = (const __nv_bfloat16*)d_in[0];
  const __nv_bfloat16* dw = (const __nv_bfloat16*)d_in[1];
  const __nv_bfloat16* w1 = (const __nv_bfloat16*)d_in[2];
  const __nv_bfloat16* w2 = (const __nv_bfloat16*)d_in[3];
  static PFN_encodeTiled encode = nullptr;
  static int nsm = 0;
  if (!encode) {
    void* fn = nullptr; cudaDriverEntryPointQueryResult qr;
    cudaGetDriverEntryPoint("cuTensorMapEncodeTiled", &fn, cudaEnableDefault, &qr);
    encode = (PFN_encodeTiled)fn;
    int dev = 0; cudaGetDevice(&dev);
    cudaDeviceGetAttribute(&nsm, cudaDevAttrMultiProcessorCount, dev);
    cudaFuncSetAttribute(convnext_kernel, cudaFuncAttributeMaxDynamicSharedMemorySize, SMEM_BYTES);
  }
  CUtensorMap tm;
  cuuint64_t dims[3] = {96, 512, 512}, strides[2] = {192, 192 * 512};
  cuuint32_t box[3] = {32, 136, 1}, es[3] = {1, 1, 1};
  encode(&tm, CU_TENSOR_MAP_DATA_TYPE_BFLOAT16, 3, (void*)x, dims, strides, box, es, CU_TENSOR_MAP_INTERLEAVE_NONE, CU_TENSOR_MAP_SWIZZLE_64B,
         CU_TENSOR_MAP_L2_PROMOTION_L2_128B, CU_TENSOR_MAP_FLOAT_OOB_FILL_NONE);
  convnext_kernel<<<nsm, 512, SMEM_BYTES>>>(tm, x, dw, w1, w2, (__nv_bfloat16*)d_out);
}
```

```cpp
#include <cuda_runtime.h>
#include <cuda_bf16.h>
#include <cuda.h>
#include <stdint.h>

template<int SCALE_D> __device__ __forceinline__ void wgmma_n48_f16(uint32_t* d, const uint32_t* a, uint64_t desc) {
  if (SCALE_D == 0) asm volatile("wgmma.mma_async.sync.aligned.m64n48k16.f16.f16.f16 {%0,%1,%2,%3,%4,%5,%6,%7,%8,%9,%10,%11}, {%12,%13,%14,%15}, %16, 0, 1, 1, 1;"
    : "=r"(d[0]),"=r"(d[1]),"=r"(d[2]),"=r"(d[3]),"=r"(d[4]),"=r"(d[5]),"=r"(d[6]),"=r"(d[7]),"=r"(d[8]),"=r"(d[9]),"=r"(d[10]),"=r"(d[11])
    : "r"(a[0]),"r"(a[1]),"r"(a[2]),"r"(a[3]),"l"(desc));
  if (SCALE_D == 1) asm volatile("wgmma.mma_async.sync.aligned.m64n48k16.f16.f16.f16 {%0,%1,%2,%3,%4,%5,%6,%7,%8,%9,%10,%11}, {%12,%13,%14,%15}, %16, 1, 1, 1, 1;"
    : "+r"(d[0]),"+r"(d[1]),"+r"(d[2]),"+r"(d[3]),"+r"(d[4]),"+r"(d[5]),"+r"(d[6]),"+r"(d[7]),"+r"(d[8]),"+r"(d[9]),"+r"(d[10]),"+r"(d[11])
    : "r"(a[0]),"r"(a[1]),"r"(a[2]),"r"(a[3]),"l"(desc));
}

template<int SCALE_D> __device__ __forceinline__ void wgmma_n96_f32(float* d, const uint32_t* a, uint64_t desc) {
  if (SCALE_D == 0) asm volatile("wgmma.mma_async.sync.aligned.m64n96k16.f32.f16.f16 {%0,%1,%2,%3,%4,%5,%6,%7,%8,%9,%10,%11,%12,%13,%14,%15,%16,%17,%18,%19,%20,%21,%22,%23,%24,%25,%26,%27,%28,%29,%30,%31,%32,%33,%34,%35,%36,%37,%38,%39,%40,%41,%42,%43,%44,%45,%46,%47}, {%48,%49,%50,%51}, %52, 0, 1, 1, 1;"
    : "=f"(d[0]),"=f"(d[1]),"=f"(d[2]),"=f"(d[3]),"=f"(d[4]),"=f"(d[5]),"=f"(d[6]),"=f"(d[7]),"=f"(d[8]),"=f"(d[9]),"=f"(d[10]),"=f"(d[11]),"=f"(d[12]),"=f"(d[13]),"=f"(d[14]),"=f"(d[15]),"=f"(d[16]),"=f"(d[17]),"=f"(d[18]),"=f"(d[19]),"=f"(d[20]),"=f"(d[21]),"=f"(d[22]),"=f"(d[23]),"=f"(d[24]),"=f"(d[25]),"=f"(d[26]),"=f"(d[27]),"=f"(d[28]),"=f"(d[29]),"=f"(d[30]),"=f"(d[31]),"=f"(d[32]),"=f"(d[33]),"=f"(d[34]),"=f"(d[35]),"=f"(d[36]),"=f"(d[37]),"=f"(d[38]),"=f"(d[39]),"=f"(d[40]),"=f"(d[41]),"=f"(d[42]),"=f"(d[43]),"=f"(d[44]),"=f"(d[45]),"=f"(d[46]),"=f"(d[47])
    : "r"(a[0]),"r"(a[1]),"r"(a[2]),"r"(a[3]),"l"(desc));
  if (SCALE_D == 1) asm volatile("wgmma.mma_async.sync.aligned.m64n96k16.f32.f16.f16 {%0,%1,%2,%3,%4,%5,%6,%7,%8,%9,%10,%11,%12,%13,%14,%15,%16,%17,%18,%19,%20,%21,%22,%23,%24,%25,%26,%27,%28,%29,%30,%31,%32,%33,%34,%35,%36,%37,%38,%39,%40,%41,%42,%43,%44,%45,%46,%47}, {%48,%49,%50,%51}, %52, 1, 1, 1, 1;"
    : "+f"(d[0]),"+f"(d[1]),"+f"(d[2]),"+f"(d[3]),"+f"(d[4]),"+f"(d[5]),"+f"(d[6]),"+f"(d[7]),"+f"(d[8]),"+f"(d[9]),"+f"(d[10]),"+f"(d[11]),"+f"(d[12]),"+f"(d[13]),"+f"(d[14]),"+f"(d[15]),"+f"(d[16]),"+f"(d[17]),"+f"(d[18]),"+f"(d[19]),"+f"(d[20]),"+f"(d[21]),"+f"(d[22]),"+f"(d[23]),"+f"(d[24]),"+f"(d[25]),"+f"(d[26]),"+f"(d[27]),"+f"(d[28]),"+f"(d[29]),"+f"(d[30]),"+f"(d[31]),"+f"(d[32]),"+f"(d[33]),"+f"(d[34]),"+f"(d[35]),"+f"(d[36]),"+f"(d[37]),"+f"(d[38]),"+f"(d[39]),"+f"(d[40]),"+f"(d[41]),"+f"(d[42]),"+f"(d[43]),"+f"(d[44]),"+f"(d[45]),"+f"(d[46]),"+f"(d[47])
    : "r"(a[0]),"r"(a[1]),"r"(a[2]),"r"(a[3]),"l"(desc));
}

__device__ const uint16_t g_sched[132][48] = {
{65535,65535,65535,65535,65535,65535,65535,65535,65535,65535,65535,65535,65535,65535,65535,65535,65535,65535,65535,65535,65535,65535,65535,65535,65535,65535,65535,65535,65535,65535,65535,65535,65535,65535,65535,65535,65535,65535,65535,65535,65535,65535,65535,65535,65535,65535,65535,65535},
{0,12,3665,35,47,59,70,82,94,105,117,129,3779,152,164,176,187,199,211,222,234,246,3893,269,281,293,304,316,328,339,351,363,4008,386,398,410,421,433,445,65535,65535,65535,65535,65535,65535,65535,65535,65535},
{65535,65535,65535,65535,65535,65535,65535,65535,65535,65535,65535,65535,65535,65535,65535,65535,65535,65535,65535,65535,65535,65535,65535,65535,65535,65535,65535,65535,65535,65535,65535,65535,65535,65535,65535,65535,65535,65535,65535,65535,65535,65535,65535,65535,65535,65535,65535,65535},
{456,468,3666,491,503,515,526,538,550,561,573,585,3780,608,620,632,643,655,667,678,690,702,3894,725,737,749,760,772,784,795,807,819,4009,842,854,866,877,889,901,65535,65535,65535,65535,65535,65535,65535,65535,65535},
{65535,65535,65535,65535,65535,65535,65535,65535,65535,65535,65535,65535,65535,65535,65535,65535,65535,65535,65535,65535,65535,65535,65535,65535,65535,65535,65535,65535,65535,65535,65535,65535,65535,65535,65535,65535,65535,65535,65535,65535,65535,65535,65535,65535,65535,65535,65535,65535},
{912,924,3667,947,959,971,982,994,1006,1017,1029,1041,3781,1064,1076,1088,1099,1111,1123,1134,1146,1158,3895,1181,1193,1205,1216,1228,1240,1251,1263,1275,4010,1298,1310,1322,1333,1345,1357,65535,65535,65535,65535,65535,65535,65535,65535,65535},
{65535,65535,65535,65535,65535,65535,65535,65535,65535,65535,65535,65535,65535,65535,65535,65535,65535,65535,65535,65535,65535,65535,65535,65535,65535,65535,65535,65535,65535,65535,65535,65535,65535,65535,65535,65535,65535,65535,65535,65535,65535,65535,65535,65535,65535,65535,65535,65535},
{1368,1380,3668,1403,1415,1427,1438,1450,1462,1473,1485,1497,3782,1520,1532,1544,1555,1567,1579,1590,1602,1614,3896,1637,1649,1661,1672,1684,1696,1707,1719,1731,4011,1754,1766,1778,1789,1801,1813,65535,65535,65535,65535,65535,65535,65535,65535,65535},
{65535,65535,65535,65535,65535,65535,65535,65535,65535,65535,65535,65535,65535,65535,65535,65535,65535,65535,65535,65535,65535,65535,65535,65535,65535,65535,65535,65535,65535,65535,65535,65535,65535,65535,65535,65535,65535,65535,65535,65535,65535,65535,65535,65535,65535,65535,65535,65535},
{1824,1836,3669,1859,1871,1883,1894,1906,1918,1929,1941,1953,3783,1976,1988,2000,2011,2023,2035,2046,2058,2070,3897,2093,2105,2117,2128,2140,2152,2163,2175,2187,4012,2210,2222,2234,2245,2257,2269,65535,65535,65535,65535,65535,65535,65535,65535,65535},
{65535,65535,65535,65535,65535,65535,65535,65535,65535,65535,65535,65535,65535,65535,65535,65535,65535,65535,65535,65535,65535,65535,65535,65535,65535,65535,65535,65535,65535,65535,65535,65535,65535,65535,65535,65535,65535,65535,65535,65535,65535,65535,65535,65535,65535,65535,65535,65535},
{2280,2292,3670,2315,2327,2339,2350,2362,2374,2385,2397,2409,3784,2432,2444,2456,2467,2479,2491,2502,2514,2526,3898,2549,2561,2573,2584,2596,2608,2619,2631,2643,4013,2666,2678,2690,2701,2713,2725,65535,65535,65535,65535,65535,65535,65535,65535,65535},
{65535,65535,65535,65535,65535,65535,65535,65535,65535,65535,65535,65535,65535,65535,65535,65535,65535,65535,65535,65535,65535,65535,65535,65535,65535,65535,65535,65535,65535,65535,65535,65535,65535,65535,65535,65535,65535,65535,65535,65535,65535,65535,65535,65535,65535,65535,65535,65535},
{2736,2748,3671,2771,2783,2795,2806,2818,2830,2841,2853,2865,3785,2888,2900,2912,2923,2935,2947,2958,2970,2982,3899,3005,3017,3029,3040,3052,3064,3075,3087,3099,4014,3122,3134,3146,3157,3169,3181,65535,65535,65535,65535,65535,65535,65535,65535,65535},
{65535,65535,65535,65535,65535,65535,65535,65535,65535,65535,65535,65535,65535,65535,65535,65535,65535,65535,65535,65535,65535,65535,65535,65535,65535,65535,65535,65535,65535,65535,65535,65535,65535,65535,65535,65535,65535,65535,65535,65535,65535,65535,65535,65535,65535,65535,65535,65535},
{3192,3204,3672,3227,3239,3251,3262,3274,3286,3297,3309,3321,3786,3344,3356,3368,3379,3391,3403,3414,3426,3438,3900,3461,3473,3485,3496,3508,3520,3531,3543,3555,4015,3578,3590,3602,3613,3625,3637,65535,65535,65535,65535,65535,65535,65535,65535,65535},
{65535,65535,65535,65535,65535,65535,65535,65535,65535,65535,65535,65535,65535,65535,65535,65535,65535,65535,65535,65535,65535,65535,65535,65535,65535,65535,65535,65535,65535,65535,65535,65535,65535,65535,65535,65535,65535,65535,65535,65535,65535,65535,65535,65535,65535,65535,65535,65535},
{1,13,24,36,48,3700,71,83,95,106,118,130,141,153,165,3814,188,200,212,223,235,247,258,270,282,3929,305,317,329,340,352,364,375,387,399,4043,422,434,446,65535,65535,65535,65535,65535,65535,65535,65535,65535},
{65535,65535,65535,65535,65535,65535,65535,65535,65535,65535,65535,65535,65535,65535,65535,65535,65535,65535,65535,65535,65535,65535,65535,65535,65535,65535,65535,65535,65535,65535,65535,65535,65535,65535,65535,65535,65535,65535,65535,65535,65535,65535,65535,65535,65535,65535,65535,65535},
{457,469,480,492,504,3701,527,539,551,562,574,586,597,609,621,3815,644,656,668,679,691,703,714,726,738,3930,761,773,785,796,808,820,831,843,855,4044,878,890,902,65535,65535,65535,65535,65535,65535,65535,65535,65535},
{65535,65535,65535,65535,65535,65535,65535,65535,65535,65535,65535,65535,65535,65535,65535,65535,65535,65535,65535,65535,65535,65535,65535,65535,65535,65535,65535,65535,65535,65535,65535,65535,65535,65535,65535,65535,65535,65535,65535,65535,65535,65535,65535,65535,65535,65535,65535,65535},
{913,925,936,948,960,3702,983,995,1007,1018,1030,1042,1053,1065,1077,3816,1100,1112,1124,1135,1147,1159,1170,1182,1194,3931,1217,1229,1241,1252,1264,1276,1287,1299,1311,4045,1334,1346,1358,65535,65535,65535,65535,65535,65535,65535,65535,65535},
{65535,65535,65535,65535,65535,65535,65535,65535,65535,65535,65535,65535,65535,65535,65535,65535,65535,65535,65535,65535,65535,65535,65535,65535,65535,65535,65535,65535,65535,65535,65535,65535,65535,65535,65535,65535,65535,65535,65535,65535,65535,65535,65535,65535,65535,65535,65535,65535},
{1369,1381,1392,1404,1416,3703,1439,1451,1463,1474,1486,1498,1509,1521,1533,3817,1556,1568,1580,1591,1603,1615,1626,1638,1650,3932,1673,1685,1697,1708,1720,1732,1743,1755,1767,4046,1790,1802,1814,65535,65535,65535,65535,65535,65535,65535,65535,65535},
{65535,65535,65535,65535,65535,65535,65535,65535,65535,65535,65535,65535,65535,65535,65535,65535,65535,65535,65535,65535,65535,65535,65535,65535,65535,65535,65535,65535,65535,65535,65535,65535,65535,65535,65535,65535,65535,65535,65535,65535,65535,65535,65535,65535,65535,65535,65535,65535},
{1825,1837,1848,1860,1872,3704,1895,1907,1919,1930,1942,1954,1965,1977,1989,3818,2012,2024,2036,2047,2059,2071,2082,2094,2106,3933,2129,2141,2153,2164,2176,2188,2199,2211,2223,4047,2246,2258,2270,65535,65535,65535,65535,65535,65535,65535,65535,65535},
{65535,65535,65535,65535,65535,65535,65535,65535,65535,65535,65535,65535,65535,65535,65535,65535,65535,65535,65535,65535,65535,65535,65535,65535,65535,65535,65535,65535,65535,65535,65535,65535,65535,65535,65535,65535,65535,65535,65535,65535,65535,65535,65535,65535,65535,65535,65535,65535},
{2281,2293,2304,2316,2328,3705,2351,2363,2375,2386,2398,2410,2421,2433,2445,3819,2468,2480,2492,2503,2515,2527,2538,2550,2562,3934,2585,2597,2609,2620,2632,2644,2655,2667,2679,4048,2702,2714,2726,65535,65535,65535,65535,65535,65535,65535,65535,65535},
{65535,65535,65535,65535,65535,65535,65535,65535,65535,65535,65535,65535,65535,65535,65535,65535,65535,65535,65535,65535,65535,65535,65535,65535,65535,65535,65535,65535,65535,65535,65535,65535,65535,65535,65535,65535,65535,65535,65535,65535,65535,65535,65535,65535,65535,65535,65535,65535},
{2737,2749,2760,2772,2784,3706,2807,2819,2831,2842,2854,2866,2877,2889,2901,3820,2924,2936,2948,2959,2971,2983,2994,3006,3018,3935,3041,3053,3065,3076,3088,3100,3111,3123,3135,4049,3158,3170,3182,65535,65535,65535,65535,65535,65535,65535,65535,65535},
{65535,65535,65535,65535,65535,65535,65535,65535,65535,65535,65535,65535,65535,65535,65535,65535,65535,65535,65535,65535,65535,65535,65535,65535,65535,65535,65535,65535,65535,65535,65535,65535,65535,65535,65535,65535,65535,65535,65535,65535,65535,65535,65535,65535,65535,65535,65535,65535},
{3193,3205,3216,3228,3240,3707,3263,3275,3287,3298,3310,3322,3333,3345,3357,3821,3380,3392,3404,3415,3427,3439,3450,3462,3474,3936,3497,3509,3521,3532,3544,3556,3567,3579,3591,4050,3614,3626,3638,65535,65535,65535,65535,65535,65535,65535,65535,65535},
{65535,65535,65535,65535,65535,65535,65535,65535,65535,65535,65535,65535,65535,65535,65535,65535,65535,65535,65535,65535,65535,65535,65535,65535,65535,65535,65535,65535,65535,65535,65535,65535,65535,65535,65535,65535,65535,65535,65535,65535,65535,65535,65535,65535,65535,65535,65535,65535},
{2,14,25,37,49,60,72,84,3735,107,119,131,142,154,166,177,189,201,3850,224,236,248,259,271,283,294,306,318,3964,341,353,365,376,388,400,411,423,435,4078,65535,65535,65535,65535,65535,65535,65535,65535,65535},
{65535,65535,65535,65535,65535,65535,65535,65535,65535,65535,65535,65535,65535,65535,65535,65535,65535,65535,65535,65535,65535,65535,65535,65535,65535,65535,65535,65535,65535,65535,65535,65535,65535,65535,65535,65535,65535,65535,65535,65535,65535,65535,65535,65535,65535,65535,65535,65535},
{458,470,481,493,505,516,528,540,3736,563,575,587,598,610,622,633,645,657,3851,680,692,704,715,727,739,750,762,774,3965,797,809,821,832,844,856,867,879,891,4079,65535,65535,65535,65535,65535,65535,65535,65535,65535},
{65535,65535,65535,65535,65535,65535,65535,65535,65535,65535,65535,65535,65535,65535,65535,65535,65535,65535,65535,65535,65535,65535,65535,65535,65535,65535,65535,65535,65535,65535,65535,65535,65535,65535,65535,65535,65535,65535,65535,65535,65535,65535,65535,65535,65535,65535,65535,65535},
{914,926,937,949,961,972,984,996,3737,1019,1031,1043,1054,1066,1078,1089,1101,1113,3852,1136,1148,1160,1171,1183,1195,1206,1218,1230,3966,1253,1265,1277,1288,1300,1312,1323,1335,1347,4080,65535,65535,65535,65535,65535,65535,65535,65535,65535},
{65535,65535,65535,65535,65535,65535,65535,65535,65535,65535,65535,65535,65535,65535,65535,65535,65535,65535,65535,65535,65535,65535,65535,65535,65535,65535,65535,65535,65535,65535,65535,65535,65535,65535,65535,65535,65535,65535,65535,65535,65535,65535,65535,65535,65535,65535,65535,65535},
{1370,1382,1393,1405,1417,1428,1440,1452,3738,1475,1487,1499,1510,1522,1534,1545,1557,1569,3853,1592,1604,1616,1627,1639,1651,1662,1674,1686,3967,1709,1721,1733,1744,1756,1768,1779,1791,1803,4081,65535,65535,65535,65535,65535,65535,65535,65535,65535},
{65535,65535,65535,65535,65535,65535,65535,65535,65535,65535,65535,65535,65535,65535,65535,65535,65535,65535,65535,65535,65535,65535,65535,65535,65535,65535,65535,65535,65535,65535,65535,65535,65535,65535,65535,65535,65535,65535,65535,65535,65535,65535,65535,65535,65535,65535,65535,65535},
{1826,1838,1849,1861,1873,1884,1896,1908,3739,1931,1943,1955,1966,1978,1990,2001,2013,2025,3854,2048,2060,2072,2083,2095,2107,2118,2130,2142,3968,2165,2177,2189,2200,2212,2224,2235,2247,2259,4082,65535,65535,65535,65535,65535,65535,65535,65535,65535},
{65535,65535,65535,65535,65535,65535,65535,65535,65535,65535,65535,65535,65535,65535,65535,65535,65535,65535,65535,65535,65535,65535,65535,65535,65535,65535,65535,65535,65535,65535,65535,65535,65535,65535,65535,65535,65535,65535,65535,65535,65535,65535,65535,65535,65535,65535,65535,65535},
{2282,2294,2305,2317,2329,2340,2352,2364,3740,2387,2399,2411,2422,2434,2446,2457,2469,2481,3855,2504,2516,2528,2539,2551,2563,2574,2586,2598,3969,2621,2633,2645,2656,2668,2680,2691,2703,2715,4083,65535,65535,65535,65535,65535,65535,65535,65535,65535},
{65535,65535,65535,65535,65535,65535,65535,65535,65535,65535,65535,65535,65535,65535,65535,65535,65535,65535,65535,65535,65535,65535,65535,65535,65535,65535,65535,65535,65535,65535,65535,65535,65535,65535,65535,65535,65535,65535,65535,65535,65535,65535,65535,65535,65535,65535,65535,65535},
{2738,2750,2761,2773,2785,2796,2808,2820,3741,2843,2855,2867,2878,2890,2902,2913,2925,2937,3856,2960,2972,2984,2995,3007,3019,3030,3042,3054,3970,3077,3089,3101,3112,3124,3136,3147,3159,3171,4084,65535,65535,65535,65535,65535,65535,65535,65535,65535},
{65535,65535,65535,65535,65535,65535,65535,65535,65535,65535,65535,65535,65535,65535,65535,65535,65535,65535,65535,65535,65535,65535,65535,65535,65535,65535,65535,65535,65535,65535,65535,65535,65535,65535,65535,65535,65535,65535,65535,65535,65535,65535,65535,65535,65535,65535,65535,65535},
{3194,3206,3217,3229,3241,3252,3264,3276,3742,3299,3311,3323,3334,3346,3358,3369,3381,3393,3857,3416,3428,3440,3451,3463,3475,3486,3498,3510,3971,3533,3545,3557,3568,3580,3592,3603,3615,3627,4085,65535,65535,65535,65535,65535,65535,65535,65535,65535},
{3,3656,26,38,50,61,73,85,96,108,120,3770,143,155,167,178,190,202,213,225,237,3885,260,272,284,295,307,319,330,342,354,3999,377,389,401,412,424,436,447,65535,65535,65535,65535,65535,65535,65535,65535,65535},
{4,15,27,39,3691,62,74,86,97,109,121,132,144,156,3806,179,191,203,214,226,238,249,261,273,3920,296,308,320,331,343,355,366,378,390,4034,413,425,437,448,65535,65535,65535,65535,65535,65535,65535,65535,65535},
{459,3657,482,494,506,517,529,541,552,564,576,3771,599,611,623,634,646,658,669,681,693,3886,716,728,740,751,763,775,786,798,810,4000,833,845,857,868,880,892,903,65535,65535,65535,65535,65535,65535,65535,65535,65535},
{460,471,483,495,3692,518,530,542,553,565,577,588,600,612,3807,635,647,659,670,682,694,705,717,729,3921,752,764,776,787,799,811,822,834,846,4035,869,881,893,904,65535,65535,65535,65535,65535,65535,65535,65535,65535},
{915,3658,938,950,962,973,985,997,1008,1020,1032,3772,1055,1067,1079,1090,1102,1114,1125,1137,1149,3887,1172,1184,1196,1207,1219,1231,1242,1254,1266,4001,1289,1301,1313,1324,1336,1348,1359,65535,65535,65535,65535,65535,65535,65535,65535,65535},
{916,927,939,951,3693,974,986,998,1009,1021,1033,1044,1056,1068,3808,1091,1103,1115,1126,1138,1150,1161,1173,1185,3922,1208,1220,1232,1243,1255,1267,1278,1290,1302,4036,1325,1337,1349,1360,65535,65535,65535,65535,65535,65535,65535,65535,65535},
{1371,3659,1394,1406,1418,1429,1441,1453,1464,1476,1488,3773,1511,1523,1535,1546,1558,1570,1581,1593,1605,3888,1628,1640,1652,1663,1675,1687,1698,1710,1722,4002,1745,1757,1769,1780,1792,1804,1815,65535,65535,65535,65535,65535,65535,65535,65535,65535},
{1372,1383,1395,1407,3694,1430,1442,1454,1465,1477,1489,1500,1512,1524,3809,1547,1559,1571,1582,1594,1606,1617,1629,1641,3923,1664,1676,1688,1699,1711,1723,1734,1746,1758,4037,1781,1793,1805,1816,65535,65535,65535,65535,65535,65535,65535,65535,65535},
{1827,3660,1850,1862,1874,1885,1897,1909,1920,1932,1944,3774,1967,1979,1991,2002,2014,2026,2037,2049,2061,3889,2084,2096,2108,2119,2131,2143,2154,2166,2178,4003,2201,2213,2225,2236,2248,2260,2271,65535,65535,65535,65535,65535,65535,65535,65535,65535},
{1828,1839,1851,1863,3695,1886,1898,1910,1921,1933,1945,1956,1968,1980,3810,2003,2015,2027,2038,2050,2062,2073,2085,2097,3924,2120,2132,2144,2155,2167,2179,2190,2202,2214,4038,2237,2249,2261,2272,65535,65535,65535,65535,65535,65535,65535,65535,65535},
{2283,3661,2306,2318,2330,2341,2353,2365,2376,2388,2400,3775,2423,2435,2447,2458,2470,2482,2493,2505,2517,3890,2540,2552,2564,2575,2587,2599,2610,2622,2634,4004,2657,2669,2681,2692,2704,2716,2727,65535,65535,65535,65535,65535,65535,65535,65535,65535},
{2284,2295,2307,2319,3696,2342,2354,2366,2377,2389,2401,2412,2424,2436,3811,2459,2471,2483,2494,2506,2518,2529,2541,2553,3925,2576,2588,2600,2611,2623,2635,2646,2658,2670,4039,2693,2705,2717,2728,65535,65535,65535,65535,65535,65535,65535,65535,65535},
{65535,65535,65535,65535,65535,65535,65535,65535,65535,65535,65535,65535,65535,65535,65535,65535,65535,65535,65535,65535,65535,65535,65535,65535,65535,65535,65535,65535,65535,65535,65535,65535,65535,65535,65535,65535,65535,65535,65535,65535,65535,65535,65535,65535,65535,65535,65535,65535},
{2739,3662,2762,2774,2786,2797,2809,2821,2832,2844,2856,3776,2879,2891,2903,2914,2926,2938,2949,2961,2973,3891,2996,3008,3020,3031,3043,3055,3066,3078,3090,4005,3113,3125,3137,3148,3160,3172,3183,65535,65535,65535,65535,65535,65535,65535,65535,65535},
{3195,3663,3218,3230,3242,3253,3265,3277,3288,3300,3312,3777,3335,3347,3359,3370,3382,3394,3405,3417,3429,3892,3452,3464,3476,3487,3499,3511,3522,3534,3546,4006,3569,3581,3593,3604,3616,3628,3639,65535,65535,65535,65535,65535,65535,65535,65535,65535},
{3196,3207,3219,3231,3698,3254,3266,3278,3289,3301,3313,3324,3336,3348,3813,3371,3383,3395,3406,3418,3430,3441,3453,3465,3927,3488,3500,3512,3523,3535,3547,3558,3570,3582,4041,3605,3617,3629,3640,65535,65535,65535,65535,65535,65535,65535,65535,65535},
{461,472,484,496,507,519,531,3728,554,566,578,589,601,613,624,636,648,3842,671,683,695,706,718,730,741,753,765,3956,788,800,812,823,835,847,858,870,882,4070,905,65535,65535,65535,65535,65535,65535,65535,65535,65535},
{3649,473,485,497,508,520,532,543,555,567,3763,590,602,614,625,637,649,660,672,684,3877,707,719,731,742,754,766,777,789,801,3991,824,836,848,859,871,883,894,906,65535,65535,65535,65535,65535,65535,65535,65535,65535},
{917,928,940,952,963,975,987,3729,1010,1022,1034,1045,1057,1069,1080,1092,1104,3843,1127,1139,1151,1162,1174,1186,1197,1209,1221,3957,1244,1256,1268,1279,1291,1303,1314,1326,1338,4071,1361,65535,65535,65535,65535,65535,65535,65535,65535,65535},
{3650,929,941,953,964,976,988,999,1011,1023,3764,1046,1058,1070,1081,1093,1105,1116,1128,1140,3878,1163,1175,1187,1198,1210,1222,1233,1245,1257,3992,1280,1292,1304,1315,1327,1339,1350,1362,65535,65535,65535,65535,65535,65535,65535,65535,65535},
{1373,1384,1396,1408,1419,1431,1443,3730,1466,1478,1490,1501,1513,1525,1536,1548,1560,3844,1583,1595,1607,1618,1630,1642,1653,1665,1677,3958,1700,1712,1724,1735,1747,1759,1770,1782,1794,4072,1817,65535,65535,65535,65535,65535,65535,65535,65535,65535},
{3651,1385,1397,1409,1420,1432,1444,1455,1467,1479,3765,1502,1514,1526,1537,1549,1561,1572,1584,1596,3879,1619,1631,1643,1654,1666,1678,1689,1701,1713,3993,1736,1748,1760,1771,1783,1795,1806,1818,65535,65535,65535,65535,65535,65535,65535,65535,65535},
{1829,1840,1852,1864,1875,1887,1899,3731,1922,1934,1946,1957,1969,1981,1992,2004,2016,3845,2039,2051,2063,2074,2086,2098,2109,2121,2133,3959,2156,2168,2180,2191,2203,2215,2226,2238,2250,4073,2273,65535,65535,65535,65535,65535,65535,65535,65535,65535},
{3652,1841,1853,1865,1876,1888,1900,1911,1923,1935,3766,1958,1970,1982,1993,2005,2017,2028,2040,2052,3880,2075,2087,2099,2110,2122,2134,2145,2157,2169,3994,2192,2204,2216,2227,2239,2251,2262,2274,65535,65535,65535,65535,65535,65535,65535,65535,65535},
{2285,2296,2308,2320,2331,2343,2355,3732,2378,2390,2402,2413,2425,2437,2448,2460,2472,3846,2495,2507,2519,2530,2542,2554,2565,2577,2589,3960,2612,2624,2636,2647,2659,2671,2682,2694,2706,4074,2729,65535,65535,65535,65535,65535,65535,65535,65535,65535},
{3653,2297,2309,2321,2332,2344,2356,2367,2379,2391,3767,2414,2426,2438,2449,2461,2473,2484,2496,2508,3881,2531,2543,2555,2566,2578,2590,2601,2613,2625,3995,2648,2660,2672,2683,2695,2707,2718,2730,65535,65535,65535,65535,65535,65535,65535,65535,65535},
{2740,2751,2763,2775,3697,2798,2810,2822,2833,2845,2857,2868,2880,2892,3812,2915,2927,2939,2950,2962,2974,2985,2997,3009,3926,3032,3044,3056,3067,3079,3091,3102,3114,3126,4040,3149,3161,3173,3184,65535,65535,65535,65535,65535,65535,65535,65535,65535},
{2741,2752,2764,2776,2787,2799,2811,3733,2834,2846,2858,2869,2881,2893,2904,2916,2928,3847,2951,2963,2975,2986,2998,3010,3021,3033,3045,3961,3068,3080,3092,3103,3115,3127,3138,3150,3162,4075,3185,65535,65535,65535,65535,65535,65535,65535,65535,65535},
{3197,3208,3220,3232,3243,3255,3267,3734,3290,3302,3314,3325,3337,3349,3360,3372,3384,3848,3407,3419,3431,3442,3454,3466,3477,3489,3501,3962,3524,3536,3548,3559,3571,3583,3594,3606,3618,4076,3641,65535,65535,65535,65535,65535,65535,65535,65535,65535},
{3655,3209,3221,3233,3244,3256,3268,3279,3291,3303,3769,3326,3338,3350,3361,3373,3385,3396,3408,3420,3883,3443,3455,3467,3478,3490,3502,3513,3525,3537,3997,3560,3572,3584,3595,3607,3619,3630,3642,65535,65535,65535,65535,65535,65535,65535,65535,65535},
{462,474,486,3684,509,521,533,544,556,568,579,591,603,3798,626,638,650,661,673,685,696,708,720,3912,743,755,767,778,790,802,813,825,837,4026,860,872,884,895,907,65535,65535,65535,65535,65535,65535,65535,65535,65535},
{463,475,487,498,510,522,3719,545,557,569,580,592,604,615,627,639,3833,662,674,686,697,709,721,732,744,756,3947,779,791,803,814,826,838,849,861,873,4061,896,908,65535,65535,65535,65535,65535,65535,65535,65535,65535},
{918,930,942,3685,965,977,989,1000,1012,1024,1035,1047,1059,3799,1082,1094,1106,1117,1129,1141,1152,1164,1176,3913,1199,1211,1223,1234,1246,1258,1269,1281,1293,4027,1316,1328,1340,1351,1363,65535,65535,65535,65535,65535,65535,65535,65535,65535},
{919,931,943,954,966,978,3720,1001,1013,1025,1036,1048,1060,1071,1083,1095,3834,1118,1130,1142,1153,1165,1177,1188,1200,1212,3948,1235,1247,1259,1270,1282,1294,1305,1317,1329,4062,1352,1364,65535,65535,65535,65535,65535,65535,65535,65535,65535},
{1374,1386,1398,3686,1421,1433,1445,1456,1468,1480,1491,1503,1515,3800,1538,1550,1562,1573,1585,1597,1608,1620,1632,3914,1655,1667,1679,1690,1702,1714,1725,1737,1749,4028,1772,1784,1796,1807,1819,65535,65535,65535,65535,65535,65535,65535,65535,65535},
{1375,1387,1399,1410,1422,1434,3721,1457,1469,1481,1492,1504,1516,1527,1539,1551,3835,1574,1586,1598,1609,1621,1633,1644,1656,1668,3949,1691,1703,1715,1726,1738,1750,1761,1773,1785,4063,1808,1820,65535,65535,65535,65535,65535,65535,65535,65535,65535},
{1830,1842,1854,3687,1877,1889,1901,1912,1924,1936,1947,1959,1971,3801,1994,2006,2018,2029,2041,2053,2064,2076,2088,3915,2111,2123,2135,2146,2158,2170,2181,2193,2205,4029,2228,2240,2252,2263,2275,65535,65535,65535,65535,65535,65535,65535,65535,65535},
{1831,1843,1855,1866,1878,1890,3722,1913,1925,1937,1948,1960,1972,1983,1995,2007,3836,2030,2042,2054,2065,2077,2089,2100,2112,2124,3950,2147,2159,2171,2182,2194,2206,2217,2229,2241,4064,2264,2276,65535,65535,65535,65535,65535,65535,65535,65535,65535},
{2286,2298,2310,3688,2333,2345,2357,2368,2380,2392,2403,2415,2427,3802,2450,2462,2474,2485,2497,2509,2520,2532,2544,3916,2567,2579,2591,2602,2614,2626,2637,2649,2661,4030,2684,2696,2708,2719,2731,65535,65535,65535,65535,65535,65535,65535,65535,65535},
{2287,2299,2311,2322,2334,2346,3723,2369,2381,2393,2404,2416,2428,2439,2451,2463,3837,2486,2498,2510,2521,2533,2545,2556,2568,2580,3951,2603,2615,2627,2638,2650,2662,2673,2685,2697,4065,2720,2732,65535,65535,65535,65535,65535,65535,65535,65535,65535},
{3654,2753,2765,2777,2788,2800,2812,2823,2835,2847,3768,2870,2882,2894,2905,2917,2929,2940,2952,2964,3882,2987,2999,3011,3022,3034,3046,3057,3069,3081,3996,3104,3116,3128,3139,3151,3163,3174,3186,65535,65535,65535,65535,65535,65535,65535,65535,65535},
{2742,2754,2766,3689,2789,2801,2813,2824,2836,2848,2859,2871,2883,3803,2906,2918,2930,2941,2953,2965,2976,2988,3000,3917,3023,3035,3047,3058,3070,3082,3093,3105,3117,4031,3140,3152,3164,3175,3187,65535,65535,65535,65535,65535,65535,65535,65535,65535},
{3198,3210,3222,3690,3245,3257,3269,3280,3292,3304,3315,3327,3339,3804,3362,3374,3386,3397,3409,3421,3432,3444,3456,3918,3479,3491,3503,3514,3526,3538,3549,3561,3573,4032,3596,3608,3620,3631,3643,65535,65535,65535,65535,65535,65535,65535,65535,65535},
{3199,3211,3223,3234,3246,3258,3725,3281,3293,3305,3316,3328,3340,3351,3363,3375,3839,3398,3410,3422,3433,3445,3457,3468,3480,3492,3953,3515,3527,3539,3550,3562,3574,3585,3597,3609,4067,3632,3644,65535,65535,65535,65535,65535,65535,65535,65535,65535},
{464,476,488,499,511,523,534,546,558,3754,581,593,605,616,628,640,651,663,675,3868,698,710,722,733,745,757,768,780,792,3982,815,827,839,850,862,874,885,897,909,65535,65535,65535,65535,65535,65535,65535,65535,65535},
{465,477,3675,500,512,524,535,547,559,570,582,594,3789,617,629,641,652,664,676,687,699,711,3903,734,746,758,769,781,793,804,816,828,4017,851,863,875,886,898,910,65535,65535,65535,65535,65535,65535,65535,65535,65535},
{920,932,944,955,967,979,990,1002,1014,3755,1037,1049,1061,1072,1084,1096,1107,1119,1131,3869,1154,1166,1178,1189,1201,1213,1224,1236,1248,3983,1271,1283,1295,1306,1318,1330,1341,1353,1365,65535,65535,65535,65535,65535,65535,65535,65535,65535},
{921,933,3676,956,968,980,991,1003,1015,1026,1038,1050,3790,1073,1085,1097,1108,1120,1132,1143,1155,1167,3904,1190,1202,1214,1225,1237,1249,1260,1272,1284,4018,1307,1319,1331,1342,1354,1366,65535,65535,65535,65535,65535,65535,65535,65535,65535},
{1376,1388,1400,1411,1423,1435,1446,1458,1470,3756,1493,1505,1517,1528,1540,1552,1563,1575,1587,3870,1610,1622,1634,1645,1657,1669,1680,1692,1704,3984,1727,1739,1751,1762,1774,1786,1797,1809,1821,65535,65535,65535,65535,65535,65535,65535,65535,65535},
{1377,1389,3677,1412,1424,1436,1447,1459,1471,1482,1494,1506,3791,1529,1541,1553,1564,1576,1588,1599,1611,1623,3905,1646,1658,1670,1681,1693,1705,1716,1728,1740,4019,1763,1775,1787,1798,1810,1822,65535,65535,65535,65535,65535,65535,65535,65535,65535},
{1832,1844,1856,1867,1879,1891,1902,1914,1926,3757,1949,1961,1973,1984,1996,2008,2019,2031,2043,3871,2066,2078,2090,2101,2113,2125,2136,2148,2160,3985,2183,2195,2207,2218,2230,2242,2253,2265,2277,65535,65535,65535,65535,65535,65535,65535,65535,65535},
{1833,1845,3678,1868,1880,1892,1903,1915,1927,1938,1950,1962,3792,1985,1997,2009,2020,2032,2044,2055,2067,2079,3906,2102,2114,2126,2137,2149,2161,2172,2184,2196,4020,2219,2231,2243,2254,2266,2278,65535,65535,65535,65535,65535,65535,65535,65535,65535},
{2288,2300,2312,2323,2335,2347,2358,2370,2382,3758,2405,2417,2429,2440,2452,2464,2475,2487,2499,3872,2522,2534,2546,2557,2569,2581,2592,2604,2616,3986,2639,2651,2663,2674,2686,2698,2709,2721,2733,65535,65535,65535,65535,65535,65535,65535,65535,65535},
{2289,2301,3679,2324,2336,2348,2359,2371,2383,2394,2406,2418,3793,2441,2453,2465,2476,2488,2500,2511,2523,2535,3907,2558,2570,2582,2593,2605,2617,2628,2640,2652,4021,2675,2687,2699,2710,2722,2734,65535,65535,65535,65535,65535,65535,65535,65535,65535},
{2743,2755,2767,2778,2790,2802,3724,2825,2837,2849,2860,2872,2884,2895,2907,2919,3838,2942,2954,2966,2977,2989,3001,3012,3024,3036,3952,3059,3071,3083,3094,3106,3118,3129,3141,3153,4066,3176,3188,65535,65535,65535,65535,65535,65535,65535,65535,65535},
{2744,2756,2768,2779,2791,2803,2814,2826,2838,3759,2861,2873,2885,2896,2908,2920,2931,2943,2955,3873,2978,2990,3002,3013,3025,3037,3048,3060,3072,3987,3095,3107,3119,3130,3142,3154,3165,3177,3189,65535,65535,65535,65535,65535,65535,65535,65535,65535},
{3200,3212,3224,3235,3247,3259,3270,3282,3294,3760,3317,3329,3341,3352,3364,3376,3387,3399,3411,3874,3434,3446,3458,3469,3481,3493,3504,3516,3528,3988,3551,3563,3575,3586,3598,3610,3621,3633,3645,65535,65535,65535,65535,65535,65535,65535,65535,65535},
{3201,3213,3681,3236,3248,3260,3271,3283,3295,3306,3318,3330,3795,3353,3365,3377,3388,3400,3412,3423,3435,3447,3909,3470,3482,3494,3505,3517,3529,3540,3552,3564,4023,3587,3599,3611,3622,3634,3646,65535,65535,65535,65535,65535,65535,65535,65535,65535},
{466,478,489,501,513,3710,536,548,560,571,583,595,606,618,630,3824,653,665,677,688,700,712,723,735,747,3938,770,782,794,805,817,829,840,852,864,4053,887,899,911,65535,65535,65535,65535,65535,65535,65535,65535,65535},
{467,479,490,502,514,525,537,549,3745,572,584,596,607,619,631,642,654,666,3859,689,701,713,724,736,748,759,771,783,3974,806,818,830,841,853,865,876,888,900,4088,65535,65535,65535,65535,65535,65535,65535,65535,65535},
{922,934,945,957,969,3711,992,1004,1016,1027,1039,1051,1062,1074,1086,3825,1109,1121,1133,1144,1156,1168,1179,1191,1203,3939,1226,1238,1250,1261,1273,1285,1296,1308,1320,4054,1343,1355,1367,65535,65535,65535,65535,65535,65535,65535,65535,65535},
{923,935,946,958,970,981,993,1005,3746,1028,1040,1052,1063,1075,1087,1098,1110,1122,3860,1145,1157,1169,1180,1192,1204,1215,1227,1239,3975,1262,1274,1286,1297,1309,1321,1332,1344,1356,4089,65535,65535,65535,65535,65535,65535,65535,65535,65535},
{1378,1390,1401,1413,1425,3712,1448,1460,1472,1483,1495,1507,1518,1530,1542,3826,1565,1577,1589,1600,1612,1624,1635,1647,1659,3940,1682,1694,1706,1717,1729,1741,1752,1764,1776,4055,1799,1811,1823,65535,65535,65535,65535,65535,65535,65535,65535,65535},
{1379,1391,1402,1414,1426,1437,1449,1461,3747,1484,1496,1508,1519,1531,1543,1554,1566,1578,3861,1601,1613,1625,1636,1648,1660,1671,1683,1695,3976,1718,1730,1742,1753,1765,1777,1788,1800,1812,4090,65535,65535,65535,65535,65535,65535,65535,65535,65535},
{1834,1846,1857,1869,1881,3713,1904,1916,1928,1939,1951,1963,1974,1986,1998,3827,2021,2033,2045,2056,2068,2080,2091,2103,2115,3941,2138,2150,2162,2173,2185,2197,2208,2220,2232,4056,2255,2267,2279,65535,65535,65535,65535,65535,65535,65535,65535,65535},
{1835,1847,1858,1870,1882,1893,1905,1917,3748,1940,1952,1964,1975,1987,1999,2010,2022,2034,3862,2057,2069,2081,2092,2104,2116,2127,2139,2151,3977,2174,2186,2198,2209,2221,2233,2244,2256,2268,4091,65535,65535,65535,65535,65535,65535,65535,65535,65535},
{2290,2302,2313,2325,2337,3714,2360,2372,2384,2395,2407,2419,2430,2442,2454,3828,2477,2489,2501,2512,2524,2536,2547,2559,2571,3942,2594,2606,2618,2629,2641,2653,2664,2676,2688,4057,2711,2723,2735,65535,65535,65535,65535,65535,65535,65535,65535,65535},
{2291,2303,2314,2326,2338,2349,2361,2373,3749,2396,2408,2420,2431,2443,2455,2466,2478,2490,3863,2513,2525,2537,2548,2560,2572,2583,2595,2607,3978,2630,2642,2654,2665,2677,2689,2700,2712,2724,4092,65535,65535,65535,65535,65535,65535,65535,65535,65535},
{2745,2757,3680,2780,2792,2804,2815,2827,2839,2850,2862,2874,3794,2897,2909,2921,2932,2944,2956,2967,2979,2991,3908,3014,3026,3038,3049,3061,3073,3084,3096,3108,4022,3131,3143,3155,3166,3178,3190,65535,65535,65535,65535,65535,65535,65535,65535,65535},
{2746,2758,2769,2781,2793,3715,2816,2828,2840,2851,2863,2875,2886,2898,2910,3829,2933,2945,2957,2968,2980,2992,3003,3015,3027,3943,3050,3062,3074,3085,3097,3109,3120,3132,3144,4058,3167,3179,3191,65535,65535,65535,65535,65535,65535,65535,65535,65535},
{3202,3214,3225,3237,3249,3716,3272,3284,3296,3307,3319,3331,3342,3354,3366,3830,3389,3401,3413,3424,3436,3448,3459,3471,3483,3944,3506,3518,3530,3541,3553,3565,3576,3588,3600,4059,3623,3635,3647,65535,65535,65535,65535,65535,65535,65535,65535,65535},
{3203,3215,3226,3238,3250,3261,3273,3285,3751,3308,3320,3332,3343,3355,3367,3378,3390,3402,3865,3425,3437,3449,3460,3472,3484,3495,3507,3519,3980,3542,3554,3566,3577,3589,3601,3612,3624,3636,4094,65535,65535,65535,65535,65535,65535,65535,65535,65535},
{65535,65535,65535,65535,65535,65535,65535,65535,65535,65535,65535,65535,65535,65535,65535,65535,65535,65535,65535,65535,65535,65535,65535,65535,65535,65535,65535,65535,65535,65535,65535,65535,65535,65535,65535,65535,65535,65535,65535,65535,65535,65535,65535,65535,65535,65535,65535,65535},
{2747,2759,2770,2782,2794,2805,2817,2829,3750,2852,2864,2876,2887,2899,2911,2922,2934,2946,3864,2969,2981,2993,3004,3016,3028,3039,3051,3063,3979,3086,3098,3110,3121,3133,3145,3156,3168,3180,4093,65535,65535,65535,65535,65535,65535,65535,65535,65535},
{65535,65535,65535,65535,65535,65535,65535,65535,65535,65535,65535,65535,65535,65535,65535,65535,65535,65535,65535,65535,65535,65535,65535,65535,65535,65535,65535,65535,65535,65535,65535,65535,65535,65535,65535,65535,65535,65535,65535,65535,65535,65535,65535,65535,65535,65535,65535,65535},
{3664,3673,3682,3699,3708,3717,3726,3743,3752,3761,3778,3787,3796,3805,3822,3831,3840,3849,3866,3875,3884,3901,3910,3919,3928,3945,3954,3963,3972,3989,3998,4007,4024,4033,4042,4051,4068,4077,4086,4095,65535,65535,65535,65535,65535,65535,65535,65535},
{5,16,28,40,51,63,75,3727,98,110,122,133,145,157,168,180,192,3841,215,227,239,250,262,274,285,297,309,3955,332,344,356,367,379,391,402,414,426,4069,449,65535,65535,65535,65535,65535,65535,65535,65535,65535},
{3648,17,29,41,52,64,76,87,99,111,3762,134,146,158,169,181,193,204,216,228,3876,251,263,275,286,298,310,321,333,345,3990,368,380,392,403,415,427,438,450,65535,65535,65535,65535,65535,65535,65535,65535,65535},
{6,18,30,3683,53,65,77,88,100,112,123,135,147,3797,170,182,194,205,217,229,240,252,264,3911,287,299,311,322,334,346,357,369,381,4025,404,416,428,439,451,65535,65535,65535,65535,65535,65535,65535,65535,65535},
{7,19,31,42,54,66,3718,89,101,113,124,136,148,159,171,183,3832,206,218,230,241,253,265,276,288,300,3946,323,335,347,358,370,382,393,405,417,4060,440,452,65535,65535,65535,65535,65535,65535,65535,65535,65535},
{8,20,32,43,55,67,78,90,102,3753,125,137,149,160,172,184,195,207,219,3867,242,254,266,277,289,301,312,324,336,3981,359,371,383,394,406,418,429,441,453,65535,65535,65535,65535,65535,65535,65535,65535,65535},
{9,21,3674,44,56,68,79,91,103,114,126,138,3788,161,173,185,196,208,220,231,243,255,3902,278,290,302,313,325,337,348,360,372,4016,395,407,419,430,442,454,65535,65535,65535,65535,65535,65535,65535,65535,65535},
{10,22,33,45,57,3709,80,92,104,115,127,139,150,162,174,3823,197,209,221,232,244,256,267,279,291,3937,314,326,338,349,361,373,384,396,408,4052,431,443,455,65535,65535,65535,65535,65535,65535,65535,65535,65535},
{11,23,34,46,58,69,81,93,3744,116,128,140,151,163,175,186,198,210,3858,233,245,257,268,280,292,303,315,327,3973,350,362,374,385,397,409,420,432,444,4087,65535,65535,65535,65535,65535,65535,65535,65535,65535},
};

#define NG 9
#define RING 16
#define NSLOT 8
#define CFETCH 5
#define TABLED 1
#define PROMO CU_TENSOR_MAP_L2_PROMOTION_L2_128B
#define TRIG 2
constexpr int NCONV = 3 * NG;
constexpr int PLEN = (1024 + NG - 1) / NG;
constexpr int TILEB = 12288;
constexpr int SLOTB = 280 * 64;
constexpr int W1S = 0, W2S = 73728, ABUF = 147456, MISC = ABUF + 16 * 3072;
constexpr int CTAB = NSLOT * SLOTB + 512;
constexpr int SMEM_BYTES = MISC + 512 + 1024 + 32;
static_assert(CTAB + (PLEN + 12) * 16 <= MISC, "conv smem");

__device__ __align__(1024) unsigned char g_scratch[(RING * NG + 1) * 4 * TILEB];
__device__ uint32_t g_ready[1024];
__device__ uint32_t g_cons[1024 + 32];
__device__ unsigned long long g_start;

#define PROF_AT(cond, idx)
#define PROF_VAL(cond, idx, v)
#define GELU_C3 0.32920349f
#define GELU_A2 0x40d940d9u
#define SPIN_LIMIT 0x1000000

__device__ __forceinline__ uint32_t smem_u32(const void* p) { return (uint32_t)__cvta_generic_to_shared(p); }
__device__ __forceinline__ void wg_fence() { asm volatile("wgmma.fence.sync.aligned;" ::: "memory"); }
__device__ __forceinline__ void wg_commit() { asm volatile("wgmma.commit_group.sync.aligned;" ::: "memory"); }
template <int N> __device__ __forceinline__ void wg_wait() { asm volatile("wgmma.wait_group.sync.aligned %0;" ::"n"(N) : "memory"); }
__device__ __forceinline__ void mbar_init(uint32_t bar, uint32_t cnt) { asm volatile("mbarrier.init.shared::cta.b64 [%0], %1;" ::"r"(bar), "r"(cnt) : "memory"); }
__device__ __forceinline__ void mbar_expect_tx(uint32_t bar, uint32_t bytes) { asm volatile("mbarrier.arrive.expect_tx.shared::cta.b64 _, [%0], %1;" ::"r"(bar), "r"(bytes) : "memory"); }
__device__ __forceinline__ void mbar_arrive(uint32_t bar) { asm volatile("mbarrier.arrive.shared::cta.b64 _, [%0];" ::"r"(bar) : "memory"); }
__device__ __forceinline__ void mbar_wait(uint32_t bar, uint32_t parity) {
  asm volatile("{\n.reg .pred p;\n.reg .u32 c;\nmbarrier.try_wait.parity.shared::cta.b64 p, [%0], %1;\n@p bra DONE_%=;\nmov.u32 c, 0;\nWAIT_%=:\nmbarrier.try_wait.parity.shared::cta.b64 p, [%0], %1;\n@p bra DONE_%=;\n"
               "add.u32 c, c, 1;\nsetp.lt.u32 p, c, 0x1000000;\n@p bra WAIT_%=;\ntrap;\nDONE_%=:\n}" ::"r"(bar), "r"(parity) : "memory");
}
__device__ __forceinline__ void bulk_g2s(uint32_t dst, const void* src, uint32_t bytes, uint32_t bar) {
  asm volatile("cp.async.bulk.shared::cluster.global.mbarrier::complete_tx::bytes [%0], [%1], %2, [%3];" ::"r"(dst), "l"(src), "r"(bytes), "r"(bar) : "memory");
}
__device__ __forceinline__ uint32_t ld_relaxed(const uint32_t* p) { uint32_t v; asm volatile("ld.relaxed.gpu.global.u32 %0, [%1];" : "=r"(v) : "l"(p) : "memory"); return v; }
__device__ __forceinline__ void red_add(uint32_t* p) { asm volatile("red.relaxed.gpu.global.add.u32 [%0], 1;" ::"l"(p) : "memory"); }
__device__ __forceinline__ void lds128(uint32_t* r, uint32_t a) { asm volatile("ld.shared.v4.b32 {%0,%1,%2,%3}, [%4];" : "=r"(r[0]), "=r"(r[1]), "=r"(r[2]), "=r"(r[3]) : "r"(a) : "memory"); }
__device__ __forceinline__ uint2 lds64(uint32_t a) { uint2 v; asm volatile("ld.shared.v2.b32 {%0,%1}, [%2];" : "=r"(v.x), "=r"(v.y) : "r"(a) : "memory"); return v; }
__device__ __forceinline__ uint32_t lds32(uint32_t a) { uint32_t v; asm volatile("ld.shared.b32 %0, [%1];" : "=r"(v) : "r"(a) : "memory"); return v; }
__device__ __forceinline__ void sts32(uint32_t a, uint32_t v) { asm volatile("st.shared.b32 [%0], %1;" ::"r"(a), "r"(v) : "memory"); }
__device__ __forceinline__ void sts128(uint32_t a, uint4 v) { asm volatile("st.shared.v4.b32 [%0], {%1,%2,%3,%4};" ::"r"(a), "r"(v.x), "r"(v.y), "r"(v.z), "r"(v.w) : "memory"); }
__device__ __forceinline__ uint4 ldg128v(const void* p) { uint4 v; asm volatile("ld.global.nc.v4.b32 {%0,%1,%2,%3}, [%4];" : "=r"(v.x), "=r"(v.y), "=r"(v.z), "=r"(v.w) : "l"(p) : "memory"); return v; }
__device__ __forceinline__ void stg128(void* p, uint4 v) { asm volatile("st.global.v4.b32 [%0], {%1,%2,%3,%4};" ::"l"(p), "r"(v.x), "r"(v.y), "r"(v.z), "r"(v.w) : "memory"); }
#define HINT 3
__device__ __forceinline__ uint64_t pol_evict_first() { uint64_t p; asm("createpolicy.fractional.L2::evict_first.b64 %0, 1.0;" : "=l"(p)); return p; }
__device__ __forceinline__ uint4 ldg128_last(const void* p, uint64_t pol) {
  if (!(HINT & 1)) return ldg128v(p);
  uint4 v; asm volatile("ld.global.nc.L1::no_allocate.L2::cache_hint.v4.b32 {%0,%1,%2,%3}, [%4], %5;" : "=r"(v.x), "=r"(v.y), "=r"(v.z), "=r"(v.w) : "l"(p), "l"(pol) : "memory"); return v;
}
__device__ __forceinline__ void stg128_stream(void* p, uint4 v, uint64_t pol) {
  if (!(HINT & 2)) { stg128(p, v); return; }
  asm volatile("st.global.L2::cache_hint.v4.b32 [%0], {%1,%2,%3,%4}, %5;" ::"l"(p), "r"(v.x), "r"(v.y), "r"(v.z), "r"(v.w), "l"(pol) : "memory");
}
__device__ __forceinline__ float bf_lo(uint32_t w) { return __uint_as_float(w << 16); }
__device__ __forceinline__ float bf_hi(uint32_t w) { return __uint_as_float(w & 0xffff0000u); }
__device__ __forceinline__ uint32_t pack_f16(float lo, float hi) { uint32_t d; asm("cvt.rn.f16x2.f32 %0, %1, %2;" : "=r"(d) : "f"(hi), "f"(lo)); return d; }
__device__ __forceinline__ uint32_t pack_f16_sat(float lo, float hi) { uint32_t d; asm("cvt.rn.satfinite.f16x2.f32 %0, %1, %2;" : "=r"(d) : "f"(hi), "f"(lo)); return d; }
__device__ __forceinline__ uint32_t pack_bf16(float lo, float hi) { uint32_t d; asm("cvt.rn.bf16x2.f32 %0, %1, %2;" : "=r"(d) : "f"(hi), "f"(lo)); return d; }
__device__ __forceinline__ uint32_t hadd2_bf16(uint32_t a, uint32_t b) { uint32_t d; asm("add.rn.bf16x2 %0, %1, %2;" : "=r"(d) : "r"(a), "r"(b)); return d; }
__device__ __forceinline__ uint32_t h2add(uint32_t a, uint32_t b) { uint32_t d; asm("add.rn.f16x2 %0, %1, %2;" : "=r"(d) : "r"(a), "r"(b)); return d; }
__device__ __forceinline__ uint32_t h2mul(uint32_t a, uint32_t b) { uint32_t d; asm("mul.rn.f16x2 %0, %1, %2;" : "=r"(d) : "r"(a), "r"(b)); return d; }
__device__ __forceinline__ uint32_t h2fma(uint32_t a, uint32_t b, uint32_t c) { uint32_t d; asm("fma.rn.f16x2 %0, %1, %2, %3;" : "=r"(d) : "r"(a), "r"(b), "r"(c)); return d; }
__device__ __forceinline__ uint32_t h2lo(uint32_t a) { uint32_t d; asm("{.reg .f16 l,h; mov.b32 {l,h}, %1; mov.b32 %0, {l,l};}" : "=r"(d) : "r"(a)); return d; }
__device__ __forceinline__ uint32_t h2hi(uint32_t a) { uint32_t d; asm("{.reg .f16 l,h; mov.b32 {l,h}, %1; mov.b32 %0, {h,h};}" : "=r"(d) : "r"(a)); return d; }
__device__ __forceinline__ float h_lo(uint32_t a) { float d; asm("{.reg .f16 l,h; mov.b32 {l,h}, %1; cvt.f32.f16 %0, l;}" : "=f"(d) : "r"(a)); return d; }
__device__ __forceinline__ float h_hi(uint32_t a) { float d; asm("{.reg .f16 l,h; mov.b32 {l,h}, %1; cvt.f32.f16 %0, h;}" : "=f"(d) : "r"(a)); return d; }
__device__ __forceinline__ uint32_t prmt(uint32_t a, uint32_t b, uint32_t s) { uint32_t d; asm("prmt.b32 %0, %1, %2, %3;" : "=r"(d) : "r"(a), "r"(b), "r"(s)); return d; }
__device__ __forceinline__ void mma_sp(float* d, const uint32_t* a, const uint32_t* b, const float* c, uint32_t e) {
  asm("mma.sp::ordered_metadata.sync.aligned.m16n8k32.row.col.f32.bf16.bf16.f32 {%0,%1,%2,%3}, {%4,%5,%6,%7}, {%8,%9,%10,%11}, {%12,%13,%14,%15}, %16, 0;"
      : "=f"(d[0]), "=f"(d[1]), "=f"(d[2]), "=f"(d[3])
      : "r"(a[0]), "r"(a[1]), "r"(a[2]), "r"(a[3]), "r"(b[0]), "r"(b[1]), "r"(b[2]), "r"(b[3]), "f"(c[0]), "f"(c[1]), "f"(c[2]), "f"(c[3]), "r"(e));
}
__device__ __forceinline__ uint32_t bf2_to_h2(uint32_t w, float s) { return pack_f16(bf_lo(w) * s, bf_hi(w) * s); }
__device__ __forceinline__ uint32_t bf2_to_h2(uint32_t w) { return pack_f16(bf_lo(w), bf_hi(w)); }

__device__ __forceinline__ uint32_t gelu_h2(uint32_t y) {
  uint32_t t, u, th, g;
  asm volatile("fma.rn.f16x2 %0, %1, %1, %2;" : "=r"(t) : "r"(y), "r"(GELU_A2));
  asm volatile("mul.rn.f16x2 %0, %1, %2;" : "=r"(u) : "r"(y), "r"(t));
  asm volatile("tanh.approx.f16x2 %0, %1;" : "=r"(th) : "r"(u));
  asm volatile("fma.rn.f16x2 %0, %1, %2, %1;" : "=r"(g) : "r"(y), "r"(th));
  return g;
}

__device__ __forceinline__ void prep_weights(uint32_t sb, const __nv_bfloat16* __restrict__ w1, const __nv_bfloat16* __restrict__ w2, int warp, int lane) {
  const int k0 = lane & 7, lq = lane >> 3;
  uint4 v[9], u[3][4];
#pragma unroll
  for (int i = 0; i < 9; i++) {
    int it = warp * 9 + i, nbq = it % 12, skh = it / 12, kh = skh & 1, s = skh >> 1;
    int ch = 16 * s + 4 * (k0 >> 1) + 2 * kh + (k0 & 1);
    v[i] = __ldg((const uint4*)(w1 + ch * 384 + (nbq * 4 + lq) * 8));
  }
#pragma unroll
  for (int i = 0; i < 3; i++) {
    int it = warp + 16 * i;
    if (it < 36) {
      int un = it * 4 + lq, j = un % 3, h8 = un / 3;
      const uint4* p = (const uint4*)(w2 + (h8 * 8 + k0) * 96 + j * 32);
#pragma unroll
      for (int q = 0; q < 4; q++) u[i][q] = __ldg(p + q);
    }
  }
#pragma unroll
  for (int i = 0; i < 9; i++) {
    int it = warp * 9 + i, nbq = it % 12, skh = it / 12, kh = skh & 1, s = skh >> 1;
    sts128(sb + W1S + s * 12288 + (nbq * 4 + lq) * 256 + kh * 128 + k0 * 16, make_uint4(bf2_to_h2(v[i].x), bf2_to_h2(v[i].y), bf2_to_h2(v[i].z), bf2_to_h2(v[i].w)));
  }
  const float sc = 0.5f / GELU_C3;
#pragma unroll
  for (int i = 0; i < 3; i++) {
    int it = warp + 16 * i;
    if (it < 36) {
      int un = it * 4 + lq, j = un % 3, h8 = un / 3;
      uint32_t base = sb + W2S + (h8 >> 1) * 3072 + (j * 4) * 256 + (h8 & 1) * 128 + k0 * 16;
      sts128(base, make_uint4(bf2_to_h2(u[i][0].x, sc), bf2_to_h2(u[i][1].x, sc), bf2_to_h2(u[i][2].x, sc), bf2_to_h2(u[i][3].x, sc)));
      sts128(base + 256, make_uint4(bf2_to_h2(u[i][0].y, sc), bf2_to_h2(u[i][1].y, sc), bf2_to_h2(u[i][2].y, sc), bf2_to_h2(u[i][3].y, sc)));
      sts128(base + 512, make_uint4(bf2_to_h2(u[i][0].z, sc), bf2_to_h2(u[i][1].z, sc), bf2_to_h2(u[i][2].z, sc), bf2_to_h2(u[i][3].z, sc)));
      sts128(base + 768, make_uint4(bf2_to_h2(u[i][0].w, sc), bf2_to_h2(u[i][1].w, sc), bf2_to_h2(u[i][2].w, sc), bf2_to_h2(u[i][3].w, sc)));
    }
  }
}

__device__ __noinline__ void ln_wide(uint32_t ad) {
  float m[2], r[2];
#pragma unroll
  for (int hi = 0; hi < 2; hi++) {
    float sm = 0.f;
    for (int s = 0; s < 6; s++) { uint2 w = lds64(ad + s * 512 + hi * 8); sm += (h_lo(w.x) + h_hi(w.x)) + (h_lo(w.y) + h_hi(w.y)); }
    sm += __shfl_xor_sync(0xffffffffu, sm, 1); sm += __shfl_xor_sync(0xffffffffu, sm, 2);
    m[hi] = sm * (1.f / 96.f);
    float q = 0.f;
    for (int s = 0; s < 6; s++) {
      uint2 w = lds64(ad + s * 512 + hi * 8);
      float d0 = h_lo(w.x) - m[hi], d1 = h_hi(w.x) - m[hi], d2 = h_lo(w.y) - m[hi], d3 = h_hi(w.y) - m[hi];
      q += (d0 * d0 + d1 * d1) + (d2 * d2 + d3 * d3);
    }
    q += __shfl_xor_sync(0xffffffffu, q, 1); q += __shfl_xor_sync(0xffffffffu, q, 2);
    r[hi] = rsqrtf(fmaf(q, 1.f / 96.f, 1e-5f)) * GELU_C3;
  }
  for (int s = 0; s < 6; s++) {
    uint32_t w[4]; lds128(w, ad + s * 512);
    sts128(ad + s * 512, make_uint4(pack_f16((h_lo(w[0]) - m[0]) * r[0], (h_hi(w[0]) - m[0]) * r[0]), pack_f16((h_lo(w[2]) - m[1]) * r[1], (h_hi(w[2]) - m[1]) * r[1]),
                                    pack_f16((h_lo(w[1]) - m[0]) * r[0], (h_hi(w[1]) - m[0]) * r[0]), pack_f16((h_lo(w[3]) - m[1]) * r[1], (h_hi(w[3]) - m[1]) * r[1])));
  }
  asm volatile("fence.proxy.async.shared::cta;" ::: "memory");
}

__device__ __forceinline__ void load_ln(uint32_t ad, uint32_t* a) {
  uint32_t raw[6][4];
#pragma unroll
  for (int s = 0; s < 6; s++) lds128(raw[s], ad + s * 512);
  uint32_t sm[2];
#pragma unroll
  for (int hi = 0; hi < 2; hi++) {
    uint32_t s0 = h2add(raw[0][2 * hi], raw[1][2 * hi]), s1 = h2add(raw[0][2 * hi + 1], raw[1][2 * hi + 1]);
    uint32_t s2 = h2add(raw[2][2 * hi], raw[3][2 * hi]), s3 = h2add(raw[2][2 * hi + 1], raw[3][2 * hi + 1]);
    uint32_t s4 = h2add(raw[4][2 * hi], raw[5][2 * hi]), s5 = h2add(raw[4][2 * hi + 1], raw[5][2 * hi + 1]);
    sm[hi] = h2add(h2add(h2add(s0, s1), h2add(s2, s3)), h2add(s4, s5));
  }
  uint32_t s = h2add(prmt(sm[0], sm[1], 0x5410), prmt(sm[0], sm[1], 0x7632));
  s = h2add(s, __shfl_xor_sync(0xffffffffu, s, 1));
  s = h2add(s, __shfl_xor_sync(0xffffffffu, s, 2));
  const uint32_t nm = h2mul(s, 0xA155A155u);
  uint32_t qq[2];
#pragma unroll
  for (int hi = 0; hi < 2; hi++) {
    const uint32_t m = hi ? h2hi(nm) : h2lo(nm);
    uint32_t q0 = 0, q1 = 0;
#pragma unroll
    for (int k = 0; k < 6; k++) {
      uint32_t d0 = h2add(raw[k][2 * hi], m), d1 = h2add(raw[k][2 * hi + 1], m);
      raw[k][2 * hi] = d0; raw[k][2 * hi + 1] = d1;
      q0 = k ? h2fma(d0, d0, q0) : h2mul(d0, d0);
      q1 = k ? h2fma(d1, d1, q1) : h2mul(d1, d1);
    }
    qq[hi] = h2add(q0, q1);
  }
  uint32_t q = h2add(prmt(qq[0], qq[1], 0x5410), prmt(qq[0], qq[1], 0x7632));
  q = h2add(q, __shfl_xor_sync(0xffffffffu, q, 1));
  q = h2add(q, __shfl_xor_sync(0xffffffffu, q, 2));
  const float r0 = rsqrtf(fmaf(h_lo(q), 1.f / 96.f, 1e-5f)) * GELU_C3, r1 = rsqrtf(fmaf(h_hi(q), 1.f / 96.f, 1e-5f)) * GELU_C3;
  const uint32_t r = pack_f16(r0, r1);
#pragma unroll
  for (int k = 0; k < 6; k++) {
    a[4 * k] = h2mul(raw[k][0], h2lo(r)); a[4 * k + 2] = h2mul(raw[k][1], h2lo(r));
    a[4 * k + 1] = h2mul(raw[k][2], h2hi(r)); a[4 * k + 3] = h2mul(raw[k][3], h2hi(r));
  }
  const bool bad = (((q & 0x7c007c00u) + 0x04000400u) & 0x80008000u) != 0;
  if (__any_sync(0xffffffffu, bad)) {
    ln_wide(ad);
#pragma unroll
    for (int k = 0; k < 6; k++) lds128(a + 4 * k, ad + k * 512);
  }
}

__device__ __forceinline__ void gemm1(uint32_t* p, const uint32_t* a, uint64_t d1, int c) {
  wgmma_n48_f16<0>(p, a, d1 + c * (1536 >> 4));
#pragma unroll
  for (int s = 1; s < 6; s++) wgmma_n48_f16<1>(p, a + 4 * s, d1 + c * (1536 >> 4) + s * (12288 >> 4));
}

__device__ __forceinline__ uint32_t tile_sofs(int n) {
  const int P = n >> 2, gm = P / PLEN, j = P - gm * PLEN;
  return (((j & (RING - 1)) * NG + gm) * 4 + (n & 3)) * TILEB;
}
__device__ __forceinline__ void fetch_slice(uint32_t abuf, uint32_t bar, uint32_t sofs, int lane) {
  if (lane == 0) {
    asm volatile("fence.acquire.gpu;" ::: "memory");
    asm volatile("fence.proxy.async.global;" ::: "memory");
    mbar_expect_tx(bar, 3072);
    bulk_g2s(abuf, g_scratch + sofs, 3072, bar);
  }
}
__device__ __forceinline__ void wait_ready(int L, uint32_t target) {
  int spins = 0;
  while (ld_relaxed(&g_ready[L]) != target) { __nanosleep(64); if (++spins > SPIN_LIMIT) __trap(); }
}

__device__ __forceinline__ void mlp_role(uint32_t sb, const __nv_bfloat16* __restrict__ x, const __nv_bfloat16* __restrict__ w1, const __nv_bfloat16* __restrict__ w2,
                                         __nv_bfloat16* __restrict__ out, int idx, bool tabled, int warp, int lane) {
  const int wg = warp >> 2, g = lane >> 2, t = lane & 3;
  const uint32_t abuf = sb + ABUF + warp * 3072;
  const uint32_t bar = sb + MISC + warp * 8;
  const uint32_t tl = sb + MISC + 512;
  if (threadIdx.x >= 256) {
    const int k = threadIdx.x - 256;
    int n = -1;
    if (tabled) { if (k < 48) n = (int16_t)g_sched[idx][k]; }
    else {
      const int i = k * (gridDim.x - NCONV) + idx, full = (1024 - (NG - 1) * PLEN) * NG;
      const int r = i >> 2, j = r < full ? r / NG : (r - full) / (NG - 1) + full / NG, gm = r < full ? r % NG : (r - full) % (NG - 1);
      if (i < 4096) n = (gm * PLEN + j) * 4 + (i & 3);
    }
    sts32(tl + k * 4, n);
  }
  if (lane == 0) { mbar_init(bar, 1); asm volatile("fence.mbarrier_init.release.cluster;" ::: "memory"); }
  if (threadIdx.x == 0) sts32(sb + MISC + 256, (uint32_t)(atomicAdd(&g_start, 1ULL) / gridDim.x) + 1);
  prep_weights(sb, w1, w2, warp, lane);
  asm volatile("fence.proxy.async.shared::cta;" ::: "memory");
  __syncthreads();
  PROF_AT(threadIdx.x == 0, 1);
  const uint32_t rtarget = 3 * lds32(sb + MISC + 256);
  const uint64_t dbase = ((uint64_t)(128 >> 4) << 16) | ((uint64_t)(256 >> 4) << 32);
  const uint64_t d1 = dbase | (uint64_t)(((sb + W1S) >> 4) & 0x3fff);
  const uint64_t d2 = dbase | (uint64_t)(((sb + W2S) >> 4) & 0x3fff);
  const uint32_t ad = abuf + t * 128 + ((g ^ (2 * t)) << 4);
  const int pofs = (16 * (g & 3) + 2 * (warp & 3) + (g >> 2)) * 192 + t * 16;
  const int mybar = 1 + wg, nxtbar = 1 + ((wg + 1) & 3);
  uint32_t ph = 0;
  bool pending = true;
  const uint64_t pol = pol_evict_first();
  uint32_t tp = tl + wg * 4;
  for (int n = lds32(tp); n >= 0; tp += 16, n = lds32(tp)) {
    PROF_AT((threadIdx.x & 127) == 0, 16 + (tp - tl)); PROF_VAL((threadIdx.x & 127) == 0, 16 + (tp - tl) + 3, pending);
    if (pending) { wait_ready(n >> 2, rtarget); fetch_slice(abuf, bar, tile_sofs(n) + (warp & 3) * 3072, lane); }
    uint32_t a[24], p[8][12], gg[8][12];
    float acc[48];
    mbar_wait(bar, ph); ph ^= 1;
    PROF_AT((threadIdx.x & 127) == 0, 16 + (tp - tl) + 1);
    if (lane == 0) red_add(&g_cons[n >> 2]);
    load_ln(ad, a);
    const size_t gofs = (size_t)((n & 1020) * 256 + (n >> 10) * 128 + (n & 1) * 64 + (n & 2) * 4) * 192 + pofs;
    uint32_t rdy = 0;
    uint4 xr[2][3];
    if (tp != tl) asm volatile("bar.sync %0, 256;" ::"r"(mybar) : "memory");
    PROF_AT((threadIdx.x & 127) == 0, 16 + (tp - tl) + 2);
    wg_fence();
    gemm1(p[0], a, d1, 0); wg_commit();
#pragma unroll
    for (int c = 0; c < 8; c++) {
      wg_wait<0>();
      if (c == TRIG) asm volatile("{.reg .pred p; setp.ge.s32 p, %1, 0; @p bar.arrive %0, 256;}" ::"r"(nxtbar), "r"(lds32(tp + 4)) : "memory");
      if (c == CFETCH - 1) rdy = ld_relaxed(&g_ready[(lds32(tp + 16) >> 2) & 1023]);
      if (c == CFETCH) {
        pending = (rdy != rtarget);
        const int nn = lds32(tp + 16);
        if (!pending && nn >= 0) fetch_slice(abuf, bar, tile_sofs(nn) + (warp & 3) * 3072, lane);
      }
      if (c == 7) {
#pragma unroll
        for (int hi = 0; hi < 2; hi++)
#pragma unroll
          for (int j = 0; j < 3; j++) xr[hi][j] = ldg128_last((const char*)x + gofs + hi * (512 * 192) + j * 64, pol);
      }
#pragma unroll
      for (int s = 0; s < 3; s++) {
#pragma unroll
        for (int i = 0; i < 4; i++) gg[c][4 * s + i] = gelu_h2(p[c][4 * s + i]);
        wg_fence();
        if (c == 0 && s == 0) wgmma_n96_f32<0>(acc, gg[c], d2); else wgmma_n96_f32<1>(acc, &gg[c][4 * s], d2 + (c * 3 + s) * (3072 >> 4));
      }
      if (c + 1 < 8) gemm1(p[c + 1], a, d1, c + 1);
      wg_commit();
    }
    wg_wait<0>();
#pragma unroll
    for (int hi = 0; hi < 2; hi++)
#pragma unroll
      for (int j = 0; j < 3; j++) {
        uint4 o;
        o.x = hadd2_bf16(xr[hi][j].x, pack_bf16(acc[(4 * j + 0) * 4 + 2 * hi], acc[(4 * j + 0) * 4 + 2 * hi + 1]));
        o.y = hadd2_bf16(xr[hi][j].y, pack_bf16(acc[(4 * j + 1) * 4 + 2 * hi], acc[(4 * j + 1) * 4 + 2 * hi + 1]));
        o.z = hadd2_bf16(xr[hi][j].z, pack_bf16(acc[(4 * j + 2) * 4 + 2 * hi], acc[(4 * j + 2) * 4 + 2 * hi + 1]));
        o.w = hadd2_bf16(xr[hi][j].w, pack_bf16(acc[(4 * j + 3) * 4 + 2 * hi], acc[(4 * j + 3) * 4 + 2 * hi + 1]));
        stg128_stream((char*)out + gofs + hi * (512 * 192) + j * 64, o, pol);
      }
  }
  PROF_AT((threadIdx.x & 127) == 0, 4 + wg);
}

__device__ __forceinline__ void conv_compute(uint32_t sb, const __nv_bfloat16* __restrict__ dw, int third, int nit, int warp, int lane) {
  const int g = lane >> 2, t = lane & 3;
  const uint32_t full = sb + MISC;
  uint32_t A[4][4][4];
  {
    uint2 w[2][9];
#pragma unroll
    for (int h = 0; h < 2; h++) {
      const int j = (4 * h + t - g) & 7;
      w[h][0] = make_uint2(0u, 0u); w[h][8] = make_uint2(0u, 0u);
#pragma unroll
      for (int i = 0; i < 7; i++) {
        w[h][i + 1] = make_uint2(0u, 0u);
        if (j < 7) w[h][i + 1] = __ldg((const uint2*)(dw + (i * 7 + j) * 96 + third * 32 + warp * 4));
      }
    }
#pragma unroll
    for (int u = 0; u < 4; u++)
#pragma unroll
      for (int r = 0; r < 4; r++) {
        const int h = r >> 1, i0 = 2 * u - (r & 1) + 1;
        A[0][u][r] = prmt(w[h][i0].x, w[h][i0 + 1].x, 0x5410); A[1][u][r] = prmt(w[h][i0].x, w[h][i0 + 1].x, 0x7632);
        A[2][u][r] = prmt(w[h][i0].y, w[h][i0 + 1].y, 0x5410); A[3][u][r] = prmt(w[h][i0].y, w[h][i0 + 1].y, 0x7632);
      }
  }
  uint32_t meta = 0;
#pragma unroll
  for (int a = 0; a < 4; a++) meta |= ((4 * (t & 1) + a + 1 >= g) ? 0x80008u : 0xD000Du) << (4 * a);
  meta = __shfl_sync(0xffffffffu, meta, lane);
  float S[2][4][3][4];
#pragma unroll
  for (int s = 0; s < 2; s++)
#pragma unroll
    for (int c = 0; c < 4; c++)
#pragma unroll
      for (int i = 0; i < 3; i++)
#pragma unroll
        for (int k = 0; k < 4; k++) S[s][c][i][k] = 0.f;
  uint32_t aq[4];
#pragma unroll
  for (int q = 0; q < 4; q++) {
    const int pp = (g & 1) * 140 + (t & 1) * 70 + 16 * (g >> 1) + 2 * q + (t >> 1);
    aq[q] = __shfl_sync(0xffffffffu, sb + pp * 64 + (((warp >> 1) ^ ((pp >> 1) & 3)) << 4) + (warp & 1) * 8, lane);
  }
  const int Q = third * 8 + warp;
  unsigned char* const obase = g_scratch + (g >> 1) * 3072 + Q * 128 + (((4 * (g & 1) + t) ^ (2 * (Q & 3))) << 4);
  const float zero4[4] = {0.f, 0.f, 0.f, 0.f};
  uint32_t sofs = 0, bar = full, ph = 0;
  uint2 X[3][4];
  mbar_wait(bar, 0);
#pragma unroll
  for (int j = 0; j < 2; j++)
#pragma unroll
    for (int q = 0; q < 4; q++) X[j][q] = lds64(aq[q] + j * 512);
  for (uint32_t ot = sb + CTAB; ot < sb + CTAB + nit * 16; ot += 16) {
    PROF_AT(threadIdx.x == 0 && ((ot - sb - CTAB) & 112) == 0, 16 + ((ot - sb - CTAB) >> 4));
    unsigned char* const o = obase + lds32(ot);
    const uint32_t dbar = bar + 64 + ph * 64;
#pragma unroll
    for (int s = 0; s < 2; s++) {
      uint32_t B[4][4];
      if (s == 1) {
        sofs += SLOTB; bar += 8;
        if (sofs == NSLOT * SLOTB) { sofs = 0; bar = full; ph ^= 1; }
        mbar_wait(bar, ph);
      }
#pragma unroll
      for (int c = 0; c < 4; c++)
#pragma unroll
        for (int q = 0; q < 4; q++) B[c][q] = prmt(c < 2 ? X[s][q].x : X[s][q].y, c < 2 ? X[s + 1][q].x : X[s + 1][q].y, (c & 1) ? 0x7632 : 0x5410);
      if (s == 0) {
#pragma unroll
        for (int q = 0; q < 4; q++) X[2][q] = lds64(aq[q] + sofs + 2 * 512);
      } else {
#pragma unroll
        for (int j = 0; j < 2; j++)
#pragma unroll
          for (int q = 0; q < 4; q++) X[j][q] = lds64(aq[q] + sofs + j * 512);
      }
      float T[4][4];
#pragma unroll
      for (int c = 0; c < 4; c++) mma_sp(T[c], A[c][3], B[c], S[s][c][2], meta);
#pragma unroll
      for (int c = 0; c < 4; c++) mma_sp(S[s][c][2], A[c][2], B[c], S[s][c][1], meta);
      stg128(o + (2 * s) * TILEB, make_uint4(pack_f16_sat(T[0][0], T[1][0]), pack_f16_sat(T[2][0], T[3][0]), pack_f16_sat(T[0][2], T[1][2]), pack_f16_sat(T[2][2], T[3][2])));
      stg128(o + (2 * s + 1) * TILEB, make_uint4(pack_f16_sat(T[0][1], T[1][1]), pack_f16_sat(T[2][1], T[3][1]), pack_f16_sat(T[0][3], T[1][3]), pack_f16_sat(T[2][3], T[3][3])));
#pragma unroll
      for (int c = 0; c < 4; c++) mma_sp(S[s][c][1], A[c][1], B[c], S[s][c][0], meta);
#pragma unroll
      for (int c = 0; c < 4; c++) mma_sp(S[s][c][0], A[c][0], B[c], zero4, meta);
    }
    asm volatile("{.reg .pred p; elect.sync _|p, 0xffffffff; @p mbarrier.arrive.shared::cta.b64 _, [%0];}" ::"r"(dbar) : "memory");
  }
  PROF_AT(threadIdx.x == 0, 4);
}

__device__ __forceinline__ void conv_loader(uint32_t sb, const CUtensorMap* tmx, int P0, int nit, int third, int lane) {
  const uint32_t full = sb + MISC;
  uint32_t ctarget = 0;
  int credit = P0 + RING;
  for (int it = 0; it <= nit; it++) {
    const int s = it & (NSLOT - 1);
    uint32_t e[4];
    lds128(e, sb + CTAB + it * 16);
    if (it >= NSLOT) {
      mbar_wait(full + 64 + ((it - NSLOT) & 15) * 8, ((it - NSLOT) >> 4) & 1);
      int spins = 0;
      while ((int)lds32(full + 192 + (it & 3) * 4) < it - 15) { __nanosleep(64); if (++spins > SPIN_LIMIT) __trap(); }
      if (it == NSLOT) {
        if (lane == 0) ctarget = 16 * ((uint32_t)(atomicAdd(&g_start, 1ULL) / gridDim.x) + 1);
        ctarget = __shfl_sync(0xffffffffu, ctarget, 0);
      }
      if ((int)e[1] >= credit) {
        spins = 0;
        while (true) {
          const uint32_t ok = __ballot_sync(0xffffffffu, ld_relaxed(&g_cons[credit - RING + lane]) == ctarget);
          const int got = __ffs(~ok) - 1;
          credit += got < 0 ? 32 : got;
          if ((int)e[1] < credit) break;
          __nanosleep(64); if (++spins > SPIN_LIMIT) __trap();
        }
        asm volatile("fence.acquire.gpu;" ::: "memory");
      }
    }
    asm volatile("{\n.reg .pred p;\n.reg .s32 c2;\n.reg .u32 d2;\nelect.sync _|p, 0xffffffff;\nadd.s32 c2, %4, 64;\nadd.u32 d2, %0, 8960;\n"
                 "@p mbarrier.arrive.expect_tx.shared::cta.b64 _, [%2], 17920;\n"
                 "@p cp.async.bulk.tensor.3d.shared::cluster.global.mbarrier::complete_tx::bytes [%0], [%1, {%3, %4, %5}], [%2];\n"
                 "@p cp.async.bulk.tensor.3d.shared::cluster.global.mbarrier::complete_tx::bytes [d2], [%1, {%3, c2, %5}], [%2];\n}"
                 ::"r"(sb + s * SLOTB), "l"(tmx), "r"(full + s * 8), "r"(third * 32), "r"(e[2]), "r"(e[3]) : "memory");
  }
}

__device__ __forceinline__ void conv_publisher(uint32_t sb, int nit, int k, int lane) {
  for (int it = k; it < nit; it += 4) {
    const int P = (int)lds32(sb + CTAB + it * 16 + 4);
    mbar_wait(sb + MISC + 64 + (it & 15) * 8, (it >> 4) & 1);
    if (lane == 0) {
      sts32(sb + MISC + 192 + k * 4, it + 1);
      if (P >= 0) {
        asm volatile("fence.release.gpu;" ::: "memory");
        red_add(&g_ready[P]);
        PROF_AT((it & 7) == 0 || it < 8, 200 + it);
      }
    }
    __syncwarp();
  }
}

__global__ void __launch_bounds__(512, 1) convnext_kernel(const __grid_constant__ CUtensorMap tmx, const __nv_bfloat16* __restrict__ x, const __nv_bfloat16* __restrict__ dw,
                                                          const __nv_bfloat16* __restrict__ w1, const __nv_bfloat16* __restrict__ w2, __nv_bfloat16* __restrict__ out) {
  extern __shared__ __align__(1024) unsigned char smem[];
  const uint32_t sb = smem_u32(smem);
  const int warp = __shfl_sync(0xffffffffu, threadIdx.x >> 5, 0), lane = threadIdx.x & 31;
  PROF_AT(threadIdx.x == 0, 0);
  uint32_t smid, nsmid;
  asm volatile("mov.u32 %0, %%smid;" : "=r"(smid));
  asm volatile("mov.u32 %0, %%nsmid;" : "=r"(nsmid));
  const bool tabled = TABLED && NG == 9 && gridDim.x == 132 && nsmid == 132;
  int cidx, idx;
  bool is_conv;
  if (tabled) {
    idx = smid;
    is_conv = (smid < 48 && !(smid & 1)) || smid == 60 || smid == 120 || smid == 122;
    cidx = smid < 48 ? ((smid >> 1) & 7) * 3 + (smid >> 4) : smid == 60 ? 26 : 24 + ((smid >> 1) & 1);
  } else {
    cidx = (blockIdx.x * NCONV) / gridDim.x;
    is_conv = ((blockIdx.x + 1) * NCONV) / gridDim.x != cidx;
    idx = blockIdx.x - cidx;
  }
  PROF_VAL(threadIdx.x == 0, 2, is_conv ? 1000 + cidx : idx);
  if (!is_conv) {
    mlp_role(sb, x, w1, w2, out, idx, tabled, warp, lane);
  } else {
    const int gm = cidx / 3, third = cidx - gm * 3;
    const int P0 = gm * PLEN, P1 = min(P0 + PLEN, 1024) - 1;
    const int Vs = P0 + 2 * (P0 >> 8) + ((P0 & 255) ? 0 : 1);
    const int nit = P1 + 2 * (P1 >> 8) + 4 - Vs;
    if (threadIdx.x == 0) {
      for (int s = 0; s < NSLOT; s++) { mbar_init(sb + MISC + s * 8, 1); mbar_init(sb + MISC + 64 + s * 8, 8); mbar_init(sb + MISC + 128 + s * 8, 8); }
      sts128(sb + MISC + 192, make_uint4(0, 0, 0, 0));
      asm volatile("fence.mbarrier_init.release.cluster;" ::: "memory");
    }
    if (threadIdx.x >= 256 && threadIdx.x - 256 <= nit) {
      const int it = threadIdx.x - 256, V = Vs + it;
      const int st = (V - 1) / 258, so = max(V - 3, 0) / 258, po = V - 3 - so * 258, P = so * 256 + po;
      const bool ok = po < 256 && P >= P0 && P <= P1;
      sts128(sb + CTAB + it * 16, make_uint4((ok ? ((P - P0) & (RING - 1)) * NG + gm : RING * NG) * (4 * TILEB), ok ? P : -1, st * 128 - 3, 2 * (V - st * 258) - 3));
    }
    __syncthreads();
    if (warp < 8) {
      asm volatile("setmaxnreg.inc.sync.aligned.u32 224;");
      conv_compute(sb, dw, third, nit, warp, lane);
    } else if (warp >= 12) {
      asm volatile("setmaxnreg.dec.sync.aligned.u32 24;");
      conv_publisher(sb, nit, warp - 12, lane);
    } else {
      asm volatile("setmaxnreg.dec.sync.aligned.u32 40;");
      if (warp == 8) conv_loader(sb, &tmx, P0, nit, third, lane);
    }
  }
}

typedef CUresult (*PFN_encodeTiled)(CUtensorMap*, CUtensorMapDataType, cuuint32_t, void*, const cuuint64_t*, const cuuint64_t*, const cuuint32_t*, const cuuint32_t*,
                                    CUtensorMapInterleave, CUtensorMapSwizzle, CUtensorMapL2promotion, CUtensorMapFloatOOBfill);

extern "C" void kernel_launch(void* const* d_in, const int* in_sizes, int n_in, void* d_out, int out_size) {
  const __nv_bfloat16* x = (const __nv_bfloat16*)d_in[0];
  const __nv_bfloat16* dw = (const __nv_bfloat16*)d_in[1];
  const __nv_bfloat16* w1 = (const __nv_bfloat16*)d_in[2];
  const __nv_bfloat16* w2 = (const __nv_bfloat16*)d_in[3];
  static PFN_encodeTiled encode = nullptr;
  static int nsm = 0;
  if (!encode) {
    void* fn = nullptr; cudaDriverEntryPointQueryResult qr;
    cudaGetDriverEntryPoint("cuTensorMapEncodeTiled", &fn, cudaEnableDefault, &qr);
    encode = (PFN_encodeTiled)fn;
    int dev = 0; cudaGetDevice(&dev);
    cudaDeviceGetAttribute(&nsm, cudaDevAttrMultiProcessorCount, dev);
    cudaFuncSetAttribute(convnext_kernel, cudaFuncAttributeMaxDynamicSharedMemorySize, SMEM_BYTES);
  }
  CUtensorMap tm;
  cuuint64_t dims[3] = {96, 512, 512}, strides[2] = {192, 192 * 512};
  cuuint32_t box[3] = {32, 70, 2}, es[3] = {1, 1, 1};
  encode(&tm, CU_TENSOR_MAP_DATA_TYPE_BFLOAT16, 3, (void*)x, dims, strides, box, es, CU_TENSOR_MAP_INTERLEAVE_NONE, CU_TENSOR_MAP_SWIZZLE_64B,
         PROMO, CU_TENSOR_MAP_FLOAT_OOB_FILL_NONE);
  convnext_kernel<<<nsm, 512, SMEM_BYTES>>>(tm, x, dw, w1, w2, (__nv_bfloat16*)d_out);
}
```

```cpp
#include <cuda_runtime.h>
#include <cuda_bf16.h>
#include <cuda.h>
#include <stdint.h>

template<int SCALE_D> __device__ __forceinline__ void wgmma_n48_f16(uint32_t* d, const uint32_t* a, uint64_t desc) {
  if (SCALE_D == 0) asm volatile("wgmma.mma_async.sync.aligned.m64n48k16.f16.f16.f16 {%0,%1,%2,%3,%4,%5,%6,%7,%8,%9,%10,%11}, {%12,%13,%14,%15}, %16, 0, 1, 1, 1;"
    : "=r"(d[0]),"=r"(d[1]),"=r"(d[2]),"=r"(d[3]),"=r"(d[4]),"=r"(d[5]),"=r"(d[6]),"=r"(d[7]),"=r"(d[8]),"=r"(d[9]),"=r"(d[10]),"=r"(d[11])
    : "r"(a[0]),"r"(a[1]),"r"(a[2]),"r"(a[3]),"l"(desc));
  if (SCALE_D == 1) asm volatile("wgmma.mma_async.sync.aligned.m64n48k16.f16.f16.f16 {%0,%1,%2,%3,%4,%5,%6,%7,%8,%9,%10,%11}, {%12,%13,%14,%15}, %16, 1, 1, 1, 1;"
    : "+r"(d[0]),"+r"(d[1]),"+r"(d[2]),"+r"(d[3]),"+r"(d[4]),"+r"(d[5]),"+r"(d[6]),"+r"(d[7]),"+r"(d[8]),"+r"(d[9]),"+r"(d[10]),"+r"(d[11])
    : "r"(a[0]),"r"(a[1]),"r"(a[2]),"r"(a[3]),"l"(desc));
}

template<int SCALE_D> __device__ __forceinline__ void wgmma_n96_f16(uint32_t* d, const uint32_t* a, uint64_t desc) {
  if (SCALE_D == 0) asm volatile("wgmma.mma_async.sync.aligned.m64n96k16.f16.f16.f16 {%0,%1,%2,%3,%4,%5,%6,%7,%8,%9,%10,%11,%12,%13,%14,%15,%16,%17,%18,%19,%20,%21,%22,%23}, {%24,%25,%26,%27}, %28, 0, 1, 1, 1;"
    : "=r"(d[0]),"=r"(d[1]),"=r"(d[2]),"=r"(d[3]),"=r"(d[4]),"=r"(d[5]),"=r"(d[6]),"=r"(d[7]),"=r"(d[8]),"=r"(d[9]),"=r"(d[10]),"=r"(d[11]),"=r"(d[12]),"=r"(d[13]),"=r"(d[14]),"=r"(d[15]),"=r"(d[16]),"=r"(d[17]),"=r"(d[18]),"=r"(d[19]),"=r"(d[20]),"=r"(d[21]),"=r"(d[22]),"=r"(d[23])
    : "r"(a[0]),"r"(a[1]),"r"(a[2]),"r"(a[3]),"l"(desc));
  if (SCALE_D == 1) asm volatile("wgmma.mma_async.sync.aligned.m64n96k16.f16.f16.f16 {%0,%1,%2,%3,%4,%5,%6,%7,%8,%9,%10,%11,%12,%13,%14,%15,%16,%17,%18,%19,%20,%21,%22,%23}, {%24,%25,%26,%27}, %28, 1, 1, 1, 1;"
    : "+r"(d[0]),"+r"(d[1]),"+r"(d[2]),"+r"(d[3]),"+r"(d[4]),"+r"(d[5]),"+r"(d[6]),"+r"(d[7]),"+r"(d[8]),"+r"(d[9]),"+r"(d[10]),"+r"(d[11]),"+r"(d[12]),"+r"(d[13]),"+r"(d[14]),"+r"(d[15]),"+r"(d[16]),"+r"(d[17]),"+r"(d[18]),"+r"(d[19]),"+r"(d[20]),"+r"(d[21]),"+r"(d[22]),"+r"(d[23])
    : "r"(a[0]),"r"(a[1]),"r"(a[2]),"r"(a[3]),"l"(desc));
}

__device__ const uint16_t g_sched[132][48] = {
{65535,65535,65535,65535,65535,65535,65535,65535,65535,65535,65535,65535,65535,65535,65535,65535,65535,65535,65535,65535,65535,65535,65535,65535,65535,65535,65535,65535,65535,65535,65535,65535,65535,65535,65535,65535,65535,65535,65535,65535,65535,65535,65535,65535,65535,65535,65535,65535},
{0,12,3665,35,47,59,70,82,94,105,117,129,3779,152,164,176,187,199,211,222,234,246,3893,269,281,293,304,316,328,339,351,363,4008,386,398,410,421,433,445,65535,65535,65535,65535,65535,65535,65535,65535,65535},
{65535,65535,65535,65535,65535,65535,65535,65535,65535,65535,65535,65535,65535,65535,65535,65535,65535,65535,65535,65535,65535,65535,65535,65535,65535,65535,65535,65535,65535,65535,65535,65535,65535,65535,65535,65535,65535,65535,65535,65535,65535,65535,65535,65535,65535,65535,65535,65535},
{456,468,3666,491,503,515,526,538,550,561,573,585,3780,608,620,632,643,655,667,678,690,702,3894,725,737,749,760,772,784,795,807,819,4009,842,854,866,877,889,901,65535,65535,65535,65535,65535,65535,65535,65535,65535},
{65535,65535,65535,65535,65535,65535,65535,65535,65535,65535,65535,65535,65535,65535,65535,65535,65535,65535,65535,65535,65535,65535,65535,65535,65535,65535,65535,65535,65535,65535,65535,65535,65535,65535,65535,65535,65535,65535,65535,65535,65535,65535,65535,65535,65535,65535,65535,65535},
{912,924,3667,947,959,971,982,994,1006,1017,1029,1041,3781,1064,1076,1088,1099,1111,1123,1134,1146,1158,3895,1181,1193,1205,1216,1228,1240,1251,1263,1275,4010,1298,1310,1322,1333,1345,1357,65535,65535,65535,65535,65535,65535,65535,65535,65535},
{65535,65535,65535,65535,65535,65535,65535,65535,65535,65535,65535,65535,65535,65535,65535,65535,65535,65535,65535,65535,65535,65535,65535,65535,65535,65535,65535,65535,65535,65535,65535,65535,65535,65535,65535,65535,65535,65535,65535,65535,65535,65535,65535,65535,65535,65535,65535,65535},
{1368,1380,3668,1403,1415,1427,1438,1450,1462,1473,1485,1497,3782,1520,1532,1544,1555,1567,1579,1590,1602,1614,3896,1637,1649,1661,1672,1684,1696,1707,1719,1731,4011,1754,1766,1778,1789,1801,1813,65535,65535,65535,65535,65535,65535,65535,65535,65535},
{65535,65535,65535,65535,65535,65535,65535,65535,65535,65535,65535,65535,65535,65535,65535,65535,65535,65535,65535,65535,65535,65535,65535,65535,65535,65535,65535,65535,65535,65535,65535,65535,65535,65535,65535,65535,65535,65535,65535,65535,65535,65535,65535,65535,65535,65535,65535,65535},
{1824,1836,3669,1859,1871,1883,1894,1906,1918,1929,1941,1953,3783,1976,1988,2000,2011,2023,2035,2046,2058,2070,3897,2093,2105,2117,2128,2140,2152,2163,2175,2187,4012,2210,2222,2234,2245,2257,2269,65535,65535,65535,65535,65535,65535,65535,65535,65535},
{65535,65535,65535,65535,65535,65535,65535,65535,65535,65535,65535,65535,65535,65535,65535,65535,65535,65535,65535,65535,65535,65535,65535,65535,65535,65535,65535,65535,65535,65535,65535,65535,65535,65535,65535,65535,65535,65535,65535,65535,65535,65535,65535,65535,65535,65535,65535,65535},
{2280,2292,3670,2315,2327,2339,2350,2362,2374,2385,2397,2409,3784,2432,2444,2456,2467,2479,2491,2502,2514,2526,3898,2549,2561,2573,2584,2596,2608,2619,2631,2643,4013,2666,2678,2690,2701,2713,2725,65535,65535,65535,65535,65535,65535,65535,65535,65535},
{65535,65535,65535,65535,65535,65535,65535,65535,65535,65535,65535,65535,65535,65535,65535,65535,65535,65535,65535,65535,65535,65535,65535,65535,65535,65535,65535,65535,65535,65535,65535,65535,65535,65535,65535,65535,65535,65535,65535,65535,65535,65535,65535,65535,65535,65535,65535,65535},
{2736,2748,3671,2771,2783,2795,2806,2818,2830,2841,2853,2865,3785,2888,2900,2912,2923,2935,2947,2958,2970,2982,3899,3005,3017,3029,3040,3052,3064,3075,3087,3099,4014,3122,3134,3146,3157,3169,3181,65535,65535,65535,65535,65535,65535,65535,65535,65535},
{65535,65535,65535,65535,65535,65535,65535,65535,65535,65535,65535,65535,65535,65535,65535,65535,65535,65535,65535,65535,65535,65535,65535,65535,65535,65535,65535,65535,65535,65535,65535,65535,65535,65535,65535,65535,65535,65535,65535,65535,65535,65535,65535,65535,65535,65535,65535,65535},
{3192,3204,3672,3227,3239,3251,3262,3274,3286,3297,3309,3321,3786,3344,3356,3368,3379,3391,3403,3414,3426,3438,3900,3461,3473,3485,3496,3508,3520,3531,3543,3555,4015,3578,3590,3602,3613,3625,3637,65535,65535,65535,65535,65535,65535,65535,65535,65535},
{65535,65535,65535,65535,65535,65535,65535,65535,65535,65535,65535,65535,65535,65535,65535,65535,65535,65535,65535,65535,65535,65535,65535,65535,65535,65535,65535,65535,65535,65535,65535,65535,65535,65535,65535,65535,65535,65535,65535,65535,65535,65535,65535,65535,65535,65535,65535,65535},
{1,13,24,36,48,3700,71,83,95,106,118,130,141,153,165,3814,188,200,212,223,235,247,258,270,282,3929,305,317,329,340,352,364,375,387,399,4043,422,434,446,65535,65535,65535,65535,65535,65535,65535,65535,65535},
{65535,65535,65535,65535,65535,65535,65535,65535,65535,65535,65535,65535,65535,65535,65535,65535,65535,65535,65535,65535,65535,65535,65535,65535,65535,65535,65535,65535,65535,65535,65535,65535,65535,65535,65535,65535,65535,65535,65535,65535,65535,65535,65535,65535,65535,65535,65535,65535},
{457,469,480,492,504,3701,527,539,551,562,574,586,597,609,621,3815,644,656,668,679,691,703,714,726,738,3930,761,773,785,796,808,820,831,843,855,4044,878,890,902,65535,65535,65535,65535,65535,65535,65535,65535,65535},
{65535,65535,65535,65535,65535,65535,65535,65535,65535,65535,65535,65535,65535,65535,65535,65535,65535,65535,65535,65535,65535,65535,65535,65535,65535,65535,65535,65535,65535,65535,65535,65535,65535,65535,65535,65535,65535,65535,65535,65535,65535,65535,65535,65535,65535,65535,65535,65535},
{913,925,936,948,960,3702,983,995,1007,1018,1030,1042,1053,1065,1077,3816,1100,1112,1124,1135,1147,1159,1170,1182,1194,3931,1217,1229,1241,1252,1264,1276,1287,1299,1311,4045,1334,1346,1358,65535,65535,65535,65535,65535,65535,65535,65535,65535},
{65535,65535,65535,65535,65535,65535,65535,65535,65535,65535,65535,65535,65535,65535,65535,65535,65535,65535,65535,65535,65535,65535,65535,65535,65535,65535,65535,65535,65535,65535,65535,65535,65535,65535,65535,65535,65535,65535,65535,65535,65535,65535,65535,65535,65535,65535,65535,65535},
{1369,1381,1392,1404,1416,3703,1439,1451,1463,1474,1486,1498,1509,1521,1533,3817,1556,1568,1580,1591,1603,1615,1626,1638,1650,3932,1673,1685,1697,1708,1720,1732,1743,1755,1767,4046,1790,1802,1814,65535,65535,65535,65535,65535,65535,65535,65535,65535},
{65535,65535,65535,65535,65535,65535,65535,65535,65535,65535,65535,65535,65535,65535,65535,65535,65535,65535,65535,65535,65535,65535,65535,65535,65535,65535,65535,65535,65535,65535,65535,65535,65535,65535,65535,65535,65535,65535,65535,65535,65535,65535,65535,65535,65535,65535,65535,65535},
{1825,1837,1848,1860,1872,3704,1895,1907,1919,1930,1942,1954,1965,1977,1989,3818,2012,2024,2036,2047,2059,2071,2082,2094,2106,3933,2129,2141,2153,2164,2176,2188,2199,2211,2223,4047,2246,2258,2270,65535,65535,65535,65535,65535,65535,65535,65535,65535},
{65535,65535,65535,65535,65535,65535,65535,65535,65535,65535,65535,65535,65535,65535,65535,65535,65535,65535,65535,65535,65535,65535,65535,65535,65535,65535,65535,65535,65535,65535,65535,65535,65535,65535,65535,65535,65535,65535,65535,65535,65535,65535,65535,65535,65535,65535,65535,65535},
{2281,2293,2304,2316,2328,3705,2351,2363,2375,2386,2398,2410,2421,2433,2445,3819,2468,2480,2492,2503,2515,2527,2538,2550,2562,3934,2585,2597,2609,2620,2632,2644,2655,2667,2679,4048,2702,2714,2726,65535,65535,65535,65535,65535,65535,65535,65535,65535},
{65535,65535,65535,65535,65535,65535,65535,65535,65535,65535,65535,65535,65535,65535,65535,65535,65535,65535,65535,65535,65535,65535,65535,65535,65535,65535,65535,65535,65535,65535,65535,65535,65535,65535,65535,65535,65535,65535,65535,65535,65535,65535,65535,65535,65535,65535,65535,65535},
{2737,2749,2760,2772,2784,3706,2807,2819,2831,2842,2854,2866,2877,2889,2901,3820,2924,2936,2948,2959,2971,2983,2994,3006,3018,3935,3041,3053,3065,3076,3088,3100,3111,3123,3135,4049,3158,3170,3182,65535,65535,65535,65535,65535,65535,65535,65535,65535},
{65535,65535,65535,65535,65535,65535,65535,65535,65535,65535,65535,65535,65535,65535,65535,65535,65535,65535,65535,65535,65535,65535,65535,65535,65535,65535,65535,65535,65535,65535,65535,65535,65535,65535,65535,65535,65535,65535,65535,65535,65535,65535,65535,65535,65535,65535,65535,65535},
{3193,3205,3216,3228,3240,3707,3263,3275,3287,3298,3310,3322,3333,3345,3357,3821,3380,3392,3404,3415,3427,3439,3450,3462,3474,3936,3497,3509,3521,3532,3544,3556,3567,3579,3591,4050,3614,3626,3638,65535,65535,65535,65535,65535,65535,65535,65535,65535},
{65535,65535,65535,65535,65535,65535,65535,65535,65535,65535,65535,65535,65535,65535,65535,65535,65535,65535,65535,65535,65535,65535,65535,65535,65535,65535,65535,65535,65535,65535,65535,65535,65535,65535,65535,65535,65535,65535,65535,65535,65535,65535,65535,65535,65535,65535,65535,65535},
{2,14,25,37,49,60,72,84,3735,107,119,131,142,154,166,177,189,201,3850,224,236,248,259,271,283,294,306,318,3964,341,353,365,376,388,400,411,423,435,4078,65535,65535,65535,65535,65535,65535,65535,65535,65535},
{65535,65535,65535,65535,65535,65535,65535,65535,65535,65535,65535,65535,65535,65535,65535,65535,65535,65535,65535,65535,65535,65535,65535,65535,65535,65535,65535,65535,65535,65535,65535,65535,65535,65535,65535,65535,65535,65535,65535,65535,65535,65535,65535,65535,65535,65535,65535,65535},
{458,470,481,493,505,516,528,540,3736,563,575,587,598,610,622,633,645,657,3851,680,692,704,715,727,739,750,762,774,3965,797,809,821,832,844,856,867,879,891,4079,65535,65535,65535,65535,65535,65535,65535,65535,65535},
{65535,65535,65535,65535,65535,65535,65535,65535,65535,65535,65535,65535,65535,65535,65535,65535,65535,65535,65535,65535,65535,65535,65535,65535,65535,65535,65535,65535,65535,65535,65535,65535,65535,65535,65535,65535,65535,65535,65535,65535,65535,65535,65535,65535,65535,65535,65535,65535},
{914,926,937,949,961,972,984,996,3737,1019,1031,1043,1054,1066,1078,1089,1101,1113,3852,1136,1148,1160,1171,1183,1195,1206,1218,1230,3966,1253,1265,1277,1288,1300,1312,1323,1335,1347,4080,65535,65535,65535,65535,65535,65535,65535,65535,65535},
{65535,65535,65535,65535,65535,65535,65535,65535,65535,65535,65535,65535,65535,65535,65535,65535,65535,65535,65535,65535,65535,65535,65535,65535,65535,65535,65535,65535,65535,65535,65535,65535,65535,65535,65535,65535,65535,65535,65535,65535,65535,65535,65535,65535,65535,65535,65535,65535},
{1370,1382,1393,1405,1417,1428,1440,1452,3738,1475,1487,1499,1510,1522,1534,1545,1557,1569,3853,1592,1604,1616,1627,1639,1651,1662,1674,1686,3967,1709,1721,1733,1744,1756,1768,1779,1791,1803,4081,65535,65535,65535,65535,65535,65535,65535,65535,65535},
{65535,65535,65535,65535,65535,65535,65535,65535,65535,65535,65535,65535,65535,65535,65535,65535,65535,65535,65535,65535,65535,65535,65535,65535,65535,65535,65535,65535,65535,65535,65535,65535,65535,65535,65535,65535,65535,65535,65535,65535,65535,65535,65535,65535,65535,65535,65535,65535},
{1826,1838,1849,1861,1873,1884,1896,1908,3739,1931,1943,1955,1966,1978,1990,2001,2013,2025,3854,2048,2060,2072,2083,2095,2107,2118,2130,2142,3968,2165,2177,2189,2200,2212,2224,2235,2247,2259,4082,65535,65535,65535,65535,65535,65535,65535,65535,65535},
{65535,65535,65535,65535,65535,65535,65535,65535,65535,65535,65535,65535,65535,65535,65535,65535,65535,65535,65535,65535,65535,65535,65535,65535,65535,65535,65535,65535,65535,65535,65535,65535,65535,65535,65535,65535,65535,65535,65535,65535,65535,65535,65535,65535,65535,65535,65535,65535},
{2282,2294,2305,2317,2329,2340,2352,2364,3740,2387,2399,2411,2422,2434,2446,2457,2469,2481,3855,2504,2516,2528,2539,2551,2563,2574,2586,2598,3969,2621,2633,2645,2656,2668,2680,2691,2703,2715,4083,65535,65535,65535,65535,65535,65535,65535,65535,65535},
{65535,65535,65535,65535,65535,65535,65535,65535,65535,65535,65535,65535,65535,65535,65535,65535,65535,65535,65535,65535,65535,65535,65535,65535,65535,65535,65535,65535,65535,65535,65535,65535,65535,65535,65535,65535,65535,65535,65535,65535,65535,65535,65535,65535,65535,65535,65535,65535},
{2738,2750,2761,2773,2785,2796,2808,2820,3741,2843,2855,2867,2878,2890,2902,2913,2925,2937,3856,2960,2972,2984,2995,3007,3019,3030,3042,3054,3970,3077,3089,3101,3112,3124,3136,3147,3159,3171,4084,65535,65535,65535,65535,65535,65535,65535,65535,65535},
{65535,65535,65535,65535,65535,65535,65535,65535,65535,65535,65535,65535,65535,65535,65535,65535,65535,65535,65535,65535,65535,65535,65535,65535,65535,65535,65535,65535,65535,65535,65535,65535,65535,65535,65535,65535,65535,65535,65535,65535,65535,65535,65535,65535,65535,65535,65535,65535},
{3194,3206,3217,3229,3241,3252,3264,3276,3742,3299,3311,3323,3334,3346,3358,3369,3381,3393,3857,3416,3428,3440,3451,3463,3475,3486,3498,3510,3971,3533,3545,3557,3568,3580,3592,3603,3615,3627,4085,65535,65535,65535,65535,65535,65535,65535,65535,65535},
{3,3656,26,38,50,61,73,85,96,108,120,3770,143,155,167,178,190,202,213,225,237,3885,260,272,284,295,307,319,330,342,354,3999,377,389,401,412,424,436,447,65535,65535,65535,65535,65535,65535,65535,65535,65535},
{4,15,27,39,3691,62,74,86,97,109,121,132,144,156,3806,179,191,203,214,226,238,249,261,273,3920,296,308,320,331,343,355,366,378,390,4034,413,425,437,448,65535,65535,65535,65535,65535,65535,65535,65535,65535},
{459,3657,482,494,506,517,529,541,552,564,576,3771,599,611,623,634,646,658,669,681,693,3886,716,728,740,751,763,775,786,798,810,4000,833,845,857,868,880,892,903,65535,65535,65535,65535,65535,65535,65535,65535,65535},
{460,471,483,495,3692,518,530,542,553,565,577,588,600,612,3807,635,647,659,670,682,694,705,717,729,3921,752,764,776,787,799,811,822,834,846,4035,869,881,893,904,65535,65535,65535,65535,65535,65535,65535,65535,65535},
{915,3658,938,950,962,973,985,997,1008,1020,1032,3772,1055,1067,1079,1090,1102,1114,1125,1137,1149,3887,1172,1184,1196,1207,1219,1231,1242,1254,1266,4001,1289,1301,1313,1324,1336,1348,1359,65535,65535,65535,65535,65535,65535,65535,65535,65535},
{916,927,939,951,3693,974,986,998,1009,1021,1033,1044,1056,1068,3808,1091,1103,1115,1126,1138,1150,1161,1173,1185,3922,1208,1220,1232,1243,1255,1267,1278,1290,1302,4036,1325,1337,1349,1360,65535,65535,65535,65535,65535,65535,65535,65535,65535},
{1371,3659,1394,1406,1418,1429,1441,1453,1464,1476,1488,3773,1511,1523,1535,1546,1558,1570,1581,1593,1605,3888,1628,1640,1652,1663,1675,1687,1698,1710,1722,4002,1745,1757,1769,1780,1792,1804,1815,65535,65535,65535,65535,65535,65535,65535,65535,65535},
{1372,1383,1395,1407,3694,1430,1442,1454,1465,1477,1489,1500,1512,1524,3809,1547,1559,1571,1582,1594,1606,1617,1629,1641,3923,1664,1676,1688,1699,1711,1723,1734,1746,1758,4037,1781,1793,1805,1816,65535,65535,65535,65535,65535,65535,65535,65535,65535},
{1827,3660,1850,1862,1874,1885,1897,1909,1920,1932,1944,3774,1967,1979,1991,2002,2014,2026,2037,2049,2061,3889,2084,2096,2108,2119,2131,2143,2154,2166,2178,4003,2201,2213,2225,2236,2248,2260,2271,65535,65535,65535,65535,65535,65535,65535,65535,65535},
{1828,1839,1851,1863,3695,1886,1898,1910,1921,1933,1945,1956,1968,1980,3810,2003,2015,2027,2038,2050,2062,2073,2085,2097,3924,2120,2132,2144,2155,2167,2179,2190,2202,2214,4038,2237,2249,2261,2272,65535,65535,65535,65535,65535,65535,65535,65535,65535},
{2283,3661,2306,2318,2330,2341,2353,2365,2376,2388,2400,3775,2423,2435,2447,2458,2470,2482,2493,2505,2517,3890,2540,2552,2564,2575,2587,2599,2610,2622,2634,4004,2657,2669,2681,2692,2704,2716,2727,65535,65535,65535,65535,65535,65535,65535,65535,65535},
{2284,2295,2307,2319,3696,2342,2354,2366,2377,2389,2401,2412,2424,2436,3811,2459,2471,2483,2494,2506,2518,2529,2541,2553,3925,2576,2588,2600,2611,2623,2635,2646,2658,2670,4039,2693,2705,2717,2728,65535,65535,65535,65535,65535,65535,65535,65535,65535},
{65535,65535,65535,65535,65535,65535,65535,65535,65535,65535,65535,65535,65535,65535,65535,65535,65535,65535,65535,65535,65535,65535,65535,65535,65535,65535,65535,65535,65535,65535,65535,65535,65535,65535,65535,65535,65535,65535,65535,65535,65535,65535,65535,65535,65535,65535,65535,65535},
{2739,3662,2762,2774,2786,2797,2809,2821,2832,2844,2856,3776,2879,2891,2903,2914,2926,2938,2949,2961,2973,3891,2996,3008,3020,3031,3043,3055,3066,3078,3090,4005,3113,3125,3137,3148,3160,3172,3183,65535,65535,65535,65535,65535,65535,65535,65535,65535},
{3195,3663,3218,3230,3242,3253,3265,3277,3288,3300,3312,3777,3335,3347,3359,3370,3382,3394,3405,3417,3429,3892,3452,3464,3476,3487,3499,3511,3522,3534,3546,4006,3569,3581,3593,3604,3616,3628,3639,65535,65535,65535,65535,65535,65535,65535,65535,65535},
{3196,3207,3219,3231,3698,3254,3266,3278,3289,3301,3313,3324,3336,3348,3813,3371,3383,3395,3406,3418,3430,3441,3453,3465,3927,3488,3500,3512,3523,3535,3547,3558,3570,3582,4041,3605,3617,3629,3640,65535,65535,65535,65535,65535,65535,65535,65535,65535},
{461,472,484,496,507,519,531,3728,554,566,578,589,601,613,624,636,648,3842,671,683,695,706,718,730,741,753,765,3956,788,800,812,823,835,847,858,870,882,4070,905,65535,65535,65535,65535,65535,65535,65535,65535,65535},
{3649,473,485,497,508,520,532,543,555,567,3763,590,602,614,625,637,649,660,672,684,3877,707,719,731,742,754,766,777,789,801,3991,824,836,848,859,871,883,894,906,65535,65535,65535,65535,65535,65535,65535,65535,65535},
{917,928,940,952,963,975,987,3729,1010,1022,1034,1045,1057,1069,1080,1092,1104,3843,1127,1139,1151,1162,1174,1186,1197,1209,1221,3957,1244,1256,1268,1279,1291,1303,1314,1326,1338,4071,1361,65535,65535,65535,65535,65535,65535,65535,65535,65535},
{3650,929,941,953,964,976,988,999,1011,1023,3764,1046,1058,1070,1081,1093,1105,1116,1128,1140,3878,1163,1175,1187,1198,1210,1222,1233,1245,1257,3992,1280,1292,1304,1315,1327,1339,1350,1362,65535,65535,65535,65535,65535,65535,65535,65535,65535},
{1373,1384,1396,1408,1419,1431,1443,3730,1466,1478,1490,1501,1513,1525,1536,1548,1560,3844,1583,1595,1607,1618,1630,1642,1653,1665,1677,3958,1700,1712,1724,1735,1747,1759,1770,1782,1794,4072,1817,65535,65535,65535,65535,65535,65535,65535,65535,65535},
{3651,1385,1397,1409,1420,1432,1444,1455,1467,1479,3765,1502,1514,1526,1537,1549,1561,1572,1584,1596,3879,1619,1631,1643,1654,1666,1678,1689,1701,1713,3993,1736,1748,1760,1771,1783,1795,1806,1818,65535,65535,65535,65535,65535,65535,65535,65535,65535},
{1829,1840,1852,1864,1875,1887,1899,3731,1922,1934,1946,1957,1969,1981,1992,2004,2016,3845,2039,2051,2063,2074,2086,2098,2109,2121,2133,3959,2156,2168,2180,2191,2203,2215,2226,2238,2250,4073,2273,65535,65535,65535,65535,65535,65535,65535,65535,65535},
{3652,1841,1853,1865,1876,1888,1900,1911,1923,1935,3766,1958,1970,1982,1993,2005,2017,2028,2040,2052,3880,2075,2087,2099,2110,2122,2134,2145,2157,2169,3994,2192,2204,2216,2227,2239,2251,2262,2274,65535,65535,65535,65535,65535,65535,65535,65535,65535},
{2285,2296,2308,2320,2331,2343,2355,3732,2378,2390,2402,2413,2425,2437,2448,2460,2472,3846,2495,2507,2519,2530,2542,2554,2565,2577,2589,3960,2612,2624,2636,2647,2659,2671,2682,2694,2706,4074,2729,65535,65535,65535,65535,65535,65535,65535,65535,65535},
{3653,2297,2309,2321,2332,2344,2356,2367,2379,2391,3767,2414,2426,2438,2449,2461,2473,2484,2496,2508,3881,2531,2543,2555,2566,2578,2590,2601,2613,2625,3995,2648,2660,2672,2683,2695,2707,2718,2730,65535,65535,65535,65535,65535,65535,65535,65535,65535},
{2740,2751,2763,2775,3697,2798,2810,2822,2833,2845,2857,2868,2880,2892,3812,2915,2927,2939,2950,2962,2974,2985,2997,3009,3926,3032,3044,3056,3067,3079,3091,3102,3114,3126,4040,3149,3161,3173,3184,65535,65535,65535,65535,65535,65535,65535,65535,65535},
{2741,2752,2764,2776,2787,2799,2811,3733,2834,2846,2858,2869,2881,2893,2904,2916,2928,3847,2951,2963,2975,2986,2998,3010,3021,3033,3045,3961,3068,3080,3092,3103,3115,3127,3138,3150,3162,4075,3185,65535,65535,65535,65535,65535,65535,65535,65535,65535},
{3197,3208,3220,3232,3243,3255,3267,3734,3290,3302,3314,3325,3337,3349,3360,3372,3384,3848,3407,3419,3431,3442,3454,3466,3477,3489,3501,3962,3524,3536,3548,3559,3571,3583,3594,3606,3618,4076,3641,65535,65535,65535,65535,65535,65535,65535,65535,65535},
{3655,3209,3221,3233,3244,3256,3268,3279,3291,3303,3769,3326,3338,3350,3361,3373,3385,3396,3408,3420,3883,3443,3455,3467,3478,3490,3502,3513,3525,3537,3997,3560,3572,3584,3595,3607,3619,3630,3642,65535,65535,65535,65535,65535,65535,65535,65535,65535},
{462,474,486,3684,509,521,533,544,556,568,579,591,603,3798,626,638,650,661,673,685,696,708,720,3912,743,755,767,778,790,802,813,825,837,4026,860,872,884,895,907,65535,65535,65535,65535,65535,65535,65535,65535,65535},
{463,475,487,498,510,522,3719,545,557,569,580,592,604,615,627,639,3833,662,674,686,697,709,721,732,744,756,3947,779,791,803,814,826,838,849,861,873,4061,896,908,65535,65535,65535,65535,65535,65535,65535,65535,65535},
{918,930,942,3685,965,977,989,1000,1012,1024,1035,1047,1059,3799,1082,1094,1106,1117,1129,1141,1152,1164,1176,3913,1199,1211,1223,1234,1246,1258,1269,1281,1293,4027,1316,1328,1340,1351,1363,65535,65535,65535,65535,65535,65535,65535,65535,65535},
{919,931,943,954,966,978,3720,1001,1013,1025,1036,1048,1060,1071,1083,1095,3834,1118,1130,1142,1153,1165,1177,1188,1200,1212,3948,1235,1247,1259,1270,1282,1294,1305,1317,1329,4062,1352,1364,65535,65535,65535,65535,65535,65535,65535,65535,65535},
{1374,1386,1398,3686,1421,1433,1445,1456,1468,1480,1491,1503,1515,3800,1538,1550,1562,1573,1585,1597,1608,1620,1632,3914,1655,1667,1679,1690,1702,1714,1725,1737,1749,4028,1772,1784,1796,1807,1819,65535,65535,65535,65535,65535,65535,65535,65535,65535},
{1375,1387,1399,1410,1422,1434,3721,1457,1469,1481,1492,1504,1516,1527,1539,1551,3835,1574,1586,1598,1609,1621,1633,1644,1656,1668,3949,1691,1703,1715,1726,1738,1750,1761,1773,1785,4063,1808,1820,65535,65535,65535,65535,65535,65535,65535,65535,65535},
{1830,1842,1854,3687,1877,1889,1901,1912,1924,1936,1947,1959,1971,3801,1994,2006,2018,2029,2041,2053,2064,2076,2088,3915,2111,2123,2135,2146,2158,2170,2181,2193,2205,4029,2228,2240,2252,2263,2275,65535,65535,65535,65535,65535,65535,65535,65535,65535},
{1831,1843,1855,1866,1878,1890,3722,1913,1925,1937,1948,1960,1972,1983,1995,2007,3836,2030,2042,2054,2065,2077,2089,2100,2112,2124,3950,2147,2159,2171,2182,2194,2206,2217,2229,2241,4064,2264,2276,65535,65535,65535,65535,65535,65535,65535,65535,65535},
{2286,2298,2310,3688,2333,2345,2357,2368,2380,2392,2403,2415,2427,3802,2450,2462,2474,2485,2497,2509,2520,2532,2544,3916,2567,2579,2591,2602,2614,2626,2637,2649,2661,4030,2684,2696,2708,2719,2731,65535,65535,65535,65535,65535,65535,65535,65535,65535},
{2287,2299,2311,2322,2334,2346,3723,2369,2381,2393,2404,2416,2428,2439,2451,2463,3837,2486,2498,2510,2521,2533,2545,2556,2568,2580,3951,2603,2615,2627,2638,2650,2662,2673,2685,2697,4065,2720,2732,65535,65535,65535,65535,65535,65535,65535,65535,65535},
{3654,2753,2765,2777,2788,2800,2812,2823,2835,2847,3768,2870,2882,2894,2905,2917,2929,2940,2952,2964,3882,2987,2999,3011,3022,3034,3046,3057,3069,3081,3996,3104,3116,3128,3139,3151,3163,3174,3186,65535,65535,65535,65535,65535,65535,65535,65535,65535},
{2742,2754,2766,3689,2789,2801,2813,2824,2836,2848,2859,2871,2883,3803,2906,2918,2930,2941,2953,2965,2976,2988,3000,3917,3023,3035,3047,3058,3070,3082,3093,3105,3117,4031,3140,3152,3164,3175,3187,65535,65535,65535,65535,65535,65535,65535,65535,65535},
{3198,3210,3222,3690,3245,3257,3269,3280,3292,3304,3315,3327,3339,3804,3362,3374,3386,3397,3409,3421,3432,3444,3456,3918,3479,3491,3503,3514,3526,3538,3549,3561,3573,4032,3596,3608,3620,3631,3643,65535,65535,65535,65535,65535,65535,65535,65535,65535},
{3199,3211,3223,3234,3246,3258,3725,3281,3293,3305,3316,3328,3340,3351,3363,3375,3839,3398,3410,3422,3433,3445,3457,3468,3480,3492,3953,3515,3527,3539,3550,3562,3574,3585,3597,3609,4067,3632,3644,65535,65535,65535,65535,65535,65535,65535,65535,65535},
{464,476,488,499,511,523,534,546,558,3754,581,593,605,616,628,640,651,663,675,3868,698,710,722,733,745,757,768,780,792,3982,815,827,839,850,862,874,885,897,909,65535,65535,65535,65535,65535,65535,65535,65535,65535},
{465,477,3675,500,512,524,535,547,559,570,582,594,3789,617,629,641,652,664,676,687,699,711,3903,734,746,758,769,781,793,804,816,828,4017,851,863,875,886,898,910,65535,65535,65535,65535,65535,65535,65535,65535,65535},
{920,932,944,955,967,979,990,1002,1014,3755,1037,1049,1061,1072,1084,1096,1107,1119,1131,3869,1154,1166,1178,1189,1201,1213,1224,1236,1248,3983,1271,1283,1295,1306,1318,1330,1341,1353,1365,65535,65535,65535,65535,65535,65535,65535,65535,65535},
{921,933,3676,956,968,980,991,1003,1015,1026,1038,1050,3790,1073,1085,1097,1108,1120,1132,1143,1155,1167,3904,1190,1202,1214,1225,1237,1249,1260,1272,1284,4018,1307,1319,1331,1342,1354,1366,65535,65535,65535,65535,65535,65535,65535,65535,65535},
{1376,1388,1400,1411,1423,1435,1446,1458,1470,3756,1493,1505,1517,1528,1540,1552,1563,1575,1587,3870,1610,1622,1634,1645,1657,1669,1680,1692,1704,3984,1727,1739,1751,1762,1774,1786,1797,1809,1821,65535,65535,65535,65535,65535,65535,65535,65535,65535},
{1377,1389,3677,1412,1424,1436,1447,1459,1471,1482,1494,1506,3791,1529,1541,1553,1564,1576,1588,1599,1611,1623,3905,1646,1658,1670,1681,1693,1705,1716,1728,1740,4019,1763,1775,1787,1798,1810,1822,65535,65535,65535,65535,65535,65535,65535,65535,65535},
{1832,1844,1856,1867,1879,1891,1902,1914,1926,3757,1949,1961,1973,1984,1996,2008,2019,2031,2043,3871,2066,2078,2090,2101,2113,2125,2136,2148,2160,3985,2183,2195,2207,2218,2230,2242,2253,2265,2277,65535,65535,65535,65535,65535,65535,65535,65535,65535},
{1833,1845,3678,1868,1880,1892,1903,1915,1927,1938,1950,1962,3792,1985,1997,2009,2020,2032,2044,2055,2067,2079,3906,2102,2114,2126,2137,2149,2161,2172,2184,2196,4020,2219,2231,2243,2254,2266,2278,65535,65535,65535,65535,65535,65535,65535,65535,65535},
{2288,2300,2312,2323,2335,2347,2358,2370,2382,3758,2405,2417,2429,2440,2452,2464,2475,2487,2499,3872,2522,2534,2546,2557,2569,2581,2592,2604,2616,3986,2639,2651,2663,2674,2686,2698,2709,2721,2733,65535,65535,65535,65535,65535,65535,65535,65535,65535},
{2289,2301,3679,2324,2336,2348,2359,2371,2383,2394,2406,2418,3793,2441,2453,2465,2476,2488,2500,2511,2523,2535,3907,2558,2570,2582,2593,2605,2617,2628,2640,2652,4021,2675,2687,2699,2710,2722,2734,65535,65535,65535,65535,65535,65535,65535,65535,65535},
{2743,2755,2767,2778,2790,2802,3724,2825,2837,2849,2860,2872,2884,2895,2907,2919,3838,2942,2954,2966,2977,2989,3001,3012,3024,3036,3952,3059,3071,3083,3094,3106,3118,3129,3141,3153,4066,3176,3188,65535,65535,65535,65535,65535,65535,65535,65535,65535},
{2744,2756,2768,2779,2791,2803,2814,2826,2838,3759,2861,2873,2885,2896,2908,2920,2931,2943,2955,3873,2978,2990,3002,3013,3025,3037,3048,3060,3072,3987,3095,3107,3119,3130,3142,3154,3165,3177,3189,65535,65535,65535,65535,65535,65535,65535,65535,65535},
{3200,3212,3224,3235,3247,3259,3270,3282,3294,3760,3317,3329,3341,3352,3364,3376,3387,3399,3411,3874,3434,3446,3458,3469,3481,3493,3504,3516,3528,3988,3551,3563,3575,3586,3598,3610,3621,3633,3645,65535,65535,65535,65535,65535,65535,65535,65535,65535},
{3201,3213,3681,3236,3248,3260,3271,3283,3295,3306,3318,3330,3795,3353,3365,3377,3388,3400,3412,3423,3435,3447,3909,3470,3482,3494,3505,3517,3529,3540,3552,3564,4023,3587,3599,3611,3622,3634,3646,65535,65535,65535,65535,65535,65535,65535,65535,65535},
{466,478,489,501,513,3710,536,548,560,571,583,595,606,618,630,3824,653,665,677,688,700,712,723,735,747,3938,770,782,794,805,817,829,840,852,864,4053,887,899,911,65535,65535,65535,65535,65535,65535,65535,65535,65535},
{467,479,490,502,514,525,537,549,3745,572,584,596,607,619,631,642,654,666,3859,689,701,713,724,736,748,759,771,783,3974,806,818,830,841,853,865,876,888,900,4088,65535,65535,65535,65535,65535,65535,65535,65535,65535},
{922,934,945,957,969,3711,992,1004,1016,1027,1039,1051,1062,1074,1086,3825,1109,1121,1133,1144,1156,1168,1179,1191,1203,3939,1226,1238,1250,1261,1273,1285,1296,1308,1320,4054,1343,1355,1367,65535,65535,65535,65535,65535,65535,65535,65535,65535},
{923,935,946,958,970,981,993,1005,3746,1028,1040,1052,1063,1075,1087,1098,1110,1122,3860,1145,1157,1169,1180,1192,1204,1215,1227,1239,3975,1262,1274,1286,1297,1309,1321,1332,1344,1356,4089,65535,65535,65535,65535,65535,65535,65535,65535,65535},
{1378,1390,1401,1413,1425,3712,1448,1460,1472,1483,1495,1507,1518,1530,1542,3826,1565,1577,1589,1600,1612,1624,1635,1647,1659,3940,1682,1694,1706,1717,1729,1741,1752,1764,1776,4055,1799,1811,1823,65535,65535,65535,65535,65535,65535,65535,65535,65535},
{1379,1391,1402,1414,1426,1437,1449,1461,3747,1484,1496,1508,1519,1531,1543,1554,1566,1578,3861,1601,1613,1625,1636,1648,1660,1671,1683,1695,3976,1718,1730,1742,1753,1765,1777,1788,1800,1812,4090,65535,65535,65535,65535,65535,65535,65535,65535,65535},
{1834,1846,1857,1869,1881,3713,1904,1916,1928,1939,1951,1963,1974,1986,1998,3827,2021,2033,2045,2056,2068,2080,2091,2103,2115,3941,2138,2150,2162,2173,2185,2197,2208,2220,2232,4056,2255,2267,2279,65535,65535,65535,65535,65535,65535,65535,65535,65535},
{1835,1847,1858,1870,1882,1893,1905,1917,3748,1940,1952,1964,1975,1987,1999,2010,2022,2034,3862,2057,2069,2081,2092,2104,2116,2127,2139,2151,3977,2174,2186,2198,2209,2221,2233,2244,2256,2268,4091,65535,65535,65535,65535,65535,65535,65535,65535,65535},
{2290,2302,2313,2325,2337,3714,2360,2372,2384,2395,2407,2419,2430,2442,2454,3828,2477,2489,2501,2512,2524,2536,2547,2559,2571,3942,2594,2606,2618,2629,2641,2653,2664,2676,2688,4057,2711,2723,2735,65535,65535,65535,65535,65535,65535,65535,65535,65535},
{2291,2303,2314,2326,2338,2349,2361,2373,3749,2396,2408,2420,2431,2443,2455,2466,2478,2490,3863,2513,2525,2537,2548,2560,2572,2583,2595,2607,3978,2630,2642,2654,2665,2677,2689,2700,2712,2724,4092,65535,65535,65535,65535,65535,65535,65535,65535,65535},
{2745,2757,3680,2780,2792,2804,2815,2827,2839,2850,2862,2874,3794,2897,2909,2921,2932,2944,2956,2967,2979,2991,3908,3014,3026,3038,3049,3061,3073,3084,3096,3108,4022,3131,3143,3155,3166,3178,3190,65535,65535,65535,65535,65535,65535,65535,65535,65535},
{2746,2758,2769,2781,2793,3715,2816,2828,2840,2851,2863,2875,2886,2898,2910,3829,2933,2945,2957,2968,2980,2992,3003,3015,3027,3943,3050,3062,3074,3085,3097,3109,3120,3132,3144,4058,3167,3179,3191,65535,65535,65535,65535,65535,65535,65535,65535,65535},
{3202,3214,3225,3237,3249,3716,3272,3284,3296,3307,3319,3331,3342,3354,3366,3830,3389,3401,3413,3424,3436,3448,3459,3471,3483,3944,3506,3518,3530,3541,3553,3565,3576,3588,3600,4059,3623,3635,3647,65535,65535,65535,65535,65535,65535,65535,65535,65535},
{3203,3215,3226,3238,3250,3261,3273,3285,3751,3308,3320,3332,3343,3355,3367,3378,3390,3402,3865,3425,3437,3449,3460,3472,3484,3495,3507,3519,3980,3542,3554,3566,3577,3589,3601,3612,3624,3636,4094,65535,65535,65535,65535,65535,65535,65535,65535,65535},
{65535,65535,65535,65535,65535,65535,65535,65535,65535,65535,65535,65535,65535,65535,65535,65535,65535,65535,65535,65535,65535,65535,65535,65535,65535,65535,65535,65535,65535,65535,65535,65535,65535,65535,65535,65535,65535,65535,65535,65535,65535,65535,65535,65535,65535,65535,65535,65535},
{2747,2759,2770,2782,2794,2805,2817,2829,3750,2852,2864,2876,2887,2899,2911,2922,2934,2946,3864,2969,2981,2993,3004,3016,3028,3039,3051,3063,3979,3086,3098,3110,3121,3133,3145,3156,3168,3180,4093,65535,65535,65535,65535,65535,65535,65535,65535,65535},
{65535,65535,65535,65535,65535,65535,65535,65535,65535,65535,65535,65535,65535,65535,65535,65535,65535,65535,65535,65535,65535,65535,65535,65535,65535,65535,65535,65535,65535,65535,65535,65535,65535,65535,65535,65535,65535,65535,65535,65535,65535,65535,65535,65535,65535,65535,65535,65535},
{3664,3673,3682,3699,3708,3717,3726,3743,3752,3761,3778,3787,3796,3805,3822,3831,3840,3849,3866,3875,3884,3901,3910,3919,3928,3945,3954,3963,3972,3989,3998,4007,4024,4033,4042,4051,4068,4077,4086,4095,65535,65535,65535,65535,65535,65535,65535,65535},
{5,16,28,40,51,63,75,3727,98,110,122,133,145,157,168,180,192,3841,215,227,239,250,262,274,285,297,309,3955,332,344,356,367,379,391,402,414,426,4069,449,65535,65535,65535,65535,65535,65535,65535,65535,65535},
{3648,17,29,41,52,64,76,87,99,111,3762,134,146,158,169,181,193,204,216,228,3876,251,263,275,286,298,310,321,333,345,3990,368,380,392,403,415,427,438,450,65535,65535,65535,65535,65535,65535,65535,65535,65535},
{6,18,30,3683,53,65,77,88,100,112,123,135,147,3797,170,182,194,205,217,229,240,252,264,3911,287,299,311,322,334,346,357,369,381,4025,404,416,428,439,451,65535,65535,65535,65535,65535,65535,65535,65535,65535},
{7,19,31,42,54,66,3718,89,101,113,124,136,148,159,171,183,3832,206,218,230,241,253,265,276,288,300,3946,323,335,347,358,370,382,393,405,417,4060,440,452,65535,65535,65535,65535,65535,65535,65535,65535,65535},
{8,20,32,43,55,67,78,90,102,3753,125,137,149,160,172,184,195,207,219,3867,242,254,266,277,289,301,312,324,336,3981,359,371,383,394,406,418,429,441,453,65535,65535,65535,65535,65535,65535,65535,65535,65535},
{9,21,3674,44,56,68,79,91,103,114,126,138,3788,161,173,185,196,208,220,231,243,255,3902,278,290,302,313,325,337,348,360,372,4016,395,407,419,430,442,454,65535,65535,65535,65535,65535,65535,65535,65535,65535},
{10,22,33,45,57,3709,80,92,104,115,127,139,150,162,174,3823,197,209,221,232,244,256,267,279,291,3937,314,326,338,349,361,373,384,396,408,4052,431,443,455,65535,65535,65535,65535,65535,65535,65535,65535,65535},
{11,23,34,46,58,69,81,93,3744,116,128,140,151,163,175,186,198,210,3858,233,245,257,268,280,292,303,315,327,3973,350,362,374,385,397,409,420,432,444,4087,65535,65535,65535,65535,65535,65535,65535,65535,65535},
};

#define NG 9
#define RING 16
#define NSLOT 8
#define CFETCH 5
#define TABLED 1
#define PROMO CU_TENSOR_MAP_L2_PROMOTION_L2_128B
#define AHEAD 6
#define CF0 5
#define CFS 2
#define ABL 0
#define CX 5
#define TRIG 7
constexpr int NCONV = 3 * NG;
constexpr int PLEN = (1024 + NG - 1) / NG;
constexpr int TILEB = 12288;
constexpr int SLOTB = 280 * 64;
constexpr int W1S = 0, W2S = 73728, ABUF = 147456, MISC = ABUF + 16 * 3072;
constexpr int CTAB = NSLOT * SLOTB + 512;
constexpr int SMEM_BYTES = MISC + 512 + 2048;
static_assert(CTAB + (PLEN + 12) * 16 <= MISC, "conv smem");

__device__ __align__(1024) unsigned char g_scratch[(RING * NG + 1) * 4 * TILEB];
__device__ uint32_t g_ready[1024];
__device__ uint32_t g_cons[1024 + 32];
__device__ unsigned long long g_start;

#define PROF_AT(cond, idx)
#define PROF_VAL(cond, idx, v)
#define PROF2_AT(c, i)
#define PROF2_VAL(c, i, v)
#define GELU_C3 0.32920349f
#define GELU_A2 0x40d940d9u
#define SPIN_LIMIT 0x1000000

__device__ __forceinline__ uint32_t smem_u32(const void* p) { return (uint32_t)__cvta_generic_to_shared(p); }
__device__ __forceinline__ void wg_fence() { asm volatile("wgmma.fence.sync.aligned;" ::: "memory"); }
__device__ __forceinline__ void wg_commit() { asm volatile("wgmma.commit_group.sync.aligned;" ::: "memory"); }
template <int N> __device__ __forceinline__ void wg_wait() { asm volatile("wgmma.wait_group.sync.aligned %0;" ::"n"(N) : "memory"); }
__device__ __forceinline__ void mbar_init(uint32_t bar, uint32_t cnt) { asm volatile("mbarrier.init.shared::cta.b64 [%0], %1;" ::"r"(bar), "r"(cnt) : "memory"); }
__device__ __forceinline__ void mbar_expect_tx(uint32_t bar, uint32_t bytes) { asm volatile("mbarrier.arrive.expect_tx.shared::cta.b64 _, [%0], %1;" ::"r"(bar), "r"(bytes) : "memory"); }
__device__ __forceinline__ void mbar_arrive(uint32_t bar) { asm volatile("mbarrier.arrive.shared::cta.b64 _, [%0];" ::"r"(bar) : "memory"); }
__device__ __forceinline__ void mbar_wait(uint32_t bar, uint32_t parity) {
  asm volatile("{\n.reg .pred p;\n.reg .u32 c;\nmbarrier.try_wait.parity.shared::cta.b64 p, [%0], %1;\n@p bra DONE_%=;\nmov.u32 c, 0;\nWAIT_%=:\nmbarrier.try_wait.parity.shared::cta.b64 p, [%0], %1;\n@p bra DONE_%=;\n"
               "add.u32 c, c, 1;\nsetp.lt.u32 p, c, 0x1000000;\n@p bra WAIT_%=;\ntrap;\nDONE_%=:\n}" ::"r"(bar), "r"(parity) : "memory");
}
__device__ __forceinline__ void bulk_g2s(uint32_t dst, const void* src, uint32_t bytes, uint32_t bar) {
  asm volatile("cp.async.bulk.shared::cluster.global.mbarrier::complete_tx::bytes [%0], [%1], %2, [%3];" ::"r"(dst), "l"(src), "r"(bytes), "r"(bar) : "memory");
}
__device__ __forceinline__ uint32_t ld_relaxed(const uint32_t* p) { uint32_t v; asm volatile("ld.relaxed.gpu.global.u32 %0, [%1];" : "=r"(v) : "l"(p) : "memory"); return v; }
__device__ __forceinline__ void red_add(uint32_t* p) { asm volatile("red.relaxed.gpu.global.add.u32 [%0], 1;" ::"l"(p) : "memory"); }
__device__ __forceinline__ void lds128(uint32_t* r, uint32_t a) { asm volatile("ld.shared.v4.b32 {%0,%1,%2,%3}, [%4];" : "=r"(r[0]), "=r"(r[1]), "=r"(r[2]), "=r"(r[3]) : "r"(a) : "memory"); }
__device__ __forceinline__ uint2 lds64(uint32_t a) { uint2 v; asm volatile("ld.shared.v2.b32 {%0,%1}, [%2];" : "=r"(v.x), "=r"(v.y) : "r"(a) : "memory"); return v; }
__device__ __forceinline__ uint32_t lds32(uint32_t a) { uint32_t v; asm volatile("ld.shared.b32 %0, [%1];" : "=r"(v) : "r"(a) : "memory"); return v; }
__device__ __forceinline__ void sts32(uint32_t a, uint32_t v) { asm volatile("st.shared.b32 [%0], %1;" ::"r"(a), "r"(v) : "memory"); }
__device__ __forceinline__ void sts128(uint32_t a, uint4 v) { asm volatile("st.shared.v4.b32 [%0], {%1,%2,%3,%4};" ::"r"(a), "r"(v.x), "r"(v.y), "r"(v.z), "r"(v.w) : "memory"); }
__device__ __forceinline__ uint4 ldg128v(const void* p) { uint4 v; asm volatile("ld.global.nc.v4.b32 {%0,%1,%2,%3}, [%4];" : "=r"(v.x), "=r"(v.y), "=r"(v.z), "=r"(v.w) : "l"(p) : "memory"); return v; }
__device__ __forceinline__ void stg128(void* p, uint4 v) { asm volatile("st.global.v4.b32 [%0], {%1,%2,%3,%4};" ::"l"(p), "r"(v.x), "r"(v.y), "r"(v.z), "r"(v.w) : "memory"); }
#define HINT 3
__device__ __forceinline__ uint64_t pol_evict_first() { uint64_t p; asm("createpolicy.fractional.L2::evict_first.b64 %0, 1.0;" : "=l"(p)); return p; }
__device__ __forceinline__ uint4 ldg128_last(const void* p, uint64_t pol) {
  if (!(HINT & 1)) return ldg128v(p);
  uint4 v; asm volatile("ld.global.nc.L1::no_allocate.L2::cache_hint.v4.b32 {%0,%1,%2,%3}, [%4], %5;" : "=r"(v.x), "=r"(v.y), "=r"(v.z), "=r"(v.w) : "l"(p), "l"(pol) : "memory"); return v;
}
__device__ __forceinline__ void stg128_stream(void* p, uint4 v, uint64_t pol) {
  if (!(HINT & 2)) { stg128(p, v); return; }
  asm volatile("st.global.L2::cache_hint.v4.b32 [%0], {%1,%2,%3,%4}, %5;" ::"l"(p), "r"(v.x), "r"(v.y), "r"(v.z), "r"(v.w), "l"(pol) : "memory");
}
__device__ __forceinline__ float bf_lo(uint32_t w) { return __uint_as_float(w << 16); }
__device__ __forceinline__ float bf_hi(uint32_t w) { return __uint_as_float(w & 0xffff0000u); }
__device__ __forceinline__ uint32_t pack_f16(float lo, float hi) { uint32_t d; asm("cvt.rn.f16x2.f32 %0, %1, %2;" : "=r"(d) : "f"(hi), "f"(lo)); return d; }
__device__ __forceinline__ uint32_t pack_f16_sat(float lo, float hi) { uint32_t d; asm("cvt.rn.satfinite.f16x2.f32 %0, %1, %2;" : "=r"(d) : "f"(hi), "f"(lo)); return d; }
__device__ __forceinline__ uint32_t pack_bf16(float lo, float hi) { uint32_t d; asm("cvt.rn.bf16x2.f32 %0, %1, %2;" : "=r"(d) : "f"(hi), "f"(lo)); return d; }
__device__ __forceinline__ uint32_t hadd2_bf16(uint32_t a, uint32_t b) { uint32_t d; asm("add.rn.bf16x2 %0, %1, %2;" : "=r"(d) : "r"(a), "r"(b)); return d; }
__device__ __forceinline__ uint32_t h2add(uint32_t a, uint32_t b) { uint32_t d; asm("add.rn.f16x2 %0, %1, %2;" : "=r"(d) : "r"(a), "r"(b)); return d; }
__device__ __forceinline__ uint32_t h2mul(uint32_t a, uint32_t b) { uint32_t d; asm("mul.rn.f16x2 %0, %1, %2;" : "=r"(d) : "r"(a), "r"(b)); return d; }
__device__ __forceinline__ uint32_t h2fma(uint32_t a, uint32_t b, uint32_t c) { uint32_t d; asm("fma.rn.f16x2 %0, %1, %2, %3;" : "=r"(d) : "r"(a), "r"(b), "r"(c)); return d; }
__device__ __forceinline__ uint32_t h2lo(uint32_t a) { uint32_t d; asm("{.reg .f16 l,h; mov.b32 {l,h}, %1; mov.b32 %0, {l,l};}" : "=r"(d) : "r"(a)); return d; }
__device__ __forceinline__ uint32_t h2hi(uint32_t a) { uint32_t d; asm("{.reg .f16 l,h; mov.b32 {l,h}, %1; mov.b32 %0, {h,h};}" : "=r"(d) : "r"(a)); return d; }
__device__ __forceinline__ float h_lo(uint32_t a) { float d; asm("{.reg .f16 l,h; mov.b32 {l,h}, %1; cvt.f32.f16 %0, l;}" : "=f"(d) : "r"(a)); return d; }
__device__ __forceinline__ float h_hi(uint32_t a) { float d; asm("{.reg .f16 l,h; mov.b32 {l,h}, %1; cvt.f32.f16 %0, h;}" : "=f"(d) : "r"(a)); return d; }
__device__ __forceinline__ uint32_t prmt(uint32_t a, uint32_t b, uint32_t s) { uint32_t d; asm("prmt.b32 %0, %1, %2, %3;" : "=r"(d) : "r"(a), "r"(b), "r"(s)); return d; }
__device__ __forceinline__ void mma_sp(float* d, const uint32_t* a, const uint32_t* b, const float* c, uint32_t e) {
  asm("mma.sp::ordered_metadata.sync.aligned.m16n8k32.row.col.f32.bf16.bf16.f32 {%0,%1,%2,%3}, {%4,%5,%6,%7}, {%8,%9,%10,%11}, {%12,%13,%14,%15}, %16, 0;"
      : "=f"(d[0]), "=f"(d[1]), "=f"(d[2]), "=f"(d[3])
      : "r"(a[0]), "r"(a[1]), "r"(a[2]), "r"(a[3]), "r"(b[0]), "r"(b[1]), "r"(b[2]), "r"(b[3]), "f"(c[0]), "f"(c[1]), "f"(c[2]), "f"(c[3]), "r"(e));
}
__device__ __forceinline__ uint32_t bf2_to_h2(uint32_t w, float s) { return pack_f16(bf_lo(w) * s, bf_hi(w) * s); }
__device__ __forceinline__ uint32_t bf2_to_h2(uint32_t w) { return pack_f16(bf_lo(w), bf_hi(w)); }

__device__ __forceinline__ uint32_t gelu_h2(uint32_t y) {
  uint32_t t, u, th, g;
  asm volatile("fma.rn.f16x2 %0, %1, %1, %2;" : "=r"(t) : "r"(y), "r"(GELU_A2));
  asm volatile("mul.rn.f16x2 %0, %1, %2;" : "=r"(u) : "r"(y), "r"(t));
  asm volatile("tanh.approx.f16x2 %0, %1;" : "=r"(th) : "r"(u));
  asm volatile("fma.rn.f16x2 %0, %1, %2, %1;" : "=r"(g) : "r"(y), "r"(th));
  return g;
}

__device__ __forceinline__ void prep_weights(uint32_t sb, const __nv_bfloat16* __restrict__ w1, const __nv_bfloat16* __restrict__ w2, int warp, int lane) {
  const int k0 = lane & 7, lq = lane >> 3;
  uint4 v[9], u[3][4];
#pragma unroll
  for (int i = 0; i < 9; i++) {
    int it = warp * 9 + i, nbq = it % 12, skh = it / 12, kh = skh & 1, s = skh >> 1;
    int ch = 16 * s + 4 * (k0 >> 1) + 2 * kh + (k0 & 1);
    v[i] = __ldg((const uint4*)(w1 + ch * 384 + (nbq * 4 + lq) * 8));
  }
#pragma unroll
  for (int i = 0; i < 3; i++) {
    int it = warp + 16 * i;
    if (it < 36) {
      int un = it * 4 + lq, j = un % 3, h8 = un / 3;
      const uint4* p = (const uint4*)(w2 + (h8 * 8 + k0) * 96 + j * 32);
#pragma unroll
      for (int q = 0; q < 4; q++) u[i][q] = __ldg(p + q);
    }
  }
#pragma unroll
  for (int i = 0; i < 9; i++) {
    int it = warp * 9 + i, nbq = it % 12, skh = it / 12, kh = skh & 1, s = skh >> 1;
    sts128(sb + W1S + s * 12288 + (nbq * 4 + lq) * 256 + kh * 128 + k0 * 16, make_uint4(bf2_to_h2(v[i].x), bf2_to_h2(v[i].y), bf2_to_h2(v[i].z), bf2_to_h2(v[i].w)));
  }
  const float sc = 0.5f / GELU_C3;
#pragma unroll
  for (int i = 0; i < 3; i++) {
    int it = warp + 16 * i;
    if (it < 36) {
      int un = it * 4 + lq, j = un % 3, h8 = un / 3;
      uint32_t base = sb + W2S + (h8 >> 1) * 3072 + (j * 4) * 256 + (h8 & 1) * 128 + k0 * 16;
      sts128(base, make_uint4(bf2_to_h2(u[i][0].x, sc), bf2_to_h2(u[i][1].x, sc), bf2_to_h2(u[i][2].x, sc), bf2_to_h2(u[i][3].x, sc)));
      sts128(base + 256, make_uint4(bf2_to_h2(u[i][0].y, sc), bf2_to_h2(u[i][1].y, sc), bf2_to_h2(u[i][2].y, sc), bf2_to_h2(u[i][3].y, sc)));
      sts128(base + 512, make_uint4(bf2_to_h2(u[i][0].z, sc), bf2_to_h2(u[i][1].z, sc), bf2_to_h2(u[i][2].z, sc), bf2_to_h2(u[i][3].z, sc)));
      sts128(base + 768, make_uint4(bf2_to_h2(u[i][0].w, sc), bf2_to_h2(u[i][1].w, sc), bf2_to_h2(u[i][2].w, sc), bf2_to_h2(u[i][3].w, sc)));
    }
  }
}

__device__ __noinline__ void ln_wide(uint32_t ad) {
  float m[2], r[2];
#pragma unroll
  for (int hi = 0; hi < 2; hi++) {
    float sm = 0.f;
    for (int s = 0; s < 6; s++) { uint2 w = lds64(ad + s * 512 + hi * 8); sm += (h_lo(w.x) + h_hi(w.x)) + (h_lo(w.y) + h_hi(w.y)); }
    sm += __shfl_xor_sync(0xffffffffu, sm, 1); sm += __shfl_xor_sync(0xffffffffu, sm, 2);
    m[hi] = sm * (1.f / 96.f);
    float q = 0.f;
    for (int s = 0; s < 6; s++) {
      uint2 w = lds64(ad + s * 512 + hi * 8);
      float d0 = h_lo(w.x) - m[hi], d1 = h_hi(w.x) - m[hi], d2 = h_lo(w.y) - m[hi], d3 = h_hi(w.y) - m[hi];
      q += (d0 * d0 + d1 * d1) + (d2 * d2 + d3 * d3);
    }
    q += __shfl_xor_sync(0xffffffffu, q, 1); q += __shfl_xor_sync(0xffffffffu, q, 2);
    r[hi] = rsqrtf(fmaf(q, 1.f / 96.f, 1e-5f)) * GELU_C3;
  }
  for (int s = 0; s < 6; s++) {
    uint32_t w[4]; lds128(w, ad + s * 512);
    sts128(ad + s * 512, make_uint4(pack_f16((h_lo(w[0]) - m[0]) * r[0], (h_hi(w[0]) - m[0]) * r[0]), pack_f16((h_lo(w[2]) - m[1]) * r[1], (h_hi(w[2]) - m[1]) * r[1]),
                                    pack_f16((h_lo(w[1]) - m[0]) * r[0], (h_hi(w[1]) - m[0]) * r[0]), pack_f16((h_lo(w[3]) - m[1]) * r[1], (h_hi(w[3]) - m[1]) * r[1])));
  }
  asm volatile("fence.proxy.async.shared::cta;" ::: "memory");
}

__device__ __forceinline__ void load_ln(uint32_t ad, uint32_t* a) {
  uint32_t raw[6][4];
#pragma unroll
  for (int s = 0; s < 6; s++) lds128(raw[s], ad + s * 512);
  uint32_t sm[2];
#pragma unroll
  for (int hi = 0; hi < 2; hi++) {
    uint32_t s0 = h2add(raw[0][2 * hi], raw[1][2 * hi]), s1 = h2add(raw[0][2 * hi + 1], raw[1][2 * hi + 1]);
    uint32_t s2 = h2add(raw[2][2 * hi], raw[3][2 * hi]), s3 = h2add(raw[2][2 * hi + 1], raw[3][2 * hi + 1]);
    uint32_t s4 = h2add(raw[4][2 * hi], raw[5][2 * hi]), s5 = h2add(raw[4][2 * hi + 1], raw[5][2 * hi + 1]);
    sm[hi] = h2add(h2add(h2add(s0, s1), h2add(s2, s3)), h2add(s4, s5));
  }
  uint32_t s = h2add(prmt(sm[0], sm[1], 0x5410), prmt(sm[0], sm[1], 0x7632));
  s = h2add(s, __shfl_xor_sync(0xffffffffu, s, 1));
  s = h2add(s, __shfl_xor_sync(0xffffffffu, s, 2));
  const uint32_t nm = h2mul(s, 0xA155A155u);
  uint32_t qq[2];
#pragma unroll
  for (int hi = 0; hi < 2; hi++) {
    const uint32_t m = hi ? h2hi(nm) : h2lo(nm);
    uint32_t q0 = 0, q1 = 0;
#pragma unroll
    for (int k = 0; k < 6; k++) {
      uint32_t d0 = h2add(raw[k][2 * hi], m), d1 = h2add(raw[k][2 * hi + 1], m);
      raw[k][2 * hi] = d0; raw[k][2 * hi + 1] = d1;
      q0 = k ? h2fma(d0, d0, q0) : h2mul(d0, d0);
      q1 = k ? h2fma(d1, d1, q1) : h2mul(d1, d1);
    }
    qq[hi] = h2add(q0, q1);
  }
  uint32_t q = h2add(prmt(qq[0], qq[1], 0x5410), prmt(qq[0], qq[1], 0x7632));
  q = h2add(q, __shfl_xor_sync(0xffffffffu, q, 1));
  q = h2add(q, __shfl_xor_sync(0xffffffffu, q, 2));
  const float r0 = rsqrtf(fmaf(h_lo(q), 1.f / 96.f, 1e-5f)) * GELU_C3, r1 = rsqrtf(fmaf(h_hi(q), 1.f / 96.f, 1e-5f)) * GELU_C3;
  const uint32_t r = pack_f16(r0, r1);
#pragma unroll
  for (int k = 0; k < 6; k++) {
    a[4 * k] = h2mul(raw[k][0], h2lo(r)); a[4 * k + 2] = h2mul(raw[k][1], h2lo(r));
    a[4 * k + 1] = h2mul(raw[k][2], h2hi(r)); a[4 * k + 3] = h2mul(raw[k][3], h2hi(r));
  }
  const bool bad = (((q & 0x7c007c00u) + 0x04000400u) & 0x80008000u) != 0;
  if (__any_sync(0xffffffffu, bad)) {
    ln_wide(ad);
#pragma unroll
    for (int k = 0; k < 6; k++) lds128(a + 4 * k, ad + k * 512);
  }
}

__device__ __forceinline__ void gemm1(uint32_t* p, const uint32_t* a, uint64_t d1, int c) {
  wgmma_n48_f16<0>(p, a, d1 + c * (1536 >> 4));
#pragma unroll
  for (int s = 1; s < 6; s++) wgmma_n48_f16<1>(p, a + 4 * s, d1 + c * (1536 >> 4) + s * (12288 >> 4));
}

__device__ __forceinline__ void fetch_a(uint32_t abuf, uint32_t bar, uint32_t sofs) {
  asm volatile("{\n.reg .pred p;\nelect.sync _|p, 0xffffffff;\n@p fence.acquire.gpu;\n@p fence.proxy.async.global;\n"
               "@p mbarrier.arrive.expect_tx.shared::cta.b64 _, [%1], 3072;\n"
               "@p cp.async.bulk.shared::cluster.global.mbarrier::complete_tx::bytes [%0], [%2], 3072, [%1];\n}"
               ::"r"(abuf), "r"(bar), "l"(g_scratch + sofs) : "memory");
}
__device__ __forceinline__ void wait_ready(int P, uint32_t target) {
  int spins = 0;
  while (ld_relaxed(&g_ready[P]) != target) { __nanosleep(64); if (++spins > SPIN_LIMIT) __trap(); }
}

__device__ __forceinline__ void mlp_role(uint32_t sb, const __nv_bfloat16* __restrict__ x, const __nv_bfloat16* __restrict__ w1, const __nv_bfloat16* __restrict__ w2,
                                         __nv_bfloat16* __restrict__ out, int idx, bool tabled, int warp, int lane) {
  const int wg = warp >> 2, w = warp & 3, g = lane >> 2, t = lane & 3;
  const uint32_t abuf = sb + ABUF + warp * 3072;
  const uint32_t bar = sb + MISC + warp * 8;
  const uint32_t tl = sb + MISC + 512;
  if (threadIdx.x >= 384) {
    const int k = threadIdx.x - 384;
    int n = -1;
    if (tabled) { if (k < 48) n = (int16_t)g_sched[idx][k]; }
    else {
      const int i = k * (gridDim.x - NCONV) + idx, full = (1024 - (NG - 1) * PLEN) * NG;
      const int r = i >> 2, j = r < full ? r / NG : (r - full) / (NG - 1) + full / NG, gm = r < full ? r % NG : (r - full) % (NG - 1);
      if (i < 4096) n = (gm * PLEN + j) * 4 + (i & 3);
    }
    const int P = n >> 2, gm = P / PLEN, j = P - gm * PLEN;
    sts128(tl + k * 16, make_uint4(P, (((j & (RING - 1)) * NG + gm) * 4 + (n & 3)) * TILEB, ((n & 1020) * 256 + (n >> 10) * 128 + (n & 1) * 64 + (n & 2) * 4) * 192, 0));
  }
  if (lane == 0) { mbar_init(bar, 1); asm volatile("fence.mbarrier_init.release.cluster;" ::: "memory"); }
  if (threadIdx.x == 0) sts32(sb + MISC + 256, (uint32_t)(atomicAdd(&g_start, 1ULL) / gridDim.x) + 1);
  prep_weights(sb, w1, w2, warp, lane);
  asm volatile("fence.proxy.async.shared::cta;" ::: "memory");
  __syncthreads();
  PROF_AT(threadIdx.x == 0, 1); PROF_VAL(threadIdx.x == 0, 8, clock64());
  const uint32_t rtarget = 3 * lds32(sb + MISC + 256);
  const uint64_t dbase = ((uint64_t)(128 >> 4) << 16) | ((uint64_t)(256 >> 4) << 32);
  const uint64_t d1 = dbase | (uint64_t)(((sb + W1S) >> 4) & 0x3fff);
  const uint64_t d2 = dbase | (uint64_t)(((sb + W2S) >> 4) & 0x3fff);
  const uint32_t ad = abuf + t * 128 + ((g ^ (2 * t)) << 4);
  const uint32_t pofs = (16 * (g & 3) + 2 * w + (g >> 2)) * 192 + t * 16;
  const int mybar = 1 + wg, nxtbar = 1 + ((wg + 1) & 3);
  const uint64_t pol = pol_evict_first();
  uint32_t ph = 0, tp = tl + wg * 16;
  bool pending = true;
  uint32_t cur[4];
  lds128(cur, tp);
  while ((int)cur[0] >= 0) {
    PROF2_AT((threadIdx.x & 127) == 0, 16 + (tp - tl) / 4); PROF2_VAL((threadIdx.x & 127) == 0, 16 + (tp - tl) / 4 + 3, pending);
    if (pending) { wait_ready(cur[0], rtarget); fetch_a(abuf, bar, cur[1] + w * 3072); }
    uint32_t a[24], p[8][12], gg[8][12], acc[24], nxt[4];
    lds128(nxt, tp + 64);
    const int sig = lds32(tp + 16);
    mbar_wait(bar, ph); ph ^= 1;
    PROF2_AT((threadIdx.x & 127) == 0, 16 + (tp - tl) / 4 + 1);
    asm volatile("{.reg .pred p; elect.sync _|p, 0xffffffff; @p red.relaxed.gpu.global.add.u32 [%0], 1;}" ::"l"(&g_cons[cur[0]]) : "memory");
    load_ln(ad, a);
    const uint32_t gofs = cur[2] + pofs;
    uint32_t rdy = 0;
    uint4 xr[2][3];
    pending = (int)nxt[0] >= 0;
    if (tp != tl) asm volatile("bar.sync %0, 256;" ::"r"(mybar) : "memory");
    PROF2_AT((threadIdx.x & 127) == 0, 16 + (tp - tl) / 4 + 2);
    wg_fence();
    gemm1(p[0], a, d1, 0); wg_commit();
#pragma unroll
    for (int c = 0; c < 8; c++) {
      wg_wait<0>();
      if (c >= CF0 && (c - CF0) % CFS == 0) {
        if (pending && rdy == rtarget) { pending = false; fetch_a(abuf, bar, nxt[1] + w * 3072); }
      }
      if (c + 1 >= CF0 && c < 7 && (c + 1 - CF0) % CFS == 0) rdy = ld_relaxed(&g_ready[nxt[0] & 1023]);
      if (c == CX) {
#pragma unroll
        for (int hi = 0; hi < 2; hi++)
#pragma unroll
          for (int j = 0; j < 3; j++) xr[hi][j] = ldg128_last((const char*)x + gofs + hi * (512 * 192) + j * 64, pol);
      }
#pragma unroll
      for (int s = 0; s < 3; s++) {
        if (3 * c + s == TRIG) asm volatile("{.reg .pred p; setp.ge.s32 p, %1, 0; @p bar.arrive %0, 256;}" ::"r"(nxtbar), "r"(sig) : "memory");
#pragma unroll
        for (int i = 0; i < 4; i++) gg[c][4 * s + i] = gelu_h2(p[c][4 * s + i]);
        wg_fence();
        if (c == 0 && s == 0) wgmma_n96_f16<0>(acc, gg[c], d2); else wgmma_n96_f16<1>(acc, &gg[c][4 * s], d2 + (c * 3 + s) * (3072 >> 4));
      }
      if (c + 1 < 8) gemm1(p[c + 1], a, d1, c + 1);
      wg_commit();
    }
    wg_wait<0>();
#pragma unroll
    for (int hi = 0; hi < 2; hi++)
#pragma unroll
      for (int j = 0; j < 3; j++) {
        uint4 o;
        o.x = hadd2_bf16(xr[hi][j].x, pack_bf16(h_lo(acc[8 * j + hi]), h_hi(acc[8 * j + hi])));
        o.y = hadd2_bf16(xr[hi][j].y, pack_bf16(h_lo(acc[8 * j + 2 + hi]), h_hi(acc[8 * j + 2 + hi])));
        o.z = hadd2_bf16(xr[hi][j].z, pack_bf16(h_lo(acc[8 * j + 4 + hi]), h_hi(acc[8 * j + 4 + hi])));
        o.w = hadd2_bf16(xr[hi][j].w, pack_bf16(h_lo(acc[8 * j + 6 + hi]), h_hi(acc[8 * j + 6 + hi])));
        stg128_stream((char*)out + gofs + hi * (512 * 192) + j * 64, o, pol);
      }
    tp += 64; cur[0] = nxt[0]; cur[1] = nxt[1]; cur[2] = nxt[2];
  }
  PROF_AT((threadIdx.x & 127) == 0, 4 + wg); PROF_VAL(threadIdx.x == 0, 9, clock64());
}

__device__ __forceinline__ void conv_compute(uint32_t sb, const __nv_bfloat16* __restrict__ dw, int third, int nit, int warp, int lane) {
  const int g = lane >> 2, t = lane & 3;
  const uint32_t full = sb + MISC;
  uint32_t A[4][4][4];
  {
    uint2 w[2][9];
#pragma unroll
    for (int h = 0; h < 2; h++) {
      const int j = (4 * h + t - g) & 7;
      w[h][0] = make_uint2(0u, 0u); w[h][8] = make_uint2(0u, 0u);
#pragma unroll
      for (int i = 0; i < 7; i++) {
        w[h][i + 1] = make_uint2(0u, 0u);
        if (j < 7) w[h][i + 1] = __ldg((const uint2*)(dw + (i * 7 + j) * 96 + third * 32 + warp * 4));
      }
    }
#pragma unroll
    for (int u = 0; u < 4; u++)
#pragma unroll
      for (int r = 0; r < 4; r++) {
        const int h = r >> 1, i0 = 2 * u - (r & 1) + 1;
        A[0][u][r] = prmt(w[h][i0].x, w[h][i0 + 1].x, 0x5410); A[1][u][r] = prmt(w[h][i0].x, w[h][i0 + 1].x, 0x7632);
        A[2][u][r] = prmt(w[h][i0].y, w[h][i0 + 1].y, 0x5410); A[3][u][r] = prmt(w[h][i0].y, w[h][i0 + 1].y, 0x7632);
      }
  }
  uint32_t meta = 0;
#pragma unroll
  for (int a = 0; a < 4; a++) meta |= ((4 * (t & 1) + a + 1 >= g) ? 0x80008u : 0xD000Du) << (4 * a);
  meta = __shfl_sync(0xffffffffu, meta, lane);
  float S[2][4][3][4];
#pragma unroll
  for (int s = 0; s < 2; s++)
#pragma unroll
    for (int c = 0; c < 4; c++)
#pragma unroll
      for (int i = 0; i < 3; i++)
#pragma unroll
        for (int k = 0; k < 4; k++) S[s][c][i][k] = 0.f;
  uint32_t aq[4];
#pragma unroll
  for (int q = 0; q < 4; q++) {
    const int pp = (g & 1) * 140 + (t & 1) * 70 + 16 * (g >> 1) + 2 * q + (t >> 1);
    aq[q] = __shfl_sync(0xffffffffu, sb + pp * 64 + (((warp >> 1) ^ ((pp >> 1) & 3)) << 4) + (warp & 1) * 8, lane);
  }
  const int Q = third * 8 + warp;
  unsigned char* const obase = g_scratch + (g >> 1) * 3072 + Q * 128 + (((4 * (g & 1) + t) ^ (2 * (Q & 3))) << 4);
  const float zero4[4] = {0.f, 0.f, 0.f, 0.f};
  uint32_t sofs = 0, bar = full, ph = 0;
  uint2 X[3][4];
  mbar_wait(bar, 0);
  PROF_AT(threadIdx.x == 0, 1); PROF_VAL(threadIdx.x == 0, 8, clock64());
#pragma unroll
  for (int j = 0; j < 2; j++)
#pragma unroll
    for (int q = 0; q < 4; q++) X[j][q] = lds64(aq[q] + j * 512);
  for (uint32_t ot = sb + CTAB; ot < sb + CTAB + nit * 16; ot += 16) {
    PROF_AT(threadIdx.x == 0 && ((ot - sb - CTAB) & 112) == 0, 16 + ((ot - sb - CTAB) >> 4));
    unsigned char* const o = obase + lds32(ot);
    const uint32_t dbar = bar + 64 + ph * 64;
#pragma unroll
    for (int s = 0; s < 2; s++) {
      uint32_t B[4][4];
      if (s == 1) {
        sofs += SLOTB; bar += 8;
        if (sofs == NSLOT * SLOTB) { sofs = 0; bar = full; ph ^= 1; }
        mbar_wait(bar, ph);
      }
#pragma unroll
      for (int c = 0; c < 4; c++)
#pragma unroll
        for (int q = 0; q < 4; q++) B[c][q] = prmt(c < 2 ? X[s][q].x : X[s][q].y, c < 2 ? X[s + 1][q].x : X[s + 1][q].y, (c & 1) ? 0x7632 : 0x5410);
      if (s == 0) {
#pragma unroll
        for (int q = 0; q < 4; q++) X[2][q] = lds64(aq[q] + sofs + 2 * 512);
      } else {
#pragma unroll
        for (int j = 0; j < 2; j++)
#pragma unroll
          for (int q = 0; q < 4; q++) X[j][q] = lds64(aq[q] + sofs + j * 512);
      }
      float T[4][4];
#pragma unroll
      for (int c = 0; c < 4; c++) mma_sp(T[c], A[c][3], B[c], S[s][c][2], meta);
#pragma unroll
      for (int c = 0; c < 4; c++) mma_sp(S[s][c][2], A[c][2], B[c], S[s][c][1], meta);
      stg128(o + (2 * s) * TILEB, make_uint4(pack_f16_sat(T[0][0], T[1][0]), pack_f16_sat(T[2][0], T[3][0]), pack_f16_sat(T[0][2], T[1][2]), pack_f16_sat(T[2][2], T[3][2])));
      stg128(o + (2 * s + 1) * TILEB, make_uint4(pack_f16_sat(T[0][1], T[1][1]), pack_f16_sat(T[2][1], T[3][1]), pack_f16_sat(T[0][3], T[1][3]), pack_f16_sat(T[2][3], T[3][3])));
#pragma unroll
      for (int c = 0; c < 4; c++) mma_sp(S[s][c][1], A[c][1], B[c], S[s][c][0], meta);
#pragma unroll
      for (int c = 0; c < 4; c++) mma_sp(S[s][c][0], A[c][0], B[c], zero4, meta);
    }
    asm volatile("{.reg .pred p; elect.sync _|p, 0xffffffff; @p mbarrier.arrive.shared::cta.b64 _, [%0];}" ::"r"(dbar) : "memory");
  }
  PROF_AT(threadIdx.x == 0, 4); PROF_VAL(threadIdx.x == 0, 9, clock64());
}

__device__ __forceinline__ void conv_loader(uint32_t sb, const CUtensorMap* tmx, int nit, int third) {
  const uint32_t full = sb + MISC;
  for (int it = 0; it <= nit; it++) {
    const int s = it & (NSLOT - 1);
    const uint2 e = lds64(sb + CTAB + it * 16 + 8);
    if (it >= AHEAD) mbar_wait(full + 64 + ((it - AHEAD) & 15) * 8, ((it - AHEAD) >> 4) & 1);
    asm volatile("{\n.reg .pred p;\n.reg .s32 c2;\n.reg .u32 d2;\nelect.sync _|p, 0xffffffff;\nadd.s32 c2, %4, 64;\nadd.u32 d2, %0, 8960;\n"
                 "@p mbarrier.arrive.expect_tx.shared::cta.b64 _, [%2], 17920;\n"
                 "@p cp.async.bulk.tensor.3d.shared::cluster.global.mbarrier::complete_tx::bytes [%0], [%1, {%3, %4, %5}], [%2];\n"
                 "@p cp.async.bulk.tensor.3d.shared::cluster.global.mbarrier::complete_tx::bytes [d2], [%1, {%3, c2, %5}], [%2];\n}"
                 ::"r"(sb + s * SLOTB), "l"(tmx), "r"(full + s * 8), "r"(third * 32), "r"(e.x), "r"(e.y) : "memory");
  }
}

__device__ __forceinline__ void conv_credit(uint32_t sb, int P0, int nit, int lane) {
  const uint32_t full = sb + MISC;
  uint32_t ctarget = 0;
  int credit = P0 + RING;
  for (int it = 0; it <= nit; it++) {
    if (it >= NSLOT) {
      if (it == NSLOT) {
        if (lane == 0) ctarget = 16 * ((uint32_t)(atomicAdd(&g_start, 1ULL) / gridDim.x) + 1);
        ctarget = __shfl_sync(0xffffffffu, ctarget, 0);
      }
      const int P = (int)lds32(sb + CTAB + it * 16 + 4);
      mbar_wait(full + 64 + ((it - NSLOT) & 15) * 8, ((it - NSLOT) >> 4) & 1);
      int spins = 0;
      while ((int)lds32(full + 192 + (it & 3) * 4) < it - 15) { __nanosleep(64); if (++spins > SPIN_LIMIT) __trap(); }
      if (P >= credit) {
        while (true) {
          const uint32_t ok = __ballot_sync(0xffffffffu, ld_relaxed(&g_cons[credit - RING + lane]) == ctarget);
          const int got = __ffs(~ok) - 1;
          credit += got < 0 ? 32 : got;
          if (P < credit) break;
          __nanosleep(200); if (++spins > SPIN_LIMIT) __trap();
        }
        asm volatile("fence.acquire.gpu;" ::: "memory");
      }
    }
    if (lane == 0) mbar_arrive(full + (it & (NSLOT - 1)) * 8);
  }
}

__device__ __forceinline__ void conv_publisher(uint32_t sb, int nit, int k, int lane) {
  for (int it = k; it < nit; it += 4) {
    const int P = (int)lds32(sb + CTAB + it * 16 + 4);
    mbar_wait(sb + MISC + 64 + (it & 15) * 8, (it >> 4) & 1);
    if (lane == 0) {
      sts32(sb + MISC + 192 + k * 4, it + 1);
      if (P >= 0) {
        asm volatile("fence.release.gpu;" ::: "memory");
        red_add(&g_ready[P]);
        PROF_AT((it & 7) == 0 || it < 8, 200 + it);
      }
    }
    __syncwarp();
  }
}

__global__ void __launch_bounds__(512, 1) convnext_kernel(const __grid_constant__ CUtensorMap tmx, const __nv_bfloat16* __restrict__ x, const __nv_bfloat16* __restrict__ dw,
                                                          const __nv_bfloat16* __restrict__ w1, const __nv_bfloat16* __restrict__ w2, __nv_bfloat16* __restrict__ out) {
  extern __shared__ __align__(1024) unsigned char smem[];
  const uint32_t sb = smem_u32(smem);
  const int warp = __shfl_sync(0xffffffffu, threadIdx.x >> 5, 0), lane = threadIdx.x & 31;
  PROF_AT(threadIdx.x == 0, 0);
  uint32_t smid, nsmid;
  asm volatile("mov.u32 %0, %%smid;" : "=r"(smid));
  asm volatile("mov.u32 %0, %%nsmid;" : "=r"(nsmid));
  const bool tabled = TABLED && NG == 9 && gridDim.x == 132 && nsmid == 132;
  int cidx, idx;
  bool is_conv;
  if (tabled) {
    idx = smid;
    is_conv = (smid < 48 && !(smid & 1)) || smid == 60 || smid == 120 || smid == 122;
    cidx = smid < 48 ? ((smid >> 1) & 7) * 3 + (smid >> 4) : smid == 60 ? 26 : 24 + ((smid >> 1) & 1);
  } else {
    cidx = (blockIdx.x * NCONV) / gridDim.x;
    is_conv = ((blockIdx.x + 1) * NCONV) / gridDim.x != cidx;
    idx = blockIdx.x - cidx;
  }
  PROF_VAL(threadIdx.x == 0, 2, is_conv ? 1000 + cidx : idx);
  if (!is_conv) {
    mlp_role(sb, x, w1, w2, out, idx, tabled, warp, lane);
  } else {
    const int gm = cidx / 3, third = cidx - gm * 3;
    const int P0 = gm * PLEN, P1 = min(P0 + PLEN, 1024) - 1;
    const int Vs = P0 + 2 * (P0 >> 8) + ((P0 & 255) ? 0 : 1);
    const int nit = P1 + 2 * (P1 >> 8) + 4 - Vs;
    if (threadIdx.x == 0) {
      for (int s = 0; s < NSLOT; s++) { mbar_init(sb + MISC + s * 8, 2); mbar_init(sb + MISC + 64 + s * 8, 8); mbar_init(sb + MISC + 128 + s * 8, 8); }
      sts128(sb + MISC + 192, make_uint4(0, 0, 0, 0));
      asm volatile("fence.mbarrier_init.release.cluster;" ::: "memory");
    }
    if (threadIdx.x >= 256 && threadIdx.x - 256 <= nit) {
      const int it = threadIdx.x - 256, V = Vs + it;
      const int st = (V - 1) / 258, so = max(V - 3, 0) / 258, po = V - 3 - so * 258, P = so * 256 + po;
      const bool ok = po < 256 && P >= P0 && P <= P1;
      sts128(sb + CTAB + it * 16, make_uint4((ok ? ((P - P0) & (RING - 1)) * NG + gm : RING * NG) * (4 * TILEB), ok ? P : -1, st * 128 - 3, 2 * (V - st * 258) - 3));
    }
    __syncthreads();
    if (warp < 8) {
      asm volatile("setmaxnreg.inc.sync.aligned.u32 224;");
      conv_compute(sb, dw, third, nit, warp, lane);
    } else if (warp >= 12) {
      asm volatile("setmaxnreg.dec.sync.aligned.u32 24;");
      conv_publisher(sb, nit, warp - 12, lane);
    } else {
      asm volatile("setmaxnreg.dec.sync.aligned.u32 40;");
      if (warp == 8) conv_loader(sb, &tmx, nit, third);
      else if (warp == 9) conv_credit(sb, P0, nit, lane);
    }
  }
}

typedef CUresult (*PFN_encodeTiled)(CUtensorMap*, CUtensorMapDataType, cuuint32_t, void*, const cuuint64_t*, const cuuint64_t*, const cuuint32_t*, const cuuint32_t*,
                                    CUtensorMapInterleave, CUtensorMapSwizzle, CUtensorMapL2promotion, CUtensorMapFloatOOBfill);

extern "C" void kernel_launch(void* const* d_in, const int* in_sizes, int n_in, void* d_out, int out_size) {
  const __nv_bfloat16* x = (const __nv_bfloat16*)d_in[0];
  const __nv_bfloat16* dw = (const __nv_bfloat16*)d_in[1];
  const __nv_bfloat16* w1 = (const __nv_bfloat16*)d_in[2];
  const __nv_bfloat16* w2 = (const __nv_bfloat16*)d_in[3];
  static PFN_encodeTiled encode = nullptr;
  static int nsm = 0;
  if (!encode) {
    void* fn = nullptr; cudaDriverEntryPointQueryResult qr;
    cudaGetDriverEntryPoint("cuTensorMapEncodeTiled", &fn, cudaEnableDefault, &qr);
    encode = (PFN_encodeTiled)fn;
    int dev = 0; cudaGetDevice(&dev);
    cudaDeviceGetAttribute(&nsm, cudaDevAttrMultiProcessorCount, dev);
    cudaFuncSetAttribute(convnext_kernel, cudaFuncAttributeMaxDynamicSharedMemorySize, SMEM_BYTES);
  }
  CUtensorMap tm;
  cuuint64_t dims[3] = {96, 512, 512}, strides[2] = {192, 192 * 512};
  cuuint32_t box[3] = {32, 70, 2}, es[3] = {1, 1, 1};
  encode(&tm, CU_TENSOR_MAP_DATA_TYPE_BFLOAT16, 3, (void*)x, dims, strides, box, es, CU_TENSOR_MAP_INTERLEAVE_NONE, CU_TENSOR_MAP_SWIZZLE_64B,
         PROMO, CU_TENSOR_MAP_FLOAT_OOB_FILL_NONE);
  convnext_kernel<<<nsm, 512, SMEM_BYTES>>>(tm, x, dw, w1, w2, (__nv_bfloat16*)d_out);
}
```

```cpp
#include <cuda_runtime.h>
#include <cuda_bf16.h>
#include <cuda.h>
#include <stdint.h>

template<int SCALE_D> __device__ __forceinline__ void wgmma_n48_f16(uint32_t* d, const uint32_t* a, uint64_t desc) {
  if (SCALE_D == 0) asm volatile("wgmma.mma_async.sync.aligned.m64n48k16.f16.f16.f16 {%0,%1,%2,%3,%4,%5,%6,%7,%8,%9,%10,%11}, {%12,%13,%14,%15}, %16, 0, 1, 1, 1;"
    : "=r"(d[0]),"=r"(d[1]),"=r"(d[2]),"=r"(d[3]),"=r"(d[4]),"=r"(d[5]),"=r"(d[6]),"=r"(d[7]),"=r"(d[8]),"=r"(d[9]),"=r"(d[10]),"=r"(d[11])
    : "r"(a[0]),"r"(a[1]),"r"(a[2]),"r"(a[3]),"l"(desc));
  if (SCALE_D == 1) asm volatile("wgmma.mma_async.sync.aligned.m64n48k16.f16.f16.f16 {%0,%1,%2,%3,%4,%5,%6,%7,%8,%9,%10,%11}, {%12,%13,%14,%15}, %16, 1, 1, 1, 1;"
    : "+r"(d[0]),"+r"(d[1]),"+r"(d[2]),"+r"(d[3]),"+r"(d[4]),"+r"(d[5]),"+r"(d[6]),"+r"(d[7]),"+r"(d[8]),"+r"(d[9]),"+r"(d[10]),"+r"(d[11])
    : "r"(a[0]),"r"(a[1]),"r"(a[2]),"r"(a[3]),"l"(desc));
}

template<int SCALE_D> __device__ __forceinline__ void wgmma_n96_f16(uint32_t* d, const uint32_t* a, uint64_t desc) {
  if (SCALE_D == 0) asm volatile("wgmma.mma_async.sync.aligned.m64n96k16.f16.f16.f16 {%0,%1,%2,%3,%4,%5,%6,%7,%8,%9,%10,%11,%12,%13,%14,%15,%16,%17,%18,%19,%20,%21,%22,%23}, {%24,%25,%26,%27}, %28, 0, 1, 1, 1;"
    : "=r"(d[0]),"=r"(d[1]),"=r"(d[2]),"=r"(d[3]),"=r"(d[4]),"=r"(d[5]),"=r"(d[6]),"=r"(d[7]),"=r"(d[8]),"=r"(d[9]),"=r"(d[10]),"=r"(d[11]),"=r"(d[12]),"=r"(d[13]),"=r"(d[14]),"=r"(d[15]),"=r"(d[16]),"=r"(d[17]),"=r"(d[18]),"=r"(d[19]),"=r"(d[20]),"=r"(d[21]),"=r"(d[22]),"=r"(d[23])
    : "r"(a[0]),"r"(a[1]),"r"(a[2]),"r"(a[3]),"l"(desc));
  if (SCALE_D == 1) asm volatile("wgmma.mma_async.sync.aligned.m64n96k16.f16.f16.f16 {%0,%1,%2,%3,%4,%5,%6,%7,%8,%9,%10,%11,%12,%13,%14,%15,%16,%17,%18,%19,%20,%21,%22,%23}, {%24,%25,%26,%27}, %28, 1, 1, 1, 1;"
    : "+r"(d[0]),"+r"(d[1]),"+r"(d[2]),"+r"(d[3]),"+r"(d[4]),"+r"(d[5]),"+r"(d[6]),"+r"(d[7]),"+r"(d[8]),"+r"(d[9]),"+r"(d[10]),"+r"(d[11]),"+r"(d[12]),"+r"(d[13]),"+r"(d[14]),"+r"(d[15]),"+r"(d[16]),"+r"(d[17]),"+r"(d[18]),"+r"(d[19]),"+r"(d[20]),"+r"(d[21]),"+r"(d[22]),"+r"(d[23])
    : "r"(a[0]),"r"(a[1]),"r"(a[2]),"r"(a[3]),"l"(desc));
}

__device__ const uint16_t g_sched[132][48] = {
{65535,65535,65535,65535,65535,65535,65535,65535,65535,65535,65535,65535,65535,65535,65535,65535,65535,65535,65535,65535,65535,65535,65535,65535,65535,65535,65535,65535,65535,65535,65535,65535,65535,65535,65535,65535,65535,65535,65535,65535,65535,65535,65535,65535,65535,65535,65535,65535},
{0,12,3665,35,47,59,70,82,94,105,117,129,3779,152,164,176,187,199,211,222,234,246,3893,269,281,293,304,316,328,339,351,363,4008,386,398,410,421,433,445,65535,65535,65535,65535,65535,65535,65535,65535,65535},
{65535,65535,65535,65535,65535,65535,65535,65535,65535,65535,65535,65535,65535,65535,65535,65535,65535,65535,65535,65535,65535,65535,65535,65535,65535,65535,65535,65535,65535,65535,65535,65535,65535,65535,65535,65535,65535,65535,65535,65535,65535,65535,65535,65535,65535,65535,65535,65535},
{456,468,3666,491,503,515,526,538,550,561,573,585,3780,608,620,632,643,655,667,678,690,702,3894,725,737,749,760,772,784,795,807,819,4009,842,854,866,877,889,901,65535,65535,65535,65535,65535,65535,65535,65535,65535},
{65535,65535,65535,65535,65535,65535,65535,65535,65535,65535,65535,65535,65535,65535,65535,65535,65535,65535,65535,65535,65535,65535,65535,65535,65535,65535,65535,65535,65535,65535,65535,65535,65535,65535,65535,65535,65535,65535,65535,65535,65535,65535,65535,65535,65535,65535,65535,65535},
{912,924,3667,947,959,971,982,994,1006,1017,1029,1041,3781,1064,1076,1088,1099,1111,1123,1134,1146,1158,3895,1181,1193,1205,1216,1228,1240,1251,1263,1275,4010,1298,1310,1322,1333,1345,1357,65535,65535,65535,65535,65535,65535,65535,65535,65535},
{65535,65535,65535,65535,65535,65535,65535,65535,65535,65535,65535,65535,65535,65535,65535,65535,65535,65535,65535,65535,65535,65535,65535,65535,65535,65535,65535,65535,65535,65535,65535,65535,65535,65535,65535,65535,65535,65535,65535,65535,65535,65535,65535,65535,65535,65535,65535,65535},
{1368,1380,3668,1403,1415,1427,1438,1450,1462,1473,1485,1497,3782,1520,1532,1544,1555,1567,1579,1590,1602,1614,3896,1637,1649,1661,1672,1684,1696,1707,1719,1731,4011,1754,1766,1778,1789,1801,1813,65535,65535,65535,65535,65535,65535,65535,65535,65535},
{65535,65535,65535,65535,65535,65535,65535,65535,65535,65535,65535,65535,65535,65535,65535,65535,65535,65535,65535,65535,65535,65535,65535,65535,65535,65535,65535,65535,65535,65535,65535,65535,65535,65535,65535,65535,65535,65535,65535,65535,65535,65535,65535,65535,65535,65535,65535,65535},
{1824,1836,3669,1859,1871,1883,1894,1906,1918,1929,1941,1953,3783,1976,1988,2000,2011,2023,2035,2046,2058,2070,3897,2093,2105,2117,2128,2140,2152,2163,2175,2187,4012,2210,2222,2234,2245,2257,2269,65535,65535,65535,65535,65535,65535,65535,65535,65535},
{65535,65535,65535,65535,65535,65535,65535,65535,65535,65535,65535,65535,65535,65535,65535,65535,65535,65535,65535,65535,65535,65535,65535,65535,65535,65535,65535,65535,65535,65535,65535,65535,65535,65535,65535,65535,65535,65535,65535,65535,65535,65535,65535,65535,65535,65535,65535,65535},
{2280,2292,3670,2315,2327,2339,2350,2362,2374,2385,2397,2409,3784,2432,2444,2456,2467,2479,2491,2502,2514,2526,3898,2549,2561,2573,2584,2596,2608,2619,2631,2643,4013,2666,2678,2690,2701,2713,2725,65535,65535,65535,65535,65535,65535,65535,65535,65535},
{65535,65535,65535,65535,65535,65535,65535,65535,65535,65535,65535,65535,65535,65535,65535,65535,65535,65535,65535,65535,65535,65535,65535,65535,65535,65535,65535,65535,65535,65535,65535,65535,65535,65535,65535,65535,65535,65535,65535,65535,65535,65535,65535,65535,65535,65535,65535,65535},
{2736,2748,3671,2771,2783,2795,2806,2818,2830,2841,2853,2865,3785,2888,2900,2912,2923,2935,2947,2958,2970,2982,3899,3005,3017,3029,3040,3052,3064,3075,3087,3099,4014,3122,3134,3146,3157,3169,3181,65535,65535,65535,65535,65535,65535,65535,65535,65535},
{65535,65535,65535,65535,65535,65535,65535,65535,65535,65535,65535,65535,65535,65535,65535,65535,65535,65535,65535,65535,65535,65535,65535,65535,65535,65535,65535,65535,65535,65535,65535,65535,65535,65535,65535,65535,65535,65535,65535,65535,65535,65535,65535,65535,65535,65535,65535,65535},
{3192,3204,3672,3227,3239,3251,3262,3274,3286,3297,3309,3321,3786,3344,3356,3368,3379,3391,3403,3414,3426,3438,3900,3461,3473,3485,3496,3508,3520,3531,3543,3555,4015,3578,3590,3602,3613,3625,3637,65535,65535,65535,65535,65535,65535,65535,65535,65535},
{65535,65535,65535,65535,65535,65535,65535,65535,65535,65535,65535,65535,65535,65535,65535,65535,65535,65535,65535,65535,65535,65535,65535,65535,65535,65535,65535,65535,65535,65535,65535,65535,65535,65535,65535,65535,65535,65535,65535,65535,65535,65535,65535,65535,65535,65535,65535,65535},
{1,13,24,36,48,3700,71,83,95,106,118,130,141,153,165,3814,188,200,212,223,235,247,258,270,282,3929,305,317,329,340,352,364,375,387,399,4043,422,434,446,65535,65535,65535,65535,65535,65535,65535,65535,65535},
{65535,65535,65535,65535,65535,65535,65535,65535,65535,65535,65535,65535,65535,65535,65535,65535,65535,65535,65535,65535,65535,65535,65535,65535,65535,65535,65535,65535,65535,65535,65535,65535,65535,65535,65535,65535,65535,65535,65535,65535,65535,65535,65535,65535,65535,65535,65535,65535},
{457,469,480,492,504,3701,527,539,551,562,574,586,597,609,621,3815,644,656,668,679,691,703,714,726,738,3930,761,773,785,796,808,820,831,843,855,4044,878,890,902,65535,65535,65535,65535,65535,65535,65535,65535,65535},
{65535,65535,65535,65535,65535,65535,65535,65535,65535,65535,65535,65535,65535,65535,65535,65535,65535,65535,65535,65535,65535,65535,65535,65535,65535,65535,65535,65535,65535,65535,65535,65535,65535,65535,65535,65535,65535,65535,65535,65535,65535,65535,65535,65535,65535,65535,65535,65535},
{913,925,936,948,960,3702,983,995,1007,1018,1030,1042,1053,1065,1077,3816,1100,1112,1124,1135,1147,1159,1170,1182,1194,3931,1217,1229,1241,1252,1264,1276,1287,1299,1311,4045,1334,1346,1358,65535,65535,65535,65535,65535,65535,65535,65535,65535},
{65535,65535,65535,65535,65535,65535,65535,65535,65535,65535,65535,65535,65535,65535,65535,65535,65535,65535,65535,65535,65535,65535,65535,65535,65535,65535,65535,65535,65535,65535,65535,65535,65535,65535,65535,65535,65535,65535,65535,65535,65535,65535,65535,65535,65535,65535,65535,65535},
{1369,1381,1392,1404,1416,3703,1439,1451,1463,1474,1486,1498,1509,1521,1533,3817,1556,1568,1580,1591,1603,1615,1626,1638,1650,3932,1673,1685,1697,1708,1720,1732,1743,1755,1767,4046,1790,1802,1814,65535,65535,65535,65535,65535,65535,65535,65535,65535},
{65535,65535,65535,65535,65535,65535,65535,65535,65535,65535,65535,65535,65535,65535,65535,65535,65535,65535,65535,65535,65535,65535,65535,65535,65535,65535,65535,65535,65535,65535,65535,65535,65535,65535,65535,65535,65535,65535,65535,65535,65535,65535,65535,65535,65535,65535,65535,65535},
{1825,1837,1848,1860,1872,3704,1895,1907,1919,1930,1942,1954,1965,1977,1989,3818,2012,2024,2036,2047,2059,2071,2082,2094,2106,3933,2129,2141,2153,2164,2176,2188,2199,2211,2223,4047,2246,2258,2270,65535,65535,65535,65535,65535,65535,65535,65535,65535},
{65535,65535,65535,65535,65535,65535,65535,65535,65535,65535,65535,65535,65535,65535,65535,65535,65535,65535,65535,65535,65535,65535,65535,65535,65535,65535,65535,65535,65535,65535,65535,65535,65535,65535,65535,65535,65535,65535,65535,65535,65535,65535,65535,65535,65535,65535,65535,65535},
{2281,2293,2304,2316,2328,3705,2351,2363,2375,2386,2398,2410,2421,2433,2445,3819,2468,2480,2492,2503,2515,2527,2538,2550,2562,3934,2585,2597,2609,2620,2632,2644,2655,2667,2679,4048,2702,2714,2726,65535,65535,65535,65535,65535,65535,65535,65535,65535},
{65535,65535,65535,65535,65535,65535,65535,65535,65535,65535,65535,65535,65535,65535,65535,65535,65535,65535,65535,65535,65535,65535,65535,65535,65535,65535,65535,65535,65535,65535,65535,65535,65535,65535,65535,65535,65535,65535,65535,65535,65535,65535,65535,65535,65535,65535,65535,65535},
{2737,2749,2760,2772,2784,3706,2807,2819,2831,2842,2854,2866,2877,2889,2901,3820,2924,2936,2948,2959,2971,2983,2994,3006,3018,3935,3041,3053,3065,3076,3088,3100,3111,3123,3135,4049,3158,3170,3182,65535,65535,65535,65535,65535,65535,65535,65535,65535},
{65535,65535,65535,65535,65535,65535,65535,65535,65535,65535,65535,65535,65535,65535,65535,65535,65535,65535,65535,65535,65535,65535,65535,65535,65535,65535,65535,65535,65535,65535,65535,65535,65535,65535,65535,65535,65535,65535,65535,65535,65535,65535,65535,65535,65535,65535,65535,65535},
{3193,3205,3216,3228,3240,3707,3263,3275,3287,3298,3310,3322,3333,3345,3357,3821,3380,3392,3404,3415,3427,3439,3450,3462,3474,3936,3497,3509,3521,3532,3544,3556,3567,3579,3591,4050,3614,3626,3638,65535,65535,65535,65535,65535,65535,65535,65535,65535},
{65535,65535,65535,65535,65535,65535,65535,65535,65535,65535,65535,65535,65535,65535,65535,65535,65535,65535,65535,65535,65535,65535,65535,65535,65535,65535,65535,65535,65535,65535,65535,65535,65535,65535,65535,65535,65535,65535,65535,65535,65535,65535,65535,65535,65535,65535,65535,65535},
{2,14,25,37,49,60,72,84,3735,107,119,131,142,154,166,177,189,201,3850,224,236,248,259,271,283,294,306,318,3964,341,353,365,376,388,400,411,423,435,4078,65535,65535,65535,65535,65535,65535,65535,65535,65535},
{65535,65535,65535,65535,65535,65535,65535,65535,65535,65535,65535,65535,65535,65535,65535,65535,65535,65535,65535,65535,65535,65535,65535,65535,65535,65535,65535,65535,65535,65535,65535,65535,65535,65535,65535,65535,65535,65535,65535,65535,65535,65535,65535,65535,65535,65535,65535,65535},
{458,470,481,493,505,516,528,540,3736,563,575,587,598,610,622,633,645,657,3851,680,692,704,715,727,739,750,762,774,3965,797,809,821,832,844,856,867,879,891,4079,65535,65535,65535,65535,65535,65535,65535,65535,65535},
{65535,65535,65535,65535,65535,65535,65535,65535,65535,65535,65535,65535,65535,65535,65535,65535,65535,65535,65535,65535,65535,65535,65535,65535,65535,65535,65535,65535,65535,65535,65535,65535,65535,65535,65535,65535,65535,65535,65535,65535,65535,65535,65535,65535,65535,65535,65535,65535},
{914,926,937,949,961,972,984,996,3737,1019,1031,1043,1054,1066,1078,1089,1101,1113,3852,1136,1148,1160,1171,1183,1195,1206,1218,1230,3966,1253,1265,1277,1288,1300,1312,1323,1335,1347,4080,65535,65535,65535,65535,65535,65535,65535,65535,65535},
{65535,65535,65535,65535,65535,65535,65535,65535,65535,65535,65535,65535,65535,65535,65535,65535,65535,65535,65535,65535,65535,65535,65535,65535,65535,65535,65535,65535,65535,65535,65535,65535,65535,65535,65535,65535,65535,65535,65535,65535,65535,65535,65535,65535,65535,65535,65535,65535},
{1370,1382,1393,1405,1417,1428,1440,1452,3738,1475,1487,1499,1510,1522,1534,1545,1557,1569,3853,1592,1604,1616,1627,1639,1651,1662,1674,1686,3967,1709,1721,1733,1744,1756,1768,1779,1791,1803,4081,65535,65535,65535,65535,65535,65535,65535,65535,65535},
{65535,65535,65535,65535,65535,65535,65535,65535,65535,65535,65535,65535,65535,65535,65535,65535,65535,65535,65535,65535,65535,65535,65535,65535,65535,65535,65535,65535,65535,65535,65535,65535,65535,65535,65535,65535,65535,65535,65535,65535,65535,65535,65535,65535,65535,65535,65535,65535},
{1826,1838,1849,1861,1873,1884,1896,1908,3739,1931,1943,1955,1966,1978,1990,2001,2013,2025,3854,2048,2060,2072,2083,2095,2107,2118,2130,2142,3968,2165,2177,2189,2200,2212,2224,2235,2247,2259,4082,65535,65535,65535,65535,65535,65535,65535,65535,65535},
{65535,65535,65535,65535,65535,65535,65535,65535,65535,65535,65535,65535,65535,65535,65535,65535,65535,65535,65535,65535,65535,65535,65535,65535,65535,65535,65535,65535,65535,65535,65535,65535,65535,65535,65535,65535,65535,65535,65535,65535,65535,65535,65535,65535,65535,65535,65535,65535},
{2282,2294,2305,2317,2329,2340,2352,2364,3740,2387,2399,2411,2422,2434,2446,2457,2469,2481,3855,2504,2516,2528,2539,2551,2563,2574,2586,2598,3969,2621,2633,2645,2656,2668,2680,2691,2703,2715,4083,65535,65535,65535,65535,65535,65535,65535,65535,65535},
{65535,65535,65535,65535,65535,65535,65535,65535,65535,65535,65535,65535,65535,65535,65535,65535,65535,65535,65535,65535,65535,65535,65535,65535,65535,65535,65535,65535,65535,65535,65535,65535,65535,65535,65535,65535,65535,65535,65535,65535,65535,65535,65535,65535,65535,65535,65535,65535},
{2738,2750,2761,2773,2785,2796,2808,2820,3741,2843,2855,2867,2878,2890,2902,2913,2925,2937,3856,2960,2972,2984,2995,3007,3019,3030,3042,3054,3970,3077,3089,3101,3112,3124,3136,3147,3159,3171,4084,65535,65535,65535,65535,65535,65535,65535,65535,65535},
{65535,65535,65535,65535,65535,65535,65535,65535,65535,65535,65535,65535,65535,65535,65535,65535,65535,65535,65535,65535,65535,65535,65535,65535,65535,65535,65535,65535,65535,65535,65535,65535,65535,65535,65535,65535,65535,65535,65535,65535,65535,65535,65535,65535,65535,65535,65535,65535},
{3194,3206,3217,3229,3241,3252,3264,3276,3742,3299,3311,3323,3334,3346,3358,3369,3381,3393,3857,3416,3428,3440,3451,3463,3475,3486,3498,3510,3971,3533,3545,3557,3568,3580,3592,3603,3615,3627,4085,65535,65535,65535,65535,65535,65535,65535,65535,65535},
{3,3656,26,38,50,61,73,85,96,108,120,3770,143,155,167,178,190,202,213,225,237,3885,260,272,284,295,307,319,330,342,354,3999,377,389,401,412,424,436,447,65535,65535,65535,65535,65535,65535,65535,65535,65535},
{4,15,27,39,3691,62,74,86,97,109,121,132,144,156,3806,179,191,203,214,226,238,249,261,273,3920,296,308,320,331,343,355,366,378,390,4034,413,425,437,448,65535,65535,65535,65535,65535,65535,65535,65535,65535},
{459,3657,482,494,506,517,529,541,552,564,576,3771,599,611,623,634,646,658,669,681,693,3886,716,728,740,751,763,775,786,798,810,4000,833,845,857,868,880,892,903,65535,65535,65535,65535,65535,65535,65535,65535,65535},
{460,471,483,495,3692,518,530,542,553,565,577,588,600,612,3807,635,647,659,670,682,694,705,717,729,3921,752,764,776,787,799,811,822,834,846,4035,869,881,893,904,65535,65535,65535,65535,65535,65535,65535,65535,65535},
{915,3658,938,950,962,973,985,997,1008,1020,1032,3772,1055,1067,1079,1090,1102,1114,1125,1137,1149,3887,1172,1184,1196,1207,1219,1231,1242,1254,1266,4001,1289,1301,1313,1324,1336,1348,1359,65535,65535,65535,65535,65535,65535,65535,65535,65535},
{916,927,939,951,3693,974,986,998,1009,1021,1033,1044,1056,1068,3808,1091,1103,1115,1126,1138,1150,1161,1173,1185,3922,1208,1220,1232,1243,1255,1267,1278,1290,1302,4036,1325,1337,1349,1360,65535,65535,65535,65535,65535,65535,65535,65535,65535},
{1371,3659,1394,1406,1418,1429,1441,1453,1464,1476,1488,3773,1511,1523,1535,1546,1558,1570,1581,1593,1605,3888,1628,1640,1652,1663,1675,1687,1698,1710,1722,4002,1745,1757,1769,1780,1792,1804,1815,65535,65535,65535,65535,65535,65535,65535,65535,65535},
{1372,1383,1395,1407,3694,1430,1442,1454,1465,1477,1489,1500,1512,1524,3809,1547,1559,1571,1582,1594,1606,1617,1629,1641,3923,1664,1676,1688,1699,1711,1723,1734,1746,1758,4037,1781,1793,1805,1816,65535,65535,65535,65535,65535,65535,65535,65535,65535},
{1827,3660,1850,1862,1874,1885,1897,1909,1920,1932,1944,3774,1967,1979,1991,2002,2014,2026,2037,2049,2061,3889,2084,2096,2108,2119,2131,2143,2154,2166,2178,4003,2201,2213,2225,2236,2248,2260,2271,65535,65535,65535,65535,65535,65535,65535,65535,65535},
{1828,1839,1851,1863,3695,1886,1898,1910,1921,1933,1945,1956,1968,1980,3810,2003,2015,2027,2038,2050,2062,2073,2085,2097,3924,2120,2132,2144,2155,2167,2179,2190,2202,2214,4038,2237,2249,2261,2272,65535,65535,65535,65535,65535,65535,65535,65535,65535},
{2283,3661,2306,2318,2330,2341,2353,2365,2376,2388,2400,3775,2423,2435,2447,2458,2470,2482,2493,2505,2517,3890,2540,2552,2564,2575,2587,2599,2610,2622,2634,4004,2657,2669,2681,2692,2704,2716,2727,65535,65535,65535,65535,65535,65535,65535,65535,65535},
{2284,2295,2307,2319,3696,2342,2354,2366,2377,2389,2401,2412,2424,2436,3811,2459,2471,2483,2494,2506,2518,2529,2541,2553,3925,2576,2588,2600,2611,2623,2635,2646,2658,2670,4039,2693,2705,2717,2728,65535,65535,65535,65535,65535,65535,65535,65535,65535},
{65535,65535,65535,65535,65535,65535,65535,65535,65535,65535,65535,65535,65535,65535,65535,65535,65535,65535,65535,65535,65535,65535,65535,65535,65535,65535,65535,65535,65535,65535,65535,65535,65535,65535,65535,65535,65535,65535,65535,65535,65535,65535,65535,65535,65535,65535,65535,65535},
{2739,3662,2762,2774,2786,2797,2809,2821,2832,2844,2856,3776,2879,2891,2903,2914,2926,2938,2949,2961,2973,3891,2996,3008,3020,3031,3043,3055,3066,3078,3090,4005,3113,3125,3137,3148,3160,3172,3183,65535,65535,65535,65535,65535,65535,65535,65535,65535},
{3195,3663,3218,3230,3242,3253,3265,3277,3288,3300,3312,3777,3335,3347,3359,3370,3382,3394,3405,3417,3429,3892,3452,3464,3476,3487,3499,3511,3522,3534,3546,4006,3569,3581,3593,3604,3616,3628,3639,65535,65535,65535,65535,65535,65535,65535,65535,65535},
{3196,3207,3219,3231,3698,3254,3266,3278,3289,3301,3313,3324,3336,3348,3813,3371,3383,3395,3406,3418,3430,3441,3453,3465,3927,3488,3500,3512,3523,3535,3547,3558,3570,3582,4041,3605,3617,3629,3640,65535,65535,65535,65535,65535,65535,65535,65535,65535},
{461,472,484,496,507,519,531,3728,554,566,578,589,601,613,624,636,648,3842,671,683,695,706,718,730,741,753,765,3956,788,800,812,823,835,847,858,870,882,4070,905,65535,65535,65535,65535,65535,65535,65535,65535,65535},
{3649,473,485,497,508,520,532,543,555,567,3763,590,602,614,625,637,649,660,672,684,3877,707,719,731,742,754,766,777,789,801,3991,824,836,848,859,871,883,894,906,65535,65535,65535,65535,65535,65535,65535,65535,65535},
{917,928,940,952,963,975,987,3729,1010,1022,1034,1045,1057,1069,1080,1092,1104,3843,1127,1139,1151,1162,1174,1186,1197,1209,1221,3957,1244,1256,1268,1279,1291,1303,1314,1326,1338,4071,1361,65535,65535,65535,65535,65535,65535,65535,65535,65535},
{3650,929,941,953,964,976,988,999,1011,1023,3764,1046,1058,1070,1081,1093,1105,1116,1128,1140,3878,1163,1175,1187,1198,1210,1222,1233,1245,1257,3992,1280,1292,1304,1315,1327,1339,1350,1362,65535,65535,65535,65535,65535,65535,65535,65535,65535},
{1373,1384,1396,1408,1419,1431,1443,3730,1466,1478,1490,1501,1513,1525,1536,1548,1560,3844,1583,1595,1607,1618,1630,1642,1653,1665,1677,3958,1700,1712,1724,1735,1747,1759,1770,1782,1794,4072,1817,65535,65535,65535,65535,65535,65535,65535,65535,65535},
{3651,1385,1397,1409,1420,1432,1444,1455,1467,1479,3765,1502,1514,1526,1537,1549,1561,1572,1584,1596,3879,1619,1631,1643,1654,1666,1678,1689,1701,1713,3993,1736,1748,1760,1771,1783,1795,1806,1818,65535,65535,65535,65535,65535,65535,65535,65535,65535},
{1829,1840,1852,1864,1875,1887,1899,3731,1922,1934,1946,1957,1969,1981,1992,2004,2016,3845,2039,2051,2063,2074,2086,2098,2109,2121,2133,3959,2156,2168,2180,2191,2203,2215,2226,2238,2250,4073,2273,65535,65535,65535,65535,65535,65535,65535,65535,65535},
{3652,1841,1853,1865,1876,1888,1900,1911,1923,1935,3766,1958,1970,1982,1993,2005,2017,2028,2040,2052,3880,2075,2087,2099,2110,2122,2134,2145,2157,2169,3994,2192,2204,2216,2227,2239,2251,2262,2274,65535,65535,65535,65535,65535,65535,65535,65535,65535},
{2285,2296,2308,2320,2331,2343,2355,3732,2378,2390,2402,2413,2425,2437,2448,2460,2472,3846,2495,2507,2519,2530,2542,2554,2565,2577,2589,3960,2612,2624,2636,2647,2659,2671,2682,2694,2706,4074,2729,65535,65535,65535,65535,65535,65535,65535,65535,65535},
{3653,2297,2309,2321,2332,2344,2356,2367,2379,2391,3767,2414,2426,2438,2449,2461,2473,2484,2496,2508,3881,2531,2543,2555,2566,2578,2590,2601,2613,2625,3995,2648,2660,2672,2683,2695,2707,2718,2730,65535,65535,65535,65535,65535,65535,65535,65535,65535},
{2740,2751,2763,2775,3697,2798,2810,2822,2833,2845,2857,2868,2880,2892,3812,2915,2927,2939,2950,2962,2974,2985,2997,3009,3926,3032,3044,3056,3067,3079,3091,3102,3114,3126,4040,3149,3161,3173,3184,65535,65535,65535,65535,65535,65535,65535,65535,65535},
{2741,2752,2764,2776,2787,2799,2811,3733,2834,2846,2858,2869,2881,2893,2904,2916,2928,3847,2951,2963,2975,2986,2998,3010,3021,3033,3045,3961,3068,3080,3092,3103,3115,3127,3138,3150,3162,4075,3185,65535,65535,65535,65535,65535,65535,65535,65535,65535},
{3197,3208,3220,3232,3243,3255,3267,3734,3290,3302,3314,3325,3337,3349,3360,3372,3384,3848,3407,3419,3431,3442,3454,3466,3477,3489,3501,3962,3524,3536,3548,3559,3571,3583,3594,3606,3618,4076,3641,65535,65535,65535,65535,65535,65535,65535,65535,65535},
{3655,3209,3221,3233,3244,3256,3268,3279,3291,3303,3769,3326,3338,3350,3361,3373,3385,3396,3408,3420,3883,3443,3455,3467,3478,3490,3502,3513,3525,3537,3997,3560,3572,3584,3595,3607,3619,3630,3642,65535,65535,65535,65535,65535,65535,65535,65535,65535},
{462,474,486,3684,509,521,533,544,556,568,579,591,603,3798,626,638,650,661,673,685,696,708,720,3912,743,755,767,778,790,802,813,825,837,4026,860,872,884,895,907,65535,65535,65535,65535,65535,65535,65535,65535,65535},
{463,475,487,498,510,522,3719,545,557,569,580,592,604,615,627,639,3833,662,674,686,697,709,721,732,744,756,3947,779,791,803,814,826,838,849,861,873,4061,896,908,65535,65535,65535,65535,65535,65535,65535,65535,65535},
{918,930,942,3685,965,977,989,1000,1012,1024,1035,1047,1059,3799,1082,1094,1106,1117,1129,1141,1152,1164,1176,3913,1199,1211,1223,1234,1246,1258,1269,1281,1293,4027,1316,1328,1340,1351,1363,65535,65535,65535,65535,65535,65535,65535,65535,65535},
{919,931,943,954,966,978,3720,1001,1013,1025,1036,1048,1060,1071,1083,1095,3834,1118,1130,1142,1153,1165,1177,1188,1200,1212,3948,1235,1247,1259,1270,1282,1294,1305,1317,1329,4062,1352,1364,65535,65535,65535,65535,65535,65535,65535,65535,65535},
{1374,1386,1398,3686,1421,1433,1445,1456,1468,1480,1491,1503,1515,3800,1538,1550,1562,1573,1585,1597,1608,1620,1632,3914,1655,1667,1679,1690,1702,1714,1725,1737,1749,4028,1772,1784,1796,1807,1819,65535,65535,65535,65535,65535,65535,65535,65535,65535},
{1375,1387,1399,1410,1422,1434,3721,1457,1469,1481,1492,1504,1516,1527,1539,1551,3835,1574,1586,1598,1609,1621,1633,1644,1656,1668,3949,1691,1703,1715,1726,1738,1750,1761,1773,1785,4063,1808,1820,65535,65535,65535,65535,65535,65535,65535,65535,65535},
{1830,1842,1854,3687,1877,1889,1901,1912,1924,1936,1947,1959,1971,3801,1994,2006,2018,2029,2041,2053,2064,2076,2088,3915,2111,2123,2135,2146,2158,2170,2181,2193,2205,4029,2228,2240,2252,2263,2275,65535,65535,65535,65535,65535,65535,65535,65535,65535},
{1831,1843,1855,1866,1878,1890,3722,1913,1925,1937,1948,1960,1972,1983,1995,2007,3836,2030,2042,2054,2065,2077,2089,2100,2112,2124,3950,2147,2159,2171,2182,2194,2206,2217,2229,2241,4064,2264,2276,65535,65535,65535,65535,65535,65535,65535,65535,65535},
{2286,2298,2310,3688,2333,2345,2357,2368,2380,2392,2403,2415,2427,3802,2450,2462,2474,2485,2497,2509,2520,2532,2544,3916,2567,2579,2591,2602,2614,2626,2637,2649,2661,4030,2684,2696,2708,2719,2731,65535,65535,65535,65535,65535,65535,65535,65535,65535},
{2287,2299,2311,2322,2334,2346,3723,2369,2381,2393,2404,2416,2428,2439,2451,2463,3837,2486,2498,2510,2521,2533,2545,2556,2568,2580,3951,2603,2615,2627,2638,2650,2662,2673,2685,2697,4065,2720,2732,65535,65535,65535,65535,65535,65535,65535,65535,65535},
{3654,2753,2765,2777,2788,2800,2812,2823,2835,2847,3768,2870,2882,2894,2905,2917,2929,2940,2952,2964,3882,2987,2999,3011,3022,3034,3046,3057,3069,3081,3996,3104,3116,3128,3139,3151,3163,3174,3186,65535,65535,65535,65535,65535,65535,65535,65535,65535},
{2742,2754,2766,3689,2789,2801,2813,2824,2836,2848,2859,2871,2883,3803,2906,2918,2930,2941,2953,2965,2976,2988,3000,3917,3023,3035,3047,3058,3070,3082,3093,3105,3117,4031,3140,3152,3164,3175,3187,65535,65535,65535,65535,65535,65535,65535,65535,65535},
{3198,3210,3222,3690,3245,3257,3269,3280,3292,3304,3315,3327,3339,3804,3362,3374,3386,3397,3409,3421,3432,3444,3456,3918,3479,3491,3503,3514,3526,3538,3549,3561,3573,4032,3596,3608,3620,3631,3643,65535,65535,65535,65535,65535,65535,65535,65535,65535},
{3199,3211,3223,3234,3246,3258,3725,3281,3293,3305,3316,3328,3340,3351,3363,3375,3839,3398,3410,3422,3433,3445,3457,3468,3480,3492,3953,3515,3527,3539,3550,3562,3574,3585,3597,3609,4067,3632,3644,65535,65535,65535,65535,65535,65535,65535,65535,65535},
{464,476,488,499,511,523,534,546,558,3754,581,593,605,616,628,640,651,663,675,3868,698,710,722,733,745,757,768,780,792,3982,815,827,839,850,862,874,885,897,909,65535,65535,65535,65535,65535,65535,65535,65535,65535},
{465,477,3675,500,512,524,535,547,559,570,582,594,3789,617,629,641,652,664,676,687,699,711,3903,734,746,758,769,781,793,804,816,828,4017,851,863,875,886,898,910,65535,65535,65535,65535,65535,65535,65535,65535,65535},
{920,932,944,955,967,979,990,1002,1014,3755,1037,1049,1061,1072,1084,1096,1107,1119,1131,3869,1154,1166,1178,1189,1201,1213,1224,1236,1248,3983,1271,1283,1295,1306,1318,1330,1341,1353,1365,65535,65535,65535,65535,65535,65535,65535,65535,65535},
{921,933,3676,956,968,980,991,1003,1015,1026,1038,1050,3790,1073,1085,1097,1108,1120,1132,1143,1155,1167,3904,1190,1202,1214,1225,1237,1249,1260,1272,1284,4018,1307,1319,1331,1342,1354,1366,65535,65535,65535,65535,65535,65535,65535,65535,65535},
{1376,1388,1400,1411,1423,1435,1446,1458,1470,3756,1493,1505,1517,1528,1540,1552,1563,1575,1587,3870,1610,1622,1634,1645,1657,1669,1680,1692,1704,3984,1727,1739,1751,1762,1774,1786,1797,1809,1821,65535,65535,65535,65535,65535,65535,65535,65535,65535},
{1377,1389,3677,1412,1424,1436,1447,1459,1471,1482,1494,1506,3791,1529,1541,1553,1564,1576,1588,1599,1611,1623,3905,1646,1658,1670,1681,1693,1705,1716,1728,1740,4019,1763,1775,1787,1798,1810,1822,65535,65535,65535,65535,65535,65535,65535,65535,65535},
{1832,1844,1856,1867,1879,1891,1902,1914,1926,3757,1949,1961,1973,1984,1996,2008,2019,2031,2043,3871,2066,2078,2090,2101,2113,2125,2136,2148,2160,3985,2183,2195,2207,2218,2230,2242,2253,2265,2277,65535,65535,65535,65535,65535,65535,65535,65535,65535},
{1833,1845,3678,1868,1880,1892,1903,1915,1927,1938,1950,1962,3792,1985,1997,2009,2020,2032,2044,2055,2067,2079,3906,2102,2114,2126,2137,2149,2161,2172,2184,2196,4020,2219,2231,2243,2254,2266,2278,65535,65535,65535,65535,65535,65535,65535,65535,65535},
{2288,2300,2312,2323,2335,2347,2358,2370,2382,3758,2405,2417,2429,2440,2452,2464,2475,2487,2499,3872,2522,2534,2546,2557,2569,2581,2592,2604,2616,3986,2639,2651,2663,2674,2686,2698,2709,2721,2733,65535,65535,65535,65535,65535,65535,65535,65535,65535},
{2289,2301,3679,2324,2336,2348,2359,2371,2383,2394,2406,2418,3793,2441,2453,2465,2476,2488,2500,2511,2523,2535,3907,2558,2570,2582,2593,2605,2617,2628,2640,2652,4021,2675,2687,2699,2710,2722,2734,65535,65535,65535,65535,65535,65535,65535,65535,65535},
{2743,2755,2767,2778,2790,2802,3724,2825,2837,2849,2860,2872,2884,2895,2907,2919,3838,2942,2954,2966,2977,2989,3001,3012,3024,3036,3952,3059,3071,3083,3094,3106,3118,3129,3141,3153,4066,3176,3188,65535,65535,65535,65535,65535,65535,65535,65535,65535},
{2744,2756,2768,2779,2791,2803,2814,2826,2838,3759,2861,2873,2885,2896,2908,2920,2931,2943,2955,3873,2978,2990,3002,3013,3025,3037,3048,3060,3072,3987,3095,3107,3119,3130,3142,3154,3165,3177,3189,65535,65535,65535,65535,65535,65535,65535,65535,65535},
{3200,3212,3224,3235,3247,3259,3270,3282,3294,3760,3317,3329,3341,3352,3364,3376,3387,3399,3411,3874,3434,3446,3458,3469,3481,3493,3504,3516,3528,3988,3551,3563,3575,3586,3598,3610,3621,3633,3645,65535,65535,65535,65535,65535,65535,65535,65535,65535},
{3201,3213,3681,3236,3248,3260,3271,3283,3295,3306,3318,3330,3795,3353,3365,3377,3388,3400,3412,3423,3435,3447,3909,3470,3482,3494,3505,3517,3529,3540,3552,3564,4023,3587,3599,3611,3622,3634,3646,65535,65535,65535,65535,65535,65535,65535,65535,65535},
{466,478,489,501,513,3710,536,548,560,571,583,595,606,618,630,3824,653,665,677,688,700,712,723,735,747,3938,770,782,794,805,817,829,840,852,864,4053,887,899,911,65535,65535,65535,65535,65535,65535,65535,65535,65535},
{467,479,490,502,514,525,537,549,3745,572,584,596,607,619,631,642,654,666,3859,689,701,713,724,736,748,759,771,783,3974,806,818,830,841,853,865,876,888,900,4088,65535,65535,65535,65535,65535,65535,65535,65535,65535},
{922,934,945,957,969,3711,992,1004,1016,1027,1039,1051,1062,1074,1086,3825,1109,1121,1133,1144,1156,1168,1179,1191,1203,3939,1226,1238,1250,1261,1273,1285,1296,1308,1320,4054,1343,1355,1367,65535,65535,65535,65535,65535,65535,65535,65535,65535},
{923,935,946,958,970,981,993,1005,3746,1028,1040,1052,1063,1075,1087,1098,1110,1122,3860,1145,1157,1169,1180,1192,1204,1215,1227,1239,3975,1262,1274,1286,1297,1309,1321,1332,1344,1356,4089,65535,65535,65535,65535,65535,65535,65535,65535,65535},
{1378,1390,1401,1413,1425,3712,1448,1460,1472,1483,1495,1507,1518,1530,1542,3826,1565,1577,1589,1600,1612,1624,1635,1647,1659,3940,1682,1694,1706,1717,1729,1741,1752,1764,1776,4055,1799,1811,1823,65535,65535,65535,65535,65535,65535,65535,65535,65535},
{1379,1391,1402,1414,1426,1437,1449,1461,3747,1484,1496,1508,1519,1531,1543,1554,1566,1578,3861,1601,1613,1625,1636,1648,1660,1671,1683,1695,3976,1718,1730,1742,1753,1765,1777,1788,1800,1812,4090,65535,65535,65535,65535,65535,65535,65535,65535,65535},
{1834,1846,1857,1869,1881,3713,1904,1916,1928,1939,1951,1963,1974,1986,1998,3827,2021,2033,2045,2056,2068,2080,2091,2103,2115,3941,2138,2150,2162,2173,2185,2197,2208,2220,2232,4056,2255,2267,2279,65535,65535,65535,65535,65535,65535,65535,65535,65535},
{1835,1847,1858,1870,1882,1893,1905,1917,3748,1940,1952,1964,1975,1987,1999,2010,2022,2034,3862,2057,2069,2081,2092,2104,2116,2127,2139,2151,3977,2174,2186,2198,2209,2221,2233,2244,2256,2268,4091,65535,65535,65535,65535,65535,65535,65535,65535,65535},
{2290,2302,2313,2325,2337,3714,2360,2372,2384,2395,2407,2419,2430,2442,2454,3828,2477,2489,2501,2512,2524,2536,2547,2559,2571,3942,2594,2606,2618,2629,2641,2653,2664,2676,2688,4057,2711,2723,2735,65535,65535,65535,65535,65535,65535,65535,65535,65535},
{2291,2303,2314,2326,2338,2349,2361,2373,3749,2396,2408,2420,2431,2443,2455,2466,2478,2490,3863,2513,2525,2537,2548,2560,2572,2583,2595,2607,3978,2630,2642,2654,2665,2677,2689,2700,2712,2724,4092,65535,65535,65535,65535,65535,65535,65535,65535,65535},
{2745,2757,3680,2780,2792,2804,2815,2827,2839,2850,2862,2874,3794,2897,2909,2921,2932,2944,2956,2967,2979,2991,3908,3014,3026,3038,3049,3061,3073,3084,3096,3108,4022,3131,3143,3155,3166,3178,3190,65535,65535,65535,65535,65535,65535,65535,65535,65535},
{2746,2758,2769,2781,2793,3715,2816,2828,2840,2851,2863,2875,2886,2898,2910,3829,2933,2945,2957,2968,2980,2992,3003,3015,3027,3943,3050,3062,3074,3085,3097,3109,3120,3132,3144,4058,3167,3179,3191,65535,65535,65535,65535,65535,65535,65535,65535,65535},
{3202,3214,3225,3237,3249,3716,3272,3284,3296,3307,3319,3331,3342,3354,3366,3830,3389,3401,3413,3424,3436,3448,3459,3471,3483,3944,3506,3518,3530,3541,3553,3565,3576,3588,3600,4059,3623,3635,3647,65535,65535,65535,65535,65535,65535,65535,65535,65535},
{3203,3215,3226,3238,3250,3261,3273,3285,3751,3308,3320,3332,3343,3355,3367,3378,3390,3402,3865,3425,3437,3449,3460,3472,3484,3495,3507,3519,3980,3542,3554,3566,3577,3589,3601,3612,3624,3636,4094,65535,65535,65535,65535,65535,65535,65535,65535,65535},
{65535,65535,65535,65535,65535,65535,65535,65535,65535,65535,65535,65535,65535,65535,65535,65535,65535,65535,65535,65535,65535,65535,65535,65535,65535,65535,65535,65535,65535,65535,65535,65535,65535,65535,65535,65535,65535,65535,65535,65535,65535,65535,65535,65535,65535,65535,65535,65535},
{2747,2759,2770,2782,2794,2805,2817,2829,3750,2852,2864,2876,2887,2899,2911,2922,2934,2946,3864,2969,2981,2993,3004,3016,3028,3039,3051,3063,3979,3086,3098,3110,3121,3133,3145,3156,3168,3180,4093,65535,65535,65535,65535,65535,65535,65535,65535,65535},
{65535,65535,65535,65535,65535,65535,65535,65535,65535,65535,65535,65535,65535,65535,65535,65535,65535,65535,65535,65535,65535,65535,65535,65535,65535,65535,65535,65535,65535,65535,65535,65535,65535,65535,65535,65535,65535,65535,65535,65535,65535,65535,65535,65535,65535,65535,65535,65535},
{3664,3673,3682,3699,3708,3717,3726,3743,3752,3761,3778,3787,3796,3805,3822,3831,3840,3849,3866,3875,3884,3901,3910,3919,3928,3945,3954,3963,3972,3989,3998,4007,4024,4033,4042,4051,4068,4077,4086,4095,65535,65535,65535,65535,65535,65535,65535,65535},
{5,16,28,40,51,63,75,3727,98,110,122,133,145,157,168,180,192,3841,215,227,239,250,262,274,285,297,309,3955,332,344,356,367,379,391,402,414,426,4069,449,65535,65535,65535,65535,65535,65535,65535,65535,65535},
{3648,17,29,41,52,64,76,87,99,111,3762,134,146,158,169,181,193,204,216,228,3876,251,263,275,286,298,310,321,333,345,3990,368,380,392,403,415,427,438,450,65535,65535,65535,65535,65535,65535,65535,65535,65535},
{6,18,30,3683,53,65,77,88,100,112,123,135,147,3797,170,182,194,205,217,229,240,252,264,3911,287,299,311,322,334,346,357,369,381,4025,404,416,428,439,451,65535,65535,65535,65535,65535,65535,65535,65535,65535},
{7,19,31,42,54,66,3718,89,101,113,124,136,148,159,171,183,3832,206,218,230,241,253,265,276,288,300,3946,323,335,347,358,370,382,393,405,417,4060,440,452,65535,65535,65535,65535,65535,65535,65535,65535,65535},
{8,20,32,43,55,67,78,90,102,3753,125,137,149,160,172,184,195,207,219,3867,242,254,266,277,289,301,312,324,336,3981,359,371,383,394,406,418,429,441,453,65535,65535,65535,65535,65535,65535,65535,65535,65535},
{9,21,3674,44,56,68,79,91,103,114,126,138,3788,161,173,185,196,208,220,231,243,255,3902,278,290,302,313,325,337,348,360,372,4016,395,407,419,430,442,454,65535,65535,65535,65535,65535,65535,65535,65535,65535},
{10,22,33,45,57,3709,80,92,104,115,127,139,150,162,174,3823,197,209,221,232,244,256,267,279,291,3937,314,326,338,349,361,373,384,396,408,4052,431,443,455,65535,65535,65535,65535,65535,65535,65535,65535,65535},
{11,23,34,46,58,69,81,93,3744,116,128,140,151,163,175,186,198,210,3858,233,245,257,268,280,292,303,315,327,3973,350,362,374,385,397,409,420,432,444,4087,65535,65535,65535,65535,65535,65535,65535,65535,65535},
};

#define NG 9
#define RING 16
#define NSLOT 8
#define CFETCH 5
#define TABLED 1
#define PROMO CU_TENSOR_MAP_L2_PROMOTION_L2_128B
#define AHEAD 6
#define CF0 5
#define CFS 2
#define ABL 0
#define CX 5
#define PUBN 2
#define PUBE 8
#define SCHED 7
#define OUT_TMA 1
#define TRIG 7
constexpr int NCONV = 3 * NG;
constexpr int PLEN = (1024 + NG - 1) / NG;
constexpr int TILEB = 12288;
constexpr int SLOTB = 280 * 64;
constexpr int W1S = 0, W2S = 73728, ABUF = 147456, XBUF = ABUF + 8 * 3072, MISC = XBUF + 16 * 3072;
constexpr int CTAB = NSLOT * SLOTB + 512;
constexpr int SMEM_BYTES = MISC + 512 + 2048;
static_assert(CTAB + (PLEN + 12) * 16 <= MISC, "conv smem");

__device__ __align__(1024) unsigned char g_scratch[(RING * NG + 1) * 4 * TILEB];
__device__ uint32_t g_ready[1024];
__device__ uint32_t g_cons[1024 + 32];
__device__ unsigned long long g_start;

#define PROF_AT(cond, idx)
#define PROF_VAL(cond, idx, v)
#define PROF2_AT(c, i)
#define PROF2_VAL(c, i, v)
#define GELU_C3 0.32920349f
#define GELU_A2 0x40d940d9u
#define SPIN_LIMIT 0x1000000

__device__ __forceinline__ uint32_t smem_u32(const void* p) { return (uint32_t)__cvta_generic_to_shared(p); }
__device__ __forceinline__ void wg_fence() { asm volatile("wgmma.fence.sync.aligned;" ::: "memory"); }
__device__ __forceinline__ void wg_commit() { asm volatile("wgmma.commit_group.sync.aligned;" ::: "memory"); }
template <int N> __device__ __forceinline__ void wg_wait() { asm volatile("wgmma.wait_group.sync.aligned %0;" ::"n"(N) : "memory"); }
__device__ __forceinline__ void mbar_init(uint32_t bar, uint32_t cnt) { asm volatile("mbarrier.init.shared::cta.b64 [%0], %1;" ::"r"(bar), "r"(cnt) : "memory"); }
__device__ __forceinline__ void mbar_expect_tx(uint32_t bar, uint32_t bytes) { asm volatile("mbarrier.arrive.expect_tx.shared::cta.b64 _, [%0], %1;" ::"r"(bar), "r"(bytes) : "memory"); }
__device__ __forceinline__ void mbar_arrive(uint32_t bar) { asm volatile("mbarrier.arrive.shared::cta.b64 _, [%0];" ::"r"(bar) : "memory"); }
__device__ __forceinline__ void mbar_wait(uint32_t bar, uint32_t parity) {
  asm volatile("{\n.reg .pred p;\n.reg .u32 c;\nmbarrier.try_wait.parity.shared::cta.b64 p, [%0], %1;\n@p bra DONE_%=;\nmov.u32 c, 0;\nWAIT_%=:\nmbarrier.try_wait.parity.shared::cta.b64 p, [%0], %1;\n@p bra DONE_%=;\n"
               "add.u32 c, c, 1;\nsetp.lt.u32 p, c, 0x1000000;\n@p bra WAIT_%=;\ntrap;\nDONE_%=:\n}" ::"r"(bar), "r"(parity) : "memory");
}
__device__ __forceinline__ void bulk_g2s(uint32_t dst, const void* src, uint32_t bytes, uint32_t bar) {
  asm volatile("cp.async.bulk.shared::cluster.global.mbarrier::complete_tx::bytes [%0], [%1], %2, [%3];" ::"r"(dst), "l"(src), "r"(bytes), "r"(bar) : "memory");
}
__device__ __forceinline__ uint32_t ld_relaxed(const uint32_t* p) { uint32_t v; asm volatile("ld.relaxed.gpu.global.u32 %0, [%1];" : "=r"(v) : "l"(p) : "memory"); return v; }
__device__ __forceinline__ void red_add(uint32_t* p) { asm volatile("red.relaxed.gpu.global.add.u32 [%0], 1;" ::"l"(p) : "memory"); }
__device__ __forceinline__ void lds128(uint32_t* r, uint32_t a) { asm volatile("ld.shared.v4.b32 {%0,%1,%2,%3}, [%4];" : "=r"(r[0]), "=r"(r[1]), "=r"(r[2]), "=r"(r[3]) : "r"(a) : "memory"); }
__device__ __forceinline__ uint2 lds64(uint32_t a) { uint2 v; asm volatile("ld.shared.v2.b32 {%0,%1}, [%2];" : "=r"(v.x), "=r"(v.y) : "r"(a) : "memory"); return v; }
__device__ __forceinline__ uint32_t lds32(uint32_t a) { uint32_t v; asm volatile("ld.shared.b32 %0, [%1];" : "=r"(v) : "r"(a) : "memory"); return v; }
__device__ __forceinline__ void sts32(uint32_t a, uint32_t v) { asm volatile("st.shared.b32 [%0], %1;" ::"r"(a), "r"(v) : "memory"); }
__device__ __forceinline__ void sts128(uint32_t a, uint4 v) { asm volatile("st.shared.v4.b32 [%0], {%1,%2,%3,%4};" ::"r"(a), "r"(v.x), "r"(v.y), "r"(v.z), "r"(v.w) : "memory"); }
__device__ __forceinline__ uint4 ldg128v(const void* p) { uint4 v; asm volatile("ld.global.nc.v4.b32 {%0,%1,%2,%3}, [%4];" : "=r"(v.x), "=r"(v.y), "=r"(v.z), "=r"(v.w) : "l"(p) : "memory"); return v; }
__device__ __forceinline__ void stg128(void* p, uint4 v) { asm volatile("st.global.v4.b32 [%0], {%1,%2,%3,%4};" ::"l"(p), "r"(v.x), "r"(v.y), "r"(v.z), "r"(v.w) : "memory"); }
#define HINT 3
__device__ __forceinline__ uint64_t pol_evict_first() { uint64_t p; asm("createpolicy.fractional.L2::evict_first.b64 %0, 1.0;" : "=l"(p)); return p; }
__device__ __forceinline__ uint4 ldg128_last(const void* p, uint64_t pol) {
  if (!(HINT & 1)) return ldg128v(p);
  uint4 v; asm volatile("ld.global.nc.L1::no_allocate.L2::cache_hint.v4.b32 {%0,%1,%2,%3}, [%4], %5;" : "=r"(v.x), "=r"(v.y), "=r"(v.z), "=r"(v.w) : "l"(p), "l"(pol) : "memory"); return v;
}
__device__ __forceinline__ void stg128_stream(void* p, uint4 v, uint64_t pol) {
  if (!(HINT & 2)) { stg128(p, v); return; }
  asm volatile("st.global.L2::cache_hint.v4.b32 [%0], {%1,%2,%3,%4}, %5;" ::"l"(p), "r"(v.x), "r"(v.y), "r"(v.z), "r"(v.w), "l"(pol) : "memory");
}
__device__ __forceinline__ float bf_lo(uint32_t w) { return __uint_as_float(w << 16); }
__device__ __forceinline__ float bf_hi(uint32_t w) { return __uint_as_float(w & 0xffff0000u); }
__device__ __forceinline__ uint32_t pack_f16(float lo, float hi) { uint32_t d; asm("cvt.rn.f16x2.f32 %0, %1, %2;" : "=r"(d) : "f"(hi), "f"(lo)); return d; }
__device__ __forceinline__ uint32_t pack_f16_sat(float lo, float hi) { uint32_t d; asm("cvt.rn.satfinite.f16x2.f32 %0, %1, %2;" : "=r"(d) : "f"(hi), "f"(lo)); return d; }
__device__ __forceinline__ uint32_t pack_bf16(float lo, float hi) { uint32_t d; asm("cvt.rn.bf16x2.f32 %0, %1, %2;" : "=r"(d) : "f"(hi), "f"(lo)); return d; }
__device__ __forceinline__ uint32_t hadd2_bf16(uint32_t a, uint32_t b) { uint32_t d; asm("add.rn.bf16x2 %0, %1, %2;" : "=r"(d) : "r"(a), "r"(b)); return d; }
__device__ __forceinline__ uint32_t h2add(uint32_t a, uint32_t b) { uint32_t d; asm("add.rn.f16x2 %0, %1, %2;" : "=r"(d) : "r"(a), "r"(b)); return d; }
__device__ __forceinline__ uint32_t h2mul(uint32_t a, uint32_t b) { uint32_t d; asm("mul.rn.f16x2 %0, %1, %2;" : "=r"(d) : "r"(a), "r"(b)); return d; }
__device__ __forceinline__ uint32_t h2fma(uint32_t a, uint32_t b, uint32_t c) { uint32_t d; asm("fma.rn.f16x2 %0, %1, %2, %3;" : "=r"(d) : "r"(a), "r"(b), "r"(c)); return d; }
__device__ __forceinline__ uint32_t h2lo(uint32_t a) { uint32_t d; asm("{.reg .f16 l,h; mov.b32 {l,h}, %1; mov.b32 %0, {l,l};}" : "=r"(d) : "r"(a)); return d; }
__device__ __forceinline__ uint32_t h2hi(uint32_t a) { uint32_t d; asm("{.reg .f16 l,h; mov.b32 {l,h}, %1; mov.b32 %0, {h,h};}" : "=r"(d) : "r"(a)); return d; }
__device__ __forceinline__ float h_lo(uint32_t a) { float d; asm("{.reg .f16 l,h; mov.b32 {l,h}, %1; cvt.f32.f16 %0, l;}" : "=f"(d) : "r"(a)); return d; }
__device__ __forceinline__ float h_hi(uint32_t a) { float d; asm("{.reg .f16 l,h; mov.b32 {l,h}, %1; cvt.f32.f16 %0, h;}" : "=f"(d) : "r"(a)); return d; }
__device__ __forceinline__ uint32_t prmt(uint32_t a, uint32_t b, uint32_t s) { uint32_t d; asm("prmt.b32 %0, %1, %2, %3;" : "=r"(d) : "r"(a), "r"(b), "r"(s)); return d; }
__device__ __forceinline__ void mma_sp(float* d, const uint32_t* a, const uint32_t* b, const float* c, uint32_t e) {
  asm("mma.sp::ordered_metadata.sync.aligned.m16n8k32.row.col.f32.bf16.bf16.f32 {%0,%1,%2,%3}, {%4,%5,%6,%7}, {%8,%9,%10,%11}, {%12,%13,%14,%15}, %16, 0;"
      : "=f"(d[0]), "=f"(d[1]), "=f"(d[2]), "=f"(d[3])
      : "r"(a[0]), "r"(a[1]), "r"(a[2]), "r"(a[3]), "r"(b[0]), "r"(b[1]), "r"(b[2]), "r"(b[3]), "f"(c[0]), "f"(c[1]), "f"(c[2]), "f"(c[3]), "r"(e));
}
__device__ __forceinline__ uint32_t bf2_to_h2(uint32_t w, float s) { return pack_f16(bf_lo(w) * s, bf_hi(w) * s); }
__device__ __forceinline__ uint32_t bf2_to_h2(uint32_t w) { return pack_f16(bf_lo(w), bf_hi(w)); }

__device__ __forceinline__ uint32_t gelu_h2(uint32_t y) {
  uint32_t t, u, th, g;
  asm volatile("fma.rn.f16x2 %0, %1, %1, %2;" : "=r"(t) : "r"(y), "r"(GELU_A2));
  asm volatile("mul.rn.f16x2 %0, %1, %2;" : "=r"(u) : "r"(y), "r"(t));
  asm volatile("tanh.approx.f16x2 %0, %1;" : "=r"(th) : "r"(u));
  asm volatile("fma.rn.f16x2 %0, %1, %2, %1;" : "=r"(g) : "r"(y), "r"(th));
  return g;
}

__device__ __forceinline__ void prep_weights(uint32_t sb, const __nv_bfloat16* __restrict__ w1, const __nv_bfloat16* __restrict__ w2, int warp, int lane) {
  const int k0 = lane & 7, lq = lane >> 3;
  uint4 v[9], u[3][4];
#pragma unroll
  for (int i = 0; i < 9; i++) {
    int it = warp * 9 + i, nbq = it % 12, skh = it / 12, kh = skh & 1, s = skh >> 1;
    int ch = 16 * s + 4 * (k0 >> 1) + 2 * kh + (k0 & 1);
    v[i] = __ldg((const uint4*)(w1 + ch * 384 + (nbq * 4 + lq) * 8));
  }
#pragma unroll
  for (int i = 0; i < 3; i++) {
    int it = warp + 16 * i;
    if (it < 36) {
      int un = it * 4 + lq, j = un % 3, h8 = un / 3;
      const uint4* p = (const uint4*)(w2 + (h8 * 8 + k0) * 96 + j * 32);
#pragma unroll
      for (int q = 0; q < 4; q++) u[i][q] = __ldg(p + q);
    }
  }
#pragma unroll
  for (int i = 0; i < 9; i++) {
    int it = warp * 9 + i, nbq = it % 12, skh = it / 12, kh = skh & 1, s = skh >> 1;
    sts128(sb + W1S + s * 12288 + (nbq * 4 + lq) * 256 + kh * 128 + k0 * 16, make_uint4(bf2_to_h2(v[i].x), bf2_to_h2(v[i].y), bf2_to_h2(v[i].z), bf2_to_h2(v[i].w)));
  }
  const float sc = 0.5f / GELU_C3;
#pragma unroll
  for (int i = 0; i < 3; i++) {
    int it = warp + 16 * i;
    if (it < 36) {
      int un = it * 4 + lq, j = un % 3, h8 = un / 3;
      uint32_t base = sb + W2S + (h8 >> 1) * 3072 + (j * 4) * 256 + (h8 & 1) * 128 + k0 * 16;
      sts128(base, make_uint4(bf2_to_h2(u[i][0].x, sc), bf2_to_h2(u[i][1].x, sc), bf2_to_h2(u[i][2].x, sc), bf2_to_h2(u[i][3].x, sc)));
      sts128(base + 256, make_uint4(bf2_to_h2(u[i][0].y, sc), bf2_to_h2(u[i][1].y, sc), bf2_to_h2(u[i][2].y, sc), bf2_to_h2(u[i][3].y, sc)));
      sts128(base + 512, make_uint4(bf2_to_h2(u[i][0].z, sc), bf2_to_h2(u[i][1].z, sc), bf2_to_h2(u[i][2].z, sc), bf2_to_h2(u[i][3].z, sc)));
      sts128(base + 768, make_uint4(bf2_to_h2(u[i][0].w, sc), bf2_to_h2(u[i][1].w, sc), bf2_to_h2(u[i][2].w, sc), bf2_to_h2(u[i][3].w, sc)));
    }
  }
}

__device__ __noinline__ void ln_wide(uint32_t ad) {
  float m[2], r[2];
#pragma unroll
  for (int hi = 0; hi < 2; hi++) {
    float sm = 0.f;
    for (int s = 0; s < 6; s++) { uint2 w = lds64(ad + s * 512 + hi * 8); sm += (h_lo(w.x) + h_hi(w.x)) + (h_lo(w.y) + h_hi(w.y)); }
    sm += __shfl_xor_sync(0xffffffffu, sm, 1); sm += __shfl_xor_sync(0xffffffffu, sm, 2);
    m[hi] = sm * (1.f / 96.f);
    float q = 0.f;
    for (int s = 0; s < 6; s++) {
      uint2 w = lds64(ad + s * 512 + hi * 8);
      float d0 = h_lo(w.x) - m[hi], d1 = h_hi(w.x) - m[hi], d2 = h_lo(w.y) - m[hi], d3 = h_hi(w.y) - m[hi];
      q += (d0 * d0 + d1 * d1) + (d2 * d2 + d3 * d3);
    }
    q += __shfl_xor_sync(0xffffffffu, q, 1); q += __shfl_xor_sync(0xffffffffu, q, 2);
    r[hi] = rsqrtf(fmaf(q, 1.f / 96.f, 1e-5f)) * GELU_C3;
  }
  for (int s = 0; s < 6; s++) {
    uint32_t w[4]; lds128(w, ad + s * 512);
    sts128(ad + s * 512, make_uint4(pack_f16((h_lo(w[0]) - m[0]) * r[0], (h_hi(w[0]) - m[0]) * r[0]), pack_f16((h_lo(w[2]) - m[1]) * r[1], (h_hi(w[2]) - m[1]) * r[1]),
                                    pack_f16((h_lo(w[1]) - m[0]) * r[0], (h_hi(w[1]) - m[0]) * r[0]), pack_f16((h_lo(w[3]) - m[1]) * r[1], (h_hi(w[3]) - m[1]) * r[1])));
  }
  asm volatile("fence.proxy.async.shared::cta;" ::: "memory");
}

__device__ __forceinline__ void load_ln(uint32_t ad, uint32_t* a) {
  uint32_t raw[6][4];
#pragma unroll
  for (int s = 0; s < 6; s++) lds128(raw[s], ad + s * 512);
  uint32_t sm[2];
#pragma unroll
  for (int hi = 0; hi < 2; hi++) {
    uint32_t s0 = h2add(raw[0][2 * hi], raw[1][2 * hi]), s1 = h2add(raw[0][2 * hi + 1], raw[1][2 * hi + 1]);
    uint32_t s2 = h2add(raw[2][2 * hi], raw[3][2 * hi]), s3 = h2add(raw[2][2 * hi + 1], raw[3][2 * hi + 1]);
    uint32_t s4 = h2add(raw[4][2 * hi], raw[5][2 * hi]), s5 = h2add(raw[4][2 * hi + 1], raw[5][2 * hi + 1]);
    sm[hi] = h2add(h2add(h2add(s0, s1), h2add(s2, s3)), h2add(s4, s5));
  }
  uint32_t s = h2add(prmt(sm[0], sm[1], 0x5410), prmt(sm[0], sm[1], 0x7632));
  s = h2add(s, __shfl_xor_sync(0xffffffffu, s, 1));
  s = h2add(s, __shfl_xor_sync(0xffffffffu, s, 2));
  const uint32_t nm = h2mul(s, 0xA155A155u);
  uint32_t qq[2];
#pragma unroll
  for (int hi = 0; hi < 2; hi++) {
    const uint32_t m = hi ? h2hi(nm) : h2lo(nm);
    uint32_t q0 = 0, q1 = 0;
#pragma unroll
    for (int k = 0; k < 6; k++) {
      uint32_t d0 = h2add(raw[k][2 * hi], m), d1 = h2add(raw[k][2 * hi + 1], m);
      raw[k][2 * hi] = d0; raw[k][2 * hi + 1] = d1;
      q0 = k ? h2fma(d0, d0, q0) : h2mul(d0, d0);
      q1 = k ? h2fma(d1, d1, q1) : h2mul(d1, d1);
    }
    qq[hi] = h2add(q0, q1);
  }
  uint32_t q = h2add(prmt(qq[0], qq[1], 0x5410), prmt(qq[0], qq[1], 0x7632));
  q = h2add(q, __shfl_xor_sync(0xffffffffu, q, 1));
  q = h2add(q, __shfl_xor_sync(0xffffffffu, q, 2));
  const float r0 = rsqrtf(fmaf(h_lo(q), 1.f / 96.f, 1e-5f)) * GELU_C3, r1 = rsqrtf(fmaf(h_hi(q), 1.f / 96.f, 1e-5f)) * GELU_C3;
  const uint32_t r = pack_f16(r0, r1);
#pragma unroll
  for (int k = 0; k < 6; k++) {
    a[4 * k] = h2mul(raw[k][0], h2lo(r)); a[4 * k + 2] = h2mul(raw[k][1], h2lo(r));
    a[4 * k + 1] = h2mul(raw[k][2], h2hi(r)); a[4 * k + 3] = h2mul(raw[k][3], h2hi(r));
  }
  const bool bad = (((q & 0x7c007c00u) + 0x04000400u) & 0x80008000u) != 0;
  if (!(ABL & 32) && __any_sync(0xffffffffu, bad)) {
    ln_wide(ad);
#pragma unroll
    for (int k = 0; k < 6; k++) lds128(a + 4 * k, ad + k * 512);
  }
}

__device__ __forceinline__ void gemm1(uint32_t* p, const uint32_t* a, uint64_t d1, int c) {
  wgmma_n48_f16<0>(p, a, d1 + c * (1536 >> 4));
#pragma unroll
  for (int s = 1; s < 6; s++) wgmma_n48_f16<1>(p, a + 4 * s, d1 + c * (1536 >> 4) + s * (12288 >> 4));
}

__device__ __forceinline__ void gemm1_piece(uint32_t* p, const uint32_t* a, uint64_t d1, int c, int u) {
  if (u == 0) wgmma_n48_f16<0>(p, a, d1 + c * (1536 >> 4)); else wgmma_n48_f16<1>(p, a + 8 * u, d1 + c * (1536 >> 4) + 2 * u * (12288 >> 4));
  wgmma_n48_f16<1>(p, a + 8 * u + 4, d1 + c * (1536 >> 4) + (2 * u + 1) * (12288 >> 4));
}
__device__ __forceinline__ void fetch_a(uint32_t abuf, uint32_t bar, uint32_t sofs) {
  asm volatile("{\n.reg .pred p;\nelect.sync _|p, 0xffffffff;\n@p fence.acquire.gpu;\n@p fence.proxy.async.global;\n"
               "@p mbarrier.arrive.expect_tx.shared::cta.b64 _, [%1], 3072;\n"
               "@p cp.async.bulk.shared::cluster.global.mbarrier::complete_tx::bytes [%0], [%2], 3072, [%1];\n}"
               ::"r"(abuf), "r"(bar), "l"(g_scratch + sofs) : "memory");
}
__device__ __forceinline__ void wait_ready(int P, uint32_t target) {
  int spins = 0;
  while (ld_relaxed(&g_ready[P]) != target) { __nanosleep(64); if (++spins > SPIN_LIMIT) __trap(); }
}

__device__ __forceinline__ void mlp_role(uint32_t sb, const CUtensorMap* tmr, const CUtensorMap* tmo, const __nv_bfloat16* __restrict__ w1, const __nv_bfloat16* __restrict__ w2,
                                         __nv_bfloat16* __restrict__ out, int idx, bool tabled, int warp, int lane) {
  const int wg = warp >> 2, w = warp & 3, g = lane >> 2, t = lane & 3;
  const uint32_t abuf = sb + ABUF + (warp & 7) * 3072, xbuf = sb + XBUF + warp * 3072;
  const uint32_t bar = sb + MISC + warp * 8, obar = sb + MISC + (warp ^ 8) * 8;
  const uint32_t tl = sb + MISC + 512;
  if (threadIdx.x >= 384) {
    const int k = threadIdx.x - 384;
    int n = -1;
    if (tabled) { if (k < 48) n = (int16_t)g_sched[idx][k]; }
    else {
      const int i = k * (gridDim.x - NCONV) + idx, full = (1024 - (NG - 1) * PLEN) * NG;
      const int r = i >> 2, j = r < full ? r / NG : (r - full) / (NG - 1) + full / NG, gm = r < full ? r % NG : (r - full) % (NG - 1);
      if (i < 4096) n = (gm * PLEN + j) * 4 + (i & 3);
    }
    const int P = n >> 2, gm = P / PLEN, j = P - gm * PLEN;
    sts128(tl + k * 16, make_uint4(P, (((j & (RING - 1)) * NG + gm) * 4 + (n & 3)) * TILEB, (n & 2) * 384, ((n >> 10) * 8 + (n & 1) * 4) | ((n & 1020) << 7)));
  }
  if (lane == 0) {
    mbar_init(bar, 1); mbar_init(bar + 128, 1); sts32(bar + 320, wg < 2);
    asm volatile("fence.mbarrier_init.release.cluster;" ::: "memory");
    if (wg < 2) mbar_arrive(bar);
  }
  if (threadIdx.x == 0) sts32(sb + MISC + 256, (uint32_t)(atomicAdd(&g_start, 1ULL) / gridDim.x) + 1);
  prep_weights(sb, w1, w2, warp, lane);
  asm volatile("fence.proxy.async.shared::cta;" ::: "memory");
  __syncthreads();
  PROF_AT(threadIdx.x == 0, 1); PROF_VAL(threadIdx.x == 0, 8, clock64());
  const uint32_t rtarget = 3 * lds32(sb + MISC + 256);
  const uint64_t dbase = ((uint64_t)(128 >> 4) << 16) | ((uint64_t)(256 >> 4) << 32);
  const uint64_t d1 = dbase | (uint64_t)(((sb + W1S) >> 4) & 0x3fff);
  const uint64_t d2 = dbase | (uint64_t)(((sb + W2S) >> 4) & 0x3fff);
  const uint32_t ad = abuf + t * 128 + ((g ^ (2 * t)) << 4);
  const uint32_t xd = xbuf + g * 192 + t * 16;
  const int mybar = 1 + wg, nxtbar = 1 + ((wg + 1) & 3);
  const uint64_t pol = pol_evict_first();
  uint32_t pha = 0, phx = 0, tp = tl + wg * 16, rdy = rtarget + 1;
  uint32_t cur[4];
  lds128(cur, tp);
  while ((int)cur[0] >= 0) {
    PROF2_AT((threadIdx.x & 127) == 0, 16 + (tp - tl) / 4);
    uint32_t a[24], p[8][12], gg[8][12], acc[24];
    const uint2 n2 = lds64(tp + 32);
    const int sig = lds32(tp + 16);
    mbar_wait(bar, pha); pha ^= 1;
    PROF2_VAL((threadIdx.x & 127) == 0, 16 + (tp - tl) / 4 + 3, lds32(bar + 320));
    if (lds32(bar + 320)) {
      wait_ready(cur[0], rtarget);
      fetch_a(abuf, bar, cur[1] + w * 3072);
      mbar_wait(bar, pha); pha ^= 1;
    }
    PROF2_AT((threadIdx.x & 127) == 0, 16 + (tp - tl) / 4 + 1);
    asm volatile("{.reg .pred p; elect.sync _|p, 0xffffffff; @p red.relaxed.gpu.global.add.u32 [%0], 1;}" ::"l"(&g_cons[cur[0]]) : "memory");
    load_ln(ad, a);
    __syncwarp();
    if ((int)n2.x >= 0) {
      if (lane == 0) sts32(obar + 320, rdy != rtarget);
      __syncwarp();
      if (rdy == rtarget) fetch_a(abuf, obar, n2.y + w * 3072);
      else if (lane == 0) mbar_arrive(obar);
    }
    asm volatile("{\n.reg .pred p;\nelect.sync _|p, 0xffffffff;\n"
                 "@p cp.async.bulk.wait_group.read 0;\n"
                 "@p mbarrier.arrive.expect_tx.shared::cta.b64 _, [%1], 3072;\n"
                 "@p cp.async.bulk.tensor.3d.shared::cluster.global.mbarrier::complete_tx::bytes.L2::cache_hint [%0], [%2, {%3, %4, %5}], [%1], %6;\n}"
                 ::"r"(xbuf), "r"(bar + 128), "l"(tmr), "r"(cur[2] + w * 192), "r"(cur[3] & 255), "r"(cur[3] >> 8), "l"(pol) : "memory");
    if (tp != tl) asm volatile("bar.sync %0, 256;" ::"r"(mybar) : "memory");
    PROF2_AT((threadIdx.x & 127) == 0, 16 + (tp - tl) / 4 + 2);
    wg_fence();
    gemm1(p[0], a, d1, 0); wg_commit();
#pragma unroll
    for (int j = 0; j < 24; j++) {
      const int c = j / 3, s = j % 3;
      if (SCHED == 9) wg_wait<1>(); else if (s == 0) wg_wait<0>();
      if (j == TRIG) asm volatile("{.reg .pred p; setp.ge.s32 p, %1, 0; @p bar.arrive %0, 256;}" ::"r"(nxtbar), "r"(sig) : "memory");
#pragma unroll
      for (int i = 0; i < 4; i++) gg[c][4 * s + i] = gelu_h2(p[c][4 * s + i]);
      wg_fence();
      if (j == 0) wgmma_n96_f16<0>(acc, gg[c], d2); else wgmma_n96_f16<1>(acc, &gg[c][4 * s], d2 + j * (3072 >> 4));
      if (SCHED == 9) {
        if (j < 20) gemm1_piece(p[(j + 1) / 3 + 1], a, d1, (j + 1) / 3 + 1, (j + 1) % 3);
        wg_commit();
      } else if (s == 2) {
        if (c < 7) gemm1(p[c + 1], a, d1, c + 1);
        wg_commit();
      }
    }
    rdy = ld_relaxed(&g_ready[lds32(tp + 96) & 1023]);
    wg_wait<0>();
    mbar_wait(bar + 128, phx); phx ^= 1;
    char* const op = (char*)out + (size_t)(cur[3] >> 8) * (512 * 192) + ((cur[3] & 255) + (g >> 1)) * 3072 + cur[2] * 2 + (2 * w + (g & 1)) * 192 + t * 16;
#pragma unroll
    for (int hi = 0; hi < 2; hi++)
#pragma unroll
      for (int j = 0; j < 3; j++) {
        uint32_t xr[4];
        lds128(xr, xd + hi * 1536 + j * 64);
        uint4 o;
        o.x = hadd2_bf16(xr[0], pack_bf16(h_lo(acc[8 * j + hi]), h_hi(acc[8 * j + hi])));
        o.y = hadd2_bf16(xr[1], pack_bf16(h_lo(acc[8 * j + 2 + hi]), h_hi(acc[8 * j + 2 + hi])));
        o.z = hadd2_bf16(xr[2], pack_bf16(h_lo(acc[8 * j + 4 + hi]), h_hi(acc[8 * j + 4 + hi])));
        o.w = hadd2_bf16(xr[3], pack_bf16(h_lo(acc[8 * j + 6 + hi]), h_hi(acc[8 * j + 6 + hi])));
        if (OUT_TMA) sts128(xd + hi * 1536 + j * 64, o);
        else stg128_stream(op + hi * (512 * 192) + j * 64, o, pol);
      }
    if (OUT_TMA) {
      asm volatile("fence.proxy.async.shared::cta;" ::: "memory");
      asm volatile("{\n.reg .pred p;\nbar.warp.sync 0xffffffff;\nelect.sync _|p, 0xffffffff;\n"
                   "@p cp.async.bulk.tensor.3d.global.shared::cta.bulk_group.L2::cache_hint [%1, {%2, %3, %4}], [%0], %5;\n@p cp.async.bulk.commit_group;\n}"
                   ::"r"(xbuf), "l"(tmo), "r"(cur[2] + w * 192), "r"(cur[3] & 255), "r"(cur[3] >> 8), "l"(pol) : "memory");
    }
    tp += 64;
    lds128(cur, tp);
  }
  if (OUT_TMA) asm volatile("cp.async.bulk.wait_group.read 0;" ::: "memory");
  PROF_AT((threadIdx.x & 127) == 0, 4 + wg); PROF_VAL(threadIdx.x == 0, 9, clock64());
}

__device__ __forceinline__ void conv_compute(uint32_t sb, const __nv_bfloat16* __restrict__ dw, int third, int nit, int warp, int lane) {
  const int g = lane >> 2, t = lane & 3;
  const uint32_t full = sb + MISC;
  uint32_t A[4][4][4];
  {
    uint2 w[2][9];
#pragma unroll
    for (int h = 0; h < 2; h++) {
      const int j = (4 * h + t - g) & 7;
      w[h][0] = make_uint2(0u, 0u); w[h][8] = make_uint2(0u, 0u);
#pragma unroll
      for (int i = 0; i < 7; i++) {
        w[h][i + 1] = make_uint2(0u, 0u);
        if (j < 7) w[h][i + 1] = __ldg((const uint2*)(dw + (i * 7 + j) * 96 + third * 32 + warp * 4));
      }
    }
#pragma unroll
    for (int u = 0; u < 4; u++)
#pragma unroll
      for (int r = 0; r < 4; r++) {
        const int h = r >> 1, i0 = 2 * u - (r & 1) + 1;
        A[0][u][r] = prmt(w[h][i0].x, w[h][i0 + 1].x, 0x5410); A[1][u][r] = prmt(w[h][i0].x, w[h][i0 + 1].x, 0x7632);
        A[2][u][r] = prmt(w[h][i0].y, w[h][i0 + 1].y, 0x5410); A[3][u][r] = prmt(w[h][i0].y, w[h][i0 + 1].y, 0x7632);
      }
  }
  uint32_t meta = 0;
#pragma unroll
  for (int a = 0; a < 4; a++) meta |= ((4 * (t & 1) + a + 1 >= g) ? 0x80008u : 0xD000Du) << (4 * a);
  meta = __shfl_sync(0xffffffffu, meta, lane);
  float S[2][4][3][4];
#pragma unroll
  for (int s = 0; s < 2; s++)
#pragma unroll
    for (int c = 0; c < 4; c++)
#pragma unroll
      for (int i = 0; i < 3; i++)
#pragma unroll
        for (int k = 0; k < 4; k++) S[s][c][i][k] = 0.f;
  uint32_t aq[4];
#pragma unroll
  for (int q = 0; q < 4; q++) {
    const int pp = (g & 1) * 140 + (t & 1) * 70 + 16 * (g >> 1) + 2 * q + (t >> 1);
    aq[q] = __shfl_sync(0xffffffffu, sb + pp * 64 + (((warp >> 1) ^ ((pp >> 1) & 3)) << 4) + (warp & 1) * 8, lane);
  }
  const int Q = third * 8 + warp;
  unsigned char* const obase = g_scratch + (g >> 1) * 3072 + Q * 128 + (((2 * t + (g & 1)) ^ (2 * (Q & 3))) << 4);
  const float zero4[4] = {0.f, 0.f, 0.f, 0.f};
  uint32_t sofs = 0, bar = full, ph = 0;
  uint2 X[3][4];
  mbar_wait(bar, 0);
  PROF_AT(threadIdx.x == 0, 1); PROF_VAL(threadIdx.x == 0, 8, clock64());
#pragma unroll
  for (int j = 0; j < 2; j++)
#pragma unroll
    for (int q = 0; q < 4; q++) X[j][q] = lds64(aq[q] + j * 512);
  for (uint32_t ot = sb + CTAB; ot < sb + CTAB + nit * 16; ot += 16) {
    PROF_AT(threadIdx.x == 0 && ((ot - sb - CTAB) & 112) == 0, 16 + ((ot - sb - CTAB) >> 4));
    unsigned char* const o = obase + lds32(ot);
    const uint32_t dbar = bar + 64 + ph * 64;
#pragma unroll
    for (int s = 0; s < 2; s++) {
      uint32_t B[4][4];
      if (s == 1) {
        sofs += SLOTB; bar += 8;
        if (sofs == NSLOT * SLOTB) { sofs = 0; bar = full; ph ^= 1; }
        mbar_wait(bar, ph);
      }
#pragma unroll
      for (int c = 0; c < 4; c++)
#pragma unroll
        for (int q = 0; q < 4; q++) B[c][q] = prmt(c < 2 ? X[s][q].x : X[s][q].y, c < 2 ? X[s + 1][q].x : X[s + 1][q].y, (c & 1) ? 0x7632 : 0x5410);
      if (s == 0) {
#pragma unroll
        for (int q = 0; q < 4; q++) X[2][q] = lds64(aq[q] + sofs + 2 * 512);
      } else {
#pragma unroll
        for (int j = 0; j < 2; j++)
#pragma unroll
          for (int q = 0; q < 4; q++) X[j][q] = lds64(aq[q] + sofs + j * 512);
      }
      float T[4][4];
#pragma unroll
      for (int c = 0; c < 4; c++) mma_sp(T[c], A[c][3], B[c], S[s][c][2], meta);
#pragma unroll
      for (int c = 0; c < 4; c++) mma_sp(S[s][c][2], A[c][2], B[c], S[s][c][1], meta);
      stg128(o + (2 * s) * TILEB, make_uint4(pack_f16_sat(T[0][0], T[1][0]), pack_f16_sat(T[2][0], T[3][0]), pack_f16_sat(T[0][2], T[1][2]), pack_f16_sat(T[2][2], T[3][2])));
      stg128(o + (2 * s + 1) * TILEB, make_uint4(pack_f16_sat(T[0][1], T[1][1]), pack_f16_sat(T[2][1], T[3][1]), pack_f16_sat(T[0][3], T[1][3]), pack_f16_sat(T[2][3], T[3][3])));
#pragma unroll
      for (int c = 0; c < 4; c++) mma_sp(S[s][c][1], A[c][1], B[c], S[s][c][0], meta);
#pragma unroll
      for (int c = 0; c < 4; c++) mma_sp(S[s][c][0], A[c][0], B[c], zero4, meta);
    }
    asm volatile("{.reg .pred p; elect.sync _|p, 0xffffffff; @p mbarrier.arrive.shared::cta.b64 _, [%0];}" ::"r"(dbar) : "memory");
  }
  PROF_AT(threadIdx.x == 0, 4); PROF_VAL(threadIdx.x == 0, 9, clock64());
}

__device__ __forceinline__ void conv_loader(uint32_t sb, const CUtensorMap* tmx, int nit, int third) {
  const uint32_t full = sb + MISC;
  for (int it = 0; it <= nit; it++) {
    const int s = it & (NSLOT - 1);
    const uint2 e = lds64(sb + CTAB + it * 16 + 8);
    if (it >= AHEAD) mbar_wait(full + 64 + ((it - AHEAD) & 15) * 8, ((it - AHEAD) >> 4) & 1);
    asm volatile("{\n.reg .pred p;\n.reg .s32 c2;\n.reg .u32 d2;\nelect.sync _|p, 0xffffffff;\nadd.s32 c2, %4, 64;\nadd.u32 d2, %0, 8960;\n"
                 "@p mbarrier.arrive.expect_tx.shared::cta.b64 _, [%2], 17920;\n"
                 "@p cp.async.bulk.tensor.3d.shared::cluster.global.mbarrier::complete_tx::bytes [%0], [%1, {%3, %4, %5}], [%2];\n"
                 "@p cp.async.bulk.tensor.3d.shared::cluster.global.mbarrier::complete_tx::bytes [d2], [%1, {%3, c2, %5}], [%2];\n}"
                 ::"r"(sb + s * SLOTB), "l"(tmx), "r"(full + s * 8), "r"(third * 32), "r"(e.x), "r"(e.y) : "memory");
  }
}

__device__ __forceinline__ void conv_credit(uint32_t sb, int P0, int nit, int lane) {
  const uint32_t full = sb + MISC;
  uint32_t ctarget = 0;
  int credit = P0 + RING;
  for (int it = 0; it <= nit; it++) {
    if (it >= NSLOT) {
      if (it == NSLOT) {
        if (lane == 0) ctarget = 16 * ((uint32_t)(atomicAdd(&g_start, 1ULL) / gridDim.x) + 1);
        ctarget = __shfl_sync(0xffffffffu, ctarget, 0);
      }
      const int P = (int)lds32(sb + CTAB + it * 16 + 4);
      mbar_wait(full + 64 + ((it - NSLOT) & 15) * 8, ((it - NSLOT) >> 4) & 1);
      int spins = 0;
      while ((int)lds32(full + 192 + (it & 3) * 4) < it - 15) { __nanosleep(64); if (++spins > SPIN_LIMIT) __trap(); }
      if (P >= credit) {
        while (true) {
          const uint32_t ok = __ballot_sync(0xffffffffu, ld_relaxed(&g_cons[credit - RING + lane]) == ctarget);
          const int got = __ffs(~ok) - 1;
          credit += got < 0 ? 32 : got;
          if (P < credit) break;
          __nanosleep(200); if (++spins > SPIN_LIMIT) __trap();
        }
        asm volatile("fence.acquire.gpu;" ::: "memory");
      }
    }
    if (lane == 0) mbar_arrive(full + (it & (NSLOT - 1)) * 8);
  }
}

__device__ __forceinline__ void conv_publisher(uint32_t sb, int nit, int k, int lane) {
  for (int it = k; it < nit; it += 4) {
    const bool edge = it < PUBE || it >= ((nit - PUBE) & ~3);
    const int cnt = edge ? 1 : ((it & (PUBN - 1)) == PUBN - 1 ? PUBN : 0);
    int P = -1;
    if (lane < cnt) P = (int)lds32(sb + CTAB + (it - lane) * 16 + 4);
    mbar_wait(sb + MISC + 64 + (it & 15) * 8, (it >> 4) & 1);
    if (lane == 0) sts32(sb + MISC + 192 + k * 4, it + 1);
    if (P >= 0) {
      if (!(ABL & 1)) asm volatile("fence.release.gpu;" ::: "memory");
      red_add(&g_ready[P]);
      PROF_AT(((it - lane) & 7) == 0 || it < 8, 200 + it - lane);
    }
    __syncwarp();
  }
}

__global__ void __launch_bounds__(512, 1) convnext_kernel(const __grid_constant__ CUtensorMap tmx, const __grid_constant__ CUtensorMap tmr, const __grid_constant__ CUtensorMap tmo, const __nv_bfloat16* __restrict__ dw,
                                                          const __nv_bfloat16* __restrict__ w1, const __nv_bfloat16* __restrict__ w2, __nv_bfloat16* __restrict__ out) {
  extern __shared__ __align__(1024) unsigned char smem[];
  const uint32_t sb = smem_u32(smem);
  const int warp = __shfl_sync(0xffffffffu, threadIdx.x >> 5, 0), lane = threadIdx.x & 31;
  PROF_AT(threadIdx.x == 0, 0);
  uint32_t smid, nsmid;
  asm volatile("mov.u32 %0, %%smid;" : "=r"(smid));
  asm volatile("mov.u32 %0, %%nsmid;" : "=r"(nsmid));
  const bool tabled = TABLED && NG == 9 && gridDim.x == 132 && nsmid == 132;
  int cidx, idx;
  bool is_conv;
  if (tabled) {
    idx = smid;
    is_conv = (smid < 48 && !(smid & 1)) || smid == 60 || smid == 120 || smid == 122;
    cidx = smid < 48 ? ((smid >> 1) & 7) * 3 + (smid >> 4) : smid == 60 ? 26 : 24 + ((smid >> 1) & 1);
  } else {
    cidx = (blockIdx.x * NCONV) / gridDim.x;
    is_conv = ((blockIdx.x + 1) * NCONV) / gridDim.x != cidx;
    idx = blockIdx.x - cidx;
  }
  PROF_VAL(threadIdx.x == 0, 2, is_conv ? 1000 + cidx : idx);
  if (!is_conv) {
    mlp_role(sb, &tmr, &tmo, w1, w2, out, idx, tabled, warp, lane);
  } else {
    const int gm = cidx / 3, third = cidx - gm * 3;
    const int P0 = gm * PLEN, P1 = min(P0 + PLEN, 1024) - 1;
    const int Vs = P0 + 2 * (P0 >> 8) + ((P0 & 255) ? 0 : 1);
    const int nit = P1 + 2 * (P1 >> 8) + 4 - Vs;
    if (threadIdx.x == 0) {
      for (int s = 0; s < NSLOT; s++) { mbar_init(sb + MISC + s * 8, 2); mbar_init(sb + MISC + 64 + s * 8, 8); mbar_init(sb + MISC + 128 + s * 8, 8); }
      sts128(sb + MISC + 192, make_uint4(0, 0, 0, 0));
      asm volatile("fence.mbarrier_init.release.cluster;" ::: "memory");
    }
    if (threadIdx.x >= 256 && threadIdx.x - 256 <= nit) {
      const int it = threadIdx.x - 256, V = Vs + it;
      const int st = (V - 1) / 258, so = max(V - 3, 0) / 258, po = V - 3 - so * 258, P = so * 256 + po;
      const bool ok = po < 256 && P >= P0 && P <= P1;
      sts128(sb + CTAB + it * 16, make_uint4((ok ? ((P - P0) & (RING - 1)) * NG + gm : RING * NG) * (4 * TILEB), ok ? P : -1, st * 128 - 3, 2 * (V - st * 258) - 3));
    }
    __syncthreads();
    if (warp < 8) {
      asm volatile("setmaxnreg.inc.sync.aligned.u32 224;");
      conv_compute(sb, dw, third, nit, warp, lane);
    } else if (warp >= 12) {
      asm volatile("setmaxnreg.dec.sync.aligned.u32 24;");
      conv_publisher(sb, nit, warp - 12, lane);
    } else {
      asm volatile("setmaxnreg.dec.sync.aligned.u32 40;");
      if (warp == 8) conv_loader(sb, &tmx, nit, third);
      else if (warp == 9) conv_credit(sb, P0, nit, lane);
    }
  }
}

typedef CUresult (*PFN_encodeTiled)(CUtensorMap*, CUtensorMapDataType, cuuint32_t, void*, const cuuint64_t*, const cuuint64_t*, const cuuint32_t*, const cuuint32_t*,
                                    CUtensorMapInterleave, CUtensorMapSwizzle, CUtensorMapL2promotion, CUtensorMapFloatOOBfill);

extern "C" void kernel_launch(void* const* d_in, const int* in_sizes, int n_in, void* d_out, int out_size) {
  const __nv_bfloat16* x = (const __nv_bfloat16*)d_in[0];
  const __nv_bfloat16* dw = (const __nv_bfloat16*)d_in[1];
  const __nv_bfloat16* w1 = (const __nv_bfloat16*)d_in[2];
  const __nv_bfloat16* w2 = (const __nv_bfloat16*)d_in[3];
  static PFN_encodeTiled encode = nullptr;
  static int nsm = 0;
  if (!encode) {
    void* fn = nullptr; cudaDriverEntryPointQueryResult qr;
    cudaGetDriverEntryPoint("cuTensorMapEncodeTiled", &fn, cudaEnableDefault, &qr);
    encode = (PFN_encodeTiled)fn;
    int dev = 0; cudaGetDevice(&dev);
    cudaDeviceGetAttribute(&nsm, cudaDevAttrMultiProcessorCount, dev);
    cudaFuncSetAttribute(convnext_kernel, cudaFuncAttributeMaxDynamicSharedMemorySize, SMEM_BYTES);
  }
  CUtensorMap tm;
  cuuint64_t dims[3] = {96, 512, 512}, strides[2] = {192, 192 * 512};
  cuuint32_t box[3] = {32, 70, 2}, es[3] = {1, 1, 1};
  encode(&tm, CU_TENSOR_MAP_DATA_TYPE_BFLOAT16, 3, (void*)x, dims, strides, box, es, CU_TENSOR_MAP_INTERLEAVE_NONE, CU_TENSOR_MAP_SWIZZLE_64B,
         PROMO, CU_TENSOR_MAP_FLOAT_OOB_FILL_NONE);
  CUtensorMap tr, to;
  cuuint64_t dims2[3] = {1536, 32, 512}, strides2[2] = {3072, 192 * 512};
  cuuint32_t box2[3] = {192, 4, 2};
  encode(&tr, CU_TENSOR_MAP_DATA_TYPE_BFLOAT16, 3, (void*)x, dims2, strides2, box2, es, CU_TENSOR_MAP_INTERLEAVE_NONE, CU_TENSOR_MAP_SWIZZLE_NONE,
         CU_TENSOR_MAP_L2_PROMOTION_NONE, CU_TENSOR_MAP_FLOAT_OOB_FILL_NONE);
  encode(&to, CU_TENSOR_MAP_DATA_TYPE_BFLOAT16, 3, d_out, dims2, strides2, box2, es, CU_TENSOR_MAP_INTERLEAVE_NONE, CU_TENSOR_MAP_SWIZZLE_NONE,
         CU_TENSOR_MAP_L2_PROMOTION_NONE, CU_TENSOR_MAP_FLOAT_OOB_FILL_NONE);
  convnext_kernel<<<nsm, 512, SMEM_BYTES>>>(tm, tr, to, dw, w1, w2, (__nv_bfloat16*)d_out);
}
```

```cpp
#include <cuda_runtime.h>
#include <cuda_bf16.h>
#include <cuda.h>
#include <stdint.h>

template<int SCALE_D> __device__ __forceinline__ void wgmma_n48_f16(uint32_t* d, const uint32_t* a, uint64_t desc) {
  if (SCALE_D == 0) asm volatile("wgmma.mma_async.sync.aligned.m64n48k16.f16.f16.f16 {%0,%1,%2,%3,%4,%5,%6,%7,%8,%9,%10,%11}, {%12,%13,%14,%15}, %16, 0, 1, 1, 1;"
    : "=r"(d[0]),"=r"(d[1]),"=r"(d[2]),"=r"(d[3]),"=r"(d[4]),"=r"(d[5]),"=r"(d[6]),"=r"(d[7]),"=r"(d[8]),"=r"(d[9]),"=r"(d[10]),"=r"(d[11])
    : "r"(a[0]),"r"(a[1]),"r"(a[2]),"r"(a[3]),"l"(desc));
  if (SCALE_D == 1) asm volatile("wgmma.mma_async.sync.aligned.m64n48k16.f16.f16.f16 {%0,%1,%2,%3,%4,%5,%6,%7,%8,%9,%10,%11}, {%12,%13,%14,%15}, %16, 1, 1, 1, 1;"
    : "+r"(d[0]),"+r"(d[1]),"+r"(d[2]),"+r"(d[3]),"+r"(d[4]),"+r"(d[5]),"+r"(d[6]),"+r"(d[7]),"+r"(d[8]),"+r"(d[9]),"+r"(d[10]),"+r"(d[11])
    : "r"(a[0]),"r"(a[1]),"r"(a[2]),"r"(a[3]),"l"(desc));
}

template<int SCALE_D> __device__ __forceinline__ void wgmma_n96_f16(uint32_t* d, const uint32_t* a, uint64_t desc) {
  if (SCALE_D == 0) asm volatile("wgmma.mma_async.sync.aligned.m64n96k16.f16.f16.f16 {%0,%1,%2,%3,%4,%5,%6,%7,%8,%9,%10,%11,%12,%13,%14,%15,%16,%17,%18,%19,%20,%21,%22,%23}, {%24,%25,%26,%27}, %28, 0, 1, 1, 1;"
    : "=r"(d[0]),"=r"(d[1]),"=r"(d[2]),"=r"(d[3]),"=r"(d[4]),"=r"(d[5]),"=r"(d[6]),"=r"(d[7]),"=r"(d[8]),"=r"(d[9]),"=r"(d[10]),"=r"(d[11]),"=r"(d[12]),"=r"(d[13]),"=r"(d[14]),"=r"(d[15]),"=r"(d[16]),"=r"(d[17]),"=r"(d[18]),"=r"(d[19]),"=r"(d[20]),"=r"(d[21]),"=r"(d[22]),"=r"(d[23])
    : "r"(a[0]),"r"(a[1]),"r"(a[2]),"r"(a[3]),"l"(desc));
  if (SCALE_D == 1) asm volatile("wgmma.mma_async.sync.aligned.m64n96k16.f16.f16.f16 {%0,%1,%2,%3,%4,%5,%6,%7,%8,%9,%10,%11,%12,%13,%14,%15,%16,%17,%18,%19,%20,%21,%22,%23}, {%24,%25,%26,%27}, %28, 1, 1, 1, 1;"
    : "+r"(d[0]),"+r"(d[1]),"+r"(d[2]),"+r"(d[3]),"+r"(d[4]),"+r"(d[5]),"+r"(d[6]),"+r"(d[7]),"+r"(d[8]),"+r"(d[9]),"+r"(d[10]),"+r"(d[11]),"+r"(d[12]),"+r"(d[13]),"+r"(d[14]),"+r"(d[15]),"+r"(d[16]),"+r"(d[17]),"+r"(d[18]),"+r"(d[19]),"+r"(d[20]),"+r"(d[21]),"+r"(d[22]),"+r"(d[23])
    : "r"(a[0]),"r"(a[1]),"r"(a[2]),"r"(a[3]),"l"(desc));
}

__device__ const uint16_t g_sched[132][48] = {
{65535,65535,65535,65535,65535,65535,65535,65535,65535,65535,65535,65535,65535,65535,65535,65535,65535,65535,65535,65535,65535,65535,65535,65535,65535,65535,65535,65535,65535,65535,65535,65535,65535,65535,65535,65535,65535,65535,65535,65535,65535,65535,65535,65535,65535,65535,65535,65535},
{0,12,3665,35,47,59,70,82,94,105,117,129,3779,152,164,176,187,199,211,222,234,246,3893,269,281,293,304,316,328,339,351,363,4008,386,398,410,421,433,445,65535,65535,65535,65535,65535,65535,65535,65535,65535},
{65535,65535,65535,65535,65535,65535,65535,65535,65535,65535,65535,65535,65535,65535,65535,65535,65535,65535,65535,65535,65535,65535,65535,65535,65535,65535,65535,65535,65535,65535,65535,65535,65535,65535,65535,65535,65535,65535,65535,65535,65535,65535,65535,65535,65535,65535,65535,65535},
{456,468,3666,491,503,515,526,538,550,561,573,585,3780,608,620,632,643,655,667,678,690,702,3894,725,737,749,760,772,784,795,807,819,4009,842,854,866,877,889,901,65535,65535,65535,65535,65535,65535,65535,65535,65535},
{65535,65535,65535,65535,65535,65535,65535,65535,65535,65535,65535,65535,65535,65535,65535,65535,65535,65535,65535,65535,65535,65535,65535,65535,65535,65535,65535,65535,65535,65535,65535,65535,65535,65535,65535,65535,65535,65535,65535,65535,65535,65535,65535,65535,65535,65535,65535,65535},
{912,924,3667,947,959,971,982,994,1006,1017,1029,1041,3781,1064,1076,1088,1099,1111,1123,1134,1146,1158,3895,1181,1193,1205,1216,1228,1240,1251,1263,1275,4010,1298,1310,1322,1333,1345,1357,65535,65535,65535,65535,65535,65535,65535,65535,65535},
{65535,65535,65535,65535,65535,65535,65535,65535,65535,65535,65535,65535,65535,65535,65535,65535,65535,65535,65535,65535,65535,65535,65535,65535,65535,65535,65535,65535,65535,65535,65535,65535,65535,65535,65535,65535,65535,65535,65535,65535,65535,65535,65535,65535,65535,65535,65535,65535},
{1368,1380,3668,1403,1415,1427,1438,1450,1462,1473,1485,1497,3782,1520,1532,1544,1555,1567,1579,1590,1602,1614,3896,1637,1649,1661,1672,1684,1696,1707,1719,1731,4011,1754,1766,1778,1789,1801,1813,65535,65535,65535,65535,65535,65535,65535,65535,65535},
{65535,65535,65535,65535,65535,65535,65535,65535,65535,65535,65535,65535,65535,65535,65535,65535,65535,65535,65535,65535,65535,65535,65535,65535,65535,65535,65535,65535,65535,65535,65535,65535,65535,65535,65535,65535,65535,65535,65535,65535,65535,65535,65535,65535,65535,65535,65535,65535},
{1824,1836,3669,1859,1871,1883,1894,1906,1918,1929,1941,1953,3783,1976,1988,2000,2011,2023,2035,2046,2058,2070,3897,2093,2105,2117,2128,2140,2152,2163,2175,2187,4012,2210,2222,2234,2245,2257,2269,65535,65535,65535,65535,65535,65535,65535,65535,65535},
{65535,65535,65535,65535,65535,65535,65535,65535,65535,65535,65535,65535,65535,65535,65535,65535,65535,65535,65535,65535,65535,65535,65535,65535,65535,65535,65535,65535,65535,65535,65535,65535,65535,65535,65535,65535,65535,65535,65535,65535,65535,65535,65535,65535,65535,65535,65535,65535},
{2280,2292,3670,2315,2327,2339,2350,2362,2374,2385,2397,2409,3784,2432,2444,2456,2467,2479,2491,2502,2514,2526,3898,2549,2561,2573,2584,2596,2608,2619,2631,2643,4013,2666,2678,2690,2701,2713,2725,65535,65535,65535,65535,65535,65535,65535,65535,65535},
{65535,65535,65535,65535,65535,65535,65535,65535,65535,65535,65535,65535,65535,65535,65535,65535,65535,65535,65535,65535,65535,65535,65535,65535,65535,65535,65535,65535,65535,65535,65535,65535,65535,65535,65535,65535,65535,65535,65535,65535,65535,65535,65535,65535,65535,65535,65535,65535},
{2736,2748,3671,2771,2783,2795,2806,2818,2830,2841,2853,2865,3785,2888,2900,2912,2923,2935,2947,2958,2970,2982,3899,3005,3017,3029,3040,3052,3064,3075,3087,3099,4014,3122,3134,3146,3157,3169,3181,65535,65535,65535,65535,65535,65535,65535,65535,65535},
{65535,65535,65535,65535,65535,65535,65535,65535,65535,65535,65535,65535,65535,65535,65535,65535,65535,65535,65535,65535,65535,65535,65535,65535,65535,65535,65535,65535,65535,65535,65535,65535,65535,65535,65535,65535,65535,65535,65535,65535,65535,65535,65535,65535,65535,65535,65535,65535},
{3192,3204,3672,3227,3239,3251,3262,3274,3286,3297,3309,3321,3786,3344,3356,3368,3379,3391,3403,3414,3426,3438,3900,3461,3473,3485,3496,3508,3520,3531,3543,3555,4015,3578,3590,3602,3613,3625,3637,65535,65535,65535,65535,65535,65535,65535,65535,65535},
{65535,65535,65535,65535,65535,65535,65535,65535,65535,65535,65535,65535,65535,65535,65535,65535,65535,65535,65535,65535,65535,65535,65535,65535,65535,65535,65535,65535,65535,65535,65535,65535,65535,65535,65535,65535,65535,65535,65535,65535,65535,65535,65535,65535,65535,65535,65535,65535},
{1,13,24,36,48,3700,71,83,95,106,118,130,141,153,165,3814,188,200,212,223,235,247,258,270,282,3929,305,317,329,340,352,364,375,387,399,4043,422,434,446,65535,65535,65535,65535,65535,65535,65535,65535,65535},
{65535,65535,65535,65535,65535,65535,65535,65535,65535,65535,65535,65535,65535,65535,65535,65535,65535,65535,65535,65535,65535,65535,65535,65535,65535,65535,65535,65535,65535,65535,65535,65535,65535,65535,65535,65535,65535,65535,65535,65535,65535,65535,65535,65535,65535,65535,65535,65535},
{457,469,480,492,504,3701,527,539,551,562,574,586,597,609,621,3815,644,656,668,679,691,703,714,726,738,3930,761,773,785,796,808,820,831,843,855,4044,878,890,902,65535,65535,65535,65535,65535,65535,65535,65535,65535},
{65535,65535,65535,65535,65535,65535,65535,65535,65535,65535,65535,65535,65535,65535,65535,65535,65535,65535,65535,65535,65535,65535,65535,65535,65535,65535,65535,65535,65535,65535,65535,65535,65535,65535,65535,65535,65535,65535,65535,65535,65535,65535,65535,65535,65535,65535,65535,65535},
{913,925,936,948,960,3702,983,995,1007,1018,1030,1042,1053,1065,1077,3816,1100,1112,1124,1135,1147,1159,1170,1182,1194,3931,1217,1229,1241,1252,1264,1276,1287,1299,1311,4045,1334,1346,1358,65535,65535,65535,65535,65535,65535,65535,65535,65535},
{65535,65535,65535,65535,65535,65535,65535,65535,65535,65535,65535,65535,65535,65535,65535,65535,65535,65535,65535,65535,65535,65535,65535,65535,65535,65535,65535,65535,65535,65535,65535,65535,65535,65535,65535,65535,65535,65535,65535,65535,65535,65535,65535,65535,65535,65535,65535,65535},
{1369,1381,1392,1404,1416,3703,1439,1451,1463,1474,1486,1498,1509,1521,1533,3817,1556,1568,1580,1591,1603,1615,1626,1638,1650,3932,1673,1685,1697,1708,1720,1732,1743,1755,1767,4046,1790,1802,1814,65535,65535,65535,65535,65535,65535,65535,65535,65535},
{65535,65535,65535,65535,65535,65535,65535,65535,65535,65535,65535,65535,65535,65535,65535,65535,65535,65535,65535,65535,65535,65535,65535,65535,65535,65535,65535,65535,65535,65535,65535,65535,65535,65535,65535,65535,65535,65535,65535,65535,65535,65535,65535,65535,65535,65535,65535,65535},
{1825,1837,1848,1860,1872,3704,1895,1907,1919,1930,1942,1954,1965,1977,1989,3818,2012,2024,2036,2047,2059,2071,2082,2094,2106,3933,2129,2141,2153,2164,2176,2188,2199,2211,2223,4047,2246,2258,2270,65535,65535,65535,65535,65535,65535,65535,65535,65535},
{65535,65535,65535,65535,65535,65535,65535,65535,65535,65535,65535,65535,65535,65535,65535,65535,65535,65535,65535,65535,65535,65535,65535,65535,65535,65535,65535,65535,65535,65535,65535,65535,65535,65535,65535,65535,65535,65535,65535,65535,65535,65535,65535,65535,65535,65535,65535,65535},
{2281,2293,2304,2316,2328,3705,2351,2363,2375,2386,2398,2410,2421,2433,2445,3819,2468,2480,2492,2503,2515,2527,2538,2550,2562,3934,2585,2597,2609,2620,2632,2644,2655,2667,2679,4048,2702,2714,2726,65535,65535,65535,65535,65535,65535,65535,65535,65535},
{65535,65535,65535,65535,65535,65535,65535,65535,65535,65535,65535,65535,65535,65535,65535,65535,65535,65535,65535,65535,65535,65535,65535,65535,65535,65535,65535,65535,65535,65535,65535,65535,65535,65535,65535,65535,65535,65535,65535,65535,65535,65535,65535,65535,65535,65535,65535,65535},
{2737,2749,2760,2772,2784,3706,2807,2819,2831,2842,2854,2866,2877,2889,2901,3820,2924,2936,2948,2959,2971,2983,2994,3006,3018,3935,3041,3053,3065,3076,3088,3100,3111,3123,3135,4049,3158,3170,3182,65535,65535,65535,65535,65535,65535,65535,65535,65535},
{65535,65535,65535,65535,65535,65535,65535,65535,65535,65535,65535,65535,65535,65535,65535,65535,65535,65535,65535,65535,65535,65535,65535,65535,65535,65535,65535,65535,65535,65535,65535,65535,65535,65535,65535,65535,65535,65535,65535,65535,65535,65535,65535,65535,65535,65535,65535,65535},
{3193,3205,3216,3228,3240,3707,3263,3275,3287,3298,3310,3322,3333,3345,3357,3821,3380,3392,3404,3415,3427,3439,3450,3462,3474,3936,3497,3509,3521,3532,3544,3556,3567,3579,3591,4050,3614,3626,3638,65535,65535,65535,65535,65535,65535,65535,65535,65535},
{65535,65535,65535,65535,65535,65535,65535,65535,65535,65535,65535,65535,65535,65535,65535,65535,65535,65535,65535,65535,65535,65535,65535,65535,65535,65535,65535,65535,65535,65535,65535,65535,65535,65535,65535,65535,65535,65535,65535,65535,65535,65535,65535,65535,65535,65535,65535,65535},
{2,14,25,37,49,60,72,84,3735,107,119,131,142,154,166,177,189,201,3850,224,236,248,259,271,283,294,306,318,3964,341,353,365,376,388,400,411,423,435,4078,65535,65535,65535,65535,65535,65535,65535,65535,65535},
{65535,65535,65535,65535,65535,65535,65535,65535,65535,65535,65535,65535,65535,65535,65535,65535,65535,65535,65535,65535,65535,65535,65535,65535,65535,65535,65535,65535,65535,65535,65535,65535,65535,65535,65535,65535,65535,65535,65535,65535,65535,65535,65535,65535,65535,65535,65535,65535},
{458,470,481,493,505,516,528,540,3736,563,575,587,598,610,622,633,645,657,3851,680,692,704,715,727,739,750,762,774,3965,797,809,821,832,844,856,867,879,891,4079,65535,65535,65535,65535,65535,65535,65535,65535,65535},
{65535,65535,65535,65535,65535,65535,65535,65535,65535,65535,65535,65535,65535,65535,65535,65535,65535,65535,65535,65535,65535,65535,65535,65535,65535,65535,65535,65535,65535,65535,65535,65535,65535,65535,65535,65535,65535,65535,65535,65535,65535,65535,65535,65535,65535,65535,65535,65535},
{914,926,937,949,961,972,984,996,3737,1019,1031,1043,1054,1066,1078,1089,1101,1113,3852,1136,1148,1160,1171,1183,1195,1206,1218,1230,3966,1253,1265,1277,1288,1300,1312,1323,1335,1347,4080,65535,65535,65535,65535,65535,65535,65535,65535,65535},
{65535,65535,65535,65535,65535,65535,65535,65535,65535,65535,65535,65535,65535,65535,65535,65535,65535,65535,65535,65535,65535,65535,65535,65535,65535,65535,65535,65535,65535,65535,65535,65535,65535,65535,65535,65535,65535,65535,65535,65535,65535,65535,65535,65535,65535,65535,65535,65535},
{1370,1382,1393,1405,1417,1428,1440,1452,3738,1475,1487,1499,1510,1522,1534,1545,1557,1569,3853,1592,1604,1616,1627,1639,1651,1662,1674,1686,3967,1709,1721,1733,1744,1756,1768,1779,1791,1803,4081,65535,65535,65535,65535,65535,65535,65535,65535,65535},
{65535,65535,65535,65535,65535,65535,65535,65535,65535,65535,65535,65535,65535,65535,65535,65535,65535,65535,65535,65535,65535,65535,65535,65535,65535,65535,65535,65535,65535,65535,65535,65535,65535,65535,65535,65535,65535,65535,65535,65535,65535,65535,65535,65535,65535,65535,65535,65535},
{1826,1838,1849,1861,1873,1884,1896,1908,3739,1931,1943,1955,1966,1978,1990,2001,2013,2025,3854,2048,2060,2072,2083,2095,2107,2118,2130,2142,3968,2165,2177,2189,2200,2212,2224,2235,2247,2259,4082,65535,65535,65535,65535,65535,65535,65535,65535,65535},
{65535,65535,65535,65535,65535,65535,65535,65535,65535,65535,65535,65535,65535,65535,65535,65535,65535,65535,65535,65535,65535,65535,65535,65535,65535,65535,65535,65535,65535,65535,65535,65535,65535,65535,65535,65535,65535,65535,65535,65535,65535,65535,65535,65535,65535,65535,65535,65535},
{2282,2294,2305,2317,2329,2340,2352,2364,3740,2387,2399,2411,2422,2434,2446,2457,2469,2481,3855,2504,2516,2528,2539,2551,2563,2574,2586,2598,3969,2621,2633,2645,2656,2668,2680,2691,2703,2715,4083,65535,65535,65535,65535,65535,65535,65535,65535,65535},
{65535,65535,65535,65535,65535,65535,65535,65535,65535,65535,65535,65535,65535,65535,65535,65535,65535,65535,65535,65535,65535,65535,65535,65535,65535,65535,65535,65535,65535,65535,65535,65535,65535,65535,65535,65535,65535,65535,65535,65535,65535,65535,65535,65535,65535,65535,65535,65535},
{2738,2750,2761,2773,2785,2796,2808,2820,3741,2843,2855,2867,2878,2890,2902,2913,2925,2937,3856,2960,2972,2984,2995,3007,3019,3030,3042,3054,3970,3077,3089,3101,3112,3124,3136,3147,3159,3171,4084,65535,65535,65535,65535,65535,65535,65535,65535,65535},
{65535,65535,65535,65535,65535,65535,65535,65535,65535,65535,65535,65535,65535,65535,65535,65535,65535,65535,65535,65535,65535,65535,65535,65535,65535,65535,65535,65535,65535,65535,65535,65535,65535,65535,65535,65535,65535,65535,65535,65535,65535,65535,65535,65535,65535,65535,65535,65535},
{3194,3206,3217,3229,3241,3252,3264,3276,3742,3299,3311,3323,3334,3346,3358,3369,3381,3393,3857,3416,3428,3440,3451,3463,3475,3486,3498,3510,3971,3533,3545,3557,3568,3580,3592,3603,3615,3627,4085,65535,65535,65535,65535,65535,65535,65535,65535,65535},
{3,3656,26,38,50,61,73,85,96,108,120,3770,143,155,167,178,190,202,213,225,237,3885,260,272,284,295,307,319,330,342,354,3999,377,389,401,412,424,436,447,65535,65535,65535,65535,65535,65535,65535,65535,65535},
{4,15,27,39,3691,62,74,86,97,109,121,132,144,156,3806,179,191,203,214,226,238,249,261,273,3920,296,308,320,331,343,355,366,378,390,4034,413,425,437,448,65535,65535,65535,65535,65535,65535,65535,65535,65535},
{459,3657,482,494,506,517,529,541,552,564,576,3771,599,611,623,634,646,658,669,681,693,3886,716,728,740,751,763,775,786,798,810,4000,833,845,857,868,880,892,903,65535,65535,65535,65535,65535,65535,65535,65535,65535},
{460,471,483,495,3692,518,530,542,553,565,577,588,600,612,3807,635,647,659,670,682,694,705,717,729,3921,752,764,776,787,799,811,822,834,846,4035,869,881,893,904,65535,65535,65535,65535,65535,65535,65535,65535,65535},
{915,3658,938,950,962,973,985,997,1008,1020,1032,3772,1055,1067,1079,1090,1102,1114,1125,1137,1149,3887,1172,1184,1196,1207,1219,1231,1242,1254,1266,4001,1289,1301,1313,1324,1336,1348,1359,65535,65535,65535,65535,65535,65535,65535,65535,65535},
{916,927,939,951,3693,974,986,998,1009,1021,1033,1044,1056,1068,3808,1091,1103,1115,1126,1138,1150,1161,1173,1185,3922,1208,1220,1232,1243,1255,1267,1278,1290,1302,4036,1325,1337,1349,1360,65535,65535,65535,65535,65535,65535,65535,65535,65535},
{1371,3659,1394,1406,1418,1429,1441,1453,1464,1476,1488,3773,1511,1523,1535,1546,1558,1570,1581,1593,1605,3888,1628,1640,1652,1663,1675,1687,1698,1710,1722,4002,1745,1757,1769,1780,1792,1804,1815,65535,65535,65535,65535,65535,65535,65535,65535,65535},
{1372,1383,1395,1407,3694,1430,1442,1454,1465,1477,1489,1500,1512,1524,3809,1547,1559,1571,1582,1594,1606,1617,1629,1641,3923,1664,1676,1688,1699,1711,1723,1734,1746,1758,4037,1781,1793,1805,1816,65535,65535,65535,65535,65535,65535,65535,65535,65535},
{1827,3660,1850,1862,1874,1885,1897,1909,1920,1932,1944,3774,1967,1979,1991,2002,2014,2026,2037,2049,2061,3889,2084,2096,2108,2119,2131,2143,2154,2166,2178,4003,2201,2213,2225,2236,2248,2260,2271,65535,65535,65535,65535,65535,65535,65535,65535,65535},
{1828,1839,1851,1863,3695,1886,1898,1910,1921,1933,1945,1956,1968,1980,3810,2003,2015,2027,2038,2050,2062,2073,2085,2097,3924,2120,2132,2144,2155,2167,2179,2190,2202,2214,4038,2237,2249,2261,2272,65535,65535,65535,65535,65535,65535,65535,65535,65535},
{2283,3661,2306,2318,2330,2341,2353,2365,2376,2388,2400,3775,2423,2435,2447,2458,2470,2482,2493,2505,2517,3890,2540,2552,2564,2575,2587,2599,2610,2622,2634,4004,2657,2669,2681,2692,2704,2716,2727,65535,65535,65535,65535,65535,65535,65535,65535,65535},
{2284,2295,2307,2319,3696,2342,2354,2366,2377,2389,2401,2412,2424,2436,3811,2459,2471,2483,2494,2506,2518,2529,2541,2553,3925,2576,2588,2600,2611,2623,2635,2646,2658,2670,4039,2693,2705,2717,2728,65535,65535,65535,65535,65535,65535,65535,65535,65535},
{65535,65535,65535,65535,65535,65535,65535,65535,65535,65535,65535,65535,65535,65535,65535,65535,65535,65535,65535,65535,65535,65535,65535,65535,65535,65535,65535,65535,65535,65535,65535,65535,65535,65535,65535,65535,65535,65535,65535,65535,65535,65535,65535,65535,65535,65535,65535,65535},
{2739,3662,2762,2774,2786,2797,2809,2821,2832,2844,2856,3776,2879,2891,2903,2914,2926,2938,2949,2961,2973,3891,2996,3008,3020,3031,3043,3055,3066,3078,3090,4005,3113,3125,3137,3148,3160,3172,3183,65535,65535,65535,65535,65535,65535,65535,65535,65535},
{3195,3663,3218,3230,3242,3253,3265,3277,3288,3300,3312,3777,3335,3347,3359,3370,3382,3394,3405,3417,3429,3892,3452,3464,3476,3487,3499,3511,3522,3534,3546,4006,3569,3581,3593,3604,3616,3628,3639,65535,65535,65535,65535,65535,65535,65535,65535,65535},
{3196,3207,3219,3231,3698,3254,3266,3278,3289,3301,3313,3324,3336,3348,3813,3371,3383,3395,3406,3418,3430,3441,3453,3465,3927,3488,3500,3512,3523,3535,3547,3558,3570,3582,4041,3605,3617,3629,3640,65535,65535,65535,65535,65535,65535,65535,65535,65535},
{461,472,484,496,507,519,531,3728,554,566,578,589,601,613,624,636,648,3842,671,683,695,706,718,730,741,753,765,3956,788,800,812,823,835,847,858,870,882,4070,905,65535,65535,65535,65535,65535,65535,65535,65535,65535},
{3649,473,485,497,508,520,532,543,555,567,3763,590,602,614,625,637,649,660,672,684,3877,707,719,731,742,754,766,777,789,801,3991,824,836,848,859,871,883,894,906,65535,65535,65535,65535,65535,65535,65535,65535,65535},
{917,928,940,952,963,975,987,3729,1010,1022,1034,1045,1057,1069,1080,1092,1104,3843,1127,1139,1151,1162,1174,1186,1197,1209,1221,3957,1244,1256,1268,1279,1291,1303,1314,1326,1338,4071,1361,65535,65535,65535,65535,65535,65535,65535,65535,65535},
{3650,929,941,953,964,976,988,999,1011,1023,3764,1046,1058,1070,1081,1093,1105,1116,1128,1140,3878,1163,1175,1187,1198,1210,1222,1233,1245,1257,3992,1280,1292,1304,1315,1327,1339,1350,1362,65535,65535,65535,65535,65535,65535,65535,65535,65535},
{1373,1384,1396,1408,1419,1431,1443,3730,1466,1478,1490,1501,1513,1525,1536,1548,1560,3844,1583,1595,1607,1618,1630,1642,1653,1665,1677,3958,1700,1712,1724,1735,1747,1759,1770,1782,1794,4072,1817,65535,65535,65535,65535,65535,65535,65535,65535,65535},
{3651,1385,1397,1409,1420,1432,1444,1455,1467,1479,3765,1502,1514,1526,1537,1549,1561,1572,1584,1596,3879,1619,1631,1643,1654,1666,1678,1689,1701,1713,3993,1736,1748,1760,1771,1783,1795,1806,1818,65535,65535,65535,65535,65535,65535,65535,65535,65535},
{1829,1840,1852,1864,1875,1887,1899,3731,1922,1934,1946,1957,1969,1981,1992,2004,2016,3845,2039,2051,2063,2074,2086,2098,2109,2121,2133,3959,2156,2168,2180,2191,2203,2215,2226,2238,2250,4073,2273,65535,65535,65535,65535,65535,65535,65535,65535,65535},
{3652,1841,1853,1865,1876,1888,1900,1911,1923,1935,3766,1958,1970,1982,1993,2005,2017,2028,2040,2052,3880,2075,2087,2099,2110,2122,2134,2145,2157,2169,3994,2192,2204,2216,2227,2239,2251,2262,2274,65535,65535,65535,65535,65535,65535,65535,65535,65535},
{2285,2296,2308,2320,2331,2343,2355,3732,2378,2390,2402,2413,2425,2437,2448,2460,2472,3846,2495,2507,2519,2530,2542,2554,2565,2577,2589,3960,2612,2624,2636,2647,2659,2671,2682,2694,2706,4074,2729,65535,65535,65535,65535,65535,65535,65535,65535,65535},
{3653,2297,2309,2321,2332,2344,2356,2367,2379,2391,3767,2414,2426,2438,2449,2461,2473,2484,2496,2508,3881,2531,2543,2555,2566,2578,2590,2601,2613,2625,3995,2648,2660,2672,2683,2695,2707,2718,2730,65535,65535,65535,65535,65535,65535,65535,65535,65535},
{2740,2751,2763,2775,3697,2798,2810,2822,2833,2845,2857,2868,2880,2892,3812,2915,2927,2939,2950,2962,2974,2985,2997,3009,3926,3032,3044,3056,3067,3079,3091,3102,3114,3126,4040,3149,3161,3173,3184,65535,65535,65535,65535,65535,65535,65535,65535,65535},
{2741,2752,2764,2776,2787,2799,2811,3733,2834,2846,2858,2869,2881,2893,2904,2916,2928,3847,2951,2963,2975,2986,2998,3010,3021,3033,3045,3961,3068,3080,3092,3103,3115,3127,3138,3150,3162,4075,3185,65535,65535,65535,65535,65535,65535,65535,65535,65535},
{3197,3208,3220,3232,3243,3255,3267,3734,3290,3302,3314,3325,3337,3349,3360,3372,3384,3848,3407,3419,3431,3442,3454,3466,3477,3489,3501,3962,3524,3536,3548,3559,3571,3583,3594,3606,3618,4076,3641,65535,65535,65535,65535,65535,65535,65535,65535,65535},
{3655,3209,3221,3233,3244,3256,3268,3279,3291,3303,3769,3326,3338,3350,3361,3373,3385,3396,3408,3420,3883,3443,3455,3467,3478,3490,3502,3513,3525,3537,3997,3560,3572,3584,3595,3607,3619,3630,3642,65535,65535,65535,65535,65535,65535,65535,65535,65535},
{462,474,486,3684,509,521,533,544,556,568,579,591,603,3798,626,638,650,661,673,685,696,708,720,3912,743,755,767,778,790,802,813,825,837,4026,860,872,884,895,907,65535,65535,65535,65535,65535,65535,65535,65535,65535},
{463,475,487,498,510,522,3719,545,557,569,580,592,604,615,627,639,3833,662,674,686,697,709,721,732,744,756,3947,779,791,803,814,826,838,849,861,873,4061,896,908,65535,65535,65535,65535,65535,65535,65535,65535,65535},
{918,930,942,3685,965,977,989,1000,1012,1024,1035,1047,1059,3799,1082,1094,1106,1117,1129,1141,1152,1164,1176,3913,1199,1211,1223,1234,1246,1258,1269,1281,1293,4027,1316,1328,1340,1351,1363,65535,65535,65535,65535,65535,65535,65535,65535,65535},
{919,931,943,954,966,978,3720,1001,1013,1025,1036,1048,1060,1071,1083,1095,3834,1118,1130,1142,1153,1165,1177,1188,1200,1212,3948,1235,1247,1259,1270,1282,1294,1305,1317,1329,4062,1352,1364,65535,65535,65535,65535,65535,65535,65535,65535,65535},
{1374,1386,1398,3686,1421,1433,1445,1456,1468,1480,1491,1503,1515,3800,1538,1550,1562,1573,1585,1597,1608,1620,1632,3914,1655,1667,1679,1690,1702,1714,1725,1737,1749,4028,1772,1784,1796,1807,1819,65535,65535,65535,65535,65535,65535,65535,65535,65535},
{1375,1387,1399,1410,1422,1434,3721,1457,1469,1481,1492,1504,1516,1527,1539,1551,3835,1574,1586,1598,1609,1621,1633,1644,1656,1668,3949,1691,1703,1715,1726,1738,1750,1761,1773,1785,4063,1808,1820,65535,65535,65535,65535,65535,65535,65535,65535,65535},
{1830,1842,1854,3687,1877,1889,1901,1912,1924,1936,1947,1959,1971,3801,1994,2006,2018,2029,2041,2053,2064,2076,2088,3915,2111,2123,2135,2146,2158,2170,2181,2193,2205,4029,2228,2240,2252,2263,2275,65535,65535,65535,65535,65535,65535,65535,65535,65535},
{1831,1843,1855,1866,1878,1890,3722,1913,1925,1937,1948,1960,1972,1983,1995,2007,3836,2030,2042,2054,2065,2077,2089,2100,2112,2124,3950,2147,2159,2171,2182,2194,2206,2217,2229,2241,4064,2264,2276,65535,65535,65535,65535,65535,65535,65535,65535,65535},
{2286,2298,2310,3688,2333,2345,2357,2368,2380,2392,2403,2415,2427,3802,2450,2462,2474,2485,2497,2509,2520,2532,2544,3916,2567,2579,2591,2602,2614,2626,2637,2649,2661,4030,2684,2696,2708,2719,2731,65535,65535,65535,65535,65535,65535,65535,65535,65535},
{2287,2299,2311,2322,2334,2346,3723,2369,2381,2393,2404,2416,2428,2439,2451,2463,3837,2486,2498,2510,2521,2533,2545,2556,2568,2580,3951,2603,2615,2627,2638,2650,2662,2673,2685,2697,4065,2720,2732,65535,65535,65535,65535,65535,65535,65535,65535,65535},
{3654,2753,2765,2777,2788,2800,2812,2823,2835,2847,3768,2870,2882,2894,2905,2917,2929,2940,2952,2964,3882,2987,2999,3011,3022,3034,3046,3057,3069,3081,3996,3104,3116,3128,3139,3151,3163,3174,3186,65535,65535,65535,65535,65535,65535,65535,65535,65535},
{2742,2754,2766,3689,2789,2801,2813,2824,2836,2848,2859,2871,2883,3803,2906,2918,2930,2941,2953,2965,2976,2988,3000,3917,3023,3035,3047,3058,3070,3082,3093,3105,3117,4031,3140,3152,3164,3175,3187,65535,65535,65535,65535,65535,65535,65535,65535,65535},
{3198,3210,3222,3690,3245,3257,3269,3280,3292,3304,3315,3327,3339,3804,3362,3374,3386,3397,3409,3421,3432,3444,3456,3918,3479,3491,3503,3514,3526,3538,3549,3561,3573,4032,3596,3608,3620,3631,3643,65535,65535,65535,65535,65535,65535,65535,65535,65535},
{3199,3211,3223,3234,3246,3258,3725,3281,3293,3305,3316,3328,3340,3351,3363,3375,3839,3398,3410,3422,3433,3445,3457,3468,3480,3492,3953,3515,3527,3539,3550,3562,3574,3585,3597,3609,4067,3632,3644,65535,65535,65535,65535,65535,65535,65535,65535,65535},
{464,476,488,499,511,523,534,546,558,3754,581,593,605,616,628,640,651,663,675,3868,698,710,722,733,745,757,768,780,792,3982,815,827,839,850,862,874,885,897,909,65535,65535,65535,65535,65535,65535,65535,65535,65535},
{465,477,3675,500,512,524,535,547,559,570,582,594,3789,617,629,641,652,664,676,687,699,711,3903,734,746,758,769,781,793,804,816,828,4017,851,863,875,886,898,910,65535,65535,65535,65535,65535,65535,65535,65535,65535},
{920,932,944,955,967,979,990,1002,1014,3755,1037,1049,1061,1072,1084,1096,1107,1119,1131,3869,1154,1166,1178,1189,1201,1213,1224,1236,1248,3983,1271,1283,1295,1306,1318,1330,1341,1353,1365,65535,65535,65535,65535,65535,65535,65535,65535,65535},
{921,933,3676,956,968,980,991,1003,1015,1026,1038,1050,3790,1073,1085,1097,1108,1120,1132,1143,1155,1167,3904,1190,1202,1214,1225,1237,1249,1260,1272,1284,4018,1307,1319,1331,1342,1354,1366,65535,65535,65535,65535,65535,65535,65535,65535,65535},
{1376,1388,1400,1411,1423,1435,1446,1458,1470,3756,1493,1505,1517,1528,1540,1552,1563,1575,1587,3870,1610,1622,1634,1645,1657,1669,1680,1692,1704,3984,1727,1739,1751,1762,1774,1786,1797,1809,1821,65535,65535,65535,65535,65535,65535,65535,65535,65535},
{1377,1389,3677,1412,1424,1436,1447,1459,1471,1482,1494,1506,3791,1529,1541,1553,1564,1576,1588,1599,1611,1623,3905,1646,1658,1670,1681,1693,1705,1716,1728,1740,4019,1763,1775,1787,1798,1810,1822,65535,65535,65535,65535,65535,65535,65535,65535,65535},
{1832,1844,1856,1867,1879,1891,1902,1914,1926,3757,1949,1961,1973,1984,1996,2008,2019,2031,2043,3871,2066,2078,2090,2101,2113,2125,2136,2148,2160,3985,2183,2195,2207,2218,2230,2242,2253,2265,2277,65535,65535,65535,65535,65535,65535,65535,65535,65535},
{1833,1845,3678,1868,1880,1892,1903,1915,1927,1938,1950,1962,3792,1985,1997,2009,2020,2032,2044,2055,2067,2079,3906,2102,2114,2126,2137,2149,2161,2172,2184,2196,4020,2219,2231,2243,2254,2266,2278,65535,65535,65535,65535,65535,65535,65535,65535,65535},
{2288,2300,2312,2323,2335,2347,2358,2370,2382,3758,2405,2417,2429,2440,2452,2464,2475,2487,2499,3872,2522,2534,2546,2557,2569,2581,2592,2604,2616,3986,2639,2651,2663,2674,2686,2698,2709,2721,2733,65535,65535,65535,65535,65535,65535,65535,65535,65535},
{2289,2301,3679,2324,2336,2348,2359,2371,2383,2394,2406,2418,3793,2441,2453,2465,2476,2488,2500,2511,2523,2535,3907,2558,2570,2582,2593,2605,2617,2628,2640,2652,4021,2675,2687,2699,2710,2722,2734,65535,65535,65535,65535,65535,65535,65535,65535,65535},
{2743,2755,2767,2778,2790,2802,3724,2825,2837,2849,2860,2872,2884,2895,2907,2919,3838,2942,2954,2966,2977,2989,3001,3012,3024,3036,3952,3059,3071,3083,3094,3106,3118,3129,3141,3153,4066,3176,3188,65535,65535,65535,65535,65535,65535,65535,65535,65535},
{2744,2756,2768,2779,2791,2803,2814,2826,2838,3759,2861,2873,2885,2896,2908,2920,2931,2943,2955,3873,2978,2990,3002,3013,3025,3037,3048,3060,3072,3987,3095,3107,3119,3130,3142,3154,3165,3177,3189,65535,65535,65535,65535,65535,65535,65535,65535,65535},
{3200,3212,3224,3235,3247,3259,3270,3282,3294,3760,3317,3329,3341,3352,3364,3376,3387,3399,3411,3874,3434,3446,3458,3469,3481,3493,3504,3516,3528,3988,3551,3563,3575,3586,3598,3610,3621,3633,3645,65535,65535,65535,65535,65535,65535,65535,65535,65535},
{3201,3213,3681,3236,3248,3260,3271,3283,3295,3306,3318,3330,3795,3353,3365,3377,3388,3400,3412,3423,3435,3447,3909,3470,3482,3494,3505,3517,3529,3540,3552,3564,4023,3587,3599,3611,3622,3634,3646,65535,65535,65535,65535,65535,65535,65535,65535,65535},
{466,478,489,501,513,3710,536,548,560,571,583,595,606,618,630,3824,653,665,677,688,700,712,723,735,747,3938,770,782,794,805,817,829,840,852,864,4053,887,899,911,65535,65535,65535,65535,65535,65535,65535,65535,65535},
{467,479,490,502,514,525,537,549,3745,572,584,596,607,619,631,642,654,666,3859,689,701,713,724,736,748,759,771,783,3974,806,818,830,841,853,865,876,888,900,4088,65535,65535,65535,65535,65535,65535,65535,65535,65535},
{922,934,945,957,969,3711,992,1004,1016,1027,1039,1051,1062,1074,1086,3825,1109,1121,1133,1144,1156,1168,1179,1191,1203,3939,1226,1238,1250,1261,1273,1285,1296,1308,1320,4054,1343,1355,1367,65535,65535,65535,65535,65535,65535,65535,65535,65535},
{923,935,946,958,970,981,993,1005,3746,1028,1040,1052,1063,1075,1087,1098,1110,1122,3860,1145,1157,1169,1180,1192,1204,1215,1227,1239,3975,1262,1274,1286,1297,1309,1321,1332,1344,1356,4089,65535,65535,65535,65535,65535,65535,65535,65535,65535},
{1378,1390,1401,1413,1425,3712,1448,1460,1472,1483,1495,1507,1518,1530,1542,3826,1565,1577,1589,1600,1612,1624,1635,1647,1659,3940,1682,1694,1706,1717,1729,1741,1752,1764,1776,4055,1799,1811,1823,65535,65535,65535,65535,65535,65535,65535,65535,65535},
{1379,1391,1402,1414,1426,1437,1449,1461,3747,1484,1496,1508,1519,1531,1543,1554,1566,1578,3861,1601,1613,1625,1636,1648,1660,1671,1683,1695,3976,1718,1730,1742,1753,1765,1777,1788,1800,1812,4090,65535,65535,65535,65535,65535,65535,65535,65535,65535},
{1834,1846,1857,1869,1881,3713,1904,1916,1928,1939,1951,1963,1974,1986,1998,3827,2021,2033,2045,2056,2068,2080,2091,2103,2115,3941,2138,2150,2162,2173,2185,2197,2208,2220,2232,4056,2255,2267,2279,65535,65535,65535,65535,65535,65535,65535,65535,65535},
{1835,1847,1858,1870,1882,1893,1905,1917,3748,1940,1952,1964,1975,1987,1999,2010,2022,2034,3862,2057,2069,2081,2092,2104,2116,2127,2139,2151,3977,2174,2186,2198,2209,2221,2233,2244,2256,2268,4091,65535,65535,65535,65535,65535,65535,65535,65535,65535},
{2290,2302,2313,2325,2337,3714,2360,2372,2384,2395,2407,2419,2430,2442,2454,3828,2477,2489,2501,2512,2524,2536,2547,2559,2571,3942,2594,2606,2618,2629,2641,2653,2664,2676,2688,4057,2711,2723,2735,65535,65535,65535,65535,65535,65535,65535,65535,65535},
{2291,2303,2314,2326,2338,2349,2361,2373,3749,2396,2408,2420,2431,2443,2455,2466,2478,2490,3863,2513,2525,2537,2548,2560,2572,2583,2595,2607,3978,2630,2642,2654,2665,2677,2689,2700,2712,2724,4092,65535,65535,65535,65535,65535,65535,65535,65535,65535},
{2745,2757,3680,2780,2792,2804,2815,2827,2839,2850,2862,2874,3794,2897,2909,2921,2932,2944,2956,2967,2979,2991,3908,3014,3026,3038,3049,3061,3073,3084,3096,3108,4022,3131,3143,3155,3166,3178,3190,65535,65535,65535,65535,65535,65535,65535,65535,65535},
{2746,2758,2769,2781,2793,3715,2816,2828,2840,2851,2863,2875,2886,2898,2910,3829,2933,2945,2957,2968,2980,2992,3003,3015,3027,3943,3050,3062,3074,3085,3097,3109,3120,3132,3144,4058,3167,3179,3191,65535,65535,65535,65535,65535,65535,65535,65535,65535},
{3202,3214,3225,3237,3249,3716,3272,3284,3296,3307,3319,3331,3342,3354,3366,3830,3389,3401,3413,3424,3436,3448,3459,3471,3483,3944,3506,3518,3530,3541,3553,3565,3576,3588,3600,4059,3623,3635,3647,65535,65535,65535,65535,65535,65535,65535,65535,65535},
{3203,3215,3226,3238,3250,3261,3273,3285,3751,3308,3320,3332,3343,3355,3367,3378,3390,3402,3865,3425,3437,3449,3460,3472,3484,3495,3507,3519,3980,3542,3554,3566,3577,3589,3601,3612,3624,3636,4094,65535,65535,65535,65535,65535,65535,65535,65535,65535},
{65535,65535,65535,65535,65535,65535,65535,65535,65535,65535,65535,65535,65535,65535,65535,65535,65535,65535,65535,65535,65535,65535,65535,65535,65535,65535,65535,65535,65535,65535,65535,65535,65535,65535,65535,65535,65535,65535,65535,65535,65535,65535,65535,65535,65535,65535,65535,65535},
{2747,2759,2770,2782,2794,2805,2817,2829,3750,2852,2864,2876,2887,2899,2911,2922,2934,2946,3864,2969,2981,2993,3004,3016,3028,3039,3051,3063,3979,3086,3098,3110,3121,3133,3145,3156,3168,3180,4093,65535,65535,65535,65535,65535,65535,65535,65535,65535},
{65535,65535,65535,65535,65535,65535,65535,65535,65535,65535,65535,65535,65535,65535,65535,65535,65535,65535,65535,65535,65535,65535,65535,65535,65535,65535,65535,65535,65535,65535,65535,65535,65535,65535,65535,65535,65535,65535,65535,65535,65535,65535,65535,65535,65535,65535,65535,65535},
{3664,3673,3682,3699,3708,3717,3726,3743,3752,3761,3778,3787,3796,3805,3822,3831,3840,3849,3866,3875,3884,3901,3910,3919,3928,3945,3954,3963,3972,3989,3998,4007,4024,4033,4042,4051,4068,4077,4086,4095,65535,65535,65535,65535,65535,65535,65535,65535},
{5,16,28,40,51,63,75,3727,98,110,122,133,145,157,168,180,192,3841,215,227,239,250,262,274,285,297,309,3955,332,344,356,367,379,391,402,414,426,4069,449,65535,65535,65535,65535,65535,65535,65535,65535,65535},
{3648,17,29,41,52,64,76,87,99,111,3762,134,146,158,169,181,193,204,216,228,3876,251,263,275,286,298,310,321,333,345,3990,368,380,392,403,415,427,438,450,65535,65535,65535,65535,65535,65535,65535,65535,65535},
{6,18,30,3683,53,65,77,88,100,112,123,135,147,3797,170,182,194,205,217,229,240,252,264,3911,287,299,311,322,334,346,357,369,381,4025,404,416,428,439,451,65535,65535,65535,65535,65535,65535,65535,65535,65535},
{7,19,31,42,54,66,3718,89,101,113,124,136,148,159,171,183,3832,206,218,230,241,253,265,276,288,300,3946,323,335,347,358,370,382,393,405,417,4060,440,452,65535,65535,65535,65535,65535,65535,65535,65535,65535},
{8,20,32,43,55,67,78,90,102,3753,125,137,149,160,172,184,195,207,219,3867,242,254,266,277,289,301,312,324,336,3981,359,371,383,394,406,418,429,441,453,65535,65535,65535,65535,65535,65535,65535,65535,65535},
{9,21,3674,44,56,68,79,91,103,114,126,138,3788,161,173,185,196,208,220,231,243,255,3902,278,290,302,313,325,337,348,360,372,4016,395,407,419,430,442,454,65535,65535,65535,65535,65535,65535,65535,65535,65535},
{10,22,33,45,57,3709,80,92,104,115,127,139,150,162,174,3823,197,209,221,232,244,256,267,279,291,3937,314,326,338,349,361,373,384,396,408,4052,431,443,455,65535,65535,65535,65535,65535,65535,65535,65535,65535},
{11,23,34,46,58,69,81,93,3744,116,128,140,151,163,175,186,198,210,3858,233,245,257,268,280,292,303,315,327,3973,350,362,374,385,397,409,420,432,444,4087,65535,65535,65535,65535,65535,65535,65535,65535,65535},
};

#define NG 9
#define RING 16
#define NSLOT 8
#define CFETCH 5
#define TABLED 1
#define PROMO CU_TENSOR_MAP_L2_PROMOTION_L2_128B
#define AHEAD 6
#define CF0 5
#define CFS 2
#define ABL 0
#define CX 5
#define PUBN 2
#define PUBE 8
#define SCHED 9
#define OUT_TMA 0
#define JB1 21
#define JB2 24
#define TRIG 6
constexpr int NCONV = 3 * NG;
constexpr int PLEN = (1024 + NG - 1) / NG;
constexpr int TILEB = 12288;
constexpr int SLOTB = 280 * 64;
constexpr int W1S = 0, W2S = 73728, ABUF = 147456, XBUF = ABUF + 16 * 3072, MISC = XBUF + 8 * 3072;
constexpr int CTAB = NSLOT * SLOTB + 512;
constexpr int SMEM_BYTES = MISC + 512 + 2048 + 128;
static_assert(CTAB + (PLEN + 12) * 16 <= MISC, "conv smem");

__device__ __align__(1024) unsigned char g_scratch[(RING * NG + 1) * 4 * TILEB];
__device__ uint32_t g_ready[1024];
__device__ uint32_t g_cons[1024 + 32];
__device__ unsigned long long g_start;

#define PROF_AT(cond, idx)
#define PROF_VAL(cond, idx, v)
#define PROF2_AT(c, i)
#define PROF2_VAL(c, i, v)
#define GELU_C3 0.32920349f
#define GELU_A2 0x40d940d9u
#define SPIN_LIMIT 0x1000000

__device__ __forceinline__ uint32_t smem_u32(const void* p) { return (uint32_t)__cvta_generic_to_shared(p); }
__device__ __forceinline__ void wg_fence() { asm volatile("wgmma.fence.sync.aligned;" ::: "memory"); }
__device__ __forceinline__ void wg_commit() { asm volatile("wgmma.commit_group.sync.aligned;" ::: "memory"); }
template <int N> __device__ __forceinline__ void wg_wait() { asm volatile("wgmma.wait_group.sync.aligned %0;" ::"n"(N) : "memory"); }
__device__ __forceinline__ void mbar_init(uint32_t bar, uint32_t cnt) { asm volatile("mbarrier.init.shared::cta.b64 [%0], %1;" ::"r"(bar), "r"(cnt) : "memory"); }
__device__ __forceinline__ void mbar_expect_tx(uint32_t bar, uint32_t bytes) { asm volatile("mbarrier.arrive.expect_tx.shared::cta.b64 _, [%0], %1;" ::"r"(bar), "r"(bytes) : "memory"); }
__device__ __forceinline__ void mbar_arrive(uint32_t bar) { asm volatile("mbarrier.arrive.shared::cta.b64 _, [%0];" ::"r"(bar) : "memory"); }
__device__ __forceinline__ void mbar_wait(uint32_t bar, uint32_t parity) {
  asm volatile("{\n.reg .pred p;\n.reg .u32 c;\nmbarrier.try_wait.parity.shared::cta.b64 p, [%0], %1;\n@p bra DONE_%=;\nmov.u32 c, 0;\nWAIT_%=:\nmbarrier.try_wait.parity.shared::cta.b64 p, [%0], %1;\n@p bra DONE_%=;\n"
               "add.u32 c, c, 1;\nsetp.lt.u32 p, c, 0x1000000;\n@p bra WAIT_%=;\ntrap;\nDONE_%=:\n}" ::"r"(bar), "r"(parity) : "memory");
}
__device__ __forceinline__ void bulk_g2s(uint32_t dst, const void* src, uint32_t bytes, uint32_t bar) {
  asm volatile("cp.async.bulk.shared::cluster.global.mbarrier::complete_tx::bytes [%0], [%1], %2, [%3];" ::"r"(dst), "l"(src), "r"(bytes), "r"(bar) : "memory");
}
__device__ __forceinline__ uint32_t ld_relaxed(const uint32_t* p) { uint32_t v; asm volatile("ld.relaxed.gpu.global.u32 %0, [%1];" : "=r"(v) : "l"(p) : "memory"); return v; }
__device__ __forceinline__ void red_add(uint32_t* p) { asm volatile("red.relaxed.gpu.global.add.u32 [%0], 1;" ::"l"(p) : "memory"); }
__device__ __forceinline__ void lds128(uint32_t* r, uint32_t a) { asm volatile("ld.shared.v4.b32 {%0,%1,%2,%3}, [%4];" : "=r"(r[0]), "=r"(r[1]), "=r"(r[2]), "=r"(r[3]) : "r"(a) : "memory"); }
__device__ __forceinline__ uint2 lds64(uint32_t a) { uint2 v; asm volatile("ld.shared.v2.b32 {%0,%1}, [%2];" : "=r"(v.x), "=r"(v.y) : "r"(a) : "memory"); return v; }
__device__ __forceinline__ uint32_t lds32(uint32_t a) { uint32_t v; asm volatile("ld.shared.b32 %0, [%1];" : "=r"(v) : "r"(a) : "memory"); return v; }
__device__ __forceinline__ void sts32(uint32_t a, uint32_t v) { asm volatile("st.shared.b32 [%0], %1;" ::"r"(a), "r"(v) : "memory"); }
__device__ __forceinline__ void sts128(uint32_t a, uint4 v) { asm volatile("st.shared.v4.b32 [%0], {%1,%2,%3,%4};" ::"r"(a), "r"(v.x), "r"(v.y), "r"(v.z), "r"(v.w) : "memory"); }
__device__ __forceinline__ uint4 ldg128v(const void* p) { uint4 v; asm volatile("ld.global.nc.v4.b32 {%0,%1,%2,%3}, [%4];" : "=r"(v.x), "=r"(v.y), "=r"(v.z), "=r"(v.w) : "l"(p) : "memory"); return v; }
__device__ __forceinline__ void stg128(void* p, uint4 v) { asm volatile("st.global.v4.b32 [%0], {%1,%2,%3,%4};" ::"l"(p), "r"(v.x), "r"(v.y), "r"(v.z), "r"(v.w) : "memory"); }
#define HINT 3
__device__ __forceinline__ uint64_t pol_evict_first() { uint64_t p; asm("createpolicy.fractional.L2::evict_first.b64 %0, 1.0;" : "=l"(p)); return p; }
__device__ __forceinline__ uint4 ldg128_last(const void* p, uint64_t pol) {
  if (!(HINT & 1)) return ldg128v(p);
  uint4 v; asm volatile("ld.global.nc.L1::no_allocate.L2::cache_hint.v4.b32 {%0,%1,%2,%3}, [%4], %5;" : "=r"(v.x), "=r"(v.y), "=r"(v.z), "=r"(v.w) : "l"(p), "l"(pol) : "memory"); return v;
}
__device__ __forceinline__ void stg128_stream(void* p, uint4 v, uint64_t pol) {
  if (!(HINT & 2)) { stg128(p, v); return; }
  asm volatile("st.global.L2::cache_hint.v4.b32 [%0], {%1,%2,%3,%4}, %5;" ::"l"(p), "r"(v.x), "r"(v.y), "r"(v.z), "r"(v.w), "l"(pol) : "memory");
}
__device__ __forceinline__ float bf_lo(uint32_t w) { return __uint_as_float(w << 16); }
__device__ __forceinline__ float bf_hi(uint32_t w) { return __uint_as_float(w & 0xffff0000u); }
__device__ __forceinline__ uint32_t pack_f16(float lo, float hi) { uint32_t d; asm("cvt.rn.f16x2.f32 %0, %1, %2;" : "=r"(d) : "f"(hi), "f"(lo)); return d; }
__device__ __forceinline__ uint32_t pack_f16_sat(float lo, float hi) { uint32_t d; asm("cvt.rn.satfinite.f16x2.f32 %0, %1, %2;" : "=r"(d) : "f"(hi), "f"(lo)); return d; }
__device__ __forceinline__ uint32_t pack_bf16(float lo, float hi) { uint32_t d; asm("cvt.rn.bf16x2.f32 %0, %1, %2;" : "=r"(d) : "f"(hi), "f"(lo)); return d; }
__device__ __forceinline__ uint32_t hadd2_bf16(uint32_t a, uint32_t b) { uint32_t d; asm("add.rn.bf16x2 %0, %1, %2;" : "=r"(d) : "r"(a), "r"(b)); return d; }
__device__ __forceinline__ uint32_t h2add(uint32_t a, uint32_t b) { uint32_t d; asm("add.rn.f16x2 %0, %1, %2;" : "=r"(d) : "r"(a), "r"(b)); return d; }
__device__ __forceinline__ uint32_t h2mul(uint32_t a, uint32_t b) { uint32_t d; asm("mul.rn.f16x2 %0, %1, %2;" : "=r"(d) : "r"(a), "r"(b)); return d; }
__device__ __forceinline__ uint32_t h2fma(uint32_t a, uint32_t b, uint32_t c) { uint32_t d; asm("fma.rn.f16x2 %0, %1, %2, %3;" : "=r"(d) : "r"(a), "r"(b), "r"(c)); return d; }
__device__ __forceinline__ uint32_t h2lo(uint32_t a) { uint32_t d; asm("{.reg .f16 l,h; mov.b32 {l,h}, %1; mov.b32 %0, {l,l};}" : "=r"(d) : "r"(a)); return d; }
__device__ __forceinline__ uint32_t h2hi(uint32_t a) { uint32_t d; asm("{.reg .f16 l,h; mov.b32 {l,h}, %1; mov.b32 %0, {h,h};}" : "=r"(d) : "r"(a)); return d; }
__device__ __forceinline__ float h_lo(uint32_t a) { float d; asm("{.reg .f16 l,h; mov.b32 {l,h}, %1; cvt.f32.f16 %0, l;}" : "=f"(d) : "r"(a)); return d; }
__device__ __forceinline__ float h_hi(uint32_t a) { float d; asm("{.reg .f16 l,h; mov.b32 {l,h}, %1; cvt.f32.f16 %0, h;}" : "=f"(d) : "r"(a)); return d; }
__device__ __forceinline__ uint32_t prmt(uint32_t a, uint32_t b, uint32_t s) { uint32_t d; asm("prmt.b32 %0, %1, %2, %3;" : "=r"(d) : "r"(a), "r"(b), "r"(s)); return d; }
__device__ __forceinline__ void mma_sp(float* d, const uint32_t* a, const uint32_t* b, const float* c, uint32_t e) {
  asm("mma.sp::ordered_metadata.sync.aligned.m16n8k32.row.col.f32.bf16.bf16.f32 {%0,%1,%2,%3}, {%4,%5,%6,%7}, {%8,%9,%10,%11}, {%12,%13,%14,%15}, %16, 0;"
      : "=f"(d[0]), "=f"(d[1]), "=f"(d[2]), "=f"(d[3])
      : "r"(a[0]), "r"(a[1]), "r"(a[2]), "r"(a[3]), "r"(b[0]), "r"(b[1]), "r"(b[2]), "r"(b[3]), "f"(c[0]), "f"(c[1]), "f"(c[2]), "f"(c[3]), "r"(e));
}
__device__ __forceinline__ uint32_t bf2_to_h2(uint32_t w, float s) { return pack_f16(bf_lo(w) * s, bf_hi(w) * s); }
__device__ __forceinline__ uint32_t bf2_to_h2(uint32_t w) { return pack_f16(bf_lo(w), bf_hi(w)); }

__device__ __forceinline__ uint32_t gelu_h2(uint32_t y) {
  uint32_t t, u, th, g;
  asm volatile("fma.rn.f16x2 %0, %1, %1, %2;" : "=r"(t) : "r"(y), "r"(GELU_A2));
  asm volatile("mul.rn.f16x2 %0, %1, %2;" : "=r"(u) : "r"(y), "r"(t));
  asm volatile("tanh.approx.f16x2 %0, %1;" : "=r"(th) : "r"(u));
  asm volatile("fma.rn.f16x2 %0, %1, %2, %1;" : "=r"(g) : "r"(y), "r"(th));
  return g;
}

__device__ __forceinline__ void convert_weights(uint32_t sb, uint32_t wbar, int rot, int warp, int lane) {
  const int l8 = lane & 7, q4 = lane >> 3;
#pragma unroll 1
  for (int u = warp; u < 36; u += 16) {
    int s = u / 6; const int i = u - s * 6;
    s += rot; if (s >= 6) s -= 6;
    mbar_wait(wbar + s * 8, 0);
    const uint32_t base = sb + W1S + s * 12288 + i * 128;
    uint32_t v[4][4];
#pragma unroll
    for (int r = 0; r < 4; r++) {
      const int kh = r & 1, c = (l8 + q4 + 4 * (r >> 1)) & 7;
      lds128(v[r], base + (4 * (l8 >> 1) + 2 * kh + (l8 & 1)) * 768 + c * 16);
    }
    __syncwarp();
#pragma unroll
    for (int r = 0; r < 4; r++) {
      const int kh = r & 1, c = (l8 + q4 + 4 * (r >> 1)) & 7;
      sts128(base + (2 * c + kh) * 768 + l8 * 16, make_uint4(bf2_to_h2(v[r][0]), bf2_to_h2(v[r][1]), bf2_to_h2(v[r][2]), bf2_to_h2(v[r][3])));
    }
  }
  const int q = lane & 3, t = (lane >> 2) & 3, b = lane >> 4;
#pragma unroll 1
  for (int u = warp ^ 15; u < 48; u += 16) {
    int s = (u >> 3) + rot; if (s >= 6) s -= 6;
    mbar_wait(wbar + 48 + s * 8, 0);
    const uint32_t base = sb + W2S + s * 12288 + (u & 7) * 1536;
    uint32_t v[4][3];
#pragma unroll
    for (int d = 0; d < 4; d++)
#pragma unroll
      for (int j = 0; j < 3; j++) v[d][j] = lds32(base + (2 * ((q + d) & 3) + b) * 192 + j * 64 + t * 16 + q * 4);
    __syncwarp();
#pragma unroll
    for (int d = 0; d < 4; d++)
#pragma unroll
      for (int j = 0; j < 3; j++) sts32(base + (4 * j + q) * 128 + (2 * ((q + d) & 3) + b) * 16 + t * 4, bf2_to_h2(v[d][j], 0.5f / GELU_C3));
  }
}

__device__ __noinline__ void ln_wide(uint32_t ad) {
  float m[2], r[2];
#pragma unroll
  for (int hi = 0; hi < 2; hi++) {
    float sm = 0.f;
    for (int s = 0; s < 6; s++) { uint2 w = lds64(ad + s * 512 + hi * 8); sm += (h_lo(w.x) + h_hi(w.x)) + (h_lo(w.y) + h_hi(w.y)); }
    sm += __shfl_xor_sync(0xffffffffu, sm, 1); sm += __shfl_xor_sync(0xffffffffu, sm, 2);
    m[hi] = sm * (1.f / 96.f);
    float q = 0.f;
    for (int s = 0; s < 6; s++) {
      uint2 w = lds64(ad + s * 512 + hi * 8);
      float d0 = h_lo(w.x) - m[hi], d1 = h_hi(w.x) - m[hi], d2 = h_lo(w.y) - m[hi], d3 = h_hi(w.y) - m[hi];
      q += (d0 * d0 + d1 * d1) + (d2 * d2 + d3 * d3);
    }
    q += __shfl_xor_sync(0xffffffffu, q, 1); q += __shfl_xor_sync(0xffffffffu, q, 2);
    r[hi] = rsqrtf(fmaf(q, 1.f / 96.f, 1e-5f)) * GELU_C3;
  }
  for (int s = 0; s < 6; s++) {
    uint32_t w[4]; lds128(w, ad + s * 512);
    sts128(ad + s * 512, make_uint4(pack_f16((h_lo(w[0]) - m[0]) * r[0], (h_hi(w[0]) - m[0]) * r[0]), pack_f16((h_lo(w[2]) - m[1]) * r[1], (h_hi(w[2]) - m[1]) * r[1]),
                                    pack_f16((h_lo(w[1]) - m[0]) * r[0], (h_hi(w[1]) - m[0]) * r[0]), pack_f16((h_lo(w[3]) - m[1]) * r[1], (h_hi(w[3]) - m[1]) * r[1])));
  }
  asm volatile("fence.proxy.async.shared::cta;" ::: "memory");
}

__device__ __forceinline__ uint32_t load_ln(uint32_t ad, uint32_t* a, uint32_t tag) {
  uint32_t raw[6][4];
#pragma unroll
  for (int s = 0; s < 6; s++) lds128(raw[s], ad + s * 512);
  const uint32_t stale = ((raw[0][0] ^ tag) | (raw[1][0] ^ tag)) | ((raw[2][0] ^ tag) | (raw[3][0] ^ tag)) | ((raw[4][0] ^ tag) | (raw[5][0] ^ tag));
  uint32_t sm[2];
#pragma unroll
  for (int hi = 0; hi < 2; hi++) {
    uint32_t s0 = h2add(raw[0][2 * hi], raw[1][2 * hi]), s1 = h2add(raw[0][2 * hi + 1], raw[1][2 * hi + 1]);
    uint32_t s2 = h2add(raw[2][2 * hi], raw[3][2 * hi]), s3 = h2add(raw[2][2 * hi + 1], raw[3][2 * hi + 1]);
    uint32_t s4 = h2add(raw[4][2 * hi], raw[5][2 * hi]), s5 = h2add(raw[4][2 * hi + 1], raw[5][2 * hi + 1]);
    sm[hi] = h2add(h2add(h2add(s0, s1), h2add(s2, s3)), h2add(s4, s5));
  }
  uint32_t s = h2add(prmt(sm[0], sm[1], 0x5410), prmt(sm[0], sm[1], 0x7632));
  s = h2add(s, __shfl_xor_sync(0xffffffffu, s, 1));
  s = h2add(s, __shfl_xor_sync(0xffffffffu, s, 2));
  const uint32_t nm = h2mul(s, 0xA155A155u);
  uint32_t qq[2];
#pragma unroll
  for (int hi = 0; hi < 2; hi++) {
    const uint32_t m = hi ? h2hi(nm) : h2lo(nm);
    uint32_t q0 = 0, q1 = 0;
#pragma unroll
    for (int k = 0; k < 6; k++) {
      uint32_t d0 = h2add(raw[k][2 * hi], m), d1 = h2add(raw[k][2 * hi + 1], m);
      raw[k][2 * hi] = d0; raw[k][2 * hi + 1] = d1;
      q0 = k ? h2fma(d0, d0, q0) : h2mul(d0, d0);
      q1 = k ? h2fma(d1, d1, q1) : h2mul(d1, d1);
    }
    qq[hi] = h2add(q0, q1);
  }
  uint32_t q = h2add(prmt(qq[0], qq[1], 0x5410), prmt(qq[0], qq[1], 0x7632));
  q = h2add(q, __shfl_xor_sync(0xffffffffu, q, 1));
  q = h2add(q, __shfl_xor_sync(0xffffffffu, q, 2));
  const float r0 = rsqrtf(fmaf(h_lo(q), 1.f / 96.f, 1e-5f)) * GELU_C3, r1 = rsqrtf(fmaf(h_hi(q), 1.f / 96.f, 1e-5f)) * GELU_C3;
  const uint32_t r = pack_f16(r0, r1);
#pragma unroll
  for (int k = 0; k < 6; k++) {
    a[4 * k] = h2mul(raw[k][0], h2lo(r)); a[4 * k + 2] = h2mul(raw[k][1], h2lo(r));
    a[4 * k + 1] = h2mul(raw[k][2], h2hi(r)); a[4 * k + 3] = h2mul(raw[k][3], h2hi(r));
  }
  return (((q & 0x7c007c00u) + 0x04000400u) & 0x80008000u) | (stale & 1);
}

__device__ __forceinline__ void gemm1(uint32_t* p, const uint32_t* a, uint64_t d1, int c) {
  wgmma_n48_f16<0>(p, a, d1 + c * (1536 >> 4));
#pragma unroll
  for (int s = 1; s < 6; s++) wgmma_n48_f16<1>(p, a + 4 * s, d1 + c * (1536 >> 4) + s * (12288 >> 4));
}

__device__ __forceinline__ void gemm1_piece(uint32_t* p, const uint32_t* a, uint64_t d1, int c, int u) {
  if (u == 0) wgmma_n48_f16<0>(p, a, d1 + c * (1536 >> 4)); else wgmma_n48_f16<1>(p, a + 8 * u, d1 + c * (1536 >> 4) + 2 * u * (12288 >> 4));
  wgmma_n48_f16<1>(p, a + 8 * u + 4, d1 + c * (1536 >> 4) + (2 * u + 1) * (12288 >> 4));
}
__device__ __forceinline__ void fetch_a(uint32_t abuf, uint32_t bar, uint32_t sofs) {
  asm volatile("{\n.reg .pred p;\nelect.sync _|p, 0xffffffff;\n"
               "@p mbarrier.arrive.expect_tx.shared::cta.b64 _, [%1], 3072;\n"
               "@p cp.async.bulk.shared::cluster.global.mbarrier::complete_tx::bytes [%0], [%2], 3072, [%1];\n}"
               ::"r"(abuf), "r"(bar), "l"(g_scratch + sofs) : "memory");
}
__device__ __forceinline__ void fetch_x(uint32_t xbuf, uint32_t bar, const CUtensorMap* tm, uint32_t c0, uint32_t c12, uint64_t pol) {
  asm volatile("{\n.reg .pred p;\nelect.sync _|p, 0xffffffff;\n"
               "@p mbarrier.arrive.expect_tx.shared::cta.b64 _, [%1], 3072;\n"
               "@p cp.async.bulk.tensor.3d.shared::cluster.global.mbarrier::complete_tx::bytes.L2::cache_hint [%0], [%2, {%3, %4, %5}], [%1], %6;\n}"
               ::"r"(xbuf), "r"(bar), "l"(tm), "r"(c0), "r"(c12 & 255), "r"(c12 >> 8), "l"(pol) : "memory");
}
__device__ __forceinline__ void wait_ready(int P, uint32_t target) {
  int spins = 0;
  while (ld_relaxed(&g_ready[P]) != target) { __nanosleep(32); if (++spins > SPIN_LIMIT) __trap(); }
}
__device__ __forceinline__ uint32_t slot_tag(int gm, int j, uint32_t epoch) {
  const int len = min(PLEN, 1024 - gm * PLEN), writes = (len - (j & (RING - 1)) + RING - 1) / RING;
  return (epoch * writes + j / RING + 1) & 1;
}

__device__ __forceinline__ void mlp_role(uint32_t sb, const CUtensorMap* tmr, const __nv_bfloat16* __restrict__ w1, const __nv_bfloat16* __restrict__ w2,
                                         __nv_bfloat16* __restrict__ out, int idx, bool tabled, int warp, int lane) {
  const int wg = warp >> 2, w = warp & 3, g = lane >> 2, t = lane & 3;
  const uint32_t abuf = sb + ABUF + warp * 3072, xbuf = sb + XBUF + (warp & 7) * 3072;
  const uint32_t bar = sb + MISC + warp * 8, obar = sb + MISC + (warp ^ 8) * 8;
  const uint32_t tl = sb + MISC + 512, wbar = sb + MISC + 2560;
  const int rot = idx % 6;
  if (warp == 0) {
    if (lane < 12) {
      mbar_init(wbar + lane * 8, 1);
      asm volatile("fence.mbarrier_init.release.cluster;" ::: "memory");
      asm volatile("fence.proxy.async.shared::cta;" ::: "memory");
    }
    __syncwarp();
    if (lane < 12) {
      const int m = lane >= 6; int s = lane - 6 * m + rot; if (s >= 6) s -= 6;
      mbar_expect_tx(wbar + (6 * m + s) * 8, 12288);
      bulk_g2s(sb + (6 * m + s) * 12288, (const char*)(m ? w2 : w1) + s * 12288, 12288, wbar + (6 * m + s) * 8);
    }
  }
  if (lane == 0) { mbar_init(bar, 1); mbar_init(bar + 128, 1); asm volatile("fence.mbarrier_init.release.cluster;" ::: "memory"); }
  __syncthreads();
  if (warp == 8) {
    uint32_t epoch = 0;
    if (lane == 0) { epoch = (uint32_t)(atomicAdd(&g_start, 1ULL) / gridDim.x); sts32(sb + MISC + 256, epoch + 1); }
#pragma unroll 1
    for (int k = lane; k < (tabled ? 64 : 128); k += 32) {
      int n = -1;
      if (tabled) { if (k < 48) n = (int16_t)g_sched[idx][k]; }
      else {
        const int i = k * (gridDim.x - NCONV) + idx, full = (1024 - (NG - 1) * PLEN) * NG;
        const int r = i >> 2, j = r < full ? r / NG : (r - full) / (NG - 1) + full / NG, gm = r < full ? r % NG : (r - full) % (NG - 1);
        if (i < 4096) n = (gm * PLEN + j) * 4 + (i & 3);
      }
      const int P = n >> 2, gm = P / PLEN, j = P - gm * PLEN;
      sts128(tl + k * 16, make_uint4(P, (((j & (RING - 1)) * NG + gm) * 4 + (n & 3)) * TILEB + slot_tag(gm, j, __shfl_sync(0xffffffffu, epoch, 0)),
                                     (n & 2) * 384, ((n >> 10) * 8 + (n & 1) * 4) | ((n & 1020) << 7)));
    }
  }
  convert_weights(sb, wbar, rot, warp, lane);
  asm volatile("fence.proxy.async.shared::cta;" ::: "memory");
  __syncthreads();
  PROF_AT(threadIdx.x == 0, 1); PROF_VAL(threadIdx.x == 0, 8, clock64());
  const uint32_t rtarget = 3 * lds32(sb + MISC + 256);
  const uint64_t d1 = ((uint64_t)(768 >> 4) << 16) | ((uint64_t)(128 >> 4) << 32) | (uint64_t)(((sb + W1S) >> 4) & 0x3fff);
  const uint64_t d2 = ((uint64_t)(12288 >> 4) << 16) | ((uint64_t)(128 >> 4) << 32) | (uint64_t)(((sb + W2S) >> 4) & 0x3fff);
  const uint32_t ad = abuf + t * 128 + ((g ^ (2 * t)) << 4);
  const uint32_t xd = xbuf + g * 192 + t * 16;
  const int mybar = 1 + wg, nxtbar = 1 + ((wg + 1) & 3);
  const uint64_t pol = pol_evict_first();
  uint32_t pha = 0, phx = 0, tp = tl + wg * 16;
  bool pending = true;
  uint32_t cur[4];
  lds128(cur, tp);
  while ((int)cur[0] >= 0) {
    PROF2_AT((threadIdx.x & 127) == 0, 16 + (tp - tl) / 4); PROF2_VAL((threadIdx.x & 127) == 0, 16 + (tp - tl) / 4 + 3, pending);
    uint32_t a[24], p[8][12], gg[8][12], acc[24];
    if (pending) {
      wait_ready(cur[0], rtarget);
      fetch_a(abuf, bar, (cur[1] & ~1u) + w * 3072);
      if (tp < tl + 32) fetch_x(xbuf, bar + 128, tmr, cur[2] + w * 192, cur[3], pol);
    }
    const uint2 n4 = lds64(tp + 64);
    const int sig = lds32(tp + 16);
    for (int tries = 0;; tries++) {
      mbar_wait(bar, pha); pha ^= 1;
      PROF2_AT((threadIdx.x & 127) == 0, 16 + (tp - tl) / 4 + 1);
      const uint32_t st = load_ln(ad, a, cur[1]);
      if (!__any_sync(0xffffffffu, st != 0)) break;
      if (!__any_sync(0xffffffffu, st & 1)) {
        ln_wide(ad);
#pragma unroll
        for (int k = 0; k < 6; k++) lds128(a + 4 * k, ad + k * 512);
        break;
      }
      if (tries > SPIN_LIMIT) __trap();
      fetch_a(abuf, bar, (cur[1] & ~1u) + w * 3072);
    }
    asm volatile("{.reg .pred p; elect.sync _|p, 0xffffffff; @p red.relaxed.gpu.global.add.u32 [%0], 1;}" ::"l"(&g_cons[cur[0]]) : "memory");
    if (tp != tl) asm volatile("bar.sync %0, 256;" ::"r"(mybar) : "memory");
    PROF2_AT((threadIdx.x & 127) == 0, 16 + (tp - tl) / 4 + 2);
    uint32_t rdy = 0;
    wg_fence();
    gemm1(p[0], a, d1, 0); wg_commit();
    gemm1_piece(p[1], a, d1, 1, 0); wg_commit();
#pragma unroll
    for (int j = 0; j < 24; j++) {
      const int c = j / 3, s = j % 3;
      if (j == JB1) {
        rdy = ld_relaxed(&g_ready[n4.x & 1023]);
        wg_wait<0>();
        mbar_wait(bar + 128, phx); phx ^= 1;
      } else if (j == JB2) {
        wg_wait<0>();
        pending = rdy != rtarget;
        if (!pending && (int)n4.x >= 0) fetch_a(abuf, bar, (n4.y & ~1u) + w * 3072);
      } else wg_wait<1>();
      if (j == TRIG) asm volatile("{.reg .pred p; setp.ge.s32 p, %1, 0; @p bar.arrive %0, 256;}" ::"r"(nxtbar), "r"(sig) : "memory");
#pragma unroll
      for (int i = 0; i < 4; i++) gg[c][4 * s + i] = gelu_h2(p[c][4 * s + i]);
      wg_fence();
      if (j == 0) wgmma_n96_f16<0>(acc, gg[c], d2); else wgmma_n96_f16<1>(acc, &gg[c][4 * s], d2 + (16 * s + c) * (1536 >> 4));
      if (j < 20) gemm1_piece(p[(j + 1) / 3 + 1], a, d1, (j + 1) / 3 + 1, (j + 1) % 3);
      wg_commit();
    }
    wg_wait<0>();
    if (JB2 == 24) {
      pending = rdy != rtarget;
      if (!pending && (int)n4.x >= 0) fetch_a(abuf, bar, (n4.y & ~1u) + w * 3072);
    }
    char* const op = (char*)out + (size_t)(cur[3] >> 8) * (512 * 192) + ((cur[3] & 255) + (g >> 1)) * 3072 + cur[2] * 2 + (2 * w + (g & 1)) * 192 + t * 16;
    uint32_t n2[4];
    lds128(n2, tp + 32);
    tp += 64;
    lds128(cur, tp);
#pragma unroll
    for (int hi = 0; hi < 2; hi++)
#pragma unroll
      for (int j = 0; j < 3; j++) {
        uint32_t xr[4];
        lds128(xr, xd + hi * 1536 + j * 64);
        uint4 o;
        o.x = hadd2_bf16(xr[0], pack_bf16(h_lo(acc[8 * j + hi]), h_hi(acc[8 * j + hi])));
        o.y = hadd2_bf16(xr[1], pack_bf16(h_lo(acc[8 * j + 2 + hi]), h_hi(acc[8 * j + 2 + hi])));
        o.z = hadd2_bf16(xr[2], pack_bf16(h_lo(acc[8 * j + 4 + hi]), h_hi(acc[8 * j + 4 + hi])));
        o.w = hadd2_bf16(xr[3], pack_bf16(h_lo(acc[8 * j + 6 + hi]), h_hi(acc[8 * j + 6 + hi])));
        stg128_stream(op + hi * (512 * 192) + j * 64, o, pol);
      }
    __syncwarp();
    if ((int)n2[0] >= 0) fetch_x(xbuf, obar + 128, tmr, n2[2] + w * 192, n2[3], pol);
  }
  PROF_AT((threadIdx.x & 127) == 0, 4 + wg); PROF_VAL(threadIdx.x == 0, 9, clock64());
}

__device__ __forceinline__ void conv_compute(uint32_t sb, const __nv_bfloat16* __restrict__ dw, int third, int nit, int warp, int lane) {
  const int g = lane >> 2, t = lane & 3;
  const uint32_t full = sb + MISC;
  uint32_t A[4][4][4];
  {
    uint2 w[2][9];
#pragma unroll
    for (int h = 0; h < 2; h++) {
      const int j = (4 * h + t - g) & 7;
      w[h][0] = make_uint2(0u, 0u); w[h][8] = make_uint2(0u, 0u);
#pragma unroll
      for (int i = 0; i < 7; i++) {
        w[h][i + 1] = make_uint2(0u, 0u);
        if (j < 7) w[h][i + 1] = __ldg((const uint2*)(dw + (i * 7 + j) * 96 + third * 32 + warp * 4));
      }
    }
#pragma unroll
    for (int u = 0; u < 4; u++)
#pragma unroll
      for (int r = 0; r < 4; r++) {
        const int h = r >> 1, i0 = 2 * u - (r & 1) + 1;
        A[0][u][r] = prmt(w[h][i0].x, w[h][i0 + 1].x, 0x5410); A[1][u][r] = prmt(w[h][i0].x, w[h][i0 + 1].x, 0x7632);
        A[2][u][r] = prmt(w[h][i0].y, w[h][i0 + 1].y, 0x5410); A[3][u][r] = prmt(w[h][i0].y, w[h][i0 + 1].y, 0x7632);
      }
  }
  uint32_t meta = 0;
#pragma unroll
  for (int a = 0; a < 4; a++) meta |= ((4 * (t & 1) + a + 1 >= g) ? 0x80008u : 0xD000Du) << (4 * a);
  meta = __shfl_sync(0xffffffffu, meta, lane);
  float S[2][4][3][4];
#pragma unroll
  for (int s = 0; s < 2; s++)
#pragma unroll
    for (int c = 0; c < 4; c++)
#pragma unroll
      for (int i = 0; i < 3; i++)
#pragma unroll
        for (int k = 0; k < 4; k++) S[s][c][i][k] = 0.f;
  uint32_t aq[4];
#pragma unroll
  for (int q = 0; q < 4; q++) {
    const int pp = (g & 1) * 140 + (t & 1) * 70 + 16 * (g >> 1) + 2 * q + (t >> 1);
    aq[q] = __shfl_sync(0xffffffffu, sb + pp * 64 + (((warp >> 1) ^ ((pp >> 1) & 3)) << 4) + (warp & 1) * 8, lane);
  }
  const int Q = third * 8 + warp;
  unsigned char* const obase = g_scratch + (g >> 1) * 3072 + Q * 128 + (((2 * t + (g & 1)) ^ (2 * (Q & 3))) << 4);
  const float zero4[4] = {0.f, 0.f, 0.f, 0.f};
  uint32_t sofs = 0, bar = full, ph = 0;
  uint2 X[3][4];
  mbar_wait(bar, 0);
  PROF_AT(threadIdx.x == 0, 1); PROF_VAL(threadIdx.x == 0, 8, clock64());
#pragma unroll
  for (int j = 0; j < 2; j++)
#pragma unroll
    for (int q = 0; q < 4; q++) X[j][q] = lds64(aq[q] + j * 512);
  for (uint32_t ot = sb + CTAB; ot < sb + CTAB + nit * 16; ot += 16) {
    PROF_AT(threadIdx.x == 0 && ((ot - sb - CTAB) & 112) == 0, 16 + ((ot - sb - CTAB) >> 4));
    const uint2 oe = lds64(ot);
    unsigned char* const o = obase + oe.x;
    const uint32_t dbar = bar + 64 + ph * 64;
#pragma unroll
    for (int s = 0; s < 2; s++) {
      uint32_t B[4][4];
      if (s == 1) {
        sofs += SLOTB; bar += 8;
        if (sofs == NSLOT * SLOTB) { sofs = 0; bar = full; ph ^= 1; }
        mbar_wait(bar, ph);
      }
#pragma unroll
      for (int c = 0; c < 4; c++)
#pragma unroll
        for (int q = 0; q < 4; q++) B[c][q] = prmt(c < 2 ? X[s][q].x : X[s][q].y, c < 2 ? X[s + 1][q].x : X[s + 1][q].y, (c & 1) ? 0x7632 : 0x5410);
      if (s == 0) {
#pragma unroll
        for (int q = 0; q < 4; q++) X[2][q] = lds64(aq[q] + sofs + 2 * 512);
      } else {
#pragma unroll
        for (int j = 0; j < 2; j++)
#pragma unroll
          for (int q = 0; q < 4; q++) X[j][q] = lds64(aq[q] + sofs + j * 512);
      }
      float T[4][4];
#pragma unroll
      for (int c = 0; c < 4; c++) mma_sp(T[c], A[c][3], B[c], S[s][c][2], meta);
#pragma unroll
      for (int c = 0; c < 4; c++) mma_sp(S[s][c][2], A[c][2], B[c], S[s][c][1], meta);
      stg128(o + (2 * s) * TILEB, make_uint4((pack_f16_sat(T[0][0], T[1][0]) & ~1u) | oe.y, pack_f16_sat(T[2][0], T[3][0]), pack_f16_sat(T[0][2], T[1][2]), pack_f16_sat(T[2][2], T[3][2])));
      stg128(o + (2 * s + 1) * TILEB, make_uint4((pack_f16_sat(T[0][1], T[1][1]) & ~1u) | oe.y, pack_f16_sat(T[2][1], T[3][1]), pack_f16_sat(T[0][3], T[1][3]), pack_f16_sat(T[2][3], T[3][3])));
#pragma unroll
      for (int c = 0; c < 4; c++) mma_sp(S[s][c][1], A[c][1], B[c], S[s][c][0], meta);
#pragma unroll
      for (int c = 0; c < 4; c++) mma_sp(S[s][c][0], A[c][0], B[c], zero4, meta);
    }
    asm volatile("{.reg .pred p; elect.sync _|p, 0xffffffff; @p mbarrier.arrive.shared::cta.b64 _, [%0];}" ::"r"(dbar) : "memory");
  }
  PROF_AT(threadIdx.x == 0, 4); PROF_VAL(threadIdx.x == 0, 9, clock64());
}

__device__ __forceinline__ void conv_loader(uint32_t sb, const CUtensorMap* tmx, int nit, int third) {
  const uint32_t full = sb + MISC;
  for (int it = 0; it <= nit; it++) {
    const int s = it & (NSLOT - 1);
    const int e = lds32(sb + CTAB + it * 16 + 12);
    if (it >= AHEAD) mbar_wait(full + 64 + ((it - AHEAD) & 15) * 8, ((it - AHEAD) >> 4) & 1);
    asm volatile("{\n.reg .pred p;\n.reg .s32 c2;\n.reg .u32 d2;\nelect.sync _|p, 0xffffffff;\nadd.s32 c2, %4, 64;\nadd.u32 d2, %0, 8960;\n"
                 "@p mbarrier.arrive.expect_tx.shared::cta.b64 _, [%2], 17920;\n"
                 "@p cp.async.bulk.tensor.3d.shared::cluster.global.mbarrier::complete_tx::bytes [%0], [%1, {%3, %4, %5}], [%2];\n"
                 "@p cp.async.bulk.tensor.3d.shared::cluster.global.mbarrier::complete_tx::bytes [d2], [%1, {%3, c2, %5}], [%2];\n}"
                 ::"r"(sb + s * SLOTB), "l"(tmx), "r"(full + s * 8), "r"(third * 32), "r"((e & 0xffff) - 3), "r"(e >> 16) : "memory");
  }
}

__device__ __forceinline__ void conv_credit(uint32_t sb, int gm, int nit, int lane) {
  const uint32_t full = sb + MISC;
  const int P0 = gm * PLEN;
  uint32_t epoch = 0;
  if (lane == 0) epoch = (uint32_t)(atomicAdd(&g_start, 1ULL) / gridDim.x);
  epoch = __shfl_sync(0xffffffffu, epoch, 0);
  for (int it = lane; it < nit; it += 32) sts32(sb + CTAB + it * 16 + 4, slot_tag(gm, max((int)lds32(sb + CTAB + it * 16 + 8) - P0, 0), epoch));
  __syncwarp();
  const uint32_t ctarget = 16 * (epoch + 1);
  int credit = P0 + RING;
  for (int it = 0; it <= nit; it++) {
    if (it >= NSLOT) {
      const int P = (int)lds32(sb + CTAB + it * 16 + 8);
      mbar_wait(full + 64 + ((it - NSLOT) & 15) * 8, ((it - NSLOT) >> 4) & 1);
      int spins = 0;
      while ((int)lds32(full + 192) < it - 15) { __nanosleep(64); if (++spins > SPIN_LIMIT) __trap(); }
      while (P >= credit) {
        const uint32_t ok = __ballot_sync(0xffffffffu, ld_relaxed(&g_cons[credit - RING + lane]) == ctarget);
        const int got = __ffs(~ok) - 1;
        credit += got < 0 ? 32 : got;
        if (P >= credit) { __nanosleep(200); if (++spins > SPIN_LIMIT) __trap(); }
      }
    }
    if (lane == 0) mbar_arrive(full + (it & (NSLOT - 1)) * 8);
  }
}

__device__ __forceinline__ void conv_publisher(uint32_t sb, int nit) {
  for (int it = 0; it < nit; it++) {
    const int P = (int)lds32(sb + CTAB + it * 16 + 8);
    mbar_wait(sb + MISC + 64 + (it & 15) * 8, (it >> 4) & 1);
    sts32(sb + MISC + 192, it + 1);
    if (P >= 0) { red_add(&g_ready[P]); PROF_AT((it & 7) == 0 || it < 8, 200 + it); }
  }
}

__global__ void __launch_bounds__(512, 1) convnext_kernel(const __grid_constant__ CUtensorMap tmx, const __grid_constant__ CUtensorMap tmr, const __nv_bfloat16* __restrict__ dw,
                                                          const __nv_bfloat16* __restrict__ w1, const __nv_bfloat16* __restrict__ w2, __nv_bfloat16* __restrict__ out) {
  extern __shared__ __align__(1024) unsigned char smem[];
  const uint32_t sb = smem_u32(smem);
  const int warp = __shfl_sync(0xffffffffu, threadIdx.x >> 5, 0), lane = threadIdx.x & 31;
  PROF_AT(threadIdx.x == 0, 0);
  uint32_t smid, nsmid;
  asm volatile("mov.u32 %0, %%smid;" : "=r"(smid));
  asm volatile("mov.u32 %0, %%nsmid;" : "=r"(nsmid));
  const bool tabled = TABLED && NG == 9 && gridDim.x == 132 && nsmid == 132;
  int cidx, idx;
  bool is_conv;
  if (tabled) {
    idx = smid;
    is_conv = (smid < 48 && !(smid & 1)) || smid == 60 || smid == 120 || smid == 122;
    cidx = smid < 48 ? ((smid >> 1) & 7) * 3 + (smid >> 4) : smid == 60 ? 26 : 24 + ((smid >> 1) & 1);
  } else {
    cidx = (blockIdx.x * NCONV) / gridDim.x;
    is_conv = ((blockIdx.x + 1) * NCONV) / gridDim.x != cidx;
    idx = blockIdx.x - cidx;
  }
  PROF_VAL(threadIdx.x == 0, 2, is_conv ? 1000 + cidx : idx);
  if (!is_conv) {
    mlp_role(sb, &tmr, w1, w2, out, idx, tabled, warp, lane);
  } else {
    const int gm = cidx / 3, third = cidx - gm * 3;
    const int P0 = gm * PLEN, P1 = min(P0 + PLEN, 1024) - 1;
    const int Vs = P0 + 2 * (P0 >> 8) + ((P0 & 255) ? 0 : 1);
    const int nit = P1 + 2 * (P1 >> 8) + 4 - Vs;
    if (threadIdx.x == 0) {
      for (int s = 0; s < NSLOT; s++) { mbar_init(sb + MISC + s * 8, 2); mbar_init(sb + MISC + 64 + s * 8, 8); mbar_init(sb + MISC + 128 + s * 8, 8); }
      sts128(sb + MISC + 192, make_uint4(0, 0, 0, 0));
      asm volatile("fence.mbarrier_init.release.cluster;" ::: "memory");
    }
    if (threadIdx.x >= 256 && threadIdx.x - 256 <= nit) {
      const int it = threadIdx.x - 256, V = Vs + it;
      const int st = (V - 1) / 258, so = max(V - 3, 0) / 258, po = V - 3 - so * 258, P = so * 256 + po;
      const bool ok = po < 256 && P >= P0 && P <= P1;
      sts128(sb + CTAB + it * 16, make_uint4((ok ? ((P - P0) & (RING - 1)) * NG + gm : RING * NG) * (4 * TILEB), 0, ok ? P : -1, (st * 128) | ((2 * (V - st * 258) - 3) << 16)));
    }
    __syncthreads();
    if (warp < 8) {
      asm volatile("setmaxnreg.inc.sync.aligned.u32 224;");
      conv_compute(sb, dw, third, nit, warp, lane);
    } else if (warp >= 12) {
      asm volatile("setmaxnreg.dec.sync.aligned.u32 24;");
    } else {
      asm volatile("setmaxnreg.dec.sync.aligned.u32 40;");
      if (warp == 8) conv_loader(sb, &tmx, nit, third);
      else if (warp == 9) conv_credit(sb, gm, nit, lane);
      else if (warp == 10 && lane == 0) conv_publisher(sb, nit);
    }
  }
}

typedef CUresult (*PFN_encodeTiled)(CUtensorMap*, CUtensorMapDataType, cuuint32_t, void*, const cuuint64_t*, const cuuint64_t*, const cuuint32_t*, const cuuint32_t*,
                                    CUtensorMapInterleave, CUtensorMapSwizzle, CUtensorMapL2promotion, CUtensorMapFloatOOBfill);

extern "C" void kernel_launch(void* const* d_in, const int* in_sizes, int n_in, void* d_out, int out_size) {
  const __nv_bfloat16* x = (const __nv_bfloat16*)d_in[0];
  const __nv_bfloat16* dw = (const __nv_bfloat16*)d_in[1];
  const __nv_bfloat16* w1 = (const __nv_bfloat16*)d_in[2];
  const __nv_bfloat16* w2 = (const __nv_bfloat16*)d_in[3];
  static PFN_encodeTiled encode = nullptr;
  static int nsm = 0;
  if (!encode) {
    void* fn = nullptr; cudaDriverEntryPointQueryResult qr;
    cudaGetDriverEntryPoint("cuTensorMapEncodeTiled", &fn, cudaEnableDefault, &qr);
    encode = (PFN_encodeTiled)fn;
    int dev = 0; cudaGetDevice(&dev);
    cudaDeviceGetAttribute(&nsm, cudaDevAttrMultiProcessorCount, dev);
    cudaFuncSetAttribute(convnext_kernel, cudaFuncAttributeMaxDynamicSharedMemorySize, SMEM_BYTES);
  }
  CUtensorMap tm;
  cuuint64_t dims[3] = {96, 512, 512}, strides[2] = {192, 192 * 512};
  cuuint32_t box[3] = {32, 70, 2}, es[3] = {1, 1, 1};
  encode(&tm, CU_TENSOR_MAP_DATA_TYPE_BFLOAT16, 3, (void*)x, dims, strides, box, es, CU_TENSOR_MAP_INTERLEAVE_NONE, CU_TENSOR_MAP_SWIZZLE_64B,
         PROMO, CU_TENSOR_MAP_FLOAT_OOB_FILL_NONE);
  CUtensorMap tr;
  cuuint64_t dims2[3] = {1536, 32, 512}, strides2[2] = {3072, 192 * 512};
  cuuint32_t box2[3] = {192, 4, 2};
  encode(&tr, CU_TENSOR_MAP_DATA_TYPE_BFLOAT16, 3, (void*)x, dims2, strides2, box2, es, CU_TENSOR_MAP_INTERLEAVE_NONE, CU_TENSOR_MAP_SWIZZLE_NONE,
         CU_TENSOR_MAP_L2_PROMOTION_NONE, CU_TENSOR_MAP_FLOAT_OOB_FILL_NONE);
  convnext_kernel<<<nsm, 512, SMEM_BYTES>>>(tm, tr, dw, w1, w2, (__nv_bfloat16*)d_out);
}
```

```cpp
#include <cuda_runtime.h>
#include <cuda_bf16.h>
#include <cuda.h>
#include <stdint.h>

template<int SCALE_D> __device__ __forceinline__ void wgmma_n48_f16(uint32_t* d, const uint32_t* a, uint64_t desc) {
  if (SCALE_D == 0) asm volatile("wgmma.mma_async.sync.aligned.m64n48k16.f16.f16.f16 {%0,%1,%2,%3,%4,%5,%6,%7,%8,%9,%10,%11}, {%12,%13,%14,%15}, %16, 0, 1, 1, 1;"
    : "=r"(d[0]),"=r"(d[1]),"=r"(d[2]),"=r"(d[3]),"=r"(d[4]),"=r"(d[5]),"=r"(d[6]),"=r"(d[7]),"=r"(d[8]),"=r"(d[9]),"=r"(d[10]),"=r"(d[11])
    : "r"(a[0]),"r"(a[1]),"r"(a[2]),"r"(a[3]),"l"(desc));
  if (SCALE_D == 1) asm volatile("wgmma.mma_async.sync.aligned.m64n48k16.f16.f16.f16 {%0,%1,%2,%3,%4,%5,%6,%7,%8,%9,%10,%11}, {%12,%13,%14,%15}, %16, 1, 1, 1, 1;"
    : "+r"(d[0]),"+r"(d[1]),"+r"(d[2]),"+r"(d[3]),"+r"(d[4]),"+r"(d[5]),"+r"(d[6]),"+r"(d[7]),"+r"(d[8]),"+r"(d[9]),"+r"(d[10]),"+r"(d[11])
    : "r"(a[0]),"r"(a[1]),"r"(a[2]),"r"(a[3]),"l"(desc));
}

template<int SCALE_D> __device__ __forceinline__ void wgmma_n96_f16(uint32_t* d, const uint32_t* a, uint64_t desc) {
  if (SCALE_D == 0) asm volatile("wgmma.mma_async.sync.aligned.m64n96k16.f16.f16.f16 {%0,%1,%2,%3,%4,%5,%6,%7,%8,%9,%10,%11,%12,%13,%14,%15,%16,%17,%18,%19,%20,%21,%22,%23}, {%24,%25,%26,%27}, %28, 0, 1, 1, 1;"
    : "=r"(d[0]),"=r"(d[1]),"=r"(d[2]),"=r"(d[3]),"=r"(d[4]),"=r"(d[5]),"=r"(d[6]),"=r"(d[7]),"=r"(d[8]),"=r"(d[9]),"=r"(d[10]),"=r"(d[11]),"=r"(d[12]),"=r"(d[13]),"=r"(d[14]),"=r"(d[15]),"=r"(d[16]),"=r"(d[17]),"=r"(d[18]),"=r"(d[19]),"=r"(d[20]),"=r"(d[21]),"=r"(d[22]),"=r"(d[23])
    : "r"(a[0]),"r"(a[1]),"r"(a[2]),"r"(a[3]),"l"(desc));
  if (SCALE_D == 1) asm volatile("wgmma.mma_async.sync.aligned.m64n96k16.f16.f16.f16 {%0,%1,%2,%3,%4,%5,%6,%7,%8,%9,%10,%11,%12,%13,%14,%15,%16,%17,%18,%19,%20,%21,%22,%23}, {%24,%25,%26,%27}, %28, 1, 1, 1, 1;"
    : "+r"(d[0]),"+r"(d[1]),"+r"(d[2]),"+r"(d[3]),"+r"(d[4]),"+r"(d[5]),"+r"(d[6]),"+r"(d[7]),"+r"(d[8]),"+r"(d[9]),"+r"(d[10]),"+r"(d[11]),"+r"(d[12]),"+r"(d[13]),"+r"(d[14]),"+r"(d[15]),"+r"(d[16]),"+r"(d[17]),"+r"(d[18]),"+r"(d[19]),"+r"(d[20]),"+r"(d[21]),"+r"(d[22]),"+r"(d[23])
    : "r"(a[0]),"r"(a[1]),"r"(a[2]),"r"(a[3]),"l"(desc));
}

__device__ const uint16_t g_sched[132][48] = {
{65535,65535,65535,65535,65535,65535,65535,65535,65535,65535,65535,65535,65535,65535,65535,65535,65535,65535,65535,65535,65535,65535,65535,65535,65535,65535,65535,65535,65535,65535,65535,65535,65535,65535,65535,65535,65535,65535,65535,65535,65535,65535,65535,65535,65535,65535,65535,65535},
{0,12,3666,35,47,59,70,82,94,105,117,129,3781,152,164,176,187,199,211,222,234,246,3896,269,281,293,304,316,328,339,351,363,4011,386,398,410,421,433,445,65535,65535,65535,65535,65535,65535,65535,65535,65535},
{65535,65535,65535,65535,65535,65535,65535,65535,65535,65535,65535,65535,65535,65535,65535,65535,65535,65535,65535,65535,65535,65535,65535,65535,65535,65535,65535,65535,65535,65535,65535,65535,65535,65535,65535,65535,65535,65535,65535,65535,65535,65535,65535,65535,65535,65535,65535,65535},
{456,468,3667,491,503,515,526,538,550,561,573,585,3782,608,620,632,643,655,667,678,690,702,3897,725,737,749,760,772,784,795,807,819,4012,842,854,866,877,889,901,65535,65535,65535,65535,65535,65535,65535,65535,65535},
{65535,65535,65535,65535,65535,65535,65535,65535,65535,65535,65535,65535,65535,65535,65535,65535,65535,65535,65535,65535,65535,65535,65535,65535,65535,65535,65535,65535,65535,65535,65535,65535,65535,65535,65535,65535,65535,65535,65535,65535,65535,65535,65535,65535,65535,65535,65535,65535},
{912,924,3668,947,959,971,982,994,1006,1017,1029,1041,3783,1064,1076,1088,1099,1111,1123,1134,1146,1158,3898,1181,1193,1205,1216,1228,1240,1251,1263,1275,4013,1298,1310,1322,1333,1345,1357,65535,65535,65535,65535,65535,65535,65535,65535,65535},
{65535,65535,65535,65535,65535,65535,65535,65535,65535,65535,65535,65535,65535,65535,65535,65535,65535,65535,65535,65535,65535,65535,65535,65535,65535,65535,65535,65535,65535,65535,65535,65535,65535,65535,65535,65535,65535,65535,65535,65535,65535,65535,65535,65535,65535,65535,65535,65535},
{1368,1380,3669,1403,1415,1427,1438,1450,1462,1473,1485,1497,3784,1520,1532,1544,1555,1567,1579,1590,1602,1614,3899,1637,1649,1661,1672,1684,1696,1707,1719,1731,4014,1754,1766,1778,1789,1801,1813,65535,65535,65535,65535,65535,65535,65535,65535,65535},
{65535,65535,65535,65535,65535,65535,65535,65535,65535,65535,65535,65535,65535,65535,65535,65535,65535,65535,65535,65535,65535,65535,65535,65535,65535,65535,65535,65535,65535,65535,65535,65535,65535,65535,65535,65535,65535,65535,65535,65535,65535,65535,65535,65535,65535,65535,65535,65535},
{1824,1836,3670,1859,1871,1883,1894,1906,1918,1929,1941,1953,3785,1976,1988,2000,2011,2023,2035,2046,2058,2070,3900,2093,2105,2117,2128,2140,2152,2163,2175,2187,4015,2210,2222,2234,2245,2257,2269,65535,65535,65535,65535,65535,65535,65535,65535,65535},
{65535,65535,65535,65535,65535,65535,65535,65535,65535,65535,65535,65535,65535,65535,65535,65535,65535,65535,65535,65535,65535,65535,65535,65535,65535,65535,65535,65535,65535,65535,65535,65535,65535,65535,65535,65535,65535,65535,65535,65535,65535,65535,65535,65535,65535,65535,65535,65535},
{2280,2292,3671,2315,2327,2339,2350,2362,2374,2385,2397,2409,3786,2432,2444,2456,2467,2479,2491,2502,2514,2526,3901,2549,2561,2573,2584,2596,2608,2619,2631,2643,4016,2666,2678,2690,2701,2713,2725,65535,65535,65535,65535,65535,65535,65535,65535,65535},
{65535,65535,65535,65535,65535,65535,65535,65535,65535,65535,65535,65535,65535,65535,65535,65535,65535,65535,65535,65535,65535,65535,65535,65535,65535,65535,65535,65535,65535,65535,65535,65535,65535,65535,65535,65535,65535,65535,65535,65535,65535,65535,65535,65535,65535,65535,65535,65535},
{2736,2748,3672,2771,2783,2795,2806,2818,2830,2841,2853,2865,3787,2888,2900,2912,2923,2935,2947,2958,2970,2982,3902,3005,3017,3029,3040,3052,3064,3075,3087,3099,4017,3122,3134,3146,3157,3169,3181,65535,65535,65535,65535,65535,65535,65535,65535,65535},
{65535,65535,65535,65535,65535,65535,65535,65535,65535,65535,65535,65535,65535,65535,65535,65535,65535,65535,65535,65535,65535,65535,65535,65535,65535,65535,65535,65535,65535,65535,65535,65535,65535,65535,65535,65535,65535,65535,65535,65535,65535,65535,65535,65535,65535,65535,65535,65535},
{3192,3204,3673,3227,3239,3251,3262,3274,3286,3297,3309,3321,3788,3344,3356,3368,3379,3391,3403,3414,3426,3438,3903,3461,3473,3485,3496,3508,3520,3531,3543,3555,4018,3578,3590,3602,3613,3625,3637,65535,65535,65535,65535,65535,65535,65535,65535,65535},
{65535,65535,65535,65535,65535,65535,65535,65535,65535,65535,65535,65535,65535,65535,65535,65535,65535,65535,65535,65535,65535,65535,65535,65535,65535,65535,65535,65535,65535,65535,65535,65535,65535,65535,65535,65535,65535,65535,65535,65535,65535,65535,65535,65535,65535,65535,65535,65535},
{1,13,24,36,48,3702,71,83,95,106,118,130,141,153,165,3817,188,200,212,223,235,247,258,270,282,3932,305,317,329,340,352,364,375,387,399,4047,422,434,446,65535,65535,65535,65535,65535,65535,65535,65535,65535},
{65535,65535,65535,65535,65535,65535,65535,65535,65535,65535,65535,65535,65535,65535,65535,65535,65535,65535,65535,65535,65535,65535,65535,65535,65535,65535,65535,65535,65535,65535,65535,65535,65535,65535,65535,65535,65535,65535,65535,65535,65535,65535,65535,65535,65535,65535,65535,65535},
{457,469,480,492,504,3703,527,539,551,562,574,586,597,609,621,3818,644,656,668,679,691,703,714,726,738,3933,761,773,785,796,808,820,831,843,855,4048,878,890,902,65535,65535,65535,65535,65535,65535,65535,65535,65535},
{65535,65535,65535,65535,65535,65535,65535,65535,65535,65535,65535,65535,65535,65535,65535,65535,65535,65535,65535,65535,65535,65535,65535,65535,65535,65535,65535,65535,65535,65535,65535,65535,65535,65535,65535,65535,65535,65535,65535,65535,65535,65535,65535,65535,65535,65535,65535,65535},
{913,925,936,948,960,3704,983,995,1007,1018,1030,1042,1053,1065,1077,3819,1100,1112,1124,1135,1147,1159,1170,1182,1194,3934,1217,1229,1241,1252,1264,1276,1287,1299,1311,4049,1334,1346,1358,65535,65535,65535,65535,65535,65535,65535,65535,65535},
{65535,65535,65535,65535,65535,65535,65535,65535,65535,65535,65535,65535,65535,65535,65535,65535,65535,65535,65535,65535,65535,65535,65535,65535,65535,65535,65535,65535,65535,65535,65535,65535,65535,65535,65535,65535,65535,65535,65535,65535,65535,65535,65535,65535,65535,65535,65535,65535},
{1369,1381,1392,1404,1416,3705,1439,1451,1463,1474,1486,1498,1509,1521,1533,3820,1556,1568,1580,1591,1603,1615,1626,1638,1650,3935,1673,1685,1697,1708,1720,1732,1743,1755,1767,4050,1790,1802,1814,65535,65535,65535,65535,65535,65535,65535,65535,65535},
{65535,65535,65535,65535,65535,65535,65535,65535,65535,65535,65535,65535,65535,65535,65535,65535,65535,65535,65535,65535,65535,65535,65535,65535,65535,65535,65535,65535,65535,65535,65535,65535,65535,65535,65535,65535,65535,65535,65535,65535,65535,65535,65535,65535,65535,65535,65535,65535},
{1825,1837,1848,1860,1872,3706,1895,1907,1919,1930,1942,1954,1965,1977,1989,3821,2012,2024,2036,2047,2059,2071,2082,2094,2106,3936,2129,2141,2153,2164,2176,2188,2199,2211,2223,4051,2246,2258,2270,65535,65535,65535,65535,65535,65535,65535,65535,65535},
{65535,65535,65535,65535,65535,65535,65535,65535,65535,65535,65535,65535,65535,65535,65535,65535,65535,65535,65535,65535,65535,65535,65535,65535,65535,65535,65535,65535,65535,65535,65535,65535,65535,65535,65535,65535,65535,65535,65535,65535,65535,65535,65535,65535,65535,65535,65535,65535},
{2281,2293,2304,2316,2328,3707,2351,2363,2375,2386,2398,2410,2421,2433,2445,3822,2468,2480,2492,2503,2515,2527,2538,2550,2562,3937,2585,2597,2609,2620,2632,2644,2655,2667,2679,4052,2702,2714,2726,65535,65535,65535,65535,65535,65535,65535,65535,65535},
{65535,65535,65535,65535,65535,65535,65535,65535,65535,65535,65535,65535,65535,65535,65535,65535,65535,65535,65535,65535,65535,65535,65535,65535,65535,65535,65535,65535,65535,65535,65535,65535,65535,65535,65535,65535,65535,65535,65535,65535,65535,65535,65535,65535,65535,65535,65535,65535},
{2737,2749,2760,2772,2784,3708,2807,2819,2831,2842,2854,2866,2877,2889,2901,3823,2924,2936,2948,2959,2971,2983,2994,3006,3018,3938,3041,3053,3065,3076,3088,3100,3111,3123,3135,4053,3158,3170,3182,65535,65535,65535,65535,65535,65535,65535,65535,65535},
{65535,65535,65535,65535,65535,65535,65535,65535,65535,65535,65535,65535,65535,65535,65535,65535,65535,65535,65535,65535,65535,65535,65535,65535,65535,65535,65535,65535,65535,65535,65535,65535,65535,65535,65535,65535,65535,65535,65535,65535,65535,65535,65535,65535,65535,65535,65535,65535},
{3193,3205,3216,3228,3240,3709,3263,3275,3287,3298,3310,3322,3333,3345,3357,3824,3380,3392,3404,3415,3427,3439,3450,3462,3474,3939,3497,3509,3521,3532,3544,3556,3567,3579,3591,4054,3614,3626,3638,65535,65535,65535,65535,65535,65535,65535,65535,65535},
{65535,65535,65535,65535,65535,65535,65535,65535,65535,65535,65535,65535,65535,65535,65535,65535,65535,65535,65535,65535,65535,65535,65535,65535,65535,65535,65535,65535,65535,65535,65535,65535,65535,65535,65535,65535,65535,65535,65535,65535,65535,65535,65535,65535,65535,65535,65535,65535},
{2,14,25,37,49,60,72,84,3737,107,119,131,142,154,166,177,189,201,3852,224,236,248,259,271,283,294,306,318,3967,341,353,365,376,388,400,411,423,435,4080,65535,65535,65535,65535,65535,65535,65535,65535,65535},
{65535,65535,65535,65535,65535,65535,65535,65535,65535,65535,65535,65535,65535,65535,65535,65535,65535,65535,65535,65535,65535,65535,65535,65535,65535,65535,65535,65535,65535,65535,65535,65535,65535,65535,65535,65535,65535,65535,65535,65535,65535,65535,65535,65535,65535,65535,65535,65535},
{458,470,481,493,505,516,528,540,3738,563,575,587,598,610,622,633,645,657,3853,680,692,704,715,727,739,750,762,774,3968,797,809,821,832,844,856,867,879,891,4081,65535,65535,65535,65535,65535,65535,65535,65535,65535},
{65535,65535,65535,65535,65535,65535,65535,65535,65535,65535,65535,65535,65535,65535,65535,65535,65535,65535,65535,65535,65535,65535,65535,65535,65535,65535,65535,65535,65535,65535,65535,65535,65535,65535,65535,65535,65535,65535,65535,65535,65535,65535,65535,65535,65535,65535,65535,65535},
{914,926,937,949,961,972,984,996,3739,1019,1031,1043,1054,1066,1078,1089,1101,1113,3854,1136,1148,1160,1171,1183,1195,1206,1218,1230,3969,1253,1265,1277,1288,1300,1312,1323,1335,1347,4082,65535,65535,65535,65535,65535,65535,65535,65535,65535},
{65535,65535,65535,65535,65535,65535,65535,65535,65535,65535,65535,65535,65535,65535,65535,65535,65535,65535,65535,65535,65535,65535,65535,65535,65535,65535,65535,65535,65535,65535,65535,65535,65535,65535,65535,65535,65535,65535,65535,65535,65535,65535,65535,65535,65535,65535,65535,65535},
{1370,1382,1393,1405,1417,1428,1440,1452,3740,1475,1487,1499,1510,1522,1534,1545,1557,1569,3855,1592,1604,1616,1627,1639,1651,1662,1674,1686,3970,1709,1721,1733,1744,1756,1768,1779,1791,1803,4083,65535,65535,65535,65535,65535,65535,65535,65535,65535},
{65535,65535,65535,65535,65535,65535,65535,65535,65535,65535,65535,65535,65535,65535,65535,65535,65535,65535,65535,65535,65535,65535,65535,65535,65535,65535,65535,65535,65535,65535,65535,65535,65535,65535,65535,65535,65535,65535,65535,65535,65535,65535,65535,65535,65535,65535,65535,65535},
{1826,1838,1849,1861,1873,1884,1896,1908,3741,1931,1943,1955,1966,1978,1990,2001,2013,2025,3856,2048,2060,2072,2083,2095,2107,2118,2130,2142,3971,2165,2177,2189,2200,2212,2224,2235,2247,2259,4084,65535,65535,65535,65535,65535,65535,65535,65535,65535},
{65535,65535,65535,65535,65535,65535,65535,65535,65535,65535,65535,65535,65535,65535,65535,65535,65535,65535,65535,65535,65535,65535,65535,65535,65535,65535,65535,65535,65535,65535,65535,65535,65535,65535,65535,65535,65535,65535,65535,65535,65535,65535,65535,65535,65535,65535,65535,65535},
{2282,2294,2305,2317,2329,2340,2352,2364,3742,2387,2399,2411,2422,2434,2446,2457,2469,2481,3857,2504,2516,2528,2539,2551,2563,2574,2586,2598,3972,2621,2633,2645,2656,2668,2680,2691,2703,2715,4085,65535,65535,65535,65535,65535,65535,65535,65535,65535},
{65535,65535,65535,65535,65535,65535,65535,65535,65535,65535,65535,65535,65535,65535,65535,65535,65535,65535,65535,65535,65535,65535,65535,65535,65535,65535,65535,65535,65535,65535,65535,65535,65535,65535,65535,65535,65535,65535,65535,65535,65535,65535,65535,65535,65535,65535,65535,65535},
{2738,2750,2761,2773,2785,2796,2808,2820,3743,2843,2855,2867,2878,2890,2902,2913,2925,2937,3858,2960,2972,2984,2995,3007,3019,3030,3042,3054,3973,3077,3089,3101,3112,3124,3136,3147,3159,3171,4086,65535,65535,65535,65535,65535,65535,65535,65535,65535},
{65535,65535,65535,65535,65535,65535,65535,65535,65535,65535,65535,65535,65535,65535,65535,65535,65535,65535,65535,65535,65535,65535,65535,65535,65535,65535,65535,65535,65535,65535,65535,65535,65535,65535,65535,65535,65535,65535,65535,65535,65535,65535,65535,65535,65535,65535,65535,65535},
{3194,3206,3217,3229,3241,3252,3264,3276,3744,3299,3311,3323,3334,3346,3358,3369,3381,3393,3859,3416,3428,3440,3451,3463,3475,3486,3498,3510,3974,3533,3545,3557,3568,3580,3592,3603,3615,3627,4087,65535,65535,65535,65535,65535,65535,65535,65535,65535},
{3,3657,26,38,50,61,73,85,96,108,120,3772,143,155,167,178,190,202,213,225,237,3887,260,272,284,295,307,319,330,342,354,4003,377,389,401,412,424,436,447,65535,65535,65535,65535,65535,65535,65535,65535,65535},
{4,15,27,39,3693,62,74,86,97,109,121,132,144,156,3808,179,191,203,214,226,238,249,261,273,3923,296,308,320,331,343,355,366,378,390,4038,413,425,437,448,65535,65535,65535,65535,65535,65535,65535,65535,65535},
{459,3658,482,494,506,517,529,541,552,564,576,3773,599,611,623,634,646,658,669,681,693,3888,716,728,740,751,763,775,786,798,810,4004,833,845,857,868,880,892,903,65535,65535,65535,65535,65535,65535,65535,65535,65535},
{460,471,483,495,3694,518,530,542,553,565,577,588,600,612,3809,635,647,659,670,682,694,705,717,729,3924,752,764,776,787,799,811,822,834,846,4039,869,881,893,904,65535,65535,65535,65535,65535,65535,65535,65535,65535},
{915,3659,938,950,962,973,985,997,1008,1020,1032,3774,1055,1067,1079,1090,1102,1114,1125,1137,1149,3889,1172,1184,1196,1207,1219,1231,1242,1254,1266,4005,1289,1301,1313,1324,1336,1348,1359,65535,65535,65535,65535,65535,65535,65535,65535,65535},
{916,927,939,951,3695,974,986,998,1009,1021,1033,1044,1056,1068,3810,1091,1103,1115,1126,1138,1150,1161,1173,1185,3925,1208,1220,1232,1243,1255,1267,1278,1290,1302,4040,1325,1337,1349,1360,65535,65535,65535,65535,65535,65535,65535,65535,65535},
{1371,3660,1394,1406,1418,1429,1441,1453,1464,1476,1488,3775,1511,1523,1535,1546,1558,1570,1581,1593,1605,3890,1628,1640,1652,1663,1675,1687,1698,1710,1722,4006,1745,1757,1769,1780,1792,1804,1815,65535,65535,65535,65535,65535,65535,65535,65535,65535},
{1372,1383,1395,1407,3696,1430,1442,1454,1465,1477,1489,1500,1512,1524,3811,1547,1559,1571,1582,1594,1606,1617,1629,1641,3926,1664,1676,1688,1699,1711,1723,1734,1746,1758,4041,1781,1793,1805,1816,65535,65535,65535,65535,65535,65535,65535,65535,65535},
{1827,3661,1850,1862,1874,1885,1897,1909,1920,1932,1944,3776,1967,1979,1991,2002,2014,2026,2037,2049,2061,3891,2084,2096,2108,2119,2131,2143,2154,2166,2178,4007,2201,2213,2225,2236,2248,2260,2271,65535,65535,65535,65535,65535,65535,65535,65535,65535},
{1828,1839,1851,1863,3697,1886,1898,1910,1921,1933,1945,1956,1968,1980,3812,2003,2015,2027,2038,2050,2062,2073,2085,2097,3927,2120,2132,2144,2155,2167,2179,2190,2202,2214,4042,2237,2249,2261,2272,65535,65535,65535,65535,65535,65535,65535,65535,65535},
{2283,3662,2306,2318,2330,2341,2353,2365,2376,2388,2400,3777,2423,2435,2447,2458,2470,2482,2493,2505,2517,3892,2540,2552,2564,2575,2587,2599,2610,2622,2634,4008,2657,2669,2681,2692,2704,2716,2727,65535,65535,65535,65535,65535,65535,65535,65535,65535},
{2284,2295,2307,2319,3698,2342,2354,2366,2377,2389,2401,2412,2424,2436,3813,2459,2471,2483,2494,2506,2518,2529,2541,2553,3928,2576,2588,2600,2611,2623,2635,2646,2658,2670,4043,2693,2705,2717,2728,65535,65535,65535,65535,65535,65535,65535,65535,65535},
{65535,65535,65535,65535,65535,65535,65535,65535,65535,65535,65535,65535,65535,65535,65535,65535,65535,65535,65535,65535,65535,65535,65535,65535,65535,65535,65535,65535,65535,65535,65535,65535,65535,65535,65535,65535,65535,65535,65535,65535,65535,65535,65535,65535,65535,65535,65535,65535},
{2739,3663,2762,2774,2786,2797,2809,2821,2832,2844,2856,3778,2879,2891,2903,2914,2926,2938,2949,2961,2973,3893,2996,3008,3020,3031,3043,3055,3066,3078,3090,4009,3113,3125,3137,3148,3160,3172,3183,65535,65535,65535,65535,65535,65535,65535,65535,65535},
{3195,3664,3218,3230,3242,3253,3265,3277,3288,3300,3312,3779,3335,3347,3359,3370,3382,3394,3405,3417,3429,3894,3452,3464,3476,3487,3499,3511,3522,3534,3546,4010,3569,3581,3593,3604,3616,3628,3639,65535,65535,65535,65535,65535,65535,65535,65535,65535},
{3196,3207,3219,3231,3700,3254,3266,3278,3289,3301,3313,3324,3336,3348,3815,3371,3383,3395,3406,3418,3430,3441,3453,3465,3930,3488,3500,3512,3523,3535,3547,3558,3570,3582,4045,3605,3617,3629,3640,65535,65535,65535,65535,65535,65535,65535,65535,65535},
{461,472,484,496,507,519,531,3729,554,566,578,589,601,613,624,636,648,3844,671,683,695,706,718,730,741,753,765,3959,788,800,812,823,835,847,858,870,882,4073,905,65535,65535,65535,65535,65535,65535,65535,65535,65535},
{3650,473,485,497,508,520,532,543,555,567,3765,590,602,614,625,637,649,660,672,684,3880,707,719,731,742,754,766,777,789,801,3995,824,836,848,859,871,883,894,906,65535,65535,65535,65535,65535,65535,65535,65535,65535},
{917,928,940,952,963,975,987,3730,1010,1022,1034,1045,1057,1069,1080,1092,1104,3845,1127,1139,1151,1162,1174,1186,1197,1209,1221,3960,1244,1256,1268,1279,1291,1303,1314,1326,1338,4074,1361,65535,65535,65535,65535,65535,65535,65535,65535,65535},
{3651,929,941,953,964,976,988,999,1011,1023,3766,1046,1058,1070,1081,1093,1105,1116,1128,1140,3881,1163,1175,1187,1198,1210,1222,1233,1245,1257,3996,1280,1292,1304,1315,1327,1339,1350,1362,65535,65535,65535,65535,65535,65535,65535,65535,65535},
{1373,1384,1396,1408,1419,1431,1443,3731,1466,1478,1490,1501,1513,1525,1536,1548,1560,3846,1583,1595,1607,1618,1630,1642,1653,1665,1677,3961,1700,1712,1724,1735,1747,1759,1770,1782,1794,4075,1817,65535,65535,65535,65535,65535,65535,65535,65535,65535},
{3652,1385,1397,1409,1420,1432,1444,1455,1467,1479,3767,1502,1514,1526,1537,1549,1561,1572,1584,1596,3882,1619,1631,1643,1654,1666,1678,1689,1701,1713,3997,1736,1748,1760,1771,1783,1795,1806,1818,65535,65535,65535,65535,65535,65535,65535,65535,65535},
{1829,1840,1852,1864,1875,1887,1899,3732,1922,1934,1946,1957,1969,1981,1992,2004,2016,3847,2039,2051,2063,2074,2086,2098,2109,2121,2133,3962,2156,2168,2180,2191,2203,2215,2226,2238,2250,4076,2273,65535,65535,65535,65535,65535,65535,65535,65535,65535},
{3653,1841,1853,1865,1876,1888,1900,1911,1923,1935,3768,1958,1970,1982,1993,2005,2017,2028,2040,2052,3883,2075,2087,2099,2110,2122,2134,2145,2157,2169,3998,2192,2204,2216,2227,2239,2251,2262,2274,65535,65535,65535,65535,65535,65535,65535,65535,65535},
{2285,2296,2308,2320,2331,2343,2355,3733,2378,2390,2402,2413,2425,2437,2448,2460,2472,3848,2495,2507,2519,2530,2542,2554,2565,2577,2589,3963,2612,2624,2636,2647,2659,2671,2682,2694,2706,4077,2729,65535,65535,65535,65535,65535,65535,65535,65535,65535},
{3654,2297,2309,2321,2332,2344,2356,2367,2379,2391,3769,2414,2426,2438,2449,2461,2473,2484,2496,2508,3884,2531,2543,2555,2566,2578,2590,2601,2613,2625,3999,2648,2660,2672,2683,2695,2707,2718,2730,65535,65535,65535,65535,65535,65535,65535,65535,65535},
{2740,2751,2763,2775,3699,2798,2810,2822,2833,2845,2857,2868,2880,2892,3814,2915,2927,2939,2950,2962,2974,2985,2997,3009,3929,3032,3044,3056,3067,3079,3091,3102,3114,3126,4044,3149,3161,3173,3184,65535,65535,65535,65535,65535,65535,65535,65535,65535},
{2741,2752,2764,2776,2787,2799,2811,3734,2834,2846,2858,2869,2881,2893,2904,2916,2928,3849,2951,2963,2975,2986,2998,3010,3021,3033,3045,3964,3068,3080,3092,3103,3115,3127,3138,3150,3162,4078,3185,65535,65535,65535,65535,65535,65535,65535,65535,65535},
{3197,3208,3220,3232,3243,3255,3267,3735,3290,3302,3314,3325,3337,3349,3360,3372,3384,3850,3407,3419,3431,3442,3454,3466,3477,3489,3501,3965,3524,3536,3548,3559,3571,3583,3594,3606,3618,4079,3641,65535,65535,65535,65535,65535,65535,65535,65535,65535},
{3656,3209,3221,3233,3244,3256,3268,3279,3291,3303,3771,3326,3338,3350,3361,3373,3385,3396,3408,3420,3886,3443,3455,3467,3478,3490,3502,3513,3525,3537,4001,3560,3572,3584,3595,3607,3619,3630,3642,65535,65535,65535,65535,65535,65535,65535,65535,65535},
{462,474,486,3685,509,521,533,544,556,568,579,591,603,3800,626,638,650,661,673,685,696,708,720,3915,743,755,767,778,790,802,813,825,837,4030,860,872,884,895,907,65535,65535,65535,65535,65535,65535,65535,65535,65535},
{463,475,487,498,510,522,3720,545,557,569,580,592,604,615,627,639,3835,662,674,686,697,709,721,732,744,756,3950,779,791,803,814,826,838,849,861,873,4065,896,908,65535,65535,65535,65535,65535,65535,65535,65535,65535},
{918,930,942,3686,965,977,989,1000,1012,1024,1035,1047,1059,3801,1082,1094,1106,1117,1129,1141,1152,1164,1176,3916,1199,1211,1223,1234,1246,1258,1269,1281,1293,4031,1316,1328,1340,1351,1363,65535,65535,65535,65535,65535,65535,65535,65535,65535},
{919,931,943,954,966,978,3721,1001,1013,1025,1036,1048,1060,1071,1083,1095,3836,1118,1130,1142,1153,1165,1177,1188,1200,1212,3951,1235,1247,1259,1270,1282,1294,1305,1317,1329,4066,1352,1364,65535,65535,65535,65535,65535,65535,65535,65535,65535},
{1374,1386,1398,3687,1421,1433,1445,1456,1468,1480,1491,1503,1515,3802,1538,1550,1562,1573,1585,1597,1608,1620,1632,3917,1655,1667,1679,1690,1702,1714,1725,1737,1749,4032,1772,1784,1796,1807,1819,65535,65535,65535,65535,65535,65535,65535,65535,65535},
{1375,1387,1399,1410,1422,1434,3722,1457,1469,1481,1492,1504,1516,1527,1539,1551,3837,1574,1586,1598,1609,1621,1633,1644,1656,1668,3952,1691,1703,1715,1726,1738,1750,1761,1773,1785,4067,1808,1820,65535,65535,65535,65535,65535,65535,65535,65535,65535},
{1830,1842,1854,3688,1877,1889,1901,1912,1924,1936,1947,1959,1971,3803,1994,2006,2018,2029,2041,2053,2064,2076,2088,3918,2111,2123,2135,2146,2158,2170,2181,2193,2205,4033,2228,2240,2252,2263,2275,65535,65535,65535,65535,65535,65535,65535,65535,65535},
{1831,1843,1855,1866,1878,1890,3723,1913,1925,1937,1948,1960,1972,1983,1995,2007,3838,2030,2042,2054,2065,2077,2089,2100,2112,2124,3953,2147,2159,2171,2182,2194,2206,2217,2229,2241,4068,2264,2276,65535,65535,65535,65535,65535,65535,65535,65535,65535},
{2286,2298,2310,3689,2333,2345,2357,2368,2380,2392,2403,2415,2427,3804,2450,2462,2474,2485,2497,2509,2520,2532,2544,3919,2567,2579,2591,2602,2614,2626,2637,2649,2661,4034,2684,2696,2708,2719,2731,65535,65535,65535,65535,65535,65535,65535,65535,65535},
{2287,2299,2311,2322,2334,2346,3724,2369,2381,2393,2404,2416,2428,2439,2451,2463,3839,2486,2498,2510,2521,2533,2545,2556,2568,2580,3954,2603,2615,2627,2638,2650,2662,2673,2685,2697,4069,2720,2732,65535,65535,65535,65535,65535,65535,65535,65535,65535},
{3655,2753,2765,2777,2788,2800,2812,2823,2835,2847,3770,2870,2882,2894,2905,2917,2929,2940,2952,2964,3885,2987,2999,3011,3022,3034,3046,3057,3069,3081,4000,3104,3116,3128,3139,3151,3163,3174,3186,65535,65535,65535,65535,65535,65535,65535,65535,65535},
{2742,2754,2766,3690,2789,2801,2813,2824,2836,2848,2859,2871,2883,3805,2906,2918,2930,2941,2953,2965,2976,2988,3000,3920,3023,3035,3047,3058,3070,3082,3093,3105,3117,4035,3140,3152,3164,3175,3187,65535,65535,65535,65535,65535,65535,65535,65535,65535},
{3198,3210,3222,3691,3245,3257,3269,3280,3292,3304,3315,3327,3339,3806,3362,3374,3386,3397,3409,3421,3432,3444,3456,3921,3479,3491,3503,3514,3526,3538,3549,3561,3573,4036,3596,3608,3620,3631,3643,65535,65535,65535,65535,65535,65535,65535,65535,65535},
{3199,3211,3223,3234,3246,3258,3726,3281,3293,3305,3316,3328,3340,3351,3363,3375,3841,3398,3410,3422,3433,3445,3457,3468,3480,3492,3956,3515,3527,3539,3550,3562,3574,3585,3597,3609,4071,3632,3644,65535,65535,65535,65535,65535,65535,65535,65535,65535},
{464,476,488,499,511,523,534,546,558,3756,581,593,605,616,628,640,651,663,675,3871,698,710,722,733,745,757,768,780,792,3986,815,827,839,850,862,874,885,897,909,65535,65535,65535,65535,65535,65535,65535,65535,65535},
{465,477,3676,500,512,524,535,547,559,570,582,594,3791,617,629,641,652,664,676,687,699,711,3906,734,746,758,769,781,793,804,816,828,4021,851,863,875,886,898,910,65535,65535,65535,65535,65535,65535,65535,65535,65535},
{920,932,944,955,967,979,990,1002,1014,3757,1037,1049,1061,1072,1084,1096,1107,1119,1131,3872,1154,1166,1178,1189,1201,1213,1224,1236,1248,3987,1271,1283,1295,1306,1318,1330,1341,1353,1365,65535,65535,65535,65535,65535,65535,65535,65535,65535},
{921,933,3677,956,968,980,991,1003,1015,1026,1038,1050,3792,1073,1085,1097,1108,1120,1132,1143,1155,1167,3907,1190,1202,1214,1225,1237,1249,1260,1272,1284,4022,1307,1319,1331,1342,1354,1366,65535,65535,65535,65535,65535,65535,65535,65535,65535},
{1376,1388,1400,1411,1423,1435,1446,1458,1470,3758,1493,1505,1517,1528,1540,1552,1563,1575,1587,3873,1610,1622,1634,1645,1657,1669,1680,1692,1704,3988,1727,1739,1751,1762,1774,1786,1797,1809,1821,65535,65535,65535,65535,65535,65535,65535,65535,65535},
{1377,1389,3678,1412,1424,1436,1447,1459,1471,1482,1494,1506,3793,1529,1541,1553,1564,1576,1588,1599,1611,1623,3908,1646,1658,1670,1681,1693,1705,1716,1728,1740,4023,1763,1775,1787,1798,1810,1822,65535,65535,65535,65535,65535,65535,65535,65535,65535},
{1832,1844,1856,1867,1879,1891,1902,1914,1926,3759,1949,1961,1973,1984,1996,2008,2019,2031,2043,3874,2066,2078,2090,2101,2113,2125,2136,2148,2160,3989,2183,2195,2207,2218,2230,2242,2253,2265,2277,65535,65535,65535,65535,65535,65535,65535,65535,65535},
{1833,1845,3679,1868,1880,1892,1903,1915,1927,1938,1950,1962,3794,1985,1997,2009,2020,2032,2044,2055,2067,2079,3909,2102,2114,2126,2137,2149,2161,2172,2184,2196,4024,2219,2231,2243,2254,2266,2278,65535,65535,65535,65535,65535,65535,65535,65535,65535},
{2288,2300,2312,2323,2335,2347,2358,2370,2382,3760,2405,2417,2429,2440,2452,2464,2475,2487,2499,3875,2522,2534,2546,2557,2569,2581,2592,2604,2616,3990,2639,2651,2663,2674,2686,2698,2709,2721,2733,65535,65535,65535,65535,65535,65535,65535,65535,65535},
{2289,2301,3680,2324,2336,2348,2359,2371,2383,2394,2406,2418,3795,2441,2453,2465,2476,2488,2500,2511,2523,2535,3910,2558,2570,2582,2593,2605,2617,2628,2640,2652,4025,2675,2687,2699,2710,2722,2734,65535,65535,65535,65535,65535,65535,65535,65535,65535},
{2743,2755,2767,2778,2790,2802,3725,2825,2837,2849,2860,2872,2884,2895,2907,2919,3840,2942,2954,2966,2977,2989,3001,3012,3024,3036,3955,3059,3071,3083,3094,3106,3118,3129,3141,3153,4070,3176,3188,65535,65535,65535,65535,65535,65535,65535,65535,65535},
{2744,2756,2768,2779,2791,2803,2814,2826,2838,3761,2861,2873,2885,2896,2908,2920,2931,2943,2955,3876,2978,2990,3002,3013,3025,3037,3048,3060,3072,3991,3095,3107,3119,3130,3142,3154,3165,3177,3189,65535,65535,65535,65535,65535,65535,65535,65535,65535},
{3200,3212,3224,3235,3247,3259,3270,3282,3294,3762,3317,3329,3341,3352,3364,3376,3387,3399,3411,3877,3434,3446,3458,3469,3481,3493,3504,3516,3528,3992,3551,3563,3575,3586,3598,3610,3621,3633,3645,65535,65535,65535,65535,65535,65535,65535,65535,65535},
{3201,3213,3682,3236,3248,3260,3271,3283,3295,3306,3318,3330,3797,3353,3365,3377,3388,3400,3412,3423,3435,3447,3912,3470,3482,3494,3505,3517,3529,3540,3552,3564,4027,3587,3599,3611,3622,3634,3646,65535,65535,65535,65535,65535,65535,65535,65535,65535},
{466,478,489,501,513,3711,536,548,560,571,583,595,606,618,630,3827,653,665,677,688,700,712,723,735,747,3942,770,782,794,805,817,829,840,852,864,4057,887,899,911,65535,65535,65535,65535,65535,65535,65535,65535,65535},
{467,479,490,502,514,525,537,549,3747,572,584,596,607,619,631,642,654,666,3862,689,701,713,724,736,748,759,771,783,3977,806,818,830,841,853,865,876,888,900,4089,65535,65535,65535,65535,65535,65535,65535,65535,65535},
{922,934,945,957,969,3712,992,1004,1016,1027,1039,1051,1062,1074,1086,3828,1109,1121,1133,1144,1156,1168,1179,1191,1203,3943,1226,1238,1250,1261,1273,1285,1296,1308,1320,4058,1343,1355,1367,65535,65535,65535,65535,65535,65535,65535,65535,65535},
{923,935,946,958,970,981,993,1005,3748,1028,1040,1052,1063,1075,1087,1098,1110,1122,3863,1145,1157,1169,1180,1192,1204,1215,1227,1239,3978,1262,1274,1286,1297,1309,1321,1332,1344,1356,4090,65535,65535,65535,65535,65535,65535,65535,65535,65535},
{1378,1390,1401,1413,1425,3713,1448,1460,1472,1483,1495,1507,1518,1530,1542,3829,1565,1577,1589,1600,1612,1624,1635,1647,1659,3944,1682,1694,1706,1717,1729,1741,1752,1764,1776,4059,1799,1811,1823,65535,65535,65535,65535,65535,65535,65535,65535,65535},
{1379,1391,1402,1414,1426,1437,1449,1461,3749,1484,1496,1508,1519,1531,1543,1554,1566,1578,3864,1601,1613,1625,1636,1648,1660,1671,1683,1695,3979,1718,1730,1742,1753,1765,1777,1788,1800,1812,4091,65535,65535,65535,65535,65535,65535,65535,65535,65535},
{1834,1846,1857,1869,1881,3714,1904,1916,1928,1939,1951,1963,1974,1986,1998,3830,2021,2033,2045,2056,2068,2080,2091,2103,2115,3945,2138,2150,2162,2173,2185,2197,2208,2220,2232,4060,2255,2267,2279,65535,65535,65535,65535,65535,65535,65535,65535,65535},
{1835,1847,1858,1870,1882,1893,1905,1917,3750,1940,1952,1964,1975,1987,1999,2010,2022,2034,3865,2057,2069,2081,2092,2104,2116,2127,2139,2151,3980,2174,2186,2198,2209,2221,2233,2244,2256,2268,4092,65535,65535,65535,65535,65535,65535,65535,65535,65535},
{2290,2302,2313,2325,2337,3715,2360,2372,2384,2395,2407,2419,2430,2442,2454,3831,2477,2489,2501,2512,2524,2536,2547,2559,2571,3946,2594,2606,2618,2629,2641,2653,2664,2676,2688,4061,2711,2723,2735,65535,65535,65535,65535,65535,65535,65535,65535,65535},
{2291,2303,2314,2326,2338,2349,2361,2373,3751,2396,2408,2420,2431,2443,2455,2466,2478,2490,3866,2513,2525,2537,2548,2560,2572,2583,2595,2607,3981,2630,2642,2654,2665,2677,2689,2700,2712,2724,4093,65535,65535,65535,65535,65535,65535,65535,65535,65535},
{2745,2757,3681,2780,2792,2804,2815,2827,2839,2850,2862,2874,3796,2897,2909,2921,2932,2944,2956,2967,2979,2991,3911,3014,3026,3038,3049,3061,3073,3084,3096,3108,4026,3131,3143,3155,3166,3178,3190,65535,65535,65535,65535,65535,65535,65535,65535,65535},
{2746,2758,2769,2781,2793,3716,2816,2828,2840,2851,2863,2875,2886,2898,2910,3832,2933,2945,2957,2968,2980,2992,3003,3015,3027,3947,3050,3062,3074,3085,3097,3109,3120,3132,3144,4062,3167,3179,3191,65535,65535,65535,65535,65535,65535,65535,65535,65535},
{3202,3214,3225,3237,3249,3717,3272,3284,3296,3307,3319,3331,3342,3354,3366,3833,3389,3401,3413,3424,3436,3448,3459,3471,3483,3948,3506,3518,3530,3541,3553,3565,3576,3588,3600,4063,3623,3635,3647,65535,65535,65535,65535,65535,65535,65535,65535,65535},
{3203,3215,3226,3238,3250,3261,3273,3285,3753,3308,3320,3332,3343,3355,3367,3378,3390,3402,3868,3425,3437,3449,3460,3472,3484,3495,3507,3519,3983,3542,3554,3566,3577,3589,3601,3612,3624,3636,4095,65535,65535,65535,65535,65535,65535,65535,65535,65535},
{65535,65535,65535,65535,65535,65535,65535,65535,65535,65535,65535,65535,65535,65535,65535,65535,65535,65535,65535,65535,65535,65535,65535,65535,65535,65535,65535,65535,65535,65535,65535,65535,65535,65535,65535,65535,65535,65535,65535,65535,65535,65535,65535,65535,65535,65535,65535,65535},
{2747,2759,2770,2782,2794,2805,2817,2829,3752,2852,2864,2876,2887,2899,2911,2922,2934,2946,3867,2969,2981,2993,3004,3016,3028,3039,3051,3063,3982,3086,3098,3110,3121,3133,3145,3156,3168,3180,4094,65535,65535,65535,65535,65535,65535,65535,65535,65535},
{65535,65535,65535,65535,65535,65535,65535,65535,65535,65535,65535,65535,65535,65535,65535,65535,65535,65535,65535,65535,65535,65535,65535,65535,65535,65535,65535,65535,65535,65535,65535,65535,65535,65535,65535,65535,65535,65535,65535,65535,65535,65535,65535,65535,65535,65535,65535,65535},
{3648,3665,3674,3683,3692,3701,3718,3727,3736,3745,3754,3763,3780,3789,3798,3807,3816,3825,3842,3851,3860,3869,3878,3895,3904,3913,3922,3931,3940,3957,3966,3975,3984,3993,4002,4019,4028,4037,4046,4055,65535,65535,65535,65535,65535,65535,65535,65535},
{5,16,28,40,51,63,75,3728,98,110,122,133,145,157,168,180,192,3843,215,227,239,250,262,274,285,297,309,3958,332,344,356,367,379,391,402,414,426,4072,449,65535,65535,65535,65535,65535,65535,65535,65535,65535},
{3649,17,29,41,52,64,76,87,99,111,3764,134,146,158,169,181,193,204,216,228,3879,251,263,275,286,298,310,321,333,345,3994,368,380,392,403,415,427,438,450,65535,65535,65535,65535,65535,65535,65535,65535,65535},
{6,18,30,3684,53,65,77,88,100,112,123,135,147,3799,170,182,194,205,217,229,240,252,264,3914,287,299,311,322,334,346,357,369,381,4029,404,416,428,439,451,65535,65535,65535,65535,65535,65535,65535,65535,65535},
{7,19,31,42,54,66,3719,89,101,113,124,136,148,159,171,183,3834,206,218,230,241,253,265,276,288,300,3949,323,335,347,358,370,382,393,405,417,4064,440,452,65535,65535,65535,65535,65535,65535,65535,65535,65535},
{8,20,32,43,55,67,78,90,102,3755,125,137,149,160,172,184,195,207,219,3870,242,254,266,277,289,301,312,324,336,3985,359,371,383,394,406,418,429,441,453,65535,65535,65535,65535,65535,65535,65535,65535,65535},
{9,21,3675,44,56,68,79,91,103,114,126,138,3790,161,173,185,196,208,220,231,243,255,3905,278,290,302,313,325,337,348,360,372,4020,395,407,419,430,442,454,65535,65535,65535,65535,65535,65535,65535,65535,65535},
{10,22,33,45,57,3710,80,92,104,115,127,139,150,162,174,3826,197,209,221,232,244,256,267,279,291,3941,314,326,338,349,361,373,384,396,408,4056,431,443,455,65535,65535,65535,65535,65535,65535,65535,65535,65535},
{11,23,34,46,58,69,81,93,3746,116,128,140,151,163,175,186,198,210,3861,233,245,257,268,280,292,303,315,327,3976,350,362,374,385,397,409,420,432,444,4088,65535,65535,65535,65535,65535,65535,65535,65535,65535},
};

#define NG 9
#define RING 16
#define NSLOT 8
#define CFETCH 5
#define TABLED 1
#define PROMO CU_TENSOR_MAP_L2_PROMOTION_L2_128B
#define AHEAD 6
#define CF0 5
#define CFS 2
#define ABL 0
#define CX 5
#define PUBN 2
#define PUBE 8
#define SCHED 9
#define OUT_TMA 0
#define JB1 21
#define JB2 24
#define TRIG 6
constexpr int NCONV = 3 * NG;
constexpr int PLEN = (1024 + NG - 1) / NG;
constexpr int TILEB = 12288;
constexpr int SLOTB = 280 * 64;
constexpr int W1S = 0, W2S = 73728, ABUF = 147456, XBUF = ABUF + 16 * 3072, MISC = XBUF + 8 * 3072;
constexpr int CTAB = NSLOT * SLOTB + 512;
constexpr int SMEM_BYTES = MISC + 512 + 2048 + 128;
static_assert(CTAB + (PLEN + 12) * 16 <= MISC, "conv smem");

struct Globals {
  unsigned char scratch[(RING * NG + 1) * 4 * TILEB];
  uint32_t ready[1024];
  uint32_t cons[1024 + 32];
  uint32_t epoch[1024];
};
__device__ __align__(1024) Globals g_state;

#define PROF_AT(cond, idx)
#define PROF_VAL(cond, idx, v)
#define PROF2_AT(c, i)
#define PROF2_VAL(c, i, v)
#define GELU_C3 0.32920349f
#define GELU_A2 0x40d940d9u
#define SPIN_LIMIT 0x1000000

__device__ __forceinline__ uint32_t smem_u32(const void* p) { return (uint32_t)__cvta_generic_to_shared(p); }
__device__ __forceinline__ void wg_fence() { asm volatile("wgmma.fence.sync.aligned;" ::: "memory"); }
__device__ __forceinline__ void wg_commit() { asm volatile("wgmma.commit_group.sync.aligned;" ::: "memory"); }
template <int N> __device__ __forceinline__ void wg_wait() { asm volatile("wgmma.wait_group.sync.aligned %0;" ::"n"(N) : "memory"); }
__device__ __forceinline__ void mbar_init(uint32_t bar, uint32_t cnt) { asm volatile("mbarrier.init.shared::cta.b64 [%0], %1;" ::"r"(bar), "r"(cnt) : "memory"); }
__device__ __forceinline__ void mbar_expect_tx(uint32_t bar, uint32_t bytes) { asm volatile("mbarrier.arrive.expect_tx.shared::cta.b64 _, [%0], %1;" ::"r"(bar), "r"(bytes) : "memory"); }
__device__ __forceinline__ void mbar_arrive(uint32_t bar) { asm volatile("mbarrier.arrive.shared::cta.b64 _, [%0];" ::"r"(bar) : "memory"); }
__device__ __forceinline__ void mbar_wait(uint32_t bar, uint32_t parity) {
  asm volatile("{\n.reg .pred p;\n.reg .u32 c;\nmbarrier.try_wait.parity.shared::cta.b64 p, [%0], %1;\n@p bra DONE_%=;\nmov.u32 c, 0;\nWAIT_%=:\nmbarrier.try_wait.parity.shared::cta.b64 p, [%0], %1;\n@p bra DONE_%=;\n"
               "add.u32 c, c, 1;\nsetp.lt.u32 p, c, 0x1000000;\n@p bra WAIT_%=;\ntrap;\nDONE_%=:\n}" ::"r"(bar), "r"(parity) : "memory");
}
__device__ __forceinline__ void bulk_g2s(uint32_t dst, const void* src, uint32_t bytes, uint32_t bar) {
  asm volatile("cp.async.bulk.shared::cluster.global.mbarrier::complete_tx::bytes [%0], [%1], %2, [%3];" ::"r"(dst), "l"(src), "r"(bytes), "r"(bar) : "memory");
}
__device__ __forceinline__ uint32_t ld_relaxed(const uint32_t* p) { uint32_t v; asm volatile("ld.relaxed.gpu.global.u32 %0, [%1];" : "=r"(v) : "l"(p) : "memory"); return v; }
__device__ __forceinline__ void red_add_elect(uint32_t* p) { asm volatile("{.reg .pred p; elect.sync _|p, 0xffffffff; @p red.relaxed.gpu.global.add.u32 [%0], 1;}" ::"l"(p) : "memory"); }
__device__ __forceinline__ void mbar_arrive_elect(uint32_t bar) { asm volatile("{.reg .pred p; elect.sync _|p, 0xffffffff; @p mbarrier.arrive.shared::cta.b64 _, [%0];}" ::"r"(bar) : "memory"); }
__device__ __forceinline__ void mbar_init_elect(uint32_t bar, uint32_t cnt) { asm volatile("{.reg .pred p; elect.sync _|p, 0xffffffff; @p mbarrier.init.shared::cta.b64 [%0], %1;}" ::"r"(bar), "r"(cnt) : "memory"); }
__device__ __forceinline__ uint32_t next_epoch(Globals* gs, int id) { const uint32_t e = ld_relaxed(&gs->epoch[id]); __syncwarp(); gs->epoch[id] = e + 1; return e; }
__device__ __forceinline__ void lds128(uint32_t* r, uint32_t a) { asm volatile("ld.shared.v4.b32 {%0,%1,%2,%3}, [%4];" : "=r"(r[0]), "=r"(r[1]), "=r"(r[2]), "=r"(r[3]) : "r"(a) : "memory"); }
__device__ __forceinline__ uint2 lds64(uint32_t a) { uint2 v; asm volatile("ld.shared.v2.b32 {%0,%1}, [%2];" : "=r"(v.x), "=r"(v.y) : "r"(a) : "memory"); return v; }
__device__ __forceinline__ uint32_t lds32(uint32_t a) { uint32_t v; asm volatile("ld.shared.b32 %0, [%1];" : "=r"(v) : "r"(a) : "memory"); return v; }
__device__ __forceinline__ void sts32(uint32_t a, uint32_t v) { asm volatile("st.shared.b32 [%0], %1;" ::"r"(a), "r"(v) : "memory"); }
__device__ __forceinline__ void sts128(uint32_t a, uint4 v) { asm volatile("st.shared.v4.b32 [%0], {%1,%2,%3,%4};" ::"r"(a), "r"(v.x), "r"(v.y), "r"(v.z), "r"(v.w) : "memory"); }
__device__ __forceinline__ uint4 ldg128v(const void* p) { uint4 v; asm volatile("ld.global.nc.v4.b32 {%0,%1,%2,%3}, [%4];" : "=r"(v.x), "=r"(v.y), "=r"(v.z), "=r"(v.w) : "l"(p) : "memory"); return v; }
__device__ __forceinline__ void stg128(void* p, uint4 v) { asm volatile("st.global.v4.b32 [%0], {%1,%2,%3,%4};" ::"l"(p), "r"(v.x), "r"(v.y), "r"(v.z), "r"(v.w) : "memory"); }
#define HINT 3
__device__ __forceinline__ uint64_t pol_evict_first() { uint64_t p; asm("createpolicy.fractional.L2::evict_first.b64 %0, 1.0;" : "=l"(p)); return p; }
__device__ __forceinline__ uint4 ldg128_last(const void* p, uint64_t pol) {
  if (!(HINT & 1)) return ldg128v(p);
  uint4 v; asm volatile("ld.global.nc.L1::no_allocate.L2::cache_hint.v4.b32 {%0,%1,%2,%3}, [%4], %5;" : "=r"(v.x), "=r"(v.y), "=r"(v.z), "=r"(v.w) : "l"(p), "l"(pol) : "memory"); return v;
}
__device__ __forceinline__ void stg128_stream(void* p, uint4 v, uint64_t pol) {
  if (!(HINT & 2)) { stg128(p, v); return; }
  asm volatile("st.global.L2::cache_hint.v4.b32 [%0], {%1,%2,%3,%4}, %5;" ::"l"(p), "r"(v.x), "r"(v.y), "r"(v.z), "r"(v.w), "l"(pol) : "memory");
}
__device__ __forceinline__ float bf_lo(uint32_t w) { return __uint_as_float(w << 16); }
__device__ __forceinline__ float bf_hi(uint32_t w) { return __uint_as_float(w & 0xffff0000u); }
__device__ __forceinline__ uint32_t pack_f16(float lo, float hi) { uint32_t d; asm("cvt.rn.f16x2.f32 %0, %1, %2;" : "=r"(d) : "f"(hi), "f"(lo)); return d; }
__device__ __forceinline__ uint32_t pack_f16_sat(float lo, float hi) { uint32_t d; asm("cvt.rn.satfinite.f16x2.f32 %0, %1, %2;" : "=r"(d) : "f"(hi), "f"(lo)); return d; }
__device__ __forceinline__ uint32_t pack_bf16(float lo, float hi) { uint32_t d; asm("cvt.rn.bf16x2.f32 %0, %1, %2;" : "=r"(d) : "f"(hi), "f"(lo)); return d; }
__device__ __forceinline__ uint32_t hadd2_bf16(uint32_t a, uint32_t b) { uint32_t d; asm("add.rn.bf16x2 %0, %1, %2;" : "=r"(d) : "r"(a), "r"(b)); return d; }
__device__ __forceinline__ uint32_t h2add(uint32_t a, uint32_t b) { uint32_t d; asm("add.rn.f16x2 %0, %1, %2;" : "=r"(d) : "r"(a), "r"(b)); return d; }
__device__ __forceinline__ uint32_t h2mul(uint32_t a, uint32_t b) { uint32_t d; asm("mul.rn.f16x2 %0, %1, %2;" : "=r"(d) : "r"(a), "r"(b)); return d; }
__device__ __forceinline__ uint32_t h2fma(uint32_t a, uint32_t b, uint32_t c) { uint32_t d; asm("fma.rn.f16x2 %0, %1, %2, %3;" : "=r"(d) : "r"(a), "r"(b), "r"(c)); return d; }
__device__ __forceinline__ uint32_t h2lo(uint32_t a) { uint32_t d; asm("{.reg .f16 l,h; mov.b32 {l,h}, %1; mov.b32 %0, {l,l};}" : "=r"(d) : "r"(a)); return d; }
__device__ __forceinline__ uint32_t h2hi(uint32_t a) { uint32_t d; asm("{.reg .f16 l,h; mov.b32 {l,h}, %1; mov.b32 %0, {h,h};}" : "=r"(d) : "r"(a)); return d; }
__device__ __forceinline__ float h_lo(uint32_t a) { float d; asm("{.reg .f16 l,h; mov.b32 {l,h}, %1; cvt.f32.f16 %0, l;}" : "=f"(d) : "r"(a)); return d; }
__device__ __forceinline__ float h_hi(uint32_t a) { float d; asm("{.reg .f16 l,h; mov.b32 {l,h}, %1; cvt.f32.f16 %0, h;}" : "=f"(d) : "r"(a)); return d; }
__device__ __forceinline__ uint32_t prmt(uint32_t a, uint32_t b, uint32_t s) { uint32_t d; asm("prmt.b32 %0, %1, %2, %3;" : "=r"(d) : "r"(a), "r"(b), "r"(s)); return d; }
__device__ __forceinline__ void mma_sp(float* d, const uint32_t* a, const uint32_t* b, const float* c, uint32_t e) {
  asm("mma.sp::ordered_metadata.sync.aligned.m16n8k32.row.col.f32.bf16.bf16.f32 {%0,%1,%2,%3}, {%4,%5,%6,%7}, {%8,%9,%10,%11}, {%12,%13,%14,%15}, %16, 0;"
      : "=f"(d[0]), "=f"(d[1]), "=f"(d[2]), "=f"(d[3])
      : "r"(a[0]), "r"(a[1]), "r"(a[2]), "r"(a[3]), "r"(b[0]), "r"(b[1]), "r"(b[2]), "r"(b[3]), "f"(c[0]), "f"(c[1]), "f"(c[2]), "f"(c[3]), "r"(e));
}
__device__ __forceinline__ uint32_t bf2_to_h2(uint32_t w, float s) { return pack_f16(bf_lo(w) * s, bf_hi(w) * s); }
__device__ __forceinline__ uint32_t bf2_to_h2(uint32_t w) { return pack_f16(bf_lo(w), bf_hi(w)); }

__device__ __forceinline__ uint32_t gelu_h2(uint32_t y) {
  uint32_t t, u, th, g;
  asm volatile("fma.rn.f16x2 %0, %1, %1, %2;" : "=r"(t) : "r"(y), "r"(GELU_A2));
  asm volatile("mul.rn.f16x2 %0, %1, %2;" : "=r"(u) : "r"(y), "r"(t));
  asm volatile("tanh.approx.f16x2 %0, %1;" : "=r"(th) : "r"(u));
  asm volatile("fma.rn.f16x2 %0, %1, %2, %1;" : "=r"(g) : "r"(y), "r"(th));
  return g;
}

__device__ __forceinline__ void convert_weights(uint32_t sb, uint32_t wbar, int rot, int warp, int lane) {
  const int l8 = lane & 7, q4 = lane >> 3;
#pragma unroll 1
  for (int u = warp; u < 36; u += 16) {
    int s = u / 6; const int i = u - s * 6;
    s += rot; if (s >= 6) s -= 6;
    mbar_wait(wbar + s * 8, 0);
    const uint32_t base = sb + W1S + s * 12288 + i * 128;
    uint32_t v[4][4];
#pragma unroll
    for (int r = 0; r < 4; r++) {
      const int kh = r & 1, c = (l8 + q4 + 4 * (r >> 1)) & 7;
      lds128(v[r], base + (4 * (l8 >> 1) + 2 * kh + (l8 & 1)) * 768 + c * 16);
    }
    __syncwarp();
#pragma unroll
    for (int r = 0; r < 4; r++) {
      const int kh = r & 1, c = (l8 + q4 + 4 * (r >> 1)) & 7;
      sts128(base + (2 * c + kh) * 768 + l8 * 16, make_uint4(bf2_to_h2(v[r][0]), bf2_to_h2(v[r][1]), bf2_to_h2(v[r][2]), bf2_to_h2(v[r][3])));
    }
  }
  const int q = lane & 3, t = (lane >> 2) & 3, b = lane >> 4;
#pragma unroll 1
  for (int u = warp ^ 15; u < 48; u += 16) {
    int s = (u >> 3) + rot; if (s >= 6) s -= 6;
    mbar_wait(wbar + 48 + s * 8, 0);
    const uint32_t base = sb + W2S + s * 12288 + (u & 7) * 1536;
    uint32_t v[4][3];
#pragma unroll
    for (int d = 0; d < 4; d++)
#pragma unroll
      for (int j = 0; j < 3; j++) v[d][j] = lds32(base + (2 * ((q + d) & 3) + b) * 192 + j * 64 + t * 16 + q * 4);
    __syncwarp();
#pragma unroll
    for (int d = 0; d < 4; d++)
#pragma unroll
      for (int j = 0; j < 3; j++) sts32(base + (4 * j + q) * 128 + (2 * ((q + d) & 3) + b) * 16 + t * 4, bf2_to_h2(v[d][j], 0.5f / GELU_C3));
  }
}

__device__ __noinline__ void ln_wide(uint32_t ad) {
  float m[2], r[2];
#pragma unroll
  for (int hi = 0; hi < 2; hi++) {
    float sm = 0.f;
    for (int s = 0; s < 6; s++) { uint2 w = lds64(ad + s * 512 + hi * 8); sm += (h_lo(w.x) + h_hi(w.x)) + (h_lo(w.y) + h_hi(w.y)); }
    sm += __shfl_xor_sync(0xffffffffu, sm, 1); sm += __shfl_xor_sync(0xffffffffu, sm, 2);
    m[hi] = sm * (1.f / 96.f);
    float q = 0.f;
    for (int s = 0; s < 6; s++) {
      uint2 w = lds64(ad + s * 512 + hi * 8);
      float d0 = h_lo(w.x) - m[hi], d1 = h_hi(w.x) - m[hi], d2 = h_lo(w.y) - m[hi], d3 = h_hi(w.y) - m[hi];
      q += (d0 * d0 + d1 * d1) + (d2 * d2 + d3 * d3);
    }
    q += __shfl_xor_sync(0xffffffffu, q, 1); q += __shfl_xor_sync(0xffffffffu, q, 2);
    r[hi] = rsqrtf(fmaf(q, 1.f / 96.f, 1e-5f)) * GELU_C3;
  }
  for (int s = 0; s < 6; s++) {
    uint32_t w[4]; lds128(w, ad + s * 512);
    sts128(ad + s * 512, make_uint4(pack_f16((h_lo(w[0]) - m[0]) * r[0], (h_hi(w[0]) - m[0]) * r[0]), pack_f16((h_lo(w[2]) - m[1]) * r[1], (h_hi(w[2]) - m[1]) * r[1]),
                                    pack_f16((h_lo(w[1]) - m[0]) * r[0], (h_hi(w[1]) - m[0]) * r[0]), pack_f16((h_lo(w[3]) - m[1]) * r[1], (h_hi(w[3]) - m[1]) * r[1])));
  }
  asm volatile("fence.proxy.async.shared::cta;" ::: "memory");
}

__device__ __forceinline__ uint32_t load_ln(uint32_t ad, uint32_t* a, uint32_t tag) {
  uint32_t raw[6][4];
#pragma unroll
  for (int s = 0; s < 6; s++) lds128(raw[s], ad + s * 512);
  const uint32_t stale = ((raw[0][0] ^ tag) | (raw[1][0] ^ tag)) | ((raw[2][0] ^ tag) | (raw[3][0] ^ tag)) | ((raw[4][0] ^ tag) | (raw[5][0] ^ tag));
  uint32_t sm[2];
#pragma unroll
  for (int hi = 0; hi < 2; hi++) {
    uint32_t s0 = h2add(raw[0][2 * hi], raw[1][2 * hi]), s1 = h2add(raw[0][2 * hi + 1], raw[1][2 * hi + 1]);
    uint32_t s2 = h2add(raw[2][2 * hi], raw[3][2 * hi]), s3 = h2add(raw[2][2 * hi + 1], raw[3][2 * hi + 1]);
    uint32_t s4 = h2add(raw[4][2 * hi], raw[5][2 * hi]), s5 = h2add(raw[4][2 * hi + 1], raw[5][2 * hi + 1]);
    sm[hi] = h2add(h2add(h2add(s0, s1), h2add(s2, s3)), h2add(s4, s5));
  }
  uint32_t s = h2add(prmt(sm[0], sm[1], 0x5410), prmt(sm[0], sm[1], 0x7632));
  s = h2add(s, __shfl_xor_sync(0xffffffffu, s, 1));
  s = h2add(s, __shfl_xor_sync(0xffffffffu, s, 2));
  const uint32_t nm = h2mul(s, 0xA155A155u);
  uint32_t qq[2];
#pragma unroll
  for (int hi = 0; hi < 2; hi++) {
    const uint32_t m = hi ? h2hi(nm) : h2lo(nm);
    uint32_t q0 = 0, q1 = 0;
#pragma unroll
    for (int k = 0; k < 6; k++) {
      uint32_t d0 = h2add(raw[k][2 * hi], m), d1 = h2add(raw[k][2 * hi + 1], m);
      raw[k][2 * hi] = d0; raw[k][2 * hi + 1] = d1;
      q0 = k ? h2fma(d0, d0, q0) : h2mul(d0, d0);
      q1 = k ? h2fma(d1, d1, q1) : h2mul(d1, d1);
    }
    qq[hi] = h2add(q0, q1);
  }
  uint32_t q = h2add(prmt(qq[0], qq[1], 0x5410), prmt(qq[0], qq[1], 0x7632));
  q = h2add(q, __shfl_xor_sync(0xffffffffu, q, 1));
  q = h2add(q, __shfl_xor_sync(0xffffffffu, q, 2));
  const float r0 = rsqrtf(fmaf(h_lo(q), 1.f / 96.f, 1e-5f)) * GELU_C3, r1 = rsqrtf(fmaf(h_hi(q), 1.f / 96.f, 1e-5f)) * GELU_C3;
  const uint32_t r = pack_f16(r0, r1);
#pragma unroll
  for (int k = 0; k < 6; k++) {
    a[4 * k] = h2mul(raw[k][0], h2lo(r)); a[4 * k + 2] = h2mul(raw[k][1], h2lo(r));
    a[4 * k + 1] = h2mul(raw[k][2], h2hi(r)); a[4 * k + 3] = h2mul(raw[k][3], h2hi(r));
  }
  return (((q & 0x7c007c00u) + 0x04000400u) & 0x80008000u) | (stale & 1);
}

__device__ __forceinline__ void gemm1(uint32_t* p, const uint32_t* a, uint64_t d1, int c) {
  wgmma_n48_f16<0>(p, a, d1 + c * (1536 >> 4));
#pragma unroll
  for (int s = 1; s < 6; s++) wgmma_n48_f16<1>(p, a + 4 * s, d1 + c * (1536 >> 4) + s * (12288 >> 4));
}

__device__ __forceinline__ void gemm1_piece(uint32_t* p, const uint32_t* a, uint64_t d1, int c, int u) {
  if (u == 0) wgmma_n48_f16<0>(p, a, d1 + c * (1536 >> 4)); else wgmma_n48_f16<1>(p, a + 8 * u, d1 + c * (1536 >> 4) + 2 * u * (12288 >> 4));
  wgmma_n48_f16<1>(p, a + 8 * u + 4, d1 + c * (1536 >> 4) + (2 * u + 1) * (12288 >> 4));
}
__device__ __forceinline__ void fetch_a(uint32_t abuf, uint32_t bar, const unsigned char* src) {
  asm volatile("{\n.reg .pred p;\nelect.sync _|p, 0xffffffff;\n"
               "@p mbarrier.arrive.expect_tx.shared::cta.b64 _, [%1], 3072;\n"
               "@p cp.async.bulk.shared::cluster.global.mbarrier::complete_tx::bytes [%0], [%2], 3072, [%1];\n}"
               ::"r"(abuf), "r"(bar), "l"(src) : "memory");
}
__device__ __forceinline__ void fetch_x(uint32_t xbuf, uint32_t bar, const CUtensorMap* tm, uint32_t c0, uint32_t c12, uint64_t pol) {
  asm volatile("{\n.reg .pred p;\nelect.sync _|p, 0xffffffff;\n"
               "@p mbarrier.arrive.expect_tx.shared::cta.b64 _, [%1], 3072;\n"
               "@p cp.async.bulk.tensor.3d.shared::cluster.global.mbarrier::complete_tx::bytes.L2::cache_hint [%0], [%2, {%3, %4, %5}], [%1], %6;\n}"
               ::"r"(xbuf), "r"(bar), "l"(tm), "r"(c0), "r"(c12 & 255), "r"(c12 >> 8), "l"(pol) : "memory");
}
__device__ __forceinline__ void wait_ready(const uint32_t* p, uint32_t target) {
  int spins = 0;
  while (ld_relaxed(p) != target) { __nanosleep(32); if (++spins > SPIN_LIMIT) __trap(); }
}
__device__ __forceinline__ uint32_t slot_tag(int gm, int j, uint32_t epoch) {
  const int len = min(PLEN, 1024 - gm * PLEN), writes = (len - (j & (RING - 1)) + RING - 1) / RING;
  return (epoch * writes + j / RING + 1) & 1;
}

__device__ __forceinline__ void mlp_role(uint32_t sb, Globals* gs, int id, const CUtensorMap* tmr, const __nv_bfloat16* __restrict__ w1, const __nv_bfloat16* __restrict__ w2,
                                         __nv_bfloat16* __restrict__ out, int idx, bool tabled, int warp, int lane) {
  const int wg = warp >> 2, w = warp & 3, g = lane >> 2, t = lane & 3;
  const uint32_t abuf = sb + ABUF + warp * 3072, xbuf = sb + XBUF + (warp & 7) * 3072;
  const uint32_t bar = sb + MISC + warp * 8, obar = sb + MISC + (warp ^ 8) * 8;
  const uint32_t tl = sb + MISC + 512, wbar = sb + MISC + 2560;
  const int rot = idx % 6;
  if (warp < 12) {
    const int m = warp >= 6; int s = warp - 6 * m + rot; if (s >= 6) s -= 6;
    asm volatile("{\n.reg .pred p;\nelect.sync _|p, 0xffffffff;\n@p mbarrier.init.shared::cta.b64 [%1], 1;\n@p fence.mbarrier_init.release.cluster;\n"
                 "@p mbarrier.arrive.expect_tx.shared::cta.b64 _, [%1], 12288;\n"
                 "@p cp.async.bulk.shared::cluster.global.mbarrier::complete_tx::bytes [%0], [%2], 12288, [%1];\n}"
                 ::"r"(sb + (6 * m + s) * 12288), "r"(wbar + (6 * m + s) * 8), "l"((const char*)(m ? w2 : w1) + s * 12288) : "memory");
  }
  mbar_init_elect(bar, 1); mbar_init_elect(bar + 128, 1);
  asm volatile("fence.mbarrier_init.release.cluster;" ::: "memory");
  __syncthreads();
  if (warp == 8) {
    const uint32_t epoch = next_epoch(gs, id);
    sts32(sb + MISC + 256, epoch + 1);
#pragma unroll 1
    for (int k = lane; k < (tabled ? 64 : 128); k += 32) {
      int n = -1;
      if (tabled) { if (k < 48) n = (int16_t)g_sched[idx][k]; }
      else {
        const int i = k * (gridDim.x - NCONV) + idx, full = (1024 - (NG - 1) * PLEN) * NG;
        const int r = i >> 2, j = r < full ? r / NG : (r - full) / (NG - 1) + full / NG, gm = r < full ? r % NG : (r - full) % (NG - 1);
        if (i < 4096) n = (gm * PLEN + j) * 4 + (i & 3);
      }
      const int P = n >> 2, gm = P / PLEN, j = P - gm * PLEN;
      sts128(tl + k * 16, make_uint4(P, (((j & (RING - 1)) * NG + gm) * 4 + (n & 3)) * TILEB + slot_tag(gm, j, epoch),
                                     (n & 2) * 384, ((n >> 10) * 8 + (n & 1) * 4) | ((n & 1020) << 7)));
    }
  }
  convert_weights(sb, wbar, rot, warp, lane);
  asm volatile("fence.proxy.async.shared::cta;" ::: "memory");
  __syncthreads();
  PROF_AT(threadIdx.x == 0, 1); PROF_VAL(threadIdx.x == 0, 8, clock64());
  const uint32_t rtarget = 3 * lds32(sb + MISC + 256);
  const uint64_t d1 = ((uint64_t)(768 >> 4) << 16) | ((uint64_t)(128 >> 4) << 32) | (uint64_t)(((sb + W1S) >> 4) & 0x3fff);
  const uint64_t d2 = ((uint64_t)(12288 >> 4) << 16) | ((uint64_t)(128 >> 4) << 32) | (uint64_t)(((sb + W2S) >> 4) & 0x3fff);
  const uint32_t ad = abuf + t * 128 + ((g ^ (2 * t)) << 4);
  const uint32_t xd = xbuf + g * 192 + t * 16;
  const int mybar = 1 + wg, nxtbar = 1 + ((wg + 1) & 3);
  const uint64_t pol = pol_evict_first();
  const unsigned char* const asrc = gs->scratch + w * 3072;
  uint32_t pha = 0, phx = 0, tp = tl + wg * 16;
  bool pending = true;
  uint32_t cur[4];
  lds128(cur, tp);
  while ((int)cur[0] >= 0) {
    PROF2_AT((threadIdx.x & 127) == 0, 16 + (tp - tl) / 4); PROF2_VAL((threadIdx.x & 127) == 0, 16 + (tp - tl) / 4 + 3, pending);
    uint32_t a[24], p[8][12], gg[8][12], acc[24];
    if (pending) {
      wait_ready(&gs->ready[cur[0]], rtarget);
      fetch_a(abuf, bar, asrc + (cur[1] & ~1u));
      if (tp < tl + 32) fetch_x(xbuf, bar + 128, tmr, cur[2] + w * 192, cur[3], pol);
    }
    const uint2 n4 = lds64(tp + 64);
    const int sig = lds32(tp + 16);
    for (int tries = 0;; tries++) {
      mbar_wait(bar, pha); pha ^= 1;
      PROF2_AT((threadIdx.x & 127) == 0, 16 + (tp - tl) / 4 + 1);
      const uint32_t st = load_ln(ad, a, cur[1]);
      if (!__any_sync(0xffffffffu, st != 0)) break;
      if (!__any_sync(0xffffffffu, st & 1)) {
        ln_wide(ad);
#pragma unroll
        for (int k = 0; k < 6; k++) lds128(a + 4 * k, ad + k * 512);
        break;
      }
      if (tries > SPIN_LIMIT) __trap();
      fetch_a(abuf, bar, asrc + (cur[1] & ~1u));
    }
    red_add_elect(&gs->cons[cur[0]]);
    if (tp != tl) asm volatile("bar.sync %0, 256;" ::"r"(mybar) : "memory");
    PROF2_AT((threadIdx.x & 127) == 0, 16 + (tp - tl) / 4 + 2);
    uint32_t rdy = 0;
    wg_fence();
    gemm1(p[0], a, d1, 0); wg_commit();
    gemm1_piece(p[1], a, d1, 1, 0); wg_commit();
#pragma unroll
    for (int j = 0; j < 24; j++) {
      const int c = j / 3, s = j % 3;
      if (j == JB1) {
        rdy = ld_relaxed(&gs->ready[n4.x & 1023]);
        wg_wait<0>();
        mbar_wait(bar + 128, phx); phx ^= 1;
      } else if (j == JB2) {
        wg_wait<0>();
        pending = rdy != rtarget;
        if (!pending && (int)n4.x >= 0) fetch_a(abuf, bar, asrc + (n4.y & ~1u));
      } else wg_wait<1>();
      if (j == TRIG) asm volatile("{.reg .pred p; setp.ge.s32 p, %1, 0; @p bar.arrive %0, 256;}" ::"r"(nxtbar), "r"(sig) : "memory");
#pragma unroll
      for (int i = 0; i < 4; i++) gg[c][4 * s + i] = gelu_h2(p[c][4 * s + i]);
      wg_fence();
      if (j == 0) wgmma_n96_f16<0>(acc, gg[c], d2); else wgmma_n96_f16<1>(acc, &gg[c][4 * s], d2 + (16 * s + c) * (1536 >> 4));
      if (j < 20) gemm1_piece(p[(j + 1) / 3 + 1], a, d1, (j + 1) / 3 + 1, (j + 1) % 3);
      wg_commit();
    }
    wg_wait<0>();
    if (JB2 == 24) {
      pending = rdy != rtarget;
      if (!pending && (int)n4.x >= 0) fetch_a(abuf, bar, asrc + (n4.y & ~1u));
    }
    char* const op = (char*)out + (size_t)(cur[3] >> 8) * (512 * 192) + ((cur[3] & 255) + (g >> 1)) * 3072 + cur[2] * 2 + (2 * w + (g & 1)) * 192 + t * 16;
    uint32_t n2[4];
    lds128(n2, tp + 32);
    tp += 64;
    lds128(cur, tp);
#pragma unroll
    for (int hi = 0; hi < 2; hi++)
#pragma unroll
      for (int j = 0; j < 3; j++) {
        uint32_t xr[4];
        lds128(xr, xd + hi * 1536 + j * 64);
        uint4 o;
        o.x = hadd2_bf16(xr[0], pack_bf16(h_lo(acc[8 * j + hi]), h_hi(acc[8 * j + hi])));
        o.y = hadd2_bf16(xr[1], pack_bf16(h_lo(acc[8 * j + 2 + hi]), h_hi(acc[8 * j + 2 + hi])));
        o.z = hadd2_bf16(xr[2], pack_bf16(h_lo(acc[8 * j + 4 + hi]), h_hi(acc[8 * j + 4 + hi])));
        o.w = hadd2_bf16(xr[3], pack_bf16(h_lo(acc[8 * j + 6 + hi]), h_hi(acc[8 * j + 6 + hi])));
        stg128_stream(op + hi * (512 * 192) + j * 64, o, pol);
      }
    __syncwarp();
    if ((int)n2[0] >= 0) fetch_x(xbuf, obar + 128, tmr, n2[2] + w * 192, n2[3], pol);
  }
  PROF_AT((threadIdx.x & 127) == 0, 4 + wg); PROF_VAL(threadIdx.x == 0, 9, clock64());
}

__device__ __forceinline__ void conv_compute(uint32_t sb, Globals* gs, const __nv_bfloat16* __restrict__ dw, int third, int nit, int warp, int lane) {
  const int g = lane >> 2, t = lane & 3;
  const uint32_t full = sb + MISC;
  uint32_t A[4][4][4];
  {
    uint2 w[2][9];
#pragma unroll
    for (int h = 0; h < 2; h++) {
      const int j = (4 * h + t - g) & 7;
      const uint2* src = (const uint2*)(dw + min(j, 6) * 96 + third * 32 + warp * 4);
      w[h][0] = make_uint2(0u, 0u); w[h][8] = make_uint2(0u, 0u);
#pragma unroll
      for (int i = 0; i < 7; i++) asm volatile("ld.global.nc.v2.b32 {%0,%1}, [%2];" : "=r"(w[h][i + 1].x), "=r"(w[h][i + 1].y) : "l"(src + i * 168) : "memory");
    }
    asm volatile("setmaxnreg.inc.sync.aligned.u32 224;");
    PROF_AT(threadIdx.x == 0, 11);
#pragma unroll
    for (int h = 0; h < 2; h++)
      if (((4 * h + t - g) & 7) == 7) {
#pragma unroll
        for (int i = 1; i < 8; i++) w[h][i] = make_uint2(0u, 0u);
      }
#pragma unroll
    for (int u = 0; u < 4; u++)
#pragma unroll
      for (int r = 0; r < 4; r++) {
        const int h = r >> 1, i0 = 2 * u - (r & 1) + 1;
        A[0][u][r] = prmt(w[h][i0].x, w[h][i0 + 1].x, 0x5410); A[1][u][r] = prmt(w[h][i0].x, w[h][i0 + 1].x, 0x7632);
        A[2][u][r] = prmt(w[h][i0].y, w[h][i0 + 1].y, 0x5410); A[3][u][r] = prmt(w[h][i0].y, w[h][i0 + 1].y, 0x7632);
      }
  }
  uint32_t meta = 0;
#pragma unroll
  for (int a = 0; a < 4; a++) meta |= ((4 * (t & 1) + a + 1 >= g) ? 0x80008u : 0xD000Du) << (4 * a);
  meta = __shfl_sync(0xffffffffu, meta, lane);
  float S[2][4][3][4];
#pragma unroll
  for (int s = 0; s < 2; s++)
#pragma unroll
    for (int c = 0; c < 4; c++)
#pragma unroll
      for (int i = 0; i < 3; i++)
#pragma unroll
        for (int k = 0; k < 4; k++) S[s][c][i][k] = 0.f;
  uint32_t aq[4];
#pragma unroll
  for (int q = 0; q < 4; q++) {
    const int pp = (g & 1) * 140 + (t & 1) * 70 + 16 * (g >> 1) + 2 * q + (t >> 1);
    aq[q] = __shfl_sync(0xffffffffu, sb + pp * 64 + (((warp >> 1) ^ ((pp >> 1) & 3)) << 4) + (warp & 1) * 8, lane);
  }
  const int Q = third * 8 + warp;
  unsigned char* const obase = gs->scratch + (g >> 1) * 3072 + Q * 128 + (((2 * t + (g & 1)) ^ (2 * (Q & 3))) << 4);
  const float zero4[4] = {0.f, 0.f, 0.f, 0.f};
  uint32_t sofs = 0, bar = full, ph = 0;
  uint2 X[3][4];
  PROF_AT(threadIdx.x == 0, 12);
  asm volatile("bar.sync 0, 512;" ::: "memory");
  PROF_AT(threadIdx.x == 0, 10);
  mbar_wait(bar, 0);
  PROF_AT(threadIdx.x == 0, 1); PROF_VAL(threadIdx.x == 0, 8, clock64());
#pragma unroll
  for (int j = 0; j < 2; j++)
#pragma unroll
    for (int q = 0; q < 4; q++) X[j][q] = lds64(aq[q] + j * 512);
  for (uint32_t ot = sb + CTAB; ot < sb + CTAB + nit * 16; ot += 16) {
    PROF_AT(threadIdx.x == 0 && ((ot - sb - CTAB) & 112) == 0, 16 + ((ot - sb - CTAB) >> 4));
    const uint2 oe = lds64(ot);
    unsigned char* const o = obase + oe.x;
    const uint32_t dbar = bar + 64 + ph * 64;
#pragma unroll
    for (int s = 0; s < 2; s++) {
      uint32_t B[4][4];
      if (s == 1) {
        sofs += SLOTB; bar += 8;
        if (sofs == NSLOT * SLOTB) { sofs = 0; bar = full; ph ^= 1; }
        mbar_wait(bar, ph);
      }
#pragma unroll
      for (int c = 0; c < 4; c++)
#pragma unroll
        for (int q = 0; q < 4; q++) B[c][q] = prmt(c < 2 ? X[s][q].x : X[s][q].y, c < 2 ? X[s + 1][q].x : X[s + 1][q].y, (c & 1) ? 0x7632 : 0x5410);
      if (s == 0) {
#pragma unroll
        for (int q = 0; q < 4; q++) X[2][q] = lds64(aq[q] + sofs + 2 * 512);
      } else {
#pragma unroll
        for (int j = 0; j < 2; j++)
#pragma unroll
          for (int q = 0; q < 4; q++) X[j][q] = lds64(aq[q] + sofs + j * 512);
      }
      float T[4][4];
#pragma unroll
      for (int c = 0; c < 4; c++) mma_sp(T[c], A[c][3], B[c], S[s][c][2], meta);
#pragma unroll
      for (int c = 0; c < 4; c++) mma_sp(S[s][c][2], A[c][2], B[c], S[s][c][1], meta);
      stg128(o + (2 * s) * TILEB, make_uint4((pack_f16_sat(T[0][0], T[1][0]) & ~1u) | oe.y, pack_f16_sat(T[2][0], T[3][0]), pack_f16_sat(T[0][2], T[1][2]), pack_f16_sat(T[2][2], T[3][2])));
      stg128(o + (2 * s + 1) * TILEB, make_uint4((pack_f16_sat(T[0][1], T[1][1]) & ~1u) | oe.y, pack_f16_sat(T[2][1], T[3][1]), pack_f16_sat(T[0][3], T[1][3]), pack_f16_sat(T[2][3], T[3][3])));
#pragma unroll
      for (int c = 0; c < 4; c++) mma_sp(S[s][c][1], A[c][1], B[c], S[s][c][0], meta);
#pragma unroll
      for (int c = 0; c < 4; c++) mma_sp(S[s][c][0], A[c][0], B[c], zero4, meta);
    }
    mbar_arrive_elect(dbar);
  }
  PROF_AT(threadIdx.x == 0, 4); PROF_VAL(threadIdx.x == 0, 9, clock64());
}

__device__ __forceinline__ void conv_loader(uint32_t sb, const CUtensorMap* tmx, int Vs, int nit, int third) {
  const uint32_t full = sb + MISC;
#pragma unroll
  for (int s = 0; s < NSLOT; s++) mbar_init_elect(full + s * 8, 2);
  asm volatile("fence.mbarrier_init.release.cluster;" ::: "memory");
  int col = (Vs - 1) / 258, row = 2 * (Vs - col * 258) - 3;
  col = col * 128 - 3;
#pragma unroll 1
  for (int it = 0; it <= nit; it++) {
    const int s = it & (NSLOT - 1);
    if (it >= AHEAD) {
      if (it == AHEAD) asm volatile("bar.sync 0, 512;" ::: "memory");
      mbar_wait(full + 64 + ((it - AHEAD) & 15) * 8, ((it - AHEAD) >> 4) & 1);
    }
    asm volatile("{\n.reg .pred p;\n.reg .s32 c2;\n.reg .u32 d2;\nelect.sync _|p, 0xffffffff;\nadd.s32 c2, %4, 64;\nadd.u32 d2, %0, 8960;\n"
                 "@p mbarrier.arrive.expect_tx.shared::cta.b64 _, [%2], 17920;\n"
                 "@p cp.async.bulk.tensor.3d.shared::cluster.global.mbarrier::complete_tx::bytes [%0], [%1, {%3, %4, %5}], [%2];\n"
                 "@p cp.async.bulk.tensor.3d.shared::cluster.global.mbarrier::complete_tx::bytes [d2], [%1, {%3, c2, %5}], [%2];\n}"
                 ::"r"(sb + s * SLOTB), "l"(tmx), "r"(full + s * 8), "r"(third * 32), "r"(col), "r"(row) : "memory");
    row += 2;
    if (row == 515) { row = -1; col += 128; }
  }
}

__device__ __forceinline__ void conv_credit(uint32_t sb, Globals* gs, int P0, int nit, int lane) {
  const uint32_t full = sb + MISC;
  asm volatile("bar.sync 0, 512;" ::: "memory");
  const uint32_t ctarget = 16 * lds32(full + 196);
  int credit = P0 + RING;
#pragma unroll 1
  for (int it = 0; it <= nit; it++) {
    if (it >= NSLOT) {
      const int P = (int)lds32(sb + CTAB + it * 16 + 8);
      mbar_wait(full + 64 + ((it - NSLOT) & 15) * 8, ((it - NSLOT) >> 4) & 1);
      int spins = 0;
      while ((int)lds32(full + 192) < it - 15) { __nanosleep(64); if (++spins > SPIN_LIMIT) __trap(); }
      while (P >= credit) {
        const uint32_t ok = __ballot_sync(0xffffffffu, ld_relaxed(&gs->cons[credit - RING + lane]) == ctarget);
        const int got = __ffs(~ok) - 1;
        credit += got < 0 ? 32 : got;
        if (P >= credit) { __nanosleep(200); if (++spins > SPIN_LIMIT) __trap(); }
      }
    }
    mbar_arrive_elect(full + (it & (NSLOT - 1)) * 8);
  }
}

__device__ __forceinline__ void conv_publisher(uint32_t sb, Globals* gs, int nit) {
#pragma unroll 1
  for (int it = 0; it < nit; it++) {
    const int P = (int)lds32(sb + CTAB + it * 16 + 8);
    mbar_wait(sb + MISC + 64 + (it & 15) * 8, (it >> 4) & 1);
    sts32(sb + MISC + 192, it + 1);
    if (P >= 0) { red_add_elect(&gs->ready[P]); PROF_AT((threadIdx.x & 31) == 0 && ((it & 7) == 0 || it < 8), 200 + it); }
  }
}

__global__ void __launch_bounds__(512, 1) convnext_kernel(const __grid_constant__ CUtensorMap tmx, const __grid_constant__ CUtensorMap tmr, const __nv_bfloat16* __restrict__ dw,
                                                          const __nv_bfloat16* __restrict__ w1, const __nv_bfloat16* __restrict__ w2, __nv_bfloat16* __restrict__ out, Globals* gs) {
  extern __shared__ __align__(1024) unsigned char smem[];
  const uint32_t sb = smem_u32(smem);
  const int warp = __shfl_sync(0xffffffffu, threadIdx.x >> 5, 0), lane = threadIdx.x & 31;
  PROF_AT(threadIdx.x == 0, 0);
  uint32_t smid, nsmid;
  asm volatile("mov.u32 %0, %%smid;" : "=r"(smid));
  asm volatile("mov.u32 %0, %%nsmid;" : "=r"(nsmid));
  const bool tabled = TABLED && NG == 9 && gridDim.x == 132 && nsmid == 132;
  const int id = tabled ? smid : blockIdx.x;
  int cidx, idx;
  bool is_conv;
  if (tabled) {
    idx = smid;
    is_conv = (smid < 48 && !(smid & 1)) || smid == 60 || smid == 120 || smid == 122;
    cidx = smid < 48 ? ((smid >> 1) & 7) * 3 + (smid >> 4) : smid == 60 ? 26 : 24 + ((smid >> 1) & 1);
  } else {
    cidx = (blockIdx.x * NCONV) / gridDim.x;
    is_conv = ((blockIdx.x + 1) * NCONV) / gridDim.x != cidx;
    idx = blockIdx.x - cidx;
  }
  PROF_VAL(threadIdx.x == 0, 2, is_conv ? 1000 + cidx : idx);
  if (!is_conv) {
    mlp_role(sb, gs, id, &tmr, w1, w2, out, idx, tabled, warp, lane);
  } else {
    const int gm = cidx / 3, third = cidx - gm * 3;
    const int P0 = gm * PLEN, P1 = min(P0 + PLEN, 1024) - 1;
    const int Vs = P0 + 2 * (P0 >> 8) + ((P0 & 255) ? 0 : 1);
    const int nit = P1 + 2 * (P1 >> 8) + 4 - Vs;
    if (warp < 8) {
      conv_compute(sb, gs, dw, third, nit, warp, lane);
    } else if (warp >= 12) {
      asm volatile("setmaxnreg.dec.sync.aligned.u32 24;");
      const uint32_t epoch = ld_relaxed(&gs->epoch[id]);
#pragma unroll 1
      for (int it = threadIdx.x - 384; it <= nit; it += 128) {
        const int V = Vs + it, so = max(V - 3, 0) / 258, po = V - 3 - so * 258, P = so * 256 + po;
        const bool ok = po < 256 && P >= P0 && P <= P1;
        sts128(sb + CTAB + it * 16, make_uint4((ok ? ((P - P0) & (RING - 1)) * NG + gm : RING * NG) * (4 * TILEB), slot_tag(gm, max(P - P0, 0), epoch), ok ? P : -1, 0));
      }
      if (threadIdx.x == 384) sts32(sb + MISC + 196, epoch + 1);
      asm volatile("bar.sync 0, 512;" ::: "memory");
      if (threadIdx.x == 384) gs->epoch[id] = epoch + 1;
    } else {
      asm volatile("setmaxnreg.dec.sync.aligned.u32 40;");
      if (warp == 8) conv_loader(sb, &tmx, Vs, nit, third);
      else if (warp == 9) conv_credit(sb, gs, P0, nit, lane);
      else {
#pragma unroll
        for (int s = 0; s < 8; s++) mbar_init_elect(sb + MISC + (warp - 9) * 64 + s * 8, 8);
        sts32(sb + MISC + 192, 0);
        asm volatile("bar.sync 0, 512;" ::: "memory");
        if (warp == 10) conv_publisher(sb, gs, nit);
      }
    }
  }
}

typedef CUresult (*PFN_encodeTiled)(CUtensorMap*, CUtensorMapDataType, cuuint32_t, void*, const cuuint64_t*, const cuuint64_t*, const cuuint32_t*, const cuuint32_t*,
                                    CUtensorMapInterleave, CUtensorMapSwizzle, CUtensorMapL2promotion, CUtensorMapFloatOOBfill);

extern "C" void kernel_launch(void* const* d_in, const int* in_sizes, int n_in, void* d_out, int out_size) {
  const __nv_bfloat16* x = (const __nv_bfloat16*)d_in[0];
  const __nv_bfloat16* dw = (const __nv_bfloat16*)d_in[1];
  const __nv_bfloat16* w1 = (const __nv_bfloat16*)d_in[2];
  const __nv_bfloat16* w2 = (const __nv_bfloat16*)d_in[3];
  static PFN_encodeTiled encode = nullptr;
  static int nsm = 0;
  static Globals* gs = nullptr;
  if (!encode) {
    void* fn = nullptr; cudaDriverEntryPointQueryResult qr;
    cudaGetDriverEntryPoint("cuTensorMapEncodeTiled", &fn, cudaEnableDefault, &qr);
    encode = (PFN_encodeTiled)fn;
    cudaGetSymbolAddress((void**)&gs, g_state);
    int dev = 0; cudaGetDevice(&dev);
    cudaDeviceGetAttribute(&nsm, cudaDevAttrMultiProcessorCount, dev);
    cudaFuncSetAttribute(convnext_kernel, cudaFuncAttributeMaxDynamicSharedMemorySize, SMEM_BYTES);
  }
  CUtensorMap tm;
  cuuint64_t dims[3] = {96, 512, 512}, strides[2] = {192, 192 * 512};
  cuuint32_t box[3] = {32, 70, 2}, es[3] = {1, 1, 1};
  encode(&tm, CU_TENSOR_MAP_DATA_TYPE_BFLOAT16, 3, (void*)x, dims, strides, box, es, CU_TENSOR_MAP_INTERLEAVE_NONE, CU_TENSOR_MAP_SWIZZLE_64B,
         PROMO, CU_TENSOR_MAP_FLOAT_OOB_FILL_NONE);
  CUtensorMap tr;
  cuuint64_t dims2[3] = {1536, 32, 512}, strides2[2] = {3072, 192 * 512};
  cuuint32_t box2[3] = {192, 4, 2};
  encode(&tr, CU_TENSOR_MAP_DATA_TYPE_BFLOAT16, 3, (void*)x, dims2, strides2, box2, es, CU_TENSOR_MAP_INTERLEAVE_NONE, CU_TENSOR_MAP_SWIZZLE_NONE,
         CU_TENSOR_MAP_L2_PROMOTION_NONE, CU_TENSOR_MAP_FLOAT_OOB_FILL_NONE);
  convnext_kernel<<<nsm, 512, SMEM_BYTES>>>(tm, tr, dw, w1, w2, (__nv_bfloat16*)d_out, gs);
}
```

```cpp
#include <cuda_runtime.h>
#include <cuda_bf16.h>
#include <cuda.h>
#include <stdint.h>
#include <stddef.h>

template<int SCALE_D> __device__ __forceinline__ void wgmma_n48_f16(uint32_t* d, const uint32_t* a, uint64_t desc) {
  if (SCALE_D == 0) asm volatile("wgmma.mma_async.sync.aligned.m64n48k16.f16.f16.f16 {%0,%1,%2,%3,%4,%5,%6,%7,%8,%9,%10,%11}, {%12,%13,%14,%15}, %16, 0, 1, 1, 1;"
    : "=r"(d[0]),"=r"(d[1]),"=r"(d[2]),"=r"(d[3]),"=r"(d[4]),"=r"(d[5]),"=r"(d[6]),"=r"(d[7]),"=r"(d[8]),"=r"(d[9]),"=r"(d[10]),"=r"(d[11])
    : "r"(a[0]),"r"(a[1]),"r"(a[2]),"r"(a[3]),"l"(desc));
  if (SCALE_D == 1) asm volatile("wgmma.mma_async.sync.aligned.m64n48k16.f16.f16.f16 {%0,%1,%2,%3,%4,%5,%6,%7,%8,%9,%10,%11}, {%12,%13,%14,%15}, %16, 1, 1, 1, 1;"
    : "+r"(d[0]),"+r"(d[1]),"+r"(d[2]),"+r"(d[3]),"+r"(d[4]),"+r"(d[5]),"+r"(d[6]),"+r"(d[7]),"+r"(d[8]),"+r"(d[9]),"+r"(d[10]),"+r"(d[11])
    : "r"(a[0]),"r"(a[1]),"r"(a[2]),"r"(a[3]),"l"(desc));
}

template<int SCALE_D> __device__ __forceinline__ void wgmma_n96_f16(uint32_t* d, const uint32_t* a, uint64_t desc) {
  if (SCALE_D == 0) asm volatile("wgmma.mma_async.sync.aligned.m64n96k16.f16.f16.f16 {%0,%1,%2,%3,%4,%5,%6,%7,%8,%9,%10,%11,%12,%13,%14,%15,%16,%17,%18,%19,%20,%21,%22,%23}, {%24,%25,%26,%27}, %28, 0, 1, 1, 1;"
    : "=r"(d[0]),"=r"(d[1]),"=r"(d[2]),"=r"(d[3]),"=r"(d[4]),"=r"(d[5]),"=r"(d[6]),"=r"(d[7]),"=r"(d[8]),"=r"(d[9]),"=r"(d[10]),"=r"(d[11]),"=r"(d[12]),"=r"(d[13]),"=r"(d[14]),"=r"(d[15]),"=r"(d[16]),"=r"(d[17]),"=r"(d[18]),"=r"(d[19]),"=r"(d[20]),"=r"(d[21]),"=r"(d[22]),"=r"(d[23])
    : "r"(a[0]),"r"(a[1]),"r"(a[2]),"r"(a[3]),"l"(desc));
  if (SCALE_D == 1) asm volatile("wgmma.mma_async.sync.aligned.m64n96k16.f16.f16.f16 {%0,%1,%2,%3,%4,%5,%6,%7,%8,%9,%10,%11,%12,%13,%14,%15,%16,%17,%18,%19,%20,%21,%22,%23}, {%24,%25,%26,%27}, %28, 1, 1, 1, 1;"
    : "+r"(d[0]),"+r"(d[1]),"+r"(d[2]),"+r"(d[3]),"+r"(d[4]),"+r"(d[5]),"+r"(d[6]),"+r"(d[7]),"+r"(d[8]),"+r"(d[9]),"+r"(d[10]),"+r"(d[11]),"+r"(d[12]),"+r"(d[13]),"+r"(d[14]),"+r"(d[15]),"+r"(d[16]),"+r"(d[17]),"+r"(d[18]),"+r"(d[19]),"+r"(d[20]),"+r"(d[21]),"+r"(d[22]),"+r"(d[23])
    : "r"(a[0]),"r"(a[1]),"r"(a[2]),"r"(a[3]),"l"(desc));
}

#define SCHED_NG 10
__device__ const uint16_t g_sched[132][48] = {
{372,379,393,406,65535,65535,65535,65535,65535,65535,65535,65535,65535,65535,65535,65535,65535,65535,65535,65535,65535,65535,65535,65535,65535,65535,65535,65535,65535,65535,65535,65535,65535,65535,65535,65535,65535,65535,65535,65535,65535,65535,65535,65535,65535,65535,65535,65535},
{0,11,19,28,37,47,57,67,78,88,98,109,119,129,139,150,160,170,180,191,201,211,221,232,242,252,262,273,283,293,303,314,324,334,344,355,365,378,392,405,65535,65535,65535,65535,65535,65535,65535,65535},
{782,793,3275,3700,65535,65535,65535,65535,65535,65535,65535,65535,65535,65535,65535,65535,65535,65535,65535,65535,65535,65535,65535,65535,65535,65535,65535,65535,65535,65535,65535,65535,65535,65535,65535,65535,65535,65535,65535,65535,65535,65535,65535,65535,65535,65535,65535,65535},
{412,422,432,443,453,464,474,484,494,505,515,525,535,546,556,566,577,587,597,607,618,628,638,648,659,669,679,689,700,710,720,730,741,751,761,771,784,797,810,65535,65535,65535,65535,65535,65535,65535,65535,65535},
{1200,1212,1222,65535,65535,65535,65535,65535,65535,65535,65535,65535,65535,65535,65535,65535,65535,65535,65535,65535,65535,65535,65535,65535,65535,65535,65535,65535,65535,65535,65535,65535,65535,65535,65535,65535,65535,65535,65535,65535,65535,65535,65535,65535,65535,65535,65535,65535},
{824,834,844,855,865,876,886,896,907,917,927,937,948,958,968,978,989,999,1009,1019,1030,1040,1050,1060,1071,1081,1091,1101,1112,1122,1132,1143,1153,1163,1173,1184,1194,1208,2871,65535,65535,65535,65535,65535,65535,65535,65535,65535},
{1606,1617,1628,1641,65535,65535,65535,65535,65535,65535,65535,65535,65535,65535,65535,65535,65535,65535,65535,65535,65535,65535,65535,65535,65535,65535,65535,65535,65535,65535,65535,65535,65535,65535,65535,65535,65535,65535,65535,65535,65535,65535,65535,65535,65535,65535,65535,65535},
{1236,1246,1257,1267,1278,1288,1298,1309,1319,1329,1339,1349,1360,1370,1380,1390,1401,1411,1421,1432,1442,1452,1462,1473,1483,1493,1503,1514,1524,1534,1544,1555,1565,1575,1586,1596,1608,1622,1634,65535,65535,65535,65535,65535,65535,65535,65535,65535},
{2024,2037,2046,65535,65535,65535,65535,65535,65535,65535,65535,65535,65535,65535,65535,65535,65535,65535,65535,65535,65535,65535,65535,65535,65535,65535,65535,65535,65535,65535,65535,65535,65535,65535,65535,65535,65535,65535,65535,65535,65535,65535,65535,65535,65535,65535,65535,65535},
{1648,1658,1669,1679,1690,1700,1710,1721,1731,1741,1751,1762,1772,1782,1792,1803,1813,1823,1834,1844,1854,1864,1875,1885,1895,1905,1916,1926,1936,1946,1957,1967,1977,1987,1998,2008,2018,2033,3695,65535,65535,65535,65535,65535,65535,65535,65535,65535},
{2430,2440,3687,2466,65535,65535,65535,65535,65535,65535,65535,65535,65535,65535,65535,65535,65535,65535,65535,65535,65535,65535,65535,65535,65535,65535,65535,65535,65535,65535,65535,65535,65535,65535,65535,65535,65535,65535,65535,65535,65535,65535,65535,65535,65535,65535,65535,65535},
{2060,2070,2081,2092,2102,2112,2123,2133,2143,2153,2164,2174,2184,2194,2205,2215,2225,2235,2246,2256,2266,2276,2287,2297,2307,2317,2328,2338,2348,2358,2369,2379,2389,2400,2410,2420,2433,2446,2459,65535,65535,65535,65535,65535,65535,65535,65535,65535},
{2843,2853,3690,3703,65535,65535,65535,65535,65535,65535,65535,65535,65535,65535,65535,65535,65535,65535,65535,65535,65535,65535,65535,65535,65535,65535,65535,65535,65535,65535,65535,65535,65535,65535,65535,65535,65535,65535,65535,65535,65535,65535,65535,65535,65535,65535,65535,65535},
{2472,2483,3317,3327,3337,2524,3358,3368,3378,2565,3399,3409,3419,2606,3440,3450,3460,2647,3481,3491,3501,3512,3522,3532,3542,3553,3563,3573,2760,3594,3604,3614,2801,3635,3645,3655,2845,3681,2872,65535,65535,65535,65535,65535,65535,65535,65535,65535},
{3261,4074,3283,65535,65535,65535,65535,65535,65535,65535,65535,65535,65535,65535,65535,65535,65535,65535,65535,65535,65535,65535,65535,65535,65535,65535,65535,65535,65535,65535,65535,65535,65535,65535,65535,65535,65535,65535,65535,65535,65535,65535,65535,65535,65535,65535,65535,65535},
{2884,3718,2905,2915,3747,2935,3766,2956,2966,3795,2987,2997,3824,3834,3028,3038,3048,3059,3882,3079,3089,3911,3110,3120,3940,3950,3959,3969,3171,3182,3998,3202,4017,4027,3233,3243,3256,3269,4085,65535,65535,65535,65535,65535,65535,65535,65535,65535},
{373,380,394,407,65535,65535,65535,65535,65535,65535,65535,65535,65535,65535,65535,65535,65535,65535,65535,65535,65535,65535,65535,65535,65535,65535,65535,65535,65535,65535,65535,65535,65535,65535,65535,65535,65535,65535,65535,65535,65535,65535,65535,65535,65535,65535,65535,65535},
{1,2894,2490,29,38,48,58,68,79,89,99,110,120,130,140,151,161,171,181,192,202,212,222,233,243,253,263,274,284,294,304,315,325,335,345,356,366,382,396,409,65535,65535,65535,65535,65535,65535,65535,65535},
{783,2852,805,818,65535,65535,65535,65535,65535,65535,65535,65535,65535,65535,65535,65535,65535,65535,65535,65535,65535,65535,65535,65535,65535,65535,65535,65535,65535,65535,65535,65535,65535,65535,65535,65535,65535,65535,65535,65535,65535,65535,65535,65535,65535,65535,65535,65535},
{413,423,433,444,454,465,475,485,495,506,516,526,536,547,557,567,578,588,598,608,619,629,639,649,660,670,680,690,701,711,721,731,742,752,762,772,785,798,811,65535,65535,65535,65535,65535,65535,65535,65535,65535},
{1201,1213,1223,65535,65535,65535,65535,65535,65535,65535,65535,65535,65535,65535,65535,65535,65535,65535,65535,65535,65535,65535,65535,65535,65535,65535,65535,65535,65535,65535,65535,65535,65535,65535,65535,65535,65535,65535,65535,65535,65535,65535,65535,65535,65535,65535,65535,65535},
{825,835,845,856,866,877,887,897,908,918,928,938,949,959,969,979,990,1000,1010,1020,1031,1041,1051,1061,1072,1082,1092,1102,1113,1123,1133,1144,1154,1164,1174,1185,1195,1209,1225,65535,65535,65535,65535,65535,65535,65535,65535,65535},
{1607,3676,1629,1642,65535,65535,65535,65535,65535,65535,65535,65535,65535,65535,65535,65535,65535,65535,65535,65535,65535,65535,65535,65535,65535,65535,65535,65535,65535,65535,65535,65535,65535,65535,65535,65535,65535,65535,65535,65535,65535,65535,65535,65535,65535,65535,65535,65535},
{1237,1247,1258,1268,1279,1289,1299,1310,1320,1330,1340,1350,1361,1371,1381,1391,1402,1412,1422,1433,1443,1453,1463,1474,1484,1494,1504,1515,1525,1535,1545,1556,1566,1576,1587,1597,1609,1623,1635,65535,65535,65535,65535,65535,65535,65535,65535,65535},
{2025,2860,2047,65535,65535,65535,65535,65535,65535,65535,65535,65535,65535,65535,65535,65535,65535,65535,65535,65535,65535,65535,65535,65535,65535,65535,65535,65535,65535,65535,65535,65535,65535,65535,65535,65535,65535,65535,65535,65535,65535,65535,65535,65535,65535,65535,65535,65535},
{1649,1659,1670,1680,1691,1701,1711,1722,1732,1742,1752,1763,1773,1783,1793,1804,1814,1824,1835,1845,1855,1865,1876,1886,1896,1906,1917,1927,1937,1947,1958,1968,1978,1988,1999,2009,2019,2034,2049,65535,65535,65535,65535,65535,65535,65535,65535,65535},
{2431,2441,2453,2877,65535,65535,65535,65535,65535,65535,65535,65535,65535,65535,65535,65535,65535,65535,65535,65535,65535,65535,65535,65535,65535,65535,65535,65535,65535,65535,65535,65535,65535,65535,65535,65535,65535,65535,65535,65535,65535,65535,65535,65535,65535,65535,65535,65535},
{2061,2071,2082,2093,2103,2113,2124,2134,2144,2154,2165,2175,2185,2195,2206,2216,2226,2236,2247,2257,2267,2277,2288,2298,2308,2318,2329,2339,2349,2359,2370,2380,2390,2401,2411,2421,2434,2447,2460,65535,65535,65535,65535,65535,65535,65535,65535,65535},
{3667,3677,2867,2880,65535,65535,65535,65535,65535,65535,65535,65535,65535,65535,65535,65535,65535,65535,65535,65535,65535,65535,65535,65535,65535,65535,65535,65535,65535,65535,65535,65535,65535,65535,65535,65535,65535,65535,65535,65535,65535,65535,65535,65535,65535,65535,65535,65535},
{3296,3307,2494,2504,2514,3348,2535,2545,2555,3389,2576,2586,2596,3430,2617,2627,2637,3471,2658,2668,2678,2689,2699,2709,2719,2730,2740,2750,3584,2771,2781,2791,3625,2812,2822,2832,3669,2858,3696,65535,65535,65535,65535,65535,65535,65535,65535,65535},
{3262,3273,4084,65535,65535,65535,65535,65535,65535,65535,65535,65535,65535,65535,65535,65535,65535,65535,65535,65535,65535,65535,65535,65535,65535,65535,65535,65535,65535,65535,65535,65535,65535,65535,65535,65535,65535,65535,65535,65535,65535,65535,65535,65535,65535,65535,65535,65535},
{3708,2895,3728,3738,2926,2936,2946,3776,3786,2977,3805,3815,3008,3018,3844,3039,3863,3873,3069,3892,3090,3100,3921,3931,3131,3141,3151,3162,3979,3989,3192,4008,3213,3223,4037,4047,4059,4071,3285,65535,65535,65535,65535,65535,65535,65535,65535,65535},
{4058,381,395,408,65535,65535,65535,65535,65535,65535,65535,65535,65535,65535,65535,65535,65535,65535,65535,65535,65535,65535,65535,65535,65535,65535,65535,65535,65535,65535,65535,65535,65535,65535,65535,65535,65535,65535,65535,65535,65535,65535,65535,65535,65535,65535,65535,65535},
{2,3306,3314,30,39,49,59,69,80,90,100,111,121,131,141,152,162,172,182,193,203,213,223,234,244,254,264,275,285,295,305,316,326,336,346,357,367,383,397,410,65535,65535,65535,65535,65535,65535,65535,65535},
{3254,4066,4077,3289,65535,65535,65535,65535,65535,65535,65535,65535,65535,65535,65535,65535,65535,65535,65535,65535,65535,65535,65535,65535,65535,65535,65535,65535,65535,65535,65535,65535,65535,65535,65535,65535,65535,65535,65535,65535,65535,65535,65535,65535,65535,65535,65535,65535},
{414,424,434,445,455,466,476,486,496,507,517,527,537,548,558,568,3461,589,599,609,3502,630,640,650,3543,671,681,691,702,712,722,732,743,753,763,773,786,799,812,65535,65535,65535,65535,65535,65535,65535,65535,65535},
{1202,1214,1224,65535,65535,65535,65535,65535,65535,65535,65535,65535,65535,65535,65535,65535,65535,65535,65535,65535,65535,65535,65535,65535,65535,65535,65535,65535,65535,65535,65535,65535,65535,65535,65535,65535,65535,65535,65535,65535,65535,65535,65535,65535,65535,65535,65535,65535},
{826,836,846,857,867,878,888,898,3379,919,929,939,3420,960,970,980,991,1001,1011,1021,1032,1042,1052,1062,1073,1083,1093,1103,1114,1124,1134,3615,1155,1165,1175,3656,1196,1210,1226,65535,65535,65535,65535,65535,65535,65535,65535,65535},
{3666,1618,2864,3701,65535,65535,65535,65535,65535,65535,65535,65535,65535,65535,65535,65535,65535,65535,65535,65535,65535,65535,65535,65535,65535,65535,65535,65535,65535,65535,65535,65535,65535,65535,65535,65535,65535,65535,65535,65535,65535,65535,65535,65535,65535,65535,65535,65535},
{1238,1248,1259,1269,3338,1290,1300,3369,1321,1331,1341,1351,1362,1372,1382,1392,1403,1413,1423,3492,1444,1454,1464,3533,1485,1495,1505,3574,1526,1536,1546,1557,1567,1577,3646,1598,1610,3682,1636,65535,65535,65535,65535,65535,65535,65535,65535,65535},
{3672,3684,2048,65535,65535,65535,65535,65535,65535,65535,65535,65535,65535,65535,65535,65535,65535,65535,65535,65535,65535,65535,65535,65535,65535,65535,65535,65535,65535,65535,65535,65535,65535,65535,65535,65535,65535,65535,65535,65535,65535,65535,65535,65535,65535,65535,65535,65535},
{1650,1660,1671,1681,1692,1702,1712,3777,1733,1743,1753,3410,1774,1784,1794,3451,1815,1825,3070,1846,1856,1866,3523,1887,1897,1907,3152,1928,1938,1948,3605,1969,1979,1989,2000,2010,2020,2035,2050,65535,65535,65535,65535,65535,65535,65535,65535,65535},
{2432,2442,3276,2467,65535,65535,65535,65535,65535,65535,65535,65535,65535,65535,65535,65535,65535,65535,65535,65535,65535,65535,65535,65535,65535,65535,65535,65535,65535,65535,65535,65535,65535,65535,65535,65535,65535,65535,65535,65535,65535,65535,65535,65535,65535,65535,65535,65535},
{2062,2072,2083,3328,2104,2114,2947,2135,2145,2155,3400,2176,2186,2196,3441,2217,2227,2237,3482,2258,2268,2278,3922,2299,2309,2319,3564,2340,2350,2360,3999,2381,2391,3224,2412,2422,2435,2448,2461,65535,65535,65535,65535,65535,65535,65535,65535,65535},
{2844,2854,3691,3704,65535,65535,65535,65535,65535,65535,65535,65535,65535,65535,65535,65535,65535,65535,65535,65535,65535,65535,65535,65535,65535,65535,65535,65535,65535,65535,65535,65535,65535,65535,65535,65535,65535,65535,65535,65535,65535,65535,65535,65535,65535,65535,65535,65535},
{2473,2484,3318,2505,2515,2525,3359,2546,2556,2566,2577,2587,2597,2607,2618,2628,2638,2648,2659,2669,2679,3513,2700,2710,2720,3554,2741,2751,2761,3595,2782,2792,2802,3636,2823,2833,2846,2859,3697,65535,65535,65535,65535,65535,65535,65535,65535,65535},
{4064,4075,3284,65535,65535,65535,65535,65535,65535,65535,65535,65535,65535,65535,65535,65535,65535,65535,65535,65535,65535,65535,65535,65535,65535,65535,65535,65535,65535,65535,65535,65535,65535,65535,65535,65535,65535,65535,65535,65535,65535,65535,65535,65535,65535,65535,65535,65535},
{2885,3719,2906,2916,3748,3757,3767,2957,2967,3796,2988,2998,3825,3835,3029,3854,3049,3060,3883,3080,3902,3912,3111,3121,3941,3142,3960,3970,3172,3183,3193,3203,4018,4028,3234,3244,3257,3270,4086,65535,65535,65535,65535,65535,65535,65535,65535,65535},
{3297,13,21,31,41,51,61,71,82,92,102,113,123,133,143,154,164,174,184,195,205,215,225,236,246,256,266,277,287,297,307,318,328,338,348,359,369,385,399,4095,65535,65535,65535,65535,65535,65535,65535,65535},
{3709,2896,3729,33,43,53,63,73,84,94,104,115,125,135,145,156,166,176,186,197,207,217,227,238,248,258,269,279,289,299,310,320,330,340,350,361,374,387,400,65535,65535,65535,65535,65535,65535,65535,65535,65535},
{415,425,435,446,456,2937,477,487,497,2978,3806,528,538,3019,559,569,579,3472,600,610,620,3101,641,651,661,3951,682,692,3980,713,723,733,3214,754,764,774,787,800,813,65535,65535,65535,65535,65535,65535,65535,65535,65535},
{2474,3308,436,447,457,467,478,488,498,508,518,529,539,549,560,570,580,590,601,611,621,631,642,652,662,672,683,693,703,714,724,734,744,755,765,775,788,801,814,65535,65535,65535,65535,65535,65535,65535,65535,65535},
{827,837,847,858,868,3349,889,899,909,3390,930,940,950,3431,971,981,3864,3874,1012,1022,3091,1043,1053,1063,3132,1084,1094,1104,3173,1125,1135,1145,3626,1166,1176,1186,1197,1211,1227,65535,65535,65535,65535,65535,65535,65535,65535,65535},
{2886,838,848,859,869,879,890,900,910,920,931,941,951,961,972,982,992,1002,1013,1023,1033,1044,1054,1064,1074,1085,1095,1105,1115,1126,1136,1146,1156,1167,1177,1187,1198,3685,1228,65535,65535,65535,65535,65535,65535,65535,65535,65535},
{1239,1249,1260,1271,1281,1291,1302,1312,1322,1333,1343,1353,1363,1374,1384,1394,1404,1415,1425,1435,1445,1456,1466,1476,1486,1497,1507,1517,1527,1538,1548,1558,1568,1579,1589,1599,1612,1625,1638,65535,65535,65535,65535,65535,65535,65535,65535,65535},
{3298,1250,2495,1270,1280,3758,1301,1311,3787,1332,1342,1352,3009,1373,1383,1393,3050,1414,1424,1434,3503,1455,1465,1475,3544,1496,1506,1516,3585,1537,1547,4009,4019,1578,1588,3245,1611,1624,1637,65535,65535,65535,65535,65535,65535,65535,65535,65535},
{1651,1661,1672,1683,1693,1704,1714,1724,1734,1745,1755,1765,1775,1786,1796,1806,1816,1827,1837,1847,1857,1868,1878,1888,1899,1909,1919,1929,1940,1950,1960,1970,1981,1991,2001,2011,2022,2038,2052,65535,65535,65535,65535,65535,65535,65535,65535,65535},
{3710,1662,2907,1682,2927,1703,1713,1723,2968,1744,1754,1764,3421,1785,1795,1805,3462,1826,1836,3893,3903,1867,1877,3932,1898,1908,1918,3163,1939,1949,1959,3204,1980,1990,4038,3657,2021,2036,2051,65535,65535,65535,65535,65535,65535,65535,65535,65535},
{2063,2073,2084,2095,3340,2116,2126,2136,3381,2157,2167,2588,2188,2198,2208,3041,2229,2239,2249,3082,2270,2280,2290,3123,2311,2321,2331,3576,2352,2362,2372,3617,2393,2403,2824,4049,2847,2450,2463,65535,65535,65535,65535,65535,65535,65535,65535,65535},
{2064,2074,2085,2506,2106,2527,3769,2959,2147,3798,2578,3000,3827,3837,3846,3453,3866,2650,3885,3494,2681,3914,2701,3535,3943,2732,2742,3972,3982,3991,3195,2383,2804,4030,3236,2424,3671,2451,2464,65535,65535,65535,65535,65535,65535,65535,65535,65535},
{3668,3678,3278,3291,65535,65535,65535,65535,65535,65535,65535,65535,65535,65535,65535,65535,65535,65535,65535,65535,65535,65535,65535,65535,65535,65535,65535,65535,65535,65535,65535,65535,65535,65535,65535,65535,65535,65535,65535,65535,65535,65535,65535,65535,65535,65535,65535,65535},
{2475,2485,3319,3329,3339,2526,2536,3370,3380,2567,3401,3411,2598,2608,3442,3452,2639,2649,3483,3493,2680,2690,3524,3534,2721,2731,3565,3575,2762,2772,3606,3616,2803,2813,3647,2834,3670,3683,2874,65535,65535,65535,65535,65535,65535,65535,65535,65535},
{3251,3259,4072,3286,65535,65535,65535,65535,65535,65535,65535,65535,65535,65535,65535,65535,65535,65535,65535,65535,65535,65535,65535,65535,65535,65535,65535,65535,65535,65535,65535,65535,65535,65535,65535,65535,65535,65535,65535,65535,65535,65535,65535,65535,65535,65535,65535,65535},
{2887,3720,3730,3739,3749,2938,3768,2958,3788,3797,2989,3816,3826,3836,3845,3040,3865,3061,3884,3081,3092,3913,3112,3122,3942,3143,3961,3971,3981,3990,3194,4010,3215,4029,3235,4048,4060,3272,3287,65535,65535,65535,65535,65535,65535,65535,65535,65535},
{416,427,2496,2918,458,468,2537,3371,499,509,519,3412,540,550,2619,3856,581,591,2660,612,622,632,3113,653,663,673,3154,694,704,2773,3607,735,745,2814,3648,776,789,802,815,65535,65535,65535,65535,65535,65535,65535,65535,65535},
{3299,426,437,3330,3750,2939,2949,489,2558,2568,2990,530,2599,2609,3031,571,2640,3062,3072,3895,3093,2691,3525,3934,2722,3144,3566,2753,2763,3185,4001,4011,3216,3226,766,2835,2848,803,816,65535,65535,65535,65535,65535,65535,65535,65535,65535},
{828,839,2908,860,2517,881,891,2548,3382,922,932,2589,3423,963,973,2630,3464,1004,1014,2671,3505,1045,2702,2712,3546,1086,2743,3577,3587,1127,2784,2794,1158,1168,2825,3659,2849,2862,1229,65535,65535,65535,65535,65535,65535,65535,65535,65535},
{3711,2897,849,2507,870,880,3361,901,911,921,3402,942,952,962,3443,983,993,1003,3484,1024,1034,3103,1055,1065,1075,3556,1096,1106,1116,3597,1137,1147,1157,3638,1178,1188,1199,1215,2875,65535,65535,65535,65535,65535,65535,65535,65535,65535},
{1240,1251,1261,1272,3341,1293,2538,2960,3789,1334,1344,3001,1365,1375,2620,3454,1406,1416,2661,3495,1447,1457,3114,3536,1488,1498,3155,1519,1529,2774,3608,3618,1570,2815,3237,4050,1614,1627,1640,65535,65535,65535,65535,65535,65535,65535,65535,65535},
{1241,2486,3320,2919,1282,1292,1303,1313,1323,2980,3808,1354,1364,3021,1385,1395,1405,3474,1426,1436,1446,3515,1467,1477,1487,3953,1508,1518,1528,1539,1549,1559,1569,1580,1590,1600,1613,1626,1639,65535,65535,65535,65535,65535,65535,65535,65535,65535},
{1652,1663,1673,1684,1695,1705,2950,3372,1736,1746,2579,3413,1777,1787,3032,3857,1818,2651,3485,1849,1859,2692,3526,1890,1900,2733,3567,1931,1941,3186,4002,1972,1982,3227,3649,2013,2026,3686,2053,65535,65535,65535,65535,65535,65535,65535,65535,65535},
{1653,2898,1674,3331,1694,3351,1715,1725,1735,3392,1756,1766,1776,3433,1797,1807,1817,1828,1838,1848,1858,1869,1879,1889,3134,1910,1920,1930,3175,1951,1961,1971,3628,1992,2002,2012,2023,2039,3699,65535,65535,65535,65535,65535,65535,65535,65535,65535},
{2065,2075,2086,2096,2107,2117,2127,2137,2148,2158,2168,2178,2189,2199,2209,2219,2230,2240,2250,2260,2271,2281,2291,2301,2312,2322,2332,2342,2353,2363,2373,2384,2394,2404,2414,2425,2437,2452,2465,65535,65535,65535,65535,65535,65535,65535,65535,65535},
{2476,3310,3731,2094,2105,2115,2125,3778,2146,2156,2166,2177,2187,2197,2207,2218,2228,2238,2248,2259,2269,2279,2289,2300,2310,2320,2330,2341,2351,2361,2371,2382,2392,2402,2413,2423,2436,2449,2462,65535,65535,65535,65535,65535,65535,65535,65535,65535},
{4057,3265,2868,2881,65535,65535,65535,65535,65535,65535,65535,65535,65535,65535,65535,65535,65535,65535,65535,65535,65535,65535,65535,65535,65535,65535,65535,65535,65535,65535,65535,65535,65535,65535,65535,65535,65535,65535,65535,65535,65535,65535,65535,65535,65535,65535,65535,65535},
{3300,2487,2497,2508,2518,2528,3362,2549,2559,2569,3403,2590,2600,2610,3444,2631,2641,3475,2662,2672,2682,3516,2703,2713,2723,3557,2744,2754,2764,3598,2785,2795,2805,3639,2826,2836,3673,2863,2876,65535,65535,65535,65535,65535,65535,65535,65535,65535},
{4054,4062,3271,4087,65535,65535,65535,65535,65535,65535,65535,65535,65535,65535,65535,65535,65535,65535,65535,65535,65535,65535,65535,65535,65535,65535,65535,65535,65535,65535,65535,65535,65535,65535,65535,65535,65535,65535,65535,65535,65535,65535,65535,65535,65535,65535,65535,65535},
{2888,3722,2909,3741,2929,3760,3770,3779,2970,3799,2991,3818,3011,3022,3847,3042,3052,3876,3073,3083,3905,3915,3924,3124,3944,3145,3963,3165,3176,3992,3196,3206,4021,4031,4040,3247,4063,3274,4088,65535,65535,65535,65535,65535,65535,65535,65535,65535},
{417,428,439,449,2930,3352,480,2961,3383,3393,521,3002,3012,552,562,3455,3053,593,603,3084,3506,634,644,3537,3547,675,685,3166,3588,716,726,3207,3629,757,3238,3660,791,3688,819,65535,65535,65535,65535,65535,65535,65535,65535,65535},
{3712,2899,438,448,459,469,479,490,500,510,520,531,541,551,561,572,582,592,602,613,623,633,643,654,664,674,684,695,705,715,725,736,746,756,767,777,790,804,817,65535,65535,65535,65535,65535,65535,65535,65535,65535},
{829,840,851,3332,3342,882,2539,3373,3790,923,933,3414,3424,964,2621,3858,3465,1005,1015,3496,3906,1046,3115,3935,1077,1087,3156,3578,1118,2775,3609,3619,1159,2816,3650,4051,2850,1217,1230,65535,65535,65535,65535,65535,65535,65535,65535,65535},
{830,3311,850,861,871,2940,892,902,912,2981,3809,943,953,3434,974,984,994,3063,3886,1025,1035,3104,1056,1066,1076,3954,1097,1107,1117,1128,1138,1148,3217,1169,1179,1189,1203,1216,3288,65535,65535,65535,65535,65535,65535,65535,65535,65535},
{1242,1252,1262,1273,1283,1294,1304,1314,1324,1335,1345,1355,1366,1376,1386,1396,1407,1417,1427,1437,1448,1458,1468,1478,1489,1499,1509,1520,1530,1540,1550,1560,1571,1581,1591,1601,1615,1630,1643,65535,65535,65535,65535,65535,65535,65535,65535,65535},
{2477,1253,1263,3742,1284,2529,2951,1315,1325,2570,2580,1356,3829,2611,3033,1397,3868,2652,3486,1438,2683,2693,3527,1479,3945,2734,3568,3974,2765,3187,4003,1561,2806,3640,1592,1602,3674,4078,4090,65535,65535,65535,65535,65535,65535,65535,65535,65535},
{1654,1664,1675,1685,1696,1706,1716,1726,1737,1747,1757,1767,1778,1788,1798,1808,1819,1829,1839,1850,1860,1870,1880,1891,1901,1911,1921,1932,1942,1952,1962,1973,1983,1993,2003,2014,2027,2040,2054,65535,65535,65535,65535,65535,65535,65535,65535,65535},
{2889,1665,2498,1686,3752,2941,3363,1727,2560,2982,3404,1768,2601,3023,3445,1809,2642,3064,3887,3897,3095,3105,1881,2714,2724,3558,1922,2755,3177,3599,1963,4013,3218,4032,2004,2837,2028,2041,2055,65535,65535,65535,65535,65535,65535,65535,65535,65535},
{2066,2076,2087,2097,2108,2118,2128,2138,2149,2159,2169,2179,2190,2200,2210,2220,2231,2241,2251,2261,2272,2282,2292,2302,2313,2323,2333,2343,2354,2364,2374,2385,2395,2405,2415,2426,2438,2454,2878,65535,65535,65535,65535,65535,65535,65535,65535,65535},
{3301,2077,2910,2098,2519,3353,2129,2139,2972,3394,3810,2180,3013,3435,2211,2221,3054,3476,2252,2262,3507,3517,2293,2303,3136,3955,2334,2344,3589,2365,2375,2796,3630,2406,2416,3249,2439,2865,3290,65535,65535,65535,65535,65535,65535,65535,65535,65535},
{3255,4067,3692,3705,65535,65535,65535,65535,65535,65535,65535,65535,65535,65535,65535,65535,65535,65535,65535,65535,65535,65535,65535,65535,65535,65535,65535,65535,65535,65535,65535,65535,65535,65535,65535,65535,65535,65535,65535,65535,65535,65535,65535,65535,65535,65535,65535,65535},
{2478,2488,3322,2509,3343,2530,2540,2550,3384,2571,2581,2591,3425,2612,2622,2632,3466,2653,2663,2673,2684,2694,2704,3538,3548,2735,2745,3579,2766,2776,2786,3620,2807,2817,2827,3661,2851,3689,3702,65535,65535,65535,65535,65535,65535,65535,65535,65535},
{3662,3260,4073,2873,65535,65535,65535,65535,65535,65535,65535,65535,65535,65535,65535,65535,65535,65535,65535,65535,65535,65535,65535,65535,65535,65535,65535,65535,65535,65535,65535,65535,65535,65535,65535,65535,65535,65535,65535,65535,65535,65535,65535,65535,65535,65535,65535,65535},
{3713,3723,3732,2920,3751,3761,3771,3780,2971,3800,2992,3819,3828,3838,3848,3043,3867,3877,3074,3896,3094,3916,3925,3125,3135,3146,3964,3973,3983,3993,3197,4012,4022,3228,4041,3248,3263,4076,4089,65535,65535,65535,65535,65535,65535,65535,65535,65535},
{418,429,440,451,461,471,482,492,502,512,523,533,543,553,564,574,584,595,605,615,625,636,646,656,666,677,687,697,707,718,728,738,748,759,769,779,794,807,821,65535,65535,65535,65535,65535,65535,65535,65535,65535},
{419,2900,3733,450,460,470,481,491,501,511,522,532,542,3839,563,573,583,594,604,614,624,635,645,655,665,676,686,696,706,717,727,737,747,758,768,778,792,806,820,65535,65535,65535,65535,65535,65535,65535,65535,65535},
{831,841,852,863,873,883,894,904,914,925,935,945,955,966,976,986,996,1007,1017,1027,1037,1048,1058,1068,3549,1089,1099,1109,1119,1130,1140,1150,1161,1171,1181,1191,1205,1219,1232,65535,65535,65535,65535,65535,65535,65535,65535,65535},
{2890,3312,2499,862,872,3762,893,903,913,924,934,944,954,965,975,985,995,1006,1016,1026,1036,1047,1057,1067,1078,1088,1098,1108,3984,1129,1139,1149,1160,1170,1180,1190,1204,1218,1231,65535,65535,65535,65535,65535,65535,65535,65535,65535},
{1243,1254,1264,1275,1285,1296,1306,1316,1326,1337,1347,1357,3426,1378,1388,1398,3467,1419,1429,1439,1449,1460,1470,1480,1491,1501,1511,1521,1532,1542,1552,1562,1573,1583,1593,1603,1619,1631,1645,65535,65535,65535,65535,65535,65535,65535,65535,65535},
{3302,3724,2911,1274,2931,1295,1305,3781,3791,1336,1346,3820,1367,1377,1387,3044,1408,1418,1428,3085,3907,1459,1469,3126,1490,1500,1510,3167,1531,1541,1551,3208,1572,1582,4042,4052,1616,3277,1644,65535,65535,65535,65535,65535,65535,65535,65535,65535},
{1655,1666,1676,1687,1697,1707,1717,1728,1738,1748,1758,1769,1779,1789,1799,1810,1820,1830,1840,1851,1861,1871,1882,1892,1902,1912,1923,1933,1943,1953,1964,1974,1984,1994,2005,2015,2029,2042,2056,65535,65535,65535,65535,65535,65535,65535,65535,65535},
{1656,3725,3324,2510,3344,1708,1718,2551,3385,1749,1759,2592,1780,1790,1800,2633,1821,1831,1841,2674,1862,1872,3927,3539,1903,1913,3966,3580,1944,1954,2787,3621,1985,1995,2828,2016,2030,2043,2057,65535,65535,65535,65535,65535,65535,65535,65535,65535},
{2067,2078,2088,2099,2109,2119,2130,2140,2150,2160,2170,2181,2191,2201,2212,2222,2232,2242,2253,2263,2273,2283,2294,2304,2314,2324,2335,2345,2355,2366,2376,2386,2396,2407,2417,2427,2443,2455,2468,65535,65535,65535,65535,65535,65535,65535,65535,65535},
{2068,2079,2089,2922,2110,2120,2541,2963,2151,2161,2171,3004,2192,2202,3850,3457,2233,2243,2664,3498,2274,2284,2705,3937,2315,2325,2746,2346,2356,3995,3199,2387,2397,2818,3240,2428,3266,2456,2469,65535,65535,65535,65535,65535,65535,65535,65535,65535},
{2479,2489,3323,3333,2520,3354,3364,3374,2561,3395,3405,3415,2602,3436,3446,3456,2643,3477,3487,3497,3508,3518,3528,2715,2725,3559,3569,2756,3590,3600,3610,2797,3631,3641,3651,2838,3675,2866,2879,65535,65535,65535,65535,65535,65535,65535,65535,65535},
{3303,3313,2500,3334,2521,2531,3365,3375,2562,2572,2582,3416,2603,2613,2623,2634,2644,2654,3488,2675,2685,2695,3529,2716,2726,2736,3570,2757,2767,2777,3611,2798,2808,3642,3652,2839,2855,4080,3292,65535,65535,65535,65535,65535,65535,65535,65535,65535},
{3714,2901,3734,2921,3753,2942,3772,2962,2973,3801,2993,3003,3830,3024,3849,3859,3869,3878,3075,3898,3096,3917,3926,3936,3946,3147,3965,3975,3178,3994,3198,4014,4023,3229,3239,3250,4065,4079,4091,65535,65535,65535,65535,65535,65535,65535,65535,65535},
{2891,2902,2912,3744,3754,2943,2953,3783,2974,3802,2994,3005,3831,3025,3035,3860,3056,3879,3076,3899,3097,3918,3117,3128,3947,3148,3158,3976,3179,3189,4005,4015,4024,3230,4044,3252,4068,3280,4093,65535,65535,65535,65535,65535,65535,65535,65535,65535},
{420,430,441,452,463,473,483,3376,504,514,524,3417,545,555,565,576,586,596,606,617,627,637,3118,658,668,678,3571,699,709,719,3612,740,750,760,3653,781,796,809,823,65535,65535,65535,65535,65535,65535,65535,65535,65535},
{421,431,442,2511,462,472,3773,493,503,513,3406,534,544,554,3447,575,585,3066,3889,616,626,3107,647,657,667,3560,688,698,708,3601,729,739,749,4034,770,780,795,808,822,65535,65535,65535,65535,65535,65535,65535,65535,65535},
{832,842,853,864,875,885,3366,906,916,926,2995,947,957,967,3036,988,998,1008,3489,1029,1039,1049,3530,1070,1080,3149,3967,1111,1121,3190,1142,1152,1162,3643,1183,1193,1207,1221,1234,65535,65535,65535,65535,65535,65535,65535,65535,65535},
{833,843,854,2923,874,884,895,905,915,2984,936,946,956,3437,977,987,997,3478,1018,1028,1038,3519,1059,1069,1079,1090,1100,1110,1120,1131,1141,1151,3220,1172,1182,1192,1206,1220,1233,65535,65535,65535,65535,65535,65535,65535,65535,65535},
{1244,1255,1265,1276,1286,1297,1307,1317,1327,1338,1348,1358,1368,1379,1389,1399,1409,1420,1430,1440,1450,1461,1471,1481,1492,1502,1512,1522,1533,1543,1553,1563,1574,1584,1594,1604,1620,1632,1646,65535,65535,65535,65535,65535,65535,65535,65535,65535},
{1245,1256,1266,1277,1287,2532,1308,1318,1328,2573,3407,1359,1369,3438,3448,1400,1410,3479,1431,1441,1451,3520,1472,1482,2727,3561,1513,1523,2768,3602,1554,1564,2809,1585,1595,1605,1621,1633,1647,65535,65535,65535,65535,65535,65535,65535,65535,65535},
{1657,1668,1678,1689,1699,3356,1720,1730,1740,3397,1761,1771,2604,3842,1802,1812,2645,1833,1843,1853,2686,1874,1884,1894,3139,1915,1925,1935,3592,1956,1966,1976,3633,1997,2007,2840,2032,2045,2059,65535,65535,65535,65535,65535,65535,65535,65535,65535},
{3715,1667,1677,1688,1698,1709,1719,1729,1739,1750,1760,1770,1781,1791,1801,1811,1822,1832,1842,1852,1863,1873,1883,1893,1904,1914,1924,1934,1945,1955,1965,1975,1986,1996,2006,2017,2031,2044,2058,65535,65535,65535,65535,65535,65535,65535,65535,65535},
{2069,2080,2091,2101,2522,2122,2132,2142,2563,2163,2173,2183,3016,2204,2214,2224,3469,2245,2255,2265,3510,2286,2296,2306,3551,2327,2337,2758,3987,2368,2378,2799,2399,2409,2419,3664,2445,2458,2471,65535,65535,65535,65535,65535,65535,65535,65535,65535},
{2480,2491,2090,2100,2111,2121,2131,2141,2152,2162,2172,2182,2193,2203,2213,2223,2234,2244,2254,2264,2275,2285,2295,2305,2316,2326,2336,2347,2357,2367,2377,2388,2398,2408,2418,2429,2444,2457,2470,65535,65535,65535,65535,65535,65535,65535,65535,65535},
{3304,3315,2501,3335,3345,3355,2542,2552,3386,3396,2583,2593,3427,2614,2624,3458,3468,2655,2665,3499,3509,2696,2706,3540,3550,2737,2747,3581,3591,2778,2788,3622,3632,2819,2829,3663,3679,2869,2882,65535,65535,65535,65535,65535,65535,65535,65535,65535},
{2481,2492,2502,2512,3346,2533,2543,2553,3387,2574,2584,2594,3428,2615,2625,2635,2646,2656,2666,2676,2687,2697,2707,2717,2728,2738,2748,3582,2769,2779,2789,3623,2810,2820,2830,2841,2856,3693,3706,65535,65535,65535,65535,65535,65535,65535,65535,65535},
{2892,2903,3735,3743,2932,3763,2952,3782,3792,2983,3811,3821,3014,3840,3034,3045,3055,3065,3888,3086,3908,3106,3116,3127,3137,3956,3157,3168,3985,3188,4004,3209,3219,4033,4043,4053,3264,3279,4092,65535,65535,65535,65535,65535,65535,65535,65535,65535},
{3716,3726,2913,3745,2933,3764,2954,2964,3793,3803,3812,3822,3015,3841,3851,3046,3870,3880,3077,3087,3909,3108,3928,3938,3138,3957,3159,3169,3986,3996,3200,3210,4025,3231,3241,4055,3267,4081,3293,65535,65535,65535,65535,65535,65535,65535,65535,65535},
{3305,3316,3326,3336,2523,3357,3367,3377,2564,3398,3408,3418,2605,3439,3449,3459,3470,3480,3490,3500,3511,3521,3531,3541,3552,3562,3572,2759,3593,3603,3613,2800,3634,3644,3654,3665,3680,2870,2883,65535,65535,65535,65535,65535,65535,65535,65535,65535},
{2482,2493,2503,2513,3347,2534,2544,2554,3388,2575,2585,2595,3429,2616,2626,2636,3871,2657,2667,2677,2688,2698,2708,2718,2729,2739,2749,3583,2770,2780,2790,3624,2811,2821,2831,2842,2857,3694,3707,65535,65535,65535,65535,65535,65535,65535,65535,65535},
{2893,2904,2914,3746,2934,3765,2955,2965,3794,3804,2996,3823,3833,3027,3037,3047,3058,3881,3078,3088,3910,3109,3119,3939,3949,3150,3968,3170,3181,3191,3201,4016,4026,3232,3242,4056,3268,4082,3294,65535,65535,65535,65535,65535,65535,65535,65535,65535},
{3717,3727,3736,2924,3755,2944,3774,3784,2975,2985,3813,3006,3832,3026,3852,3861,3057,3067,3890,3900,3098,3919,3929,3129,3948,3958,3160,3977,3180,3997,4006,3211,3221,4035,4045,3253,4069,3281,4094,65535,65535,65535,65535,65535,65535,65535,65535,65535},
{3,12,20,3325,40,50,60,70,81,91,101,112,122,132,142,153,163,173,183,194,204,214,224,235,245,255,265,276,286,296,306,317,327,337,347,358,368,384,398,411,65535,65535,65535,65535,65535,65535,65535,65535},
{4,14,22,32,42,52,62,72,83,93,103,114,124,134,144,155,165,175,185,3891,206,216,226,237,247,257,267,278,288,298,308,319,329,339,349,360,370,386,3282,3295,65535,65535,65535,65535,65535,65535,65535,65535},
{5,3309,24,34,44,54,64,74,85,95,105,116,126,136,146,157,167,177,187,198,208,218,228,239,249,259,270,280,290,300,311,321,331,341,351,362,375,388,401,65535,65535,65535,65535,65535,65535,65535,65535,65535},
{6,15,23,3737,2925,3756,2945,3775,3785,2976,2986,3814,3007,3017,3843,3853,3862,3872,3068,196,3901,3099,3920,3930,3130,3140,268,3161,3978,3988,309,4007,3212,3222,4036,4046,371,4070,4083,1235,65535,65535,65535,65535,65535,65535,65535,65535},
{7,3721,25,2917,45,55,65,75,86,96,106,2999,127,137,147,3855,168,178,188,199,209,219,229,240,250,260,3153,281,291,301,4000,322,332,342,352,363,3258,389,402,65535,65535,65535,65535,65535,65535,65535,65535,65535},
{8,16,26,35,2516,3350,2948,76,2557,2979,3807,117,3010,3020,3030,158,3051,3473,3071,3894,3504,3102,3923,3933,3133,3555,271,2752,3174,3184,312,2793,3627,3225,353,3246,376,390,403,65535,65535,65535,65535,65535,65535,65535,65535,65535},
{9,17,3321,36,46,56,66,77,87,97,108,118,128,138,149,159,169,179,190,200,210,220,231,241,251,261,272,282,292,302,313,323,333,343,354,364,377,391,404,65535,65535,65535,65535,65535,65535,65535,65535,65535},
{10,18,27,3740,2928,3759,3360,2547,2969,3391,107,3817,3422,3432,148,2629,3463,3875,189,2670,3904,3514,230,2711,3545,3952,3962,3164,3586,3596,2783,3205,4020,3637,4039,3658,4061,2861,3698,65535,65535,65535,65535,65535,65535,65535,65535,65535},
};

#define NG SCHED_NG
#define RING 16
#define NSLOT 8
#define CFETCH 5
#define TABLED 1
#define PROMO CU_TENSOR_MAP_L2_PROMOTION_L2_128B
#define AHEAD 6
#define CF0 5
#define CFS 2
#define ABL 0
#define CX 5
#define PUBN 2
#define PUBE 8
#define SCHED 9
#define OUT_TMA 0
#define JB1 21
#define JB2 24
#define CVAR 2
#define CFN 0
#define CREGS 224
#define CSLEEP 200
#define TRIG 6
constexpr int NCONV = 3 * NG;
constexpr int PLEN = (1024 + NG - 1) / NG;
constexpr int TILEB = 12288;
constexpr int SLOTB = 280 * 64;
constexpr int W1S = 0, W2S = 73728, ABUF = 147456, XBUF = ABUF + 16 * 3072, MISC = XBUF + 8 * 3072;
constexpr int WBAR = MISC + 2560;
constexpr int RBUF = ABUF - 4 * SLOTB;
constexpr int CM = MISC + 2816, CTAB = CM + 256;
constexpr int SMEM_BYTES = CTAB + (PLEN + 12) * 16;
static_assert(RBUF % 512 == 0 && RBUF >= W2S && RBUF + NSLOT * SLOTB + 128 <= MISC && SMEM_BYTES <= 232448, "smem layout");

struct Globals {
  unsigned char scratch[(RING * NG + 1) * 4 * TILEB];
  unsigned char wimg[147456];
  uint32_t wflag[32];
  uint32_t ready[1024 + 32];
  uint32_t cons[1024 + 32];
  uint32_t epoch[1024];
};
__device__ __align__(1024) Globals g_state;

#define PROF_AT(cond, idx)
#define PROF_VAL(cond, idx, v)
#define PROF2_AT(c, i)
#define PROF2_VAL(c, i, v)
#define GELU_C3 0.32920349f
#define GELU_A2 0x40d940d9u
#define SCHED_FENCE() asm volatile("pmevent 0;" ::: "memory")
#define SPIN_LIMIT 0x1000000

__device__ __forceinline__ uint32_t smem_u32(const void* p) { return (uint32_t)__cvta_generic_to_shared(p); }
__device__ __forceinline__ void wg_fence() { asm volatile("wgmma.fence.sync.aligned;" ::: "memory"); }
__device__ __forceinline__ void wg_commit() { asm volatile("wgmma.commit_group.sync.aligned;" ::: "memory"); }
template <int N> __device__ __forceinline__ void wg_wait() { asm volatile("wgmma.wait_group.sync.aligned %0;" ::"n"(N) : "memory"); }
__device__ __forceinline__ void mbar_init(uint32_t bar, uint32_t cnt) { asm volatile("mbarrier.init.shared::cta.b64 [%0], %1;" ::"r"(bar), "r"(cnt) : "memory"); }
__device__ __forceinline__ void mbar_expect_tx(uint32_t bar, uint32_t bytes) { asm volatile("mbarrier.arrive.expect_tx.shared::cta.b64 _, [%0], %1;" ::"r"(bar), "r"(bytes) : "memory"); }
__device__ __forceinline__ void mbar_arrive(uint32_t bar) { asm volatile("mbarrier.arrive.shared::cta.b64 _, [%0];" ::"r"(bar) : "memory"); }
__device__ __forceinline__ void mbar_wait(uint32_t bar, uint32_t parity) {
  asm volatile("{\n.reg .pred p;\n.reg .u32 c;\nmbarrier.try_wait.parity.shared::cta.b64 p, [%0], %1;\n@p bra DONE_%=;\nmov.u32 c, 0;\nWAIT_%=:\nmbarrier.try_wait.parity.shared::cta.b64 p, [%0], %1;\n@p bra DONE_%=;\n"
               "add.u32 c, c, 1;\nsetp.lt.u32 p, c, 0x1000000;\n@p bra WAIT_%=;\ntrap;\nDONE_%=:\n}" ::"r"(bar), "r"(parity) : "memory");
}
__device__ __forceinline__ void bulk_g2s(uint32_t dst, const void* src, uint32_t bytes, uint32_t bar) {
  asm volatile("cp.async.bulk.shared::cluster.global.mbarrier::complete_tx::bytes [%0], [%1], %2, [%3];" ::"r"(dst), "l"(src), "r"(bytes), "r"(bar) : "memory");
}
__device__ __forceinline__ uint32_t ld_relaxed(const uint32_t* p) { uint32_t v; asm volatile("ld.relaxed.gpu.global.u32 %0, [%1];" : "=r"(v) : "l"(p) : "memory"); return v; }
__device__ __forceinline__ void red_add_elect(uint32_t* p) { asm volatile("{.reg .pred p; elect.sync _|p, 0xffffffff; @p red.relaxed.gpu.global.add.u32 [%0], 1;}" ::"l"(p) : "memory"); }
__device__ __forceinline__ void mbar_arrive_elect(uint32_t bar) { asm volatile("{.reg .pred p; elect.sync _|p, 0xffffffff; @p mbarrier.arrive.shared::cta.b64 _, [%0];}" ::"r"(bar) : "memory"); }
__device__ __forceinline__ void mbar_init_elect(uint32_t bar, uint32_t cnt) { asm volatile("{.reg .pred p; elect.sync _|p, 0xffffffff; @p mbarrier.init.shared::cta.b64 [%0], %1;}" ::"r"(bar), "r"(cnt) : "memory"); }
__device__ __forceinline__ void lds128(uint32_t* r, uint32_t a) { asm volatile("ld.shared.v4.b32 {%0,%1,%2,%3}, [%4];" : "=r"(r[0]), "=r"(r[1]), "=r"(r[2]), "=r"(r[3]) : "r"(a) : "memory"); }
__device__ __forceinline__ uint2 lds64(uint32_t a) { uint2 v; asm volatile("ld.shared.v2.b32 {%0,%1}, [%2];" : "=r"(v.x), "=r"(v.y) : "r"(a) : "memory"); return v; }
__device__ __forceinline__ uint32_t lds32(uint32_t a) { uint32_t v; asm volatile("ld.shared.b32 %0, [%1];" : "=r"(v) : "r"(a) : "memory"); return v; }
__device__ __forceinline__ void sts32(uint32_t a, uint32_t v) { asm volatile("st.shared.b32 [%0], %1;" ::"r"(a), "r"(v) : "memory"); }
__device__ __forceinline__ void sts128(uint32_t a, uint4 v) { asm volatile("st.shared.v4.b32 [%0], {%1,%2,%3,%4};" ::"r"(a), "r"(v.x), "r"(v.y), "r"(v.z), "r"(v.w) : "memory"); }
__device__ __forceinline__ uint4 ldg128v(const void* p) { uint4 v; asm volatile("ld.global.nc.v4.b32 {%0,%1,%2,%3}, [%4];" : "=r"(v.x), "=r"(v.y), "=r"(v.z), "=r"(v.w) : "l"(p) : "memory"); return v; }
__device__ __forceinline__ void stg128(void* p, uint4 v) { asm volatile("st.global.v4.b32 [%0], {%1,%2,%3,%4};" ::"l"(p), "r"(v.x), "r"(v.y), "r"(v.z), "r"(v.w) : "memory"); }
#define HINT 3
__device__ __forceinline__ uint64_t pol_evict_first() { uint64_t p; asm("createpolicy.fractional.L2::evict_first.b64 %0, 1.0;" : "=l"(p)); return p; }
__device__ __forceinline__ uint4 ldg128_last(const void* p, uint64_t pol) {
  if (!(HINT & 1)) return ldg128v(p);
  uint4 v; asm volatile("ld.global.nc.L1::no_allocate.L2::cache_hint.v4.b32 {%0,%1,%2,%3}, [%4], %5;" : "=r"(v.x), "=r"(v.y), "=r"(v.z), "=r"(v.w) : "l"(p), "l"(pol) : "memory"); return v;
}
__device__ __forceinline__ void stg128_stream(void* p, uint4 v, uint64_t pol) {
  if (!(HINT & 2)) { stg128(p, v); return; }
  asm volatile("st.global.L2::cache_hint.v4.b32 [%0], {%1,%2,%3,%4}, %5;" ::"l"(p), "r"(v.x), "r"(v.y), "r"(v.z), "r"(v.w), "l"(pol) : "memory");
}
__device__ __forceinline__ float bf_lo(uint32_t w) { return __uint_as_float(w << 16); }
__device__ __forceinline__ float bf_hi(uint32_t w) { return __uint_as_float(w & 0xffff0000u); }
__device__ __forceinline__ uint32_t pack_f16(float lo, float hi) { uint32_t d; asm("cvt.rn.f16x2.f32 %0, %1, %2;" : "=r"(d) : "f"(hi), "f"(lo)); return d; }
__device__ __forceinline__ uint32_t pack_f16_sat(float lo, float hi) { uint32_t d; asm("cvt.rn.satfinite.f16x2.f32 %0, %1, %2;" : "=r"(d) : "f"(hi), "f"(lo)); return d; }
__device__ __forceinline__ uint32_t pack_bf16(float lo, float hi) { uint32_t d; asm("cvt.rn.bf16x2.f32 %0, %1, %2;" : "=r"(d) : "f"(hi), "f"(lo)); return d; }
__device__ __forceinline__ uint32_t hadd2_bf16(uint32_t a, uint32_t b) { uint32_t d; asm("add.rn.bf16x2 %0, %1, %2;" : "=r"(d) : "r"(a), "r"(b)); return d; }
__device__ __forceinline__ uint32_t h2add(uint32_t a, uint32_t b) { uint32_t d; asm("add.rn.f16x2 %0, %1, %2;" : "=r"(d) : "r"(a), "r"(b)); return d; }
__device__ __forceinline__ uint32_t h2mul(uint32_t a, uint32_t b) { uint32_t d; asm("mul.rn.f16x2 %0, %1, %2;" : "=r"(d) : "r"(a), "r"(b)); return d; }
__device__ __forceinline__ uint32_t h2fma(uint32_t a, uint32_t b, uint32_t c) { uint32_t d; asm("fma.rn.f16x2 %0, %1, %2, %3;" : "=r"(d) : "r"(a), "r"(b), "r"(c)); return d; }
__device__ __forceinline__ uint32_t h2lo(uint32_t a) { uint32_t d; asm("{.reg .f16 l,h; mov.b32 {l,h}, %1; mov.b32 %0, {l,l};}" : "=r"(d) : "r"(a)); return d; }
__device__ __forceinline__ uint32_t h2hi(uint32_t a) { uint32_t d; asm("{.reg .f16 l,h; mov.b32 {l,h}, %1; mov.b32 %0, {h,h};}" : "=r"(d) : "r"(a)); return d; }
__device__ __forceinline__ float h_lo(uint32_t a) { float d; asm("{.reg .f16 l,h; mov.b32 {l,h}, %1; cvt.f32.f16 %0, l;}" : "=f"(d) : "r"(a)); return d; }
__device__ __forceinline__ float h_hi(uint32_t a) { float d; asm("{.reg .f16 l,h; mov.b32 {l,h}, %1; cvt.f32.f16 %0, h;}" : "=f"(d) : "r"(a)); return d; }
__device__ __forceinline__ uint32_t prmt(uint32_t a, uint32_t b, uint32_t s) { uint32_t d; asm("prmt.b32 %0, %1, %2, %3;" : "=r"(d) : "r"(a), "r"(b), "r"(s)); return d; }
__device__ __forceinline__ void mma_sp(float* d, const uint32_t* a, const uint32_t* b, const float* c, uint32_t e) {
  asm("mma.sp::ordered_metadata.sync.aligned.m16n8k32.row.col.f32.bf16.bf16.f32 {%0,%1,%2,%3}, {%4,%5,%6,%7}, {%8,%9,%10,%11}, {%12,%13,%14,%15}, %16, 0;"
      : "=f"(d[0]), "=f"(d[1]), "=f"(d[2]), "=f"(d[3])
      : "r"(a[0]), "r"(a[1]), "r"(a[2]), "r"(a[3]), "r"(b[0]), "r"(b[1]), "r"(b[2]), "r"(b[3]), "f"(c[0]), "f"(c[1]), "f"(c[2]), "f"(c[3]), "r"(e));
}
__device__ __forceinline__ uint32_t bf2_to_h2(uint32_t w, float s) { return pack_f16(bf_lo(w) * s, bf_hi(w) * s); }
__device__ __forceinline__ uint32_t bf2_to_h2(uint32_t w) { return pack_f16(bf_lo(w), bf_hi(w)); }

__device__ __forceinline__ uint32_t gelu_h2(uint32_t y) {
  uint32_t t, u, th, g;
  asm volatile("fma.rn.f16x2 %0, %1, %1, %2;" : "=r"(t) : "r"(y), "r"(GELU_A2));
  asm volatile("mul.rn.f16x2 %0, %1, %2;" : "=r"(u) : "r"(y), "r"(t));
  asm volatile("tanh.approx.f16x2 %0, %1;" : "=r"(th) : "r"(u));
  asm volatile("fma.rn.f16x2 %0, %1, %2, %1;" : "=r"(g) : "r"(y), "r"(th));
  return g;
}

__device__ __forceinline__ void copy_weights(uint32_t sb, int piece, const void* src) {
  asm volatile("{\n.reg .pred p;\nelect.sync _|p, 0xffffffff;\n@p mbarrier.init.shared::cta.b64 [%1], 1;\n@p fence.mbarrier_init.release.cluster;\n"
               "@p mbarrier.arrive.expect_tx.shared::cta.b64 _, [%1], 12288;\n"
               "@p cp.async.bulk.shared::cluster.global.mbarrier::complete_tx::bytes [%0], [%2], 12288, [%1];\n}"
               ::"r"(sb + piece * 12288), "r"(sb + WBAR + piece * 8), "l"(src) : "memory");
}
__device__ __forceinline__ void convert_weights(uint32_t sb, uint32_t wbar, int rot, int warp, int lane) {
  if (warp < 12) {
    const int l8 = lane & 7, q4 = lane >> 3;
    int s = (warp >> 1) + rot; if (s >= 6) s -= 6;
    const uint32_t base = sb + W1S + s * 12288 + (warp & 1) * 384;
    mbar_wait(wbar + s * 8, 0);
    uint32_t v[3][4][4];
#pragma unroll
    for (int r = 0; r < 4; r++)
#pragma unroll
      for (int i = 0; i < 3; i++) lds128(v[i][r], base + i * 128 + (4 * (l8 >> 1) + 2 * (r & 1) + (l8 & 1)) * 768 + ((l8 + q4 + 4 * (r >> 1)) & 7) * 16);
    __syncwarp();
#pragma unroll
    for (int r = 0; r < 4; r++)
#pragma unroll
      for (int i = 0; i < 3; i++)
        sts128(base + i * 128 + (2 * ((l8 + q4 + 4 * (r >> 1)) & 7) + (r & 1)) * 768 + l8 * 16,
               make_uint4(bf2_to_h2(v[i][r][0]), bf2_to_h2(v[i][r][1]), bf2_to_h2(v[i][r][2]), bf2_to_h2(v[i][r][3])));
  }
  PROF2_AT(lane == 0, 440 + warp);
  const int q = lane & 3, t = (lane >> 2) & 3, b = lane >> 4;
  int u = 3 * (warp ^ 15) + 8 * rot; if (u >= 48) u -= 48;
  uint32_t base[3], v[3][4][3];
#pragma unroll
  for (int i = 0; i < 3; i++) {
    const int ui = u + i >= 48 ? u + i - 48 : u + i;
    base[i] = sb + W2S + ui * 1536;
    if (i != 1) mbar_wait(wbar + 48 + (ui >> 3) * 8, 0);
  }
#pragma unroll
  for (int i = 0; i < 3; i++)
#pragma unroll
    for (int d = 0; d < 4; d++)
#pragma unroll
      for (int j = 0; j < 3; j++) v[i][d][j] = lds32(base[i] + (2 * ((q + d) & 3) + b) * 192 + j * 64 + t * 16 + q * 4);
  __syncwarp();
#pragma unroll
  for (int i = 0; i < 3; i++)
#pragma unroll
    for (int d = 0; d < 4; d++)
#pragma unroll
      for (int j = 0; j < 3; j++) sts32(base[i] + (4 * j + q) * 128 + (2 * ((q + d) & 3) + b) * 16 + t * 4, bf2_to_h2(v[i][d][j], 0.5f / GELU_C3));
}

__device__ __noinline__ void ln_wide(uint32_t ad) {
  float m[2], r[2];
#pragma unroll
  for (int hi = 0; hi < 2; hi++) {
    float sm = 0.f;
    for (int s = 0; s < 6; s++) { uint2 w = lds64(ad + s * 512 + hi * 8); sm += (h_lo(w.x) + h_hi(w.x)) + (h_lo(w.y) + h_hi(w.y)); }
    sm += __shfl_xor_sync(0xffffffffu, sm, 1); sm += __shfl_xor_sync(0xffffffffu, sm, 2);
    m[hi] = sm * (1.f / 96.f);
    float q = 0.f;
    for (int s = 0; s < 6; s++) {
      uint2 w = lds64(ad + s * 512 + hi * 8);
      float d0 = h_lo(w.x) - m[hi], d1 = h_hi(w.x) - m[hi], d2 = h_lo(w.y) - m[hi], d3 = h_hi(w.y) - m[hi];
      q += (d0 * d0 + d1 * d1) + (d2 * d2 + d3 * d3);
    }
    q += __shfl_xor_sync(0xffffffffu, q, 1); q += __shfl_xor_sync(0xffffffffu, q, 2);
    r[hi] = rsqrtf(fmaf(q, 1.f / 96.f, 1e-5f)) * GELU_C3;
  }
  for (int s = 0; s < 6; s++) {
    uint32_t w[4]; lds128(w, ad + s * 512);
    sts128(ad + s * 512, make_uint4(pack_f16((h_lo(w[0]) - m[0]) * r[0], (h_hi(w[0]) - m[0]) * r[0]), pack_f16((h_lo(w[2]) - m[1]) * r[1], (h_hi(w[2]) - m[1]) * r[1]),
                                    pack_f16((h_lo(w[1]) - m[0]) * r[0], (h_hi(w[1]) - m[0]) * r[0]), pack_f16((h_lo(w[3]) - m[1]) * r[1], (h_hi(w[3]) - m[1]) * r[1])));
  }
  asm volatile("fence.proxy.async.shared::cta;" ::: "memory");
}

__device__ __forceinline__ uint32_t load_ln(uint32_t ad, uint32_t* a, uint32_t tag) {
  uint32_t raw[6][4];
#pragma unroll
  for (int s = 0; s < 6; s++) lds128(raw[s], ad + s * 512);
  const uint32_t stale = ((raw[0][0] ^ tag) | (raw[1][0] ^ tag)) | ((raw[2][0] ^ tag) | (raw[3][0] ^ tag)) | ((raw[4][0] ^ tag) | (raw[5][0] ^ tag));
  uint32_t sm[2];
#pragma unroll
  for (int hi = 0; hi < 2; hi++) {
    uint32_t s0 = h2add(raw[0][2 * hi], raw[1][2 * hi]), s1 = h2add(raw[0][2 * hi + 1], raw[1][2 * hi + 1]);
    uint32_t s2 = h2add(raw[2][2 * hi], raw[3][2 * hi]), s3 = h2add(raw[2][2 * hi + 1], raw[3][2 * hi + 1]);
    uint32_t s4 = h2add(raw[4][2 * hi], raw[5][2 * hi]), s5 = h2add(raw[4][2 * hi + 1], raw[5][2 * hi + 1]);
    sm[hi] = h2add(h2add(h2add(s0, s1), h2add(s2, s3)), h2add(s4, s5));
  }
  uint32_t s = h2add(prmt(sm[0], sm[1], 0x5410), prmt(sm[0], sm[1], 0x7632));
  s = h2add(s, __shfl_xor_sync(0xffffffffu, s, 1));
  s = h2add(s, __shfl_xor_sync(0xffffffffu, s, 2));
  const uint32_t nm = h2mul(s, 0xA155A155u);
  uint32_t qq[2];
#pragma unroll
  for (int hi = 0; hi < 2; hi++) {
    const uint32_t m = hi ? h2hi(nm) : h2lo(nm);
    uint32_t q0 = 0, q1 = 0;
#pragma unroll
    for (int k = 0; k < 6; k++) {
      uint32_t d0 = h2add(raw[k][2 * hi], m), d1 = h2add(raw[k][2 * hi + 1], m);
      raw[k][2 * hi] = d0; raw[k][2 * hi + 1] = d1;
      q0 = k ? h2fma(d0, d0, q0) : h2mul(d0, d0);
      q1 = k ? h2fma(d1, d1, q1) : h2mul(d1, d1);
    }
    qq[hi] = h2add(q0, q1);
  }
  uint32_t q = h2add(prmt(qq[0], qq[1], 0x5410), prmt(qq[0], qq[1], 0x7632));
  q = h2add(q, __shfl_xor_sync(0xffffffffu, q, 1));
  q = h2add(q, __shfl_xor_sync(0xffffffffu, q, 2));
  const float r0 = rsqrtf(fmaf(h_lo(q), 1.f / 96.f, 1e-5f)) * GELU_C3, r1 = rsqrtf(fmaf(h_hi(q), 1.f / 96.f, 1e-5f)) * GELU_C3;
  const uint32_t r = pack_f16(r0, r1);
#pragma unroll
  for (int k = 0; k < 6; k++) {
    a[4 * k] = h2mul(raw[k][0], h2lo(r)); a[4 * k + 2] = h2mul(raw[k][1], h2lo(r));
    a[4 * k + 1] = h2mul(raw[k][2], h2hi(r)); a[4 * k + 3] = h2mul(raw[k][3], h2hi(r));
  }
  return (((q & 0x7c007c00u) + 0x04000400u) & 0x80008000u) | (stale & 1);
}

__device__ __forceinline__ void gemm1(uint32_t* p, const uint32_t* a, uint64_t d1, int c) {
  wgmma_n48_f16<0>(p, a, d1 + c * (1536 >> 4));
#pragma unroll
  for (int s = 1; s < 6; s++) wgmma_n48_f16<1>(p, a + 4 * s, d1 + c * (1536 >> 4) + s * (12288 >> 4));
}

__device__ __forceinline__ void gemm1_piece(uint32_t* p, const uint32_t* a, uint64_t d1, int c, int u) {
  if (u == 0) wgmma_n48_f16<0>(p, a, d1 + c * (1536 >> 4)); else wgmma_n48_f16<1>(p, a + 8 * u, d1 + c * (1536 >> 4) + 2 * u * (12288 >> 4));
  wgmma_n48_f16<1>(p, a + 8 * u + 4, d1 + c * (1536 >> 4) + (2 * u + 1) * (12288 >> 4));
}
__device__ __forceinline__ void fetch_a(uint32_t abuf, uint32_t bar, const unsigned char* src) {
  asm volatile("{\n.reg .pred p;\nelect.sync _|p, 0xffffffff;\n"
               "@p mbarrier.arrive.expect_tx.shared::cta.b64 _, [%1], 3072;\n"
               "@p cp.async.bulk.shared::cluster.global.mbarrier::complete_tx::bytes [%0], [%2], 3072, [%1];\n}"
               ::"r"(abuf), "r"(bar), "l"(src) : "memory");
}
__device__ __forceinline__ void fetch_x(uint32_t xbuf, uint32_t bar, const CUtensorMap* tm, uint32_t c0, uint32_t c12, uint64_t pol) {
  asm volatile("{\n.reg .pred p;\nelect.sync _|p, 0xffffffff;\n"
               "@p mbarrier.arrive.expect_tx.shared::cta.b64 _, [%1], 3072;\n"
               "@p cp.async.bulk.tensor.3d.shared::cluster.global.mbarrier::complete_tx::bytes.L2::cache_hint [%0], [%2, {%3, %4, %5}], [%1], %6;\n}"
               ::"r"(xbuf), "r"(bar), "l"(tm), "r"(c0), "r"(c12 & 255), "r"(c12 >> 8), "l"(pol) : "memory");
}
__device__ __forceinline__ void wait_ready(const uint32_t* p, uint32_t target) {
  int spins = 0;
  while (ld_relaxed(p) != target) { __nanosleep(32); if (++spins > SPIN_LIMIT) __trap(); }
}
__device__ __forceinline__ uint32_t slot_tag(int gm, int j, uint32_t epoch) {
  const int len = min(PLEN, 1024 - gm * PLEN), writes = (len - (j & (RING - 1)) + RING - 1) / RING;
  return (epoch * writes + j / RING + 1) & 1;
}

__device__ __forceinline__ void build_tile_list(uint32_t sb, int k, int idx, bool tabled, bool is_conv, uint32_t epoch) {
  int n = -1;
  if (tabled) { if (k < 48) n = (int16_t)g_sched[idx][k]; }
  else if (!is_conv) {
    const int i = k * (gridDim.x - NCONV) + idx, full = (1024 - (NG - 1) * PLEN) * NG;
    const int r = i >> 2, j = r < full ? r / NG : (r - full) / (NG - 1) + full / NG, gm = r < full ? r % NG : (r - full) % (NG - 1);
    if (i < 4096) n = (gm * PLEN + j) * 4 + (i & 3);
  }
  const int P = n >> 2, gm = P / PLEN, j = P - gm * PLEN;
  sts128(sb + MISC + 512 + k * 16, make_uint4(P, (((j & (RING - 1)) * NG + gm) * 4 + (n & 3)) * TILEB + slot_tag(gm, j, epoch),
                                              (n & 2) * 384, ((n >> 10) * 8 + (n & 1) * 4) | ((n & 1020) << 7)));
  if (k == 0) sts32(sb + MISC + 256, epoch + 1);
}

__device__ __forceinline__ void mlp_setup(uint32_t sb, Globals* gs, int id, const __nv_bfloat16* __restrict__ w1, const __nv_bfloat16* __restrict__ w2,
                                          int idx, bool tabled, int warp, int lane) {
  const int rot = idx % 6;
  PROF2_AT(lane == 0, 400 + warp);
  if (warp < 12) {
    const int m = warp >= 6; int s = warp - 6 * m + rot; if (s >= 6) s -= 6;
    copy_weights(sb, 6 * m + s, (const char*)(m ? w2 : w1) + s * 12288);
  }
  __syncthreads();
  PROF2_AT(threadIdx.x == 0, 416);
  if (warp >= 12) build_tile_list(sb, threadIdx.x - 384, idx, tabled, false, ld_relaxed(&gs->epoch[id]));
  PROF2_AT(lane == 0, 420 + warp);
  convert_weights(sb, sb + WBAR, rot, warp, lane);
  PROF2_AT(lane == 0, 460 + warp);
  asm volatile("fence.proxy.async.shared::cta;" ::: "memory");
  __syncthreads();
  if (threadIdx.x == 480) {
    const uint32_t e1 = lds32(sb + MISC + 256);
    gs->epoch[id] = e1;
    if (idx < 24 && (idx & 1)) {
      asm volatile("cp.async.bulk.global.shared::cta.bulk_group [%0], [%1], 12288;\ncp.async.bulk.commit_group;\ncp.async.bulk.wait_group 0;\nfence.proxy.async.global;\n"
                   "red.release.gpu.global.add.u32 [%2], 1;" ::"l"(gs->wimg + (idx >> 1) * 12288), "r"(sb + (idx >> 1) * 12288), "l"(gs->wflag) : "memory");
    }
  }
  __syncwarp();
}

__device__ __forceinline__ void mlp_role(uint32_t sb, Globals* gs, const CUtensorMap* tmr, __nv_bfloat16* __restrict__ out) {
  uint32_t tid;
  asm volatile("mov.u32 %0, %%tid.x;" : "=r"(tid));
  const int warp = __shfl_sync(0xffffffffu, tid >> 5, 0), lane = tid & 31;
  const int wg = warp >> 2, w = warp & 3, g = lane >> 2, t = lane & 3;
  const uint32_t abuf = sb + ABUF + warp * 3072, xbuf = sb + XBUF + (warp & 7) * 3072;
  const uint32_t bar = sb + MISC + warp * 8, obar = sb + MISC + (warp ^ 8) * 8;
  const uint32_t tl = sb + MISC + 512;
  PROF_AT(threadIdx.x == 0, 1); PROF_VAL(threadIdx.x == 0, 8, clock64());
  const uint32_t rtarget = 3 * lds32(sb + MISC + 256);
  const uint64_t d1 = ((uint64_t)(768 >> 4) << 16) | ((uint64_t)(128 >> 4) << 32) | (uint64_t)(((sb + W1S) >> 4) & 0x3fff);
  const uint64_t d2 = ((uint64_t)(12288 >> 4) << 16) | ((uint64_t)(128 >> 4) << 32) | (uint64_t)(((sb + W2S) >> 4) & 0x3fff);
  const uint32_t ad = abuf + t * 128 + ((g ^ (2 * t)) << 4);
  const uint32_t xd = xbuf + g * 192 + t * 16;
  const int mybar = 1 + wg, nxtbar = 1 + ((wg + 1) & 3);
  const uint64_t pol = pol_evict_first();
  const unsigned char* const asrc = gs->scratch + w * 3072;
  uint32_t pha = 0, phx = 0, tp = tl + wg * 16;
  bool pending = true;
  uint32_t cur[4];
  lds128(cur, tp);
  while ((int)cur[0] >= 0) {
    PROF2_AT((threadIdx.x & 127) == 0, 16 + (tp - tl) / 4); PROF2_VAL((threadIdx.x & 127) == 0, 16 + (tp - tl) / 4 + 3, pending);
    uint32_t a[24], p[8][12], gg[8][12], acc[24];
    if (pending) {
      wait_ready(&gs->ready[cur[0]], rtarget);
      fetch_a(abuf, bar, asrc + (cur[1] & ~1u));
      if (tp < tl + 32) fetch_x(xbuf, bar + 128, tmr, cur[2] + w * 192, cur[3], pol);
    }
    const uint2 n4 = lds64(tp + 64);
    const int sig = lds32(tp + 16);
    for (int tries = 0;; tries++) {
      mbar_wait(bar, pha); pha ^= 1;
      PROF2_AT((threadIdx.x & 127) == 0, 16 + (tp - tl) / 4 + 1);
      const uint32_t st = load_ln(ad, a, cur[1]);
      if (!__any_sync(0xffffffffu, st != 0)) break;
      if (!__any_sync(0xffffffffu, st & 1)) {
        ln_wide(ad);
#pragma unroll
        for (int k = 0; k < 6; k++) lds128(a + 4 * k, ad + k * 512);
        break;
      }
      if (tries > SPIN_LIMIT) __trap();
      fetch_a(abuf, bar, asrc + (cur[1] & ~1u));
    }
    red_add_elect(&gs->cons[cur[0]]);
    if (tp != tl) asm volatile("bar.sync %0, 256;" ::"r"(mybar) : "memory");
    PROF2_AT((threadIdx.x & 127) == 0, 16 + (tp - tl) / 4 + 2);
    uint32_t rdy = 0;
    wg_fence();
    gemm1(p[0], a, d1, 0); wg_commit();
    gemm1_piece(p[1], a, d1, 1, 0); wg_commit();
#pragma unroll
    for (int j = 0; j < 24; j++) {
      const int c = j / 3, s = j % 3;
      if (j == JB1) {
        rdy = ld_relaxed(&gs->ready[n4.x & 1023]);
        wg_wait<0>();
        mbar_wait(bar + 128, phx); phx ^= 1;
      } else if (j == JB2) {
        wg_wait<0>();
        pending = rdy != rtarget;
        if (!pending && (int)n4.x >= 0) fetch_a(abuf, bar, asrc + (n4.y & ~1u));
      } else wg_wait<1>();
      if (j == TRIG) asm volatile("{.reg .pred p; setp.ge.s32 p, %1, 0; @p bar.arrive %0, 256;}" ::"r"(nxtbar), "r"(sig) : "memory");
#pragma unroll
      for (int i = 0; i < 4; i++) gg[c][4 * s + i] = gelu_h2(p[c][4 * s + i]);
      wg_fence();
      if (j == 0) wgmma_n96_f16<0>(acc, gg[c], d2); else wgmma_n96_f16<1>(acc, &gg[c][4 * s], d2 + (16 * s + c) * (1536 >> 4));
      if (j < 20) gemm1_piece(p[(j + 1) / 3 + 1], a, d1, (j + 1) / 3 + 1, (j + 1) % 3);
      wg_commit();
    }
    wg_wait<0>();
    if (JB2 == 24) {
      pending = rdy != rtarget;
      if (!pending && (int)n4.x >= 0) fetch_a(abuf, bar, asrc + (n4.y & ~1u));
    }
    char* const op = (char*)out + (size_t)(cur[3] >> 8) * (512 * 192) + ((cur[3] & 255) + (g >> 1)) * 3072 + cur[2] * 2 + (2 * w + (g & 1)) * 192 + t * 16;
    uint32_t n2[4];
    lds128(n2, tp + 32);
    tp += 64;
    lds128(cur, tp);
#pragma unroll
    for (int hi = 0; hi < 2; hi++)
#pragma unroll
      for (int j = 0; j < 3; j++) {
        uint32_t xr[4];
        lds128(xr, xd + hi * 1536 + j * 64);
        uint4 o;
        o.x = hadd2_bf16(xr[0], pack_bf16(h_lo(acc[8 * j + hi]), h_hi(acc[8 * j + hi])));
        o.y = hadd2_bf16(xr[1], pack_bf16(h_lo(acc[8 * j + 2 + hi]), h_hi(acc[8 * j + 2 + hi])));
        o.z = hadd2_bf16(xr[2], pack_bf16(h_lo(acc[8 * j + 4 + hi]), h_hi(acc[8 * j + 4 + hi])));
        o.w = hadd2_bf16(xr[3], pack_bf16(h_lo(acc[8 * j + 6 + hi]), h_hi(acc[8 * j + 6 + hi])));
        stg128_stream(op + hi * (512 * 192) + j * 64, o, pol);
      }
    __syncwarp();
    if ((int)n2[0] >= 0) fetch_x(xbuf, obar + 128, tmr, n2[2] + w * 192, n2[3], pol);
  }
  PROF_AT((threadIdx.x & 127) == 0, 4 + wg); PROF_VAL(threadIdx.x == 0, 9, clock64());
}

__device__ __forceinline__ void conv_compute(uint32_t sb, Globals* gs, const __nv_bfloat16* __restrict__ dw, int third, int nit, int off, int warp, int lane) {
  const int g = lane >> 2, t = lane & 3;
  const uint32_t full = sb + CM;
  uint32_t A[4][4][4];
  {
    uint2 w[2][9];
#pragma unroll
    for (int h = 0; h < 2; h++) {
      const int j = (4 * h + t - g) & 7;
      const uint2* src = (const uint2*)(dw + min(j, 6) * 96 + third * 32 + warp * 4);
      w[h][0] = make_uint2(0u, 0u); w[h][8] = make_uint2(0u, 0u);
#pragma unroll
      for (int i = 0; i < 7; i++) asm volatile("ld.global.nc.v2.b32 {%0,%1}, [%2];" : "=r"(w[h][i + 1].x), "=r"(w[h][i + 1].y) : "l"(src + i * 168) : "memory");
    }
    asm volatile("setmaxnreg.inc.sync.aligned.u32 %0;" ::"n"(CREGS));
    PROF2_AT(threadIdx.x == 0, 11);
#pragma unroll
    for (int h = 0; h < 2; h++)
      if (((4 * h + t - g) & 7) == 7) {
#pragma unroll
        for (int i = 1; i < 8; i++) w[h][i] = make_uint2(0u, 0u);
      }
#pragma unroll
    for (int u = 0; u < 4; u++)
#pragma unroll
      for (int r = 0; r < 4; r++) {
        const int h = r >> 1, i0 = 2 * u - (r & 1) + 1;
        A[0][u][r] = prmt(w[h][i0].x, w[h][i0 + 1].x, 0x5410); A[1][u][r] = prmt(w[h][i0].x, w[h][i0 + 1].x, 0x7632);
        A[2][u][r] = prmt(w[h][i0].y, w[h][i0 + 1].y, 0x5410); A[3][u][r] = prmt(w[h][i0].y, w[h][i0 + 1].y, 0x7632);
      }
  }
  uint32_t meta = 0;
#pragma unroll
  for (int a = 0; a < 4; a++) meta |= ((4 * (t & 1) + a + 1 >= g) ? 0x80008u : 0xD000Du) << (4 * a);
  meta = __shfl_sync(0xffffffffu, meta, lane);
  float S[2][4][3][4];
#pragma unroll
  for (int s = 0; s < 2; s++)
#pragma unroll
    for (int c = 0; c < 4; c++)
#pragma unroll
      for (int i = 0; i < 3; i++)
#pragma unroll
        for (int k = 0; k < 4; k++) S[s][c][i][k] = 0.f;
  uint32_t aq[4];
#pragma unroll
  for (int q = 0; q < 4; q++) {
    const int pp = (g & 1) * 140 + (t & 1) * 70 + 16 * (g >> 1) + 2 * q + (t >> 1);
    aq[q] = __shfl_sync(0xffffffffu, sb + RBUF + pp * 64 + (((warp >> 1) ^ ((pp >> 1) & 3)) << 4) + (warp & 1) * 8, lane);
  }
  const int Q = third * 8 + warp;
  unsigned char* const obase = gs->scratch + (g >> 1) * 3072 + Q * 128 + (((2 * t + (g & 1)) ^ (2 * (Q & 3))) << 4);
  const float zero4[4] = {0.f, 0.f, 0.f, 0.f};
  uint32_t sofs = off * SLOTB, bar = full + off * 8, ph = 0;
  uint2 X[3][4];
  PROF_AT(threadIdx.x == 0, 12);
  asm volatile("bar.sync 0, 512;" ::: "memory");
  PROF2_AT(threadIdx.x == 0, 10);
  mbar_wait(bar, 0);
  PROF_AT(threadIdx.x == 0, 14);
#pragma unroll
  for (int j = 0; j < 2; j++)
#pragma unroll
    for (int q = 0; q < 4; q++) X[j][q] = lds64(aq[q] + sofs + j * 512);
  for (uint32_t ot = sb + CTAB; ot < sb + CTAB + nit * 16; ot += 16) {
    const uint2 oe = lds64(ot);
    unsigned char* const o = obase + oe.x;
    const uint32_t dbar = bar + 64;
#pragma unroll
    for (int s = 0; s < 2; s++) {
      uint32_t B[4][4];
      if (s == 1) {
        sofs += SLOTB; bar += 8;
        if (sofs == NSLOT * SLOTB) { sofs = 0; bar = full; ph ^= 1; }
        mbar_wait(bar, ph);
      }
#pragma unroll
      for (int c = 0; c < 4; c++)
#pragma unroll
        for (int q = 0; q < 4; q++) B[c][q] = prmt(c < 2 ? X[s][q].x : X[s][q].y, c < 2 ? X[s + 1][q].x : X[s + 1][q].y, (c & 1) ? 0x7632 : 0x5410);
      if (s == 0) {
#pragma unroll
        for (int q = 0; q < 4; q++) X[2][q] = lds64(aq[q] + sofs + 2 * 512);
      } else {
#pragma unroll
        for (int j = 0; j < 2; j++)
#pragma unroll
          for (int q = 0; q < 4; q++) X[j][q] = lds64(aq[q] + sofs + j * 512);
      }
      float T[4][4];
      if (CFN & 1) SCHED_FENCE();
#pragma unroll
      for (int c = 0; c < 4; c++) mma_sp(T[c], A[c][3], B[c], S[s][c][2], meta);
#pragma unroll
      for (int c = 0; c < 4; c++) mma_sp(S[s][c][2], A[c][2], B[c], S[s][c][1], meta);
      if (CFN & 2) SCHED_FENCE();
      stg128(o + (2 * s) * TILEB, make_uint4((pack_f16_sat(T[0][0], T[1][0]) & ~1u) | oe.y, pack_f16_sat(T[2][0], T[3][0]), pack_f16_sat(T[0][2], T[1][2]), pack_f16_sat(T[2][2], T[3][2])));
      stg128(o + (2 * s + 1) * TILEB, make_uint4((pack_f16_sat(T[0][1], T[1][1]) & ~1u) | oe.y, pack_f16_sat(T[2][1], T[3][1]), pack_f16_sat(T[0][3], T[1][3]), pack_f16_sat(T[2][3], T[3][3])));
      if (s == 1) mbar_arrive_elect(dbar);
      if (CFN & 4) SCHED_FENCE();
#pragma unroll
      for (int c = 0; c < 4; c++) mma_sp(S[s][c][1], A[c][1], B[c], S[s][c][0], meta);
#pragma unroll
      for (int c = 0; c < 4; c++) mma_sp(S[s][c][0], A[c][0], B[c], zero4, meta);
    }
  }
  PROF_AT(threadIdx.x == 0, 13);
}

__device__ __forceinline__ void conv_loader(uint32_t sb, Globals* gs, const CUtensorMap* tmx, int Vs, int nit, int off, int cidx, int third, int k) {
  static_assert(AHEAD > 4 && AHEAD <= NSLOT && NCONV >= 24, "loader");
  const uint32_t full = sb + CM;
#pragma unroll
  for (int h = 0; h < 2; h++) {
    const int s = (k + off + 4 * h) & 7;
    asm volatile("{\n.reg .pred p, q;\nelect.sync _|p, 0xffffffff;\n@p mbarrier.init.shared::cta.b64 [%0], 2;\n@p mbarrier.init.shared::cta.b64 [%0+64], 8;\n"
                 "setp.ne.and.u32 q, %1, 0, p;\n@q mbarrier.arrive.shared::cta.b64 _, [%0], 2;\n@q mbarrier.arrive.shared::cta.b64 _, [%0+64], 8;\n}"
                 ::"r"(full + s * 8), "r"((uint32_t)(s < off)) : "memory");
  }
  if (k == 0) mbar_init_elect(sb + WBAR, 2);
  asm volatile("fence.mbarrier_init.release.cluster;" ::: "memory");
  bool synced = false;
#pragma unroll 1
  for (int it = k; it < nit + AHEAD; it += 4) {
    const int u = it + off, s = u & 7, V = Vs + it, st = (V - 1) / 258;
    if (it >= AHEAD) {
      if (!synced) { asm volatile("bar.sync 0, 512;" ::: "memory"); synced = true; }
      const uint32_t ro = lds32(sb + CTAB + (it - AHEAD) * 16 + 8);
      mbar_wait(full + 64 + ((u - AHEAD) & 7) * 8, ((u - AHEAD) >> 3) & 1);
      red_add_elect((uint32_t*)((char*)gs + ro));
      PROF_AT((threadIdx.x & 31) == 0 && ((it - AHEAD) & (PROF > 1 ? 7 : 15)) == 0, 200 + it - AHEAD);
    }
    if (it <= nit)
      asm volatile("{\n.reg .pred p;\n.reg .s32 c2;\n.reg .u32 d2;\nelect.sync _|p, 0xffffffff;\nadd.s32 c2, %4, 64;\nadd.u32 d2, %0, 8960;\n"
                   "@p mbarrier.arrive.expect_tx.shared::cta.b64 _, [%2], 17920;\n"
                   "@p cp.async.bulk.tensor.3d.shared::cluster.global.mbarrier::complete_tx::bytes [%0], [%1, {%3, %4, %5}], [%2];\n"
                   "@p cp.async.bulk.tensor.3d.shared::cluster.global.mbarrier::complete_tx::bytes [d2], [%1, {%3, c2, %5}], [%2];\n}"
                   ::"r"(sb + RBUF + s * SLOTB), "l"(tmx), "r"(full + s * 8), "r"(third * 32), "r"(st * 128 - 3), "r"(2 * (V - st * 258) - 3) : "memory");
    if (it >= nit - 16) {
      if (it < nit - 12) {
        wait_ready(gs->wflag, 12 * lds32(sb + MISC + 256));
        asm volatile("fence.acquire.gpu;\nfence.proxy.async.global;" ::: "memory");
        if (cidx < 24) asm volatile("{.reg .pred p; elect.sync _|p, 0xffffffff; @p cp.async.bulk.prefetch.L2.global [%0], 1536;}" ::"l"(gs->wimg + (cidx * 4 + k) * 1536) : "memory");
      }
      const int m = it == nit ? 0 : W2S;
      if (it == nit || it == nit + AHEAD - 4)
        asm volatile("{\n.reg .pred p;\nelect.sync _|p, 0xffffffff;\n@p mbarrier.arrive.expect_tx.shared::cta.b64 _, [%1], 73728;\n"
                     "@p cp.async.bulk.shared::cluster.global.mbarrier::complete_tx::bytes [%0], [%2], 73728, [%1];\n}"
                     ::"r"(sb + m), "r"(sb + WBAR), "l"(gs->wimg + m) : "memory");
    }
  }
}

__device__ __forceinline__ void conv_credit(uint32_t sb, Globals* gs, int P0, int nit, int off, uint32_t ctarget, int k) {
  const uint32_t full = sb + CM;
#pragma unroll 1
  for (int it = k + NSLOT; it <= nit; it += 4) {
    const int u = it + off, P = (int)lds32(sb + CTAB + it * 16 + 12) - RING;
    int spins = 0;
    mbar_wait(full + 64 + (u & 7) * 8, ((u >> 3) & 1) ^ 1);
    if (P >= P0) while (ld_relaxed(&gs->cons[P]) != ctarget) { __nanosleep(CSLEEP); if (++spins > SPIN_LIMIT) __trap(); }
    mbar_arrive_elect(full + (u & 7) * 8);
  }
}

__global__ void __launch_bounds__(512, 1) convnext_kernel(const __grid_constant__ CUtensorMap tmx, const __grid_constant__ CUtensorMap tmr, const __nv_bfloat16* __restrict__ dw,
                                                          const __nv_bfloat16* __restrict__ w1, const __nv_bfloat16* __restrict__ w2, __nv_bfloat16* __restrict__ out, Globals* gs) {
  extern __shared__ __align__(1024) unsigned char smem[];
  const uint32_t sb = smem_u32(smem);
  const int warp = __shfl_sync(0xffffffffu, threadIdx.x >> 5, 0), lane = threadIdx.x & 31;
  PROF_AT(threadIdx.x == 0, 0);
  if (threadIdx.x == 256) asm volatile("prefetch.tensormap [%0];" ::"l"(&tmx) : "memory");
  if (threadIdx.x == 288) asm volatile("prefetch.tensormap [%0];" ::"l"(&tmr) : "memory");
  uint32_t smid, nsmid;
  asm volatile("mov.u32 %0, %%smid;" : "=r"(smid));
  asm volatile("mov.u32 %0, %%nsmid;" : "=r"(nsmid));
  const bool tabled = TABLED && gridDim.x == 132 && nsmid == 132;
  const int id = tabled ? smid : blockIdx.x;
  int cidx, idx;
  int is_conv;
  if (tabled) {
    idx = smid;
    const int k = (smid - 60) / 14, r = smid - 60 - 14 * k;
    is_conv = smid < 48 ? !(smid & 1) : (smid >= 60 && smid <= 90 && (r & ~2) == 0);
    cidx = smid < 48 ? ((smid >> 1) & 7) * 3 + (smid >> 4) : 24 + (r >> 1) * 3 + k;
  } else {
    cidx = (blockIdx.x * NCONV) / gridDim.x;
    is_conv = ((blockIdx.x + 1) * NCONV) / gridDim.x != cidx;
    idx = blockIdx.x - cidx;
  }
  PROF_VAL(threadIdx.x == 0, 2, is_conv ? 1000 + cidx : idx);
  mbar_init_elect(sb + MISC + warp * 8, 1); mbar_init_elect(sb + MISC + 128 + warp * 8, 1);
  asm volatile("fence.mbarrier_init.release.cluster;" ::: "memory");
  if (is_conv) {
    const int gm = cidx / 3, third = cidx - gm * 3;
    const int P0 = gm * PLEN, P1 = min(P0 + PLEN, 1024) - 1;
    const int Vs = P0 + 2 * (P0 >> 8) + ((P0 & 255) ? 0 : 1);
    const int nit = P1 + 2 * (P1 >> 8) + 4 - Vs, off = (7 - nit) & 7;
    if (warp < 8) {
      conv_compute(sb, gs, dw, third, nit, off, warp, lane);
      asm volatile("setmaxnreg.dec.sync.aligned.u32 128;");
    } else if (warp >= 12) {
      asm volatile("setmaxnreg.dec.sync.aligned.u32 24;");
      const uint32_t epoch = ld_relaxed(&gs->epoch[id]);
#pragma unroll 1
      for (int it = threadIdx.x - 384; it <= nit; it += 128) {
        const int V = Vs + it, so = max(V - 3, 0) / 258, po = V - 3 - so * 258, P = so * 256 + po;
        const bool ok = po < 256 && P >= P0 && P <= P1;
        sts128(sb + CTAB + it * 16, make_uint4((ok ? ((P - P0) & (RING - 1)) * NG + gm : RING * NG) * (4 * TILEB), slot_tag(gm, max(P - P0, 0), epoch),
                                               offsetof(Globals, ready) + (ok ? P : 1024) * 4, ok ? P : -1));
      }
      asm volatile("bar.sync 0, 512;" ::: "memory");
      mbar_arrive_elect(sb + CM + ((((warp + 2) & 3) + off) & 7) * 8);
      mbar_arrive_elect(sb + CM + ((((warp + 2) & 3) + off + 4) & 7) * 8);
      build_tile_list(sb, threadIdx.x - 384, idx, tabled, true, epoch);
      if (threadIdx.x == 384) gs->epoch[id] = epoch + 1;
      conv_credit(sb, gs, P0, nit, off, 16 * (epoch + 1), (warp + 2) & 3);
      mbar_wait(sb + CM + 64 + 3 * 8, ((nit + off) >> 3) & 1);
      mbar_wait(sb + CM + 64 + 6 * 8, ((nit + off) >> 3) & 1);
      asm volatile("setmaxnreg.inc.sync.aligned.u32 128;");
    } else {
      asm volatile("setmaxnreg.dec.sync.aligned.u32 %0;" ::"n"(488 - 2 * CREGS));
      conv_loader(sb, gs, &tmx, Vs, nit, off, cidx, third, warp & 3);
      mbar_wait(sb + CM + 64 + 3 * 8, ((nit + off) >> 3) & 1);
      mbar_wait(sb + CM + 64 + 6 * 8, ((nit + off) >> 3) & 1);
      asm volatile("setmaxnreg.inc.sync.aligned.u32 128;");
    }
    PROF2_AT((threadIdx.x & 31) == 0, 400 + (threadIdx.x >> 5));
    mbar_wait(sb + WBAR, 0);
    asm volatile("bar.sync 0, 512;" ::: "memory");
  } else {
    mlp_setup(sb, gs, id, w1, w2, idx, tabled, warp, lane);
  }
  mlp_role(sb, gs, &tmr, out);
}

typedef CUresult (*PFN_encodeTiled)(CUtensorMap*, CUtensorMapDataType, cuuint32_t, void*, const cuuint64_t*, const cuuint64_t*, const cuuint32_t*, const cuuint32_t*,
                                    CUtensorMapInterleave, CUtensorMapSwizzle, CUtensorMapL2promotion, CUtensorMapFloatOOBfill);

extern "C" void kernel_launch(void* const* d_in, const int* in_sizes, int n_in, void* d_out, int out_size) {
  const __nv_bfloat16* x = (const __nv_bfloat16*)d_in[0];
  const __nv_bfloat16* dw = (const __nv_bfloat16*)d_in[1];
  const __nv_bfloat16* w1 = (const __nv_bfloat16*)d_in[2];
  const __nv_bfloat16* w2 = (const __nv_bfloat16*)d_in[3];
  static PFN_encodeTiled encode = nullptr;
  static int nsm = 0;
  static Globals* gs = nullptr;
  if (!encode) {
    void* fn = nullptr; cudaDriverEntryPointQueryResult qr;
    cudaGetDriverEntryPoint("cuTensorMapEncodeTiled", &fn, cudaEnableDefault, &qr);
    encode = (PFN_encodeTiled)fn;
    cudaGetSymbolAddress((void**)&gs, g_state);
    int dev = 0; cudaGetDevice(&dev);
    cudaDeviceGetAttribute(&nsm, cudaDevAttrMultiProcessorCount, dev);
    cudaFuncSetAttribute(convnext_kernel, cudaFuncAttributeMaxDynamicSharedMemorySize, SMEM_BYTES);
  }
  CUtensorMap tm;
  cuuint64_t dims[3] = {96, 512, 512}, strides[2] = {192, 192 * 512};
  cuuint32_t box[3] = {32, 70, 2}, es[3] = {1, 1, 1};
  encode(&tm, CU_TENSOR_MAP_DATA_TYPE_BFLOAT16, 3, (void*)x, dims, strides, box, es, CU_TENSOR_MAP_INTERLEAVE_NONE, CU_TENSOR_MAP_SWIZZLE_64B,
         PROMO, CU_TENSOR_MAP_FLOAT_OOB_FILL_NONE);
  CUtensorMap tr;
  cuuint64_t dims2[3] = {1536, 32, 512}, strides2[2] = {3072, 192 * 512};
  cuuint32_t box2[3] = {192, 4, 2};
  encode(&tr, CU_TENSOR_MAP_DATA_TYPE_BFLOAT16, 3, (void*)x, dims2, strides2, box2, es, CU_TENSOR_MAP_INTERLEAVE_NONE, CU_TENSOR_MAP_SWIZZLE_NONE,
         CU_TENSOR_MAP_L2_PROMOTION_NONE, CU_TENSOR_MAP_FLOAT_OOB_FILL_NONE);
  convnext_kernel<<<nsm, 512, SMEM_BYTES>>>(tm, tr, dw, w1, w2, (__nv_bfloat16*)d_out, gs);
}
```

```cpp
#include <cuda_runtime.h>
#include <cuda_bf16.h>
#include <cuda.h>
#include <stdint.h>
#include <stddef.h>

template<int SCALE_D> __device__ __forceinline__ void wgmma_n48_f16(uint32_t* d, const uint32_t* a, uint64_t desc) {
  if (SCALE_D == 0) asm volatile("wgmma.mma_async.sync.aligned.m64n48k16.f16.f16.f16 {%0,%1,%2,%3,%4,%5,%6,%7,%8,%9,%10,%11}, {%12,%13,%14,%15}, %16, 0, 1, 1, 1;"
    : "=r"(d[0]),"=r"(d[1]),"=r"(d[2]),"=r"(d[3]),"=r"(d[4]),"=r"(d[5]),"=r"(d[6]),"=r"(d[7]),"=r"(d[8]),"=r"(d[9]),"=r"(d[10]),"=r"(d[11])
    : "r"(a[0]),"r"(a[1]),"r"(a[2]),"r"(a[3]),"l"(desc));
  if (SCALE_D == 1) asm volatile("wgmma.mma_async.sync.aligned.m64n48k16.f16.f16.f16 {%0,%1,%2,%3,%4,%5,%6,%7,%8,%9,%10,%11}, {%12,%13,%14,%15}, %16, 1, 1, 1, 1;"
    : "+r"(d[0]),"+r"(d[1]),"+r"(d[2]),"+r"(d[3]),"+r"(d[4]),"+r"(d[5]),"+r"(d[6]),"+r"(d[7]),"+r"(d[8]),"+r"(d[9]),"+r"(d[10]),"+r"(d[11])
    : "r"(a[0]),"r"(a[1]),"r"(a[2]),"r"(a[3]),"l"(desc));
}

template<int SCALE_D> __device__ __forceinline__ void wgmma_n96_f16(uint32_t* d, const uint32_t* a, uint64_t desc) {
  if (SCALE_D == 0) asm volatile("wgmma.mma_async.sync.aligned.m64n96k16.f16.f16.f16 {%0,%1,%2,%3,%4,%5,%6,%7,%8,%9,%10,%11,%12,%13,%14,%15,%16,%17,%18,%19,%20,%21,%22,%23}, {%24,%25,%26,%27}, %28, 0, 1, 1, 1;"
    : "=r"(d[0]),"=r"(d[1]),"=r"(d[2]),"=r"(d[3]),"=r"(d[4]),"=r"(d[5]),"=r"(d[6]),"=r"(d[7]),"=r"(d[8]),"=r"(d[9]),"=r"(d[10]),"=r"(d[11]),"=r"(d[12]),"=r"(d[13]),"=r"(d[14]),"=r"(d[15]),"=r"(d[16]),"=r"(d[17]),"=r"(d[18]),"=r"(d[19]),"=r"(d[20]),"=r"(d[21]),"=r"(d[22]),"=r"(d[23])
    : "r"(a[0]),"r"(a[1]),"r"(a[2]),"r"(a[3]),"l"(desc));
  if (SCALE_D == 1) asm volatile("wgmma.mma_async.sync.aligned.m64n96k16.f16.f16.f16 {%0,%1,%2,%3,%4,%5,%6,%7,%8,%9,%10,%11,%12,%13,%14,%15,%16,%17,%18,%19,%20,%21,%22,%23}, {%24,%25,%26,%27}, %28, 1, 1, 1, 1;"
    : "+r"(d[0]),"+r"(d[1]),"+r"(d[2]),"+r"(d[3]),"+r"(d[4]),"+r"(d[5]),"+r"(d[6]),"+r"(d[7]),"+r"(d[8]),"+r"(d[9]),"+r"(d[10]),"+r"(d[11]),"+r"(d[12]),"+r"(d[13]),"+r"(d[14]),"+r"(d[15]),"+r"(d[16]),"+r"(d[17]),"+r"(d[18]),"+r"(d[19]),"+r"(d[20]),"+r"(d[21]),"+r"(d[22]),"+r"(d[23])
    : "r"(a[0]),"r"(a[1]),"r"(a[2]),"r"(a[3]),"l"(desc));
}

#define SCHED_NG 10
#define SCHED_LE 103
__device__ const uint16_t g_sched[132][48] = {
{367,3260,389,403,65535,65535,65535,65535,65535,65535,65535,65535,65535,65535,65535,65535,65535,65535,65535,65535,65535,65535,65535,65535,65535,65535,65535,65535,65535,65535,65535,65535,65535,65535,65535,65535,65535,65535,65535,65535,65535,65535,65535,65535,65535,65535,65535,65535},
{0,2483,22,2915,2925,2935,3765,73,83,93,2986,3816,124,134,144,3037,3867,175,185,195,3088,218,3111,3121,3939,259,269,279,3172,3990,310,320,330,3223,4041,361,374,387,400,65535,65535,65535,65535,65535,65535,65535,65535,65535},
{2838,788,802,815,65535,65535,65535,65535,65535,65535,65535,65535,65535,65535,65535,65535,65535,65535,65535,65535,65535,65535,65535,65535,65535,65535,65535,65535,65535,65535,65535,65535,65535,65535,65535,65535,65535,65535,65535,65535,65535,65535,65535,65535,65535,65535,65535,65535},
{412,422,432,442,452,463,473,483,493,503,514,524,534,544,554,565,575,585,595,605,616,628,638,649,659,669,679,689,700,710,720,730,740,751,761,771,784,798,811,65535,65535,65535,65535,65535,65535,65535,65535,65535},
{3646,1199,1213,1226,65535,65535,65535,65535,65535,65535,65535,65535,65535,65535,65535,65535,65535,65535,65535,65535,65535,65535,65535,65535,65535,65535,65535,65535,65535,65535,65535,65535,65535,65535,65535,65535,65535,65535,65535,65535,65535,65535,65535,65535,65535,65535,65535,65535},
{824,834,845,855,865,876,886,896,906,917,927,937,947,957,968,978,988,998,1008,1019,1029,1041,1051,1062,1072,1082,1092,1103,1113,1123,1133,1143,1154,1164,1174,1184,1196,1210,1223,65535,65535,65535,65535,65535,65535,65535,65535,65535},
{1603,1612,1624,1638,65535,65535,65535,65535,65535,65535,65535,65535,65535,65535,65535,65535,65535,65535,65535,65535,65535,65535,65535,65535,65535,65535,65535,65535,65535,65535,65535,65535,65535,65535,65535,65535,65535,65535,65535,65535,65535,65535,65535,65535,65535,65535,65535,65535},
{1236,1247,1257,1267,1278,1288,1298,1308,1318,1329,1339,1349,1359,1369,1380,1390,1400,1410,1420,1431,1441,1453,1464,1474,1484,1494,1504,1515,1525,1535,1545,1555,1566,1576,1586,1596,1609,1622,1636,65535,65535,65535,65535,65535,65535,65535,65535,65535},
{2015,2024,2037,2050,65535,65535,65535,65535,65535,65535,65535,65535,65535,65535,65535,65535,65535,65535,65535,65535,65535,65535,65535,65535,65535,65535,65535,65535,65535,65535,65535,65535,65535,65535,65535,65535,65535,65535,65535,65535,65535,65535,65535,65535,65535,65535,65535,65535},
{1648,1659,1669,1680,1690,1700,1710,1720,1731,1741,1751,1761,1771,1782,1792,1802,1812,1822,1833,1843,1853,1865,1876,1886,1896,1906,1917,1927,1937,1947,1957,1968,1978,1988,1998,2008,2021,2035,2048,65535,65535,65535,65535,65535,65535,65535,65535,65535},
{4058,2436,2449,2462,65535,65535,65535,65535,65535,65535,65535,65535,65535,65535,65535,65535,65535,65535,65535,65535,65535,65535,65535,65535,65535,65535,65535,65535,65535,65535,65535,65535,65535,65535,65535,65535,65535,65535,65535,65535,65535,65535,65535,65535,65535,65535,65535,65535},
{2060,2071,2081,2092,2102,2112,2122,2132,2143,2153,2163,2173,2183,2194,2204,2214,2224,2234,2245,2255,2265,2277,2288,2298,2308,2318,2329,2339,2349,2359,2369,2380,2390,2400,2410,2420,2433,2447,2460,65535,65535,65535,65535,65535,65535,65535,65535,65535},
{2839,3656,2861,2874,65535,65535,65535,65535,65535,65535,65535,65535,65535,65535,65535,65535,65535,65535,65535,65535,65535,65535,65535,65535,65535,65535,65535,65535,65535,65535,65535,65535,65535,65535,65535,65535,65535,65535,65535,65535,65535,65535,65535,65535,65535,65535,65535,65535},
{2472,3303,3313,3323,3333,3343,2534,3364,3374,3384,3394,2585,3415,3425,3435,3445,2636,3466,3476,3486,2677,2690,3507,3517,2720,3538,3548,3558,3568,2771,3589,3599,3609,3619,2822,3640,3654,2859,2872,65535,65535,65535,65535,65535,65535,65535,65535,65535},
{3251,4068,3273,3286,65535,65535,65535,65535,65535,65535,65535,65535,65535,65535,65535,65535,65535,65535,65535,65535,65535,65535,65535,65535,65535,65535,65535,65535,65535,65535,65535,65535,65535,65535,65535,65535,65535,65535,65535,65535,65535,65535,65535,65535,65535,65535,65535,65535},
{2884,2895,2905,3735,3745,3755,2946,2956,2966,2976,3806,2997,3007,3017,3027,3857,3048,3058,3068,3078,3089,3909,3919,3929,3132,3142,3152,3162,3980,3183,3193,3203,3213,4031,3234,3244,4065,3270,4091,65535,65535,65535,65535,65535,65535,65535,65535,65535},
{368,378,390,3682,65535,65535,65535,65535,65535,65535,65535,65535,65535,65535,65535,65535,65535,65535,65535,65535,65535,65535,65535,65535,65535,65535,65535,65535,65535,65535,65535,65535,65535,65535,65535,65535,65535,65535,65535,65535,65535,65535,65535,65535,65535,65535,65535,65535},
{1,3715,3725,33,43,53,63,3776,3786,3796,104,114,3827,3837,3847,155,165,3878,3888,3898,206,219,229,239,249,3950,3960,3970,290,300,4001,4011,4021,341,351,4052,375,4078,401,65535,65535,65535,65535,65535,65535,65535,65535,65535},
{780,789,3669,4094,65535,65535,65535,65535,65535,65535,65535,65535,65535,65535,65535,65535,65535,65535,65535,65535,65535,65535,65535,65535,65535,65535,65535,65535,65535,65535,65535,65535,65535,65535,65535,65535,65535,65535,65535,65535,65535,65535,65535,65535,65535,65535,65535,65535},
{413,423,433,443,453,464,474,484,494,504,515,525,535,545,555,566,576,586,596,606,617,629,639,650,660,670,680,690,701,711,721,731,741,752,762,772,785,799,812,65535,65535,65535,65535,65535,65535,65535,65535,65535},
{1192,1200,1214,1227,65535,65535,65535,65535,65535,65535,65535,65535,65535,65535,65535,65535,65535,65535,65535,65535,65535,65535,65535,65535,65535,65535,65535,65535,65535,65535,65535,65535,65535,65535,65535,65535,65535,65535,65535,65535,65535,65535,65535,65535,65535,65535,65535,65535},
{825,835,846,856,866,877,887,897,907,918,928,938,948,958,969,979,989,999,1009,1020,1030,1042,1052,1063,1073,1083,1093,1104,1114,1124,1134,1144,1155,1165,1175,1185,1197,1211,1224,65535,65535,65535,65535,65535,65535,65535,65535,65535},
{1604,1613,1625,1639,65535,65535,65535,65535,65535,65535,65535,65535,65535,65535,65535,65535,65535,65535,65535,65535,65535,65535,65535,65535,65535,65535,65535,65535,65535,65535,65535,65535,65535,65535,65535,65535,65535,65535,65535,65535,65535,65535,65535,65535,65535,65535,65535,65535},
{1237,1248,1258,1268,1279,1289,1299,1309,1319,1330,1340,1350,1360,1370,1381,1391,1401,1411,1421,1432,1442,1454,1465,1475,1485,1495,1505,1516,1526,1536,1546,1556,1567,1577,1587,1597,1610,1623,1637,65535,65535,65535,65535,65535,65535,65535,65535,65535},
{2016,2025,2038,2051,65535,65535,65535,65535,65535,65535,65535,65535,65535,65535,65535,65535,65535,65535,65535,65535,65535,65535,65535,65535,65535,65535,65535,65535,65535,65535,65535,65535,65535,65535,65535,65535,65535,65535,65535,65535,65535,65535,65535,65535,65535,65535,65535,65535},
{1649,1660,1670,1681,1691,1701,1711,1721,1732,1742,1752,1762,1772,1783,1793,1803,1813,1823,1834,1844,1854,1866,1877,1887,1897,1907,1918,1928,1938,1948,1958,1969,1979,1989,1999,2009,2022,2036,2049,65535,65535,65535,65535,65535,65535,65535,65535,65535},
{2428,2437,2450,2463,65535,65535,65535,65535,65535,65535,65535,65535,65535,65535,65535,65535,65535,65535,65535,65535,65535,65535,65535,65535,65535,65535,65535,65535,65535,65535,65535,65535,65535,65535,65535,65535,65535,65535,65535,65535,65535,65535,65535,65535,65535,65535,65535,65535},
{2061,2072,2082,2093,2103,2113,2123,2133,2144,2154,2164,2174,2184,2195,2205,2215,2225,2235,2246,2256,2266,2278,2289,2299,2309,2319,2330,2340,2350,2360,2370,2381,2391,2401,2411,2421,2434,2448,2461,65535,65535,65535,65535,65535,65535,65535,65535,65535},
{3647,2849,2862,2875,65535,65535,65535,65535,65535,65535,65535,65535,65535,65535,65535,65535,65535,65535,65535,65535,65535,65535,65535,65535,65535,65535,65535,65535,65535,65535,65535,65535,65535,65535,65535,65535,65535,65535,65535,65535,65535,65535,65535,65535,65535,65535,65535,65535},
{2473,2484,2494,2504,3334,3344,2535,2545,2555,2565,3395,2586,2596,2606,2616,3446,2637,2647,2657,2667,2678,3498,3508,3518,2721,2731,2741,2751,3569,2772,2782,2792,2802,3620,2823,2833,2847,3667,3680,65535,65535,65535,65535,65535,65535,65535,65535,65535},
{4059,3261,4081,3287,65535,65535,65535,65535,65535,65535,65535,65535,65535,65535,65535,65535,65535,65535,65535,65535,65535,65535,65535,65535,65535,65535,65535,65535,65535,65535,65535,65535,65535,65535,65535,65535,65535,65535,65535,65535,65535,65535,65535,65535,65535,65535,65535,65535},
{2885,2896,2906,2916,2926,2936,3766,2957,2967,2977,2987,3817,3008,3018,3028,3038,3868,3059,3069,3079,3090,3910,3112,3122,3940,3143,3153,3163,3173,3991,3194,3204,3214,3224,4042,3245,4066,3271,4092,65535,65535,65535,65535,65535,65535,65535,65535,65535},
{369,3657,391,404,65535,65535,65535,65535,65535,65535,65535,65535,65535,65535,65535,65535,65535,65535,65535,65535,65535,65535,65535,65535,65535,65535,65535,65535,65535,65535,65535,65535,65535,65535,65535,65535,65535,65535,65535,65535,65535,65535,65535,65535,65535,65535,65535,65535},
{2,13,23,3324,3746,3756,64,3365,3375,3385,3807,115,3416,3426,3436,3858,166,3467,3477,3487,208,220,3920,3930,250,3539,3549,3559,3981,301,3590,3600,3610,4032,352,3641,376,4079,402,65535,65535,65535,65535,65535,65535,65535,65535,65535},
{781,790,803,816,65535,65535,65535,65535,65535,65535,65535,65535,65535,65535,65535,65535,65535,65535,65535,65535,65535,65535,65535,65535,65535,65535,65535,65535,65535,65535,65535,65535,65535,65535,65535,65535,65535,65535,65535,65535,65535,65535,65535,65535,65535,65535,65535,65535},
{414,424,434,444,454,465,475,485,495,505,516,526,536,546,556,567,577,587,597,607,618,630,640,651,661,671,681,691,702,712,722,732,742,753,763,773,786,800,813,65535,65535,65535,65535,65535,65535,65535,65535,65535},
{1193,1201,1215,1228,65535,65535,65535,65535,65535,65535,65535,65535,65535,65535,65535,65535,65535,65535,65535,65535,65535,65535,65535,65535,65535,65535,65535,65535,65535,65535,65535,65535,65535,65535,65535,65535,65535,65535,65535,65535,65535,65535,65535,65535,65535,65535,65535,65535},
{826,836,847,857,867,878,888,898,908,3797,929,939,949,959,3848,980,990,1000,1010,3899,1031,1043,1053,1064,1074,1084,1094,3971,1115,1125,1135,1145,4022,1166,1176,1186,1198,1212,1225,65535,65535,65535,65535,65535,65535,65535,65535,65535},
{1605,1614,1626,1640,65535,65535,65535,65535,65535,65535,65535,65535,65535,65535,65535,65535,65535,65535,65535,65535,65535,65535,65535,65535,65535,65535,65535,65535,65535,65535,65535,65535,65535,65535,65535,65535,65535,65535,65535,65535,65535,65535,65535,65535,65535,65535,65535,65535},
{1238,1249,1259,1269,1280,1290,1300,1310,1320,1331,1341,1351,1361,1371,1382,1392,1402,1412,1422,1433,1443,1455,1466,1476,1486,1496,1506,1517,1527,1537,1547,1557,1568,1578,1588,1598,1611,1627,1641,65535,65535,65535,65535,65535,65535,65535,65535,65535},
{2017,2026,2039,2052,65535,65535,65535,65535,65535,65535,65535,65535,65535,65535,65535,65535,65535,65535,65535,65535,65535,65535,65535,65535,65535,65535,65535,65535,65535,65535,65535,65535,65535,65535,65535,65535,65535,65535,65535,65535,65535,65535,65535,65535,65535,65535,65535,65535},
{1650,1661,1671,3736,1692,1702,1712,1722,1733,1743,1753,1763,1773,1784,1794,1804,1814,1824,1835,1845,1855,1867,1878,1888,1898,1908,1919,1929,1939,1949,1959,1970,1980,1990,2000,2010,2023,4082,2053,65535,65535,65535,65535,65535,65535,65535,65535,65535},
{2429,2438,2451,2464,65535,65535,65535,65535,65535,65535,65535,65535,65535,65535,65535,65535,65535,65535,65535,65535,65535,65535,65535,65535,65535,65535,65535,65535,65535,65535,65535,65535,65535,65535,65535,65535,65535,65535,65535,65535,65535,65535,65535,65535,65535,65535,65535,65535},
{2062,2073,2083,2094,2104,2114,2124,2134,2145,2155,2165,2175,2185,2196,2206,2216,2226,2236,2247,2257,2267,2279,2290,2300,2310,2320,2331,2341,2351,2361,2371,2382,2392,2402,2412,2422,2435,2452,2465,65535,65535,65535,65535,65535,65535,65535,65535,65535},
{2840,2850,3670,3683,65535,65535,65535,65535,65535,65535,65535,65535,65535,65535,65535,65535,65535,65535,65535,65535,65535,65535,65535,65535,65535,65535,65535,65535,65535,65535,65535,65535,65535,65535,65535,65535,65535,65535,65535,65535,65535,65535,65535,65535,65535,65535,65535,65535},
{2474,3304,3314,2505,2515,2525,3355,2546,2556,2566,2576,3406,2597,2607,2617,2627,3457,2648,2658,2668,2679,2691,2701,2711,3529,2732,2742,2752,2762,3580,2783,2793,2803,2813,3631,2834,3655,2860,2873,65535,65535,65535,65535,65535,65535,65535,65535,65535},
{3252,4069,3274,4095,65535,65535,65535,65535,65535,65535,65535,65535,65535,65535,65535,65535,65535,65535,65535,65535,65535,65535,65535,65535,65535,65535,65535,65535,65535,65535,65535,65535,65535,65535,65535,65535,65535,65535,65535,65535,65535,65535,65535,65535,65535,65535,65535,65535},
{2886,3716,3726,2917,2927,2937,2947,3777,3787,2978,2988,2998,3828,3838,3029,3039,3049,3879,3889,3080,3091,3103,3113,3123,3133,3951,3961,3164,3174,3184,4002,4012,3215,3225,3235,4053,3259,3272,3285,65535,65535,65535,65535,65535,65535,65535,65535,65535},
{3,14,24,35,45,55,2948,3778,3788,96,106,2999,3829,3839,147,157,3050,3880,3890,198,210,2692,231,241,3134,3952,3962,282,292,3185,4003,4013,333,343,3236,4054,379,2863,2876,65535,65535,65535,65535,65535,65535,65535,65535,65535},
{4,3305,3727,34,44,54,65,75,85,95,105,116,126,136,146,156,167,177,187,197,209,221,230,240,251,261,271,281,291,302,312,322,332,342,353,363,377,392,405,65535,65535,65535,65535,65535,65535,65535,65535,65535},
{415,425,435,445,455,466,476,486,496,506,517,527,537,547,557,568,578,588,598,608,619,631,641,652,662,672,682,692,703,713,723,733,743,754,764,774,787,801,814,65535,65535,65535,65535,65535,65535,65535,65535,65535},
{416,426,436,446,456,467,477,487,497,507,518,528,538,548,558,569,579,589,599,609,620,632,642,653,663,673,683,693,704,714,724,734,744,755,765,775,791,804,817,65535,65535,65535,65535,65535,65535,65535,65535,65535},
{827,837,848,858,868,879,889,899,909,919,930,940,950,960,970,981,991,1001,1011,1021,1032,1044,1054,1065,1075,1085,1095,1105,1116,1126,1136,1146,1156,1167,1177,1187,1202,1216,1229,65535,65535,65535,65535,65535,65535,65535,65535,65535},
{828,838,849,859,869,2526,3356,900,910,920,2577,3407,951,961,971,2628,3458,1002,1012,1022,1033,1045,1055,2712,3530,1086,1096,1106,2763,3581,1137,1147,1157,2814,3632,1188,1203,3275,3288,65535,65535,65535,65535,65535,65535,65535,65535,65535},
{1239,1250,1260,1270,1281,1291,1301,1311,1321,1332,1342,1352,1362,1372,1383,1393,1403,1413,1423,1434,1444,1456,1467,1477,1487,1497,1507,1518,1528,1538,1548,1558,1569,1579,1589,1599,1615,1628,3684,65535,65535,65535,65535,65535,65535,65535,65535,65535},
{1240,3717,1261,1271,2516,2938,3768,1312,1322,2567,2989,3819,1363,1373,2618,3040,3870,1414,1424,2669,1445,1457,2702,3124,3942,1498,1508,2753,3175,3993,1549,1559,2804,3226,4044,1600,3262,3671,4096,65535,65535,65535,65535,65535,65535,65535,65535,65535},
{1651,1662,1672,1682,1693,1703,1713,1723,1734,1744,1754,1764,1774,1785,1795,1805,1815,1825,1836,1846,1856,1868,1879,1889,1899,1909,1920,1930,1940,1950,1960,1971,1981,1991,2001,2011,2027,2040,2054,65535,65535,65535,65535,65535,65535,65535,65535,65535},
{1652,1663,1673,1683,2928,3346,1714,1724,2557,2979,3397,1765,1775,2608,3030,3448,1816,1826,2659,3081,1857,1869,3114,3520,1900,1910,2743,3165,3571,1951,1961,2794,3216,3622,2002,2012,3658,4083,2877,65535,65535,65535,65535,65535,65535,65535,65535,65535},
{2063,2074,2084,2095,2105,2115,2125,2135,2146,2156,2166,2176,2186,2197,2207,2217,2227,2237,2248,2258,2268,2280,2291,2301,2311,2321,2332,2342,2352,2362,2372,2383,2393,2403,2413,2423,2439,2453,2466,65535,65535,65535,65535,65535,65535,65535,65535,65535},
{2064,2075,2085,2506,3336,3758,2126,2136,2969,3387,3809,2177,2187,3020,3438,3860,2228,2238,3071,3489,2269,2281,3510,3932,2312,2322,3155,3561,3983,2363,2373,3206,3612,4034,2414,2424,4070,2864,3289,65535,65535,65535,65535,65535,65535,65535,65535,65535},
{2845,2854,2867,2880,65535,65535,65535,65535,65535,65535,65535,65535,65535,65535,65535,65535,65535,65535,65535,65535,65535,65535,65535,65535,65535,65535,65535,65535,65535,65535,65535,65535,65535,65535,65535,65535,65535,65535,65535,65535,65535,65535,65535,65535,65535,65535,65535,65535},
{2475,2485,2495,3325,3335,3345,2536,3366,3376,3386,3396,2587,3417,3427,3437,3447,2638,3468,3478,3488,2680,3499,3509,3519,2722,3540,3550,3560,3570,2773,3591,3601,3611,3621,2824,3642,2848,3668,3681,65535,65535,65535,65535,65535,65535,65535,65535,65535},
{3256,3266,4087,4100,65535,65535,65535,65535,65535,65535,65535,65535,65535,65535,65535,65535,65535,65535,65535,65535,65535,65535,65535,65535,65535,65535,65535,65535,65535,65535,65535,65535,65535,65535,65535,65535,65535,65535,65535,65535,65535,65535,65535,65535,65535,65535,65535,65535},
{2887,2897,2907,3737,3747,3757,3767,2958,2968,3798,3808,3818,3009,3019,3849,3859,3869,3060,3070,3900,3092,3911,3921,3931,3941,3144,3154,3972,3982,3992,3195,3205,4023,4033,4043,3246,4067,4080,4093,65535,65535,65535,65535,65535,65535,65535,65535,65535},
{417,427,437,447,457,468,478,488,498,508,519,529,539,549,559,570,580,590,600,610,621,633,643,654,664,674,684,694,705,715,725,735,745,756,766,776,792,805,818,65535,65535,65535,65535,65535,65535,65535,65535,65535},
{2476,2486,2496,2918,3748,2527,2537,2547,3377,3799,2578,2588,2598,3428,3850,2629,2639,2649,3479,3901,622,3104,3922,2713,2723,2733,3551,3973,2764,2774,2784,3602,4024,2815,2825,2835,2851,3276,3685,65535,65535,65535,65535,65535,65535,65535,65535,65535},
{829,839,2908,3326,870,880,890,2959,3789,921,931,941,3010,3840,972,982,992,3061,3891,1023,1034,3500,1056,1066,1076,3145,3963,1107,1117,1127,3196,4014,1158,1168,1178,3247,1204,1217,1230,65535,65535,65535,65535,65535,65535,65535,65535,65535},
{2888,2898,3316,3738,2517,2939,2949,3367,911,2568,2990,3000,3418,962,2619,3041,3051,3469,1013,2670,2681,3912,2703,3125,3135,3541,1097,2754,3176,3186,3592,1148,2805,3227,3237,3643,3263,3672,4097,65535,65535,65535,65535,65535,65535,65535,65535,65535},
{1241,1251,3728,1272,3749,1293,1303,1313,3378,3800,1344,1354,1364,3429,3851,1395,1405,1415,3480,3902,1447,3501,3923,1479,1489,1499,3552,3974,1530,1540,1550,3603,4025,1581,1591,1601,1617,1630,1643,65535,65535,65535,65535,65535,65535,65535,65535,65535},
{3296,3306,1262,2507,1282,1292,1302,3779,1323,1333,1343,1353,3830,1374,1384,1394,1404,3881,1425,1435,1446,1458,1468,1478,1488,3953,1509,1519,1529,1539,4004,1560,1570,1580,1590,4055,1616,1629,1642,65535,65535,65535,65535,65535,65535,65535,65535,65535},
{1653,3718,1674,1684,1694,1704,1715,1725,1735,1745,1755,1766,1776,1786,1796,1806,1817,1827,1837,1847,1858,1870,1880,1890,1901,1911,1921,1931,1941,1952,1962,1972,1982,1992,2003,2013,2028,2041,2055,65535,65535,65535,65535,65535,65535,65535,65535,65535},
{3708,1664,3317,3739,1695,1705,2538,3368,3790,1746,1756,2589,3419,3841,1797,1807,2640,3470,3892,1848,1859,3913,1881,1891,2724,3542,3964,1932,1942,2775,3593,4015,1983,1993,2826,3644,2029,2042,3686,65535,65535,65535,65535,65535,65535,65535,65535,65535},
{2065,2076,3729,2097,2107,2117,2950,3780,2148,2158,2168,3001,3831,2199,2209,2219,3052,3882,2250,2260,2271,2283,2293,2303,3136,3954,2334,2344,2354,3187,4005,2385,2395,2405,3238,4056,2441,3277,4098,65535,65535,65535,65535,65535,65535,65535,65535,65535},
{2066,2487,2086,2096,2106,2116,2127,2137,2147,2157,2167,2178,2188,2198,2208,2218,2229,2239,2249,2259,2270,2282,2292,2302,2313,2323,2333,2343,2353,2364,2374,2384,2394,2404,2415,2425,2440,2454,2467,65535,65535,65535,65535,65535,65535,65535,65535,65535},
{3653,3662,3675,3688,65535,65535,65535,65535,65535,65535,65535,65535,65535,65535,65535,65535,65535,65535,65535,65535,65535,65535,65535,65535,65535,65535,65535,65535,65535,65535,65535,65535,65535,65535,65535,65535,65535,65535,65535,65535,65535,65535,65535,65535,65535,65535,65535,65535},
{2477,3307,2497,3327,3337,3347,3357,2548,2558,3388,3398,3408,2599,2609,3439,3449,3459,2650,2660,3490,2682,2693,3511,3521,3531,2734,2744,3562,3572,3582,2785,2795,3613,3623,3633,2836,3659,2865,2878,65535,65535,65535,65535,65535,65535,65535,65535,65535},
{4064,4074,3280,3293,65535,65535,65535,65535,65535,65535,65535,65535,65535,65535,65535,65535,65535,65535,65535,65535,65535,65535,65535,65535,65535,65535,65535,65535,65535,65535,65535,65535,65535,65535,65535,65535,65535,65535,65535,65535,65535,65535,65535,65535,65535,65535,65535,65535},
{2889,2899,2909,2919,2929,3759,3769,2960,2970,2980,3810,3820,3011,3021,3031,3861,3871,3062,3072,3082,3093,3105,3115,3933,3943,3146,3156,3166,3984,3994,3197,3207,3217,4035,4045,3248,4071,4084,3290,65535,65535,65535,65535,65535,65535,65535,65535,65535},
{418,428,439,449,459,2528,3358,490,500,510,2579,3409,541,551,561,2630,3460,592,602,612,3094,635,645,2714,3532,676,686,696,2765,3583,727,737,747,2816,3634,778,2852,3673,820,65535,65535,65535,65535,65535,65535,65535,65535,65535},
{3297,3719,438,448,458,469,479,489,499,509,520,530,540,550,560,571,581,591,601,611,623,634,644,655,665,675,685,695,706,716,726,736,746,757,767,777,793,806,819,65535,65535,65535,65535,65535,65535,65535,65535,65535},
{830,840,850,860,871,881,891,901,912,922,932,942,952,963,973,983,993,1003,1014,1024,1035,1046,1057,1067,1077,1087,1098,1108,1118,1128,1138,1149,1159,1169,1179,1189,1205,1218,1231,65535,65535,65535,65535,65535,65535,65535,65535,65535},
{3709,841,851,861,2518,2940,3770,902,2559,2569,2991,3821,953,2610,2620,3042,3872,1004,2661,2671,1036,1047,2704,3126,3944,1088,2745,2755,3177,3995,1139,2796,2806,3228,4046,1190,3264,4085,1232,65535,65535,65535,65535,65535,65535,65535,65535,65535},
{1242,1252,1263,1273,1283,3348,1304,1314,1324,1334,3399,1355,1365,1375,1385,3450,1406,1416,1426,1436,1448,1459,1469,3522,1490,1500,1510,1520,3573,1541,1551,1561,1571,3624,1592,1602,3660,1631,1644,65535,65535,65535,65535,65535,65535,65535,65535,65535},
{1243,1253,2498,2508,2930,3760,2539,2549,2971,2981,3811,2590,2600,3022,3032,3862,2641,2651,3073,3083,2683,2694,3116,3934,2725,2735,3157,3167,3985,2776,2786,3208,3218,4036,2827,2837,4072,2866,2879,65535,65535,65535,65535,65535,65535,65535,65535,65535},
{1654,1665,1675,1685,3338,1706,1716,1726,1736,3389,1757,1767,1777,1787,3440,1808,1818,1828,1838,3491,1860,1871,3512,1892,1902,1912,1922,3563,1943,1953,1963,1973,3614,1994,2004,2014,2030,2043,2056,65535,65535,65535,65535,65535,65535,65535,65535,65535},
{1655,2488,2910,2920,3750,2529,2951,2961,3379,3801,2580,3002,3012,3430,3852,2631,3053,3063,3481,3903,3095,3106,3924,2715,3137,3147,3553,3975,2766,3188,3198,3604,4026,2817,3239,3249,2853,3278,3291,65535,65535,65535,65535,65535,65535,65535,65535,65535},
{2067,2077,2087,3328,2108,2119,2129,2139,2149,3390,2170,2180,2190,2200,3441,2221,2231,2241,2251,3492,2273,2284,3513,2305,2315,2325,2335,3564,2356,2366,2376,2386,3615,2407,2417,2427,2443,2456,2469,65535,65535,65535,65535,65535,65535,65535,65535,65535},
{2478,2900,3318,3740,2519,2118,2128,2138,3791,2159,2169,2179,2189,3842,2210,2220,2230,2240,3893,2261,2272,3502,2294,2304,2314,2324,3965,2345,2355,2365,2375,4016,2396,2406,2416,2426,2442,2455,2468,65535,65535,65535,65535,65535,65535,65535,65535,65535},
{2846,2855,2868,2881,65535,65535,65535,65535,65535,65535,65535,65535,65535,65535,65535,65535,65535,65535,65535,65535,65535,65535,65535,65535,65535,65535,65535,65535,65535,65535,65535,65535,65535,65535,65535,65535,65535,65535,65535,65535,65535,65535,65535,65535,65535,65535,65535,65535},
{3298,3308,2499,2509,3339,3349,3359,3369,2560,2570,3400,3410,3420,2611,2621,3451,3461,3471,2662,2672,2684,2695,2705,3523,3533,3543,2746,2756,3574,3584,3594,2797,2807,3625,3635,3645,3661,3674,3687,65535,65535,65535,65535,65535,65535,65535,65535,65535},
{3257,3267,4088,4101,65535,65535,65535,65535,65535,65535,65535,65535,65535,65535,65535,65535,65535,65535,65535,65535,65535,65535,65535,65535,65535,65535,65535,65535,65535,65535,65535,65535,65535,65535,65535,65535,65535,65535,65535,65535,65535,65535,65535,65535,65535,65535,65535,65535},
{2890,3720,3730,2921,2931,2941,3771,3781,2972,2982,2992,3822,3832,3023,3033,3043,3873,3883,3074,3084,3096,3914,3117,3127,3945,3955,3158,3168,3178,3996,4006,3209,3219,3229,4047,4057,3265,4086,4099,65535,65535,65535,65535,65535,65535,65535,65535,65535},
{419,429,440,3329,461,471,481,2550,3380,512,522,532,2601,3431,563,573,583,2652,3482,614,625,3503,647,657,667,2736,3554,698,708,718,2787,3605,749,759,769,3648,795,808,822,65535,65535,65535,65535,65535,65535,65535,65535,65535},
{3710,430,2911,450,460,470,480,491,501,511,521,531,542,552,562,572,582,593,603,613,624,636,646,656,666,677,687,697,707,717,728,738,748,758,768,779,794,807,821,65535,65535,65535,65535,65535,65535,65535,65535,65535},
{831,842,852,863,873,883,893,3370,914,924,934,944,3421,965,975,985,995,3472,1016,1026,1038,3915,1059,1069,1079,3544,1100,1110,1120,1130,3595,1151,1161,1171,1181,4060,1207,1220,1234,65535,65535,65535,65535,65535,65535,65535,65535,65535},
{832,2489,3319,862,872,882,892,903,913,923,933,943,954,964,974,984,994,1005,1015,1025,1037,1048,1058,1068,1078,1089,1099,1109,1119,1129,1140,1150,1160,1170,1180,1191,1206,1219,1233,65535,65535,65535,65535,65535,65535,65535,65535,65535},
{1244,3309,1265,1274,1284,1294,1305,1315,1325,1335,1345,1356,1366,1376,1386,1396,1407,1417,1427,1437,1449,1460,1470,1480,1491,1501,1511,1521,1531,1542,1552,1562,1572,1582,1593,1606,1618,1632,1645,65535,65535,65535,65535,65535,65535,65535,65535,65535},
{2479,1254,1264,1275,1285,1295,2540,3782,1326,1336,1346,2591,3833,1377,1387,1397,2642,3884,1428,1438,1450,1461,1471,1481,2726,3956,1512,1522,1532,2777,4007,1563,1573,1583,2828,2841,1619,1633,1646,65535,65535,65535,65535,65535,65535,65535,65535,65535},
{1656,3721,1677,1686,1696,1707,1717,1727,1737,1747,1758,1768,1778,1788,1798,1809,1819,1829,1839,1849,1861,1872,1882,1893,1903,1913,1923,1933,1944,1954,1964,1974,1984,1995,2005,2018,2031,2044,2057,65535,65535,65535,65535,65535,65535,65535,65535,65535},
{2891,1666,1676,1687,1697,2530,3360,1728,1738,1748,2581,3411,1779,1789,1799,2632,3462,1830,1840,1850,1862,1873,1883,2716,3534,1914,1924,1934,2767,3585,1965,1975,1985,2818,3636,3253,2032,2045,2058,65535,65535,65535,65535,65535,65535,65535,65535,65535},
{2068,2079,2089,2098,2109,2942,3772,2140,2150,2160,2993,3823,2191,2201,2211,3044,3874,2242,2252,2262,2274,2285,2295,3128,3946,2326,2336,2346,3179,3997,2377,2387,2397,3230,4048,2430,2444,2457,2470,65535,65535,65535,65535,65535,65535,65535,65535,65535},
{3299,2078,2088,2099,2520,3350,2130,2551,2561,2571,3401,2181,2602,2612,2622,3452,2232,2653,2663,2673,2685,2696,2706,3524,2316,2737,2747,2757,3575,2367,2788,2798,2808,3626,2418,3649,3663,3676,3689,65535,65535,65535,65535,65535,65535,65535,65535,65535},
{2480,2490,2500,2510,3340,2531,2541,3371,3381,3391,2582,2592,3422,3432,3442,2633,2643,3473,3483,3493,2686,3504,3514,2717,2727,3545,3555,3565,2768,2778,3596,3606,3616,2819,2829,2842,2856,2869,2882,65535,65535,65535,65535,65535,65535,65535,65535,65535},
{3300,3310,3320,3330,2521,3351,3361,2552,2562,2572,3402,3412,2603,2613,2623,3453,3463,2654,2664,2674,2687,2697,2707,3525,3535,2738,2748,2758,3576,3586,2789,2799,2809,3627,3637,3650,3664,3677,3690,65535,65535,65535,65535,65535,65535,65535,65535,65535},
{3711,2901,3731,3741,3751,3761,2952,2962,3792,3802,3812,3003,3013,3843,3853,3863,3054,3064,3894,3904,3097,3107,3925,3935,3138,3148,3966,3976,3986,3189,3199,4017,4027,4037,3240,3250,4073,3279,3292,65535,65535,65535,65535,65535,65535,65535,65535,65535},
{2892,2902,2912,2922,2932,3762,2953,2963,2973,2983,3813,3004,3014,3024,3034,3864,3055,3065,3075,3085,3098,3108,3118,3936,3139,3149,3159,3169,3987,3190,3200,3210,3220,4038,3241,4061,4075,3281,3294,65535,65535,65535,65535,65535,65535,65535,65535,65535},
{420,431,441,451,3752,472,482,492,502,3803,523,533,543,553,3854,574,584,594,604,3905,626,637,3926,658,668,678,688,3977,709,719,729,739,4028,760,770,782,796,809,823,65535,65535,65535,65535,65535,65535,65535,65535,65535},
{421,3722,3732,3742,462,2943,3773,3783,3793,513,2994,3824,3834,3844,564,3045,3875,3885,3895,615,627,3916,648,3129,3947,3957,3967,699,3180,3998,4008,4018,750,3231,4049,783,797,810,4102,65535,65535,65535,65535,65535,65535,65535,65535,65535},
{833,843,853,864,874,884,894,904,915,925,935,945,955,966,976,986,996,1006,1017,1027,1039,1049,1060,1070,1080,1090,1101,1111,1121,1131,1141,1152,1162,1172,1182,1194,1208,1221,1235,65535,65535,65535,65535,65535,65535,65535,65535,65535},
{3712,844,854,3331,875,885,895,905,916,926,936,946,956,967,977,987,997,1007,1018,1028,1040,1050,1061,1071,1081,1091,1102,1112,1122,1132,1142,1153,1163,1173,1183,1195,1209,1222,3691,65535,65535,65535,65535,65535,65535,65535,65535,65535},
{1245,1255,1266,1276,1286,1296,1306,1316,1327,1337,1347,1357,1367,1378,1388,1398,1408,1418,1429,1439,1451,1462,1472,1482,1492,1502,1513,1523,1533,1543,1553,1564,1574,1584,1594,1607,1620,1634,1647,65535,65535,65535,65535,65535,65535,65535,65535,65535},
{1246,1256,3321,1277,1287,1297,1307,1317,1328,1338,1348,1358,1368,1379,1389,1399,1409,1419,1430,1440,1452,1463,1473,1483,1493,1503,1514,1524,1534,1544,1554,1565,1575,1585,1595,1608,1621,1635,3692,65535,65535,65535,65535,65535,65535,65535,65535,65535},
{1657,1667,1678,1688,1698,1708,1718,1729,1739,1749,1759,1769,1780,1790,1800,1810,1820,1831,1841,1851,1863,1874,1884,1894,1904,1915,1925,1935,1945,1955,1966,1976,1986,1996,2006,2019,2033,2046,2059,65535,65535,65535,65535,65535,65535,65535,65535,65535},
{1658,1668,1679,1689,1699,1709,1719,1730,1740,1750,1760,1770,1781,1791,1801,1811,1821,1832,1842,1852,1864,1875,1885,1895,1905,1916,1926,1936,1946,1956,1967,1977,1987,1997,2007,2020,2034,2047,4104,65535,65535,65535,65535,65535,65535,65535,65535,65535},
{2069,2080,2091,2101,2111,2121,3362,2142,2152,2162,2172,3413,2193,2203,2213,2223,3464,2244,2254,2264,2276,2287,2297,2307,3536,2328,2338,2348,2358,3587,2379,2389,2399,2409,3638,2432,2446,2459,3693,65535,65535,65535,65535,65535,65535,65535,65535,65535},
{2070,2491,2090,2100,2110,2120,2131,2141,2151,2161,2171,2182,2192,2202,2212,2222,2233,2243,2253,2263,2275,2286,2296,2306,2317,2327,2337,2347,2357,2368,2378,2388,2398,2408,2419,2431,2445,2458,2471,65535,65535,65535,65535,65535,65535,65535,65535,65535},
{2481,3311,2501,2511,3341,2532,2542,3372,3382,3392,2583,2593,3423,3433,3443,2634,2644,3474,3484,3494,2688,3505,3515,2718,2728,3546,3556,3566,2769,2779,3597,3607,3617,2820,2830,2843,2857,2870,2883,65535,65535,65535,65535,65535,65535,65535,65535,65535},
{3301,2492,2502,2512,2522,3352,2543,2553,2563,2573,3403,2594,2604,2614,2624,3454,2645,2655,2665,2675,3496,2698,2708,3526,2729,2739,2749,2759,3577,2780,2790,2800,2810,3628,2831,3651,3665,3678,3694,65535,65535,65535,65535,65535,65535,65535,65535,65535},
{2893,2903,2913,2923,2933,3763,2954,2964,2974,2984,3814,3005,3015,3025,3035,3865,3056,3066,3076,3086,3099,3109,3119,3937,3140,3150,3160,3170,3988,3191,3201,3211,3221,4039,3242,3254,3268,4089,3295,65535,65535,65535,65535,65535,65535,65535,65535,65535},
{3713,3723,3733,3743,3753,2944,3774,3784,3794,3804,2995,3825,3835,3845,3855,3046,3876,3886,3896,3906,3100,3917,3927,3130,3948,3958,3968,3978,3181,3999,4009,4019,4029,3232,4050,4062,4076,3282,4103,65535,65535,65535,65535,65535,65535,65535,65535,65535},
{2482,3312,3322,3332,3342,2533,3363,3373,3383,3393,2584,3414,3424,3434,3444,2635,3465,3475,3485,3495,2689,3506,3516,2719,3537,3547,3557,3567,2770,3588,3598,3608,3618,2821,3639,2844,2858,2871,4105,65535,65535,65535,65535,65535,65535,65535,65535,65535},
{3302,2493,2503,2513,2523,3353,2544,2554,2564,2574,3404,2595,2605,2615,2625,3455,2646,2656,2666,2676,3497,2699,2709,3527,2730,2740,2750,2760,3578,2781,2791,2801,2811,3629,2832,3652,3666,3679,3695,65535,65535,65535,65535,65535,65535,65535,65535,65535},
{2894,2904,2914,2924,2934,3764,2955,2965,2975,2985,3815,3006,3016,3026,3036,3866,3057,3067,3077,3087,3908,3110,3120,3938,3141,3151,3161,3171,3989,3192,3202,3212,3222,4040,3243,3255,3269,4090,4106,65535,65535,65535,65535,65535,65535,65535,65535,65535},
{3714,3724,3734,3744,3754,2945,3775,3785,3795,3805,2996,3826,3836,3846,3856,3047,3877,3887,3897,3907,3101,3918,3928,3131,3949,3959,3969,3979,3182,4000,4010,4020,4030,3233,4051,4063,4077,3283,4107,65535,65535,65535,65535,65535,65535,65535,65535,65535},
{5,15,25,36,46,56,66,76,86,97,107,117,127,137,148,158,168,178,188,199,211,222,232,242,252,262,272,283,293,303,313,323,334,344,354,364,380,393,406,65535,65535,65535,65535,65535,65535,65535,65535,65535},
{6,16,26,37,47,57,67,77,87,98,108,118,128,138,149,159,169,179,189,200,212,223,233,243,253,263,273,284,294,304,314,324,335,345,355,365,381,394,407,65535,65535,65535,65535,65535,65535,65535,65535,65535},
{7,17,27,38,48,58,68,78,88,99,109,119,129,139,150,160,170,180,190,201,213,224,234,244,254,264,274,285,295,305,315,325,336,346,356,366,382,395,408,65535,65535,65535,65535,65535,65535,65535,65535,65535},
{8,18,28,39,49,59,69,79,89,100,110,120,130,140,151,161,171,181,191,202,214,225,235,245,255,265,275,286,296,306,316,326,337,347,357,370,383,396,409,65535,65535,65535,65535,65535,65535,65535,65535,65535},
{9,19,29,40,50,60,70,80,90,101,111,121,131,141,152,162,172,182,192,203,215,226,236,246,256,266,276,287,297,307,317,327,338,348,358,371,384,397,410,65535,65535,65535,65535,65535,65535,65535,65535,65535},
{10,20,30,41,51,61,71,81,91,102,112,122,132,142,153,163,173,183,193,204,216,227,237,247,257,267,277,288,298,308,318,328,339,349,359,372,385,398,411,65535,65535,65535,65535,65535,65535,65535,65535,65535},
{11,21,31,42,52,62,72,82,92,103,113,123,133,143,154,164,174,184,194,205,217,228,238,248,258,268,278,289,299,309,319,329,340,350,360,373,386,399,65535,65535,65535,65535,65535,65535,65535,65535,65535,65535},
{12,3315,32,2514,2524,3354,74,84,94,2575,3405,125,135,145,2626,3456,176,186,196,207,3102,2700,2710,3528,260,270,280,2761,3579,311,321,331,2812,3630,362,3258,388,3284,65535,65535,65535,65535,65535,65535,65535,65535,65535,65535},
};

#define NG SCHED_NG
#define RING 16
#define NSLOT 8
#define CFETCH 5
#define TABLED 1
#define PROMO CU_TENSOR_MAP_L2_PROMOTION_L2_128B
#define AHEAD 6
#define CF0 5
#define CFS 2
#define ABL 0
#define CX 5
#define PUBN 2
#define PUBE 8
#define SCHED 9
#define OUT_TMA 0
#define JB1 21
#define JB2 24
#define CVAR 2
#define CFN 0
#define CREGS 224
#define CSLEEP 200
#define JB 21
#define JF JB
#define JR 17
#define HOIST 1
#define XEARLY 0
#define FPRED 0
#define LATERED 1
#define TRIG 6
constexpr int NCONV = 3 * NG;
constexpr int PLEN = SCHED_LE, LM = 256 - 2 * PLEN, NSEG = 4 / (NG - 8), LMID = NSEG * LM;
static_assert(LMID <= PLEN && (NG == 9 || NG == 10), "geometry");
constexpr int TILEB = 12288;
constexpr int SLOTB = 280 * 64;
constexpr int W1S = 0, W2S = 73728, ABUF = 147456, XBUF = ABUF + 16 * 3072, MISC = XBUF + 8 * 3072;
constexpr int WBAR = MISC + 2560;
constexpr int RBUF = ABUF - 4 * SLOTB;
constexpr int CM = MISC + 2816, CTAB = CM + 256;
constexpr int SMEM_BYTES = CTAB + (PLEN + 16) * 16;
static_assert(RBUF % 512 == 0 && RBUF >= W2S && RBUF + NSLOT * SLOTB + 128 <= MISC && SMEM_BYTES <= 232448, "smem layout");

struct Globals {
  unsigned char scratch[(RING * NG + 1) * 4 * TILEB];
  unsigned char wimg[147456];
  uint32_t wflag[32];
  uint32_t ready[NG * PLEN + 1];
  uint32_t cons[NG * PLEN];
  uint32_t epoch[1024];
};
__device__ __align__(1024) Globals g_state;

#define PROF_AT(cond, idx)
#define PROF_VAL(cond, idx, v)
#define PROF2_AT(c, i)
#define PROF2_VAL(c, i, v)
#define GELU_C3 0.32920349f
#define GELU_A2 0x40d940d9u
#define SCHED_FENCE() asm volatile("pmevent 0;" ::: "memory")
#define SPIN_LIMIT 0x1000000

__device__ __forceinline__ uint32_t smem_u32(const void* p) { return (uint32_t)__cvta_generic_to_shared(p); }
__device__ __forceinline__ void wg_fence() { asm volatile("wgmma.fence.sync.aligned;" ::: "memory"); }
__device__ __forceinline__ void wg_commit() { asm volatile("wgmma.commit_group.sync.aligned;" ::: "memory"); }
template <int N> __device__ __forceinline__ void wg_wait() { asm volatile("wgmma.wait_group.sync.aligned %0;" ::"n"(N) : "memory"); }
__device__ __forceinline__ void mbar_init(uint32_t bar, uint32_t cnt) { asm volatile("mbarrier.init.shared::cta.b64 [%0], %1;" ::"r"(bar), "r"(cnt) : "memory"); }
__device__ __forceinline__ void mbar_expect_tx(uint32_t bar, uint32_t bytes) { asm volatile("mbarrier.arrive.expect_tx.shared::cta.b64 _, [%0], %1;" ::"r"(bar), "r"(bytes) : "memory"); }
__device__ __forceinline__ void mbar_arrive(uint32_t bar) { asm volatile("mbarrier.arrive.shared::cta.b64 _, [%0];" ::"r"(bar) : "memory"); }
__device__ __forceinline__ void mbar_wait(uint32_t bar, uint32_t parity) {
  asm volatile("{\n.reg .pred p;\n.reg .u32 c;\nmbarrier.try_wait.parity.shared::cta.b64 p, [%0], %1;\n@p bra DONE_%=;\nmov.u32 c, 0;\nWAIT_%=:\nmbarrier.try_wait.parity.shared::cta.b64 p, [%0], %1;\n@p bra DONE_%=;\n"
               "add.u32 c, c, 1;\nsetp.lt.u32 p, c, 0x1000000;\n@p bra WAIT_%=;\ntrap;\nDONE_%=:\n}" ::"r"(bar), "r"(parity) : "memory");
}
__device__ __forceinline__ void bulk_g2s(uint32_t dst, const void* src, uint32_t bytes, uint32_t bar) {
  asm volatile("cp.async.bulk.shared::cluster.global.mbarrier::complete_tx::bytes [%0], [%1], %2, [%3];" ::"r"(dst), "l"(src), "r"(bytes), "r"(bar) : "memory");
}
__device__ __forceinline__ uint32_t ld_relaxed(const uint32_t* p) { uint32_t v; asm volatile("ld.relaxed.gpu.global.u32 %0, [%1];" : "=r"(v) : "l"(p) : "memory"); return v; }
__device__ __forceinline__ void red_add_elect(uint32_t* p) { asm volatile("{.reg .pred p; elect.sync _|p, 0xffffffff; @p red.relaxed.gpu.global.add.u32 [%0], 1;}" ::"l"(p) : "memory"); }
__device__ __forceinline__ void mbar_arrive_elect(uint32_t bar) { asm volatile("{.reg .pred p; elect.sync _|p, 0xffffffff; @p mbarrier.arrive.shared::cta.b64 _, [%0];}" ::"r"(bar) : "memory"); }
__device__ __forceinline__ void mbar_init_elect(uint32_t bar, uint32_t cnt) { asm volatile("{.reg .pred p; elect.sync _|p, 0xffffffff; @p mbarrier.init.shared::cta.b64 [%0], %1;}" ::"r"(bar), "r"(cnt) : "memory"); }
__device__ __forceinline__ void lds128(uint32_t* r, uint32_t a) { asm volatile("ld.shared.v4.b32 {%0,%1,%2,%3}, [%4];" : "=r"(r[0]), "=r"(r[1]), "=r"(r[2]), "=r"(r[3]) : "r"(a) : "memory"); }
__device__ __forceinline__ uint2 lds64(uint32_t a) { uint2 v; asm volatile("ld.shared.v2.b32 {%0,%1}, [%2];" : "=r"(v.x), "=r"(v.y) : "r"(a) : "memory"); return v; }
__device__ __forceinline__ uint32_t lds32(uint32_t a) { uint32_t v; asm volatile("ld.shared.b32 %0, [%1];" : "=r"(v) : "r"(a) : "memory"); return v; }
__device__ __forceinline__ void sts32(uint32_t a, uint32_t v) { asm volatile("st.shared.b32 [%0], %1;" ::"r"(a), "r"(v) : "memory"); }
__device__ __forceinline__ void sts128(uint32_t a, uint4 v) { asm volatile("st.shared.v4.b32 [%0], {%1,%2,%3,%4};" ::"r"(a), "r"(v.x), "r"(v.y), "r"(v.z), "r"(v.w) : "memory"); }
__device__ __forceinline__ uint4 ldg128v(const void* p) { uint4 v; asm volatile("ld.global.nc.v4.b32 {%0,%1,%2,%3}, [%4];" : "=r"(v.x), "=r"(v.y), "=r"(v.z), "=r"(v.w) : "l"(p) : "memory"); return v; }
__device__ __forceinline__ void stg128(void* p, uint4 v) { asm volatile("st.global.v4.b32 [%0], {%1,%2,%3,%4};" ::"l"(p), "r"(v.x), "r"(v.y), "r"(v.z), "r"(v.w) : "memory"); }
#define HINT 3
__device__ __forceinline__ uint64_t pol_evict_first() { uint64_t p; asm("createpolicy.fractional.L2::evict_first.b64 %0, 1.0;" : "=l"(p)); return p; }
__device__ __forceinline__ uint4 ldg128_last(const void* p, uint64_t pol) {
  if (!(HINT & 1)) return ldg128v(p);
  uint4 v; asm volatile("ld.global.nc.L1::no_allocate.L2::cache_hint.v4.b32 {%0,%1,%2,%3}, [%4], %5;" : "=r"(v.x), "=r"(v.y), "=r"(v.z), "=r"(v.w) : "l"(p), "l"(pol) : "memory"); return v;
}
__device__ __forceinline__ void stg128_stream(void* p, uint4 v, uint64_t pol) {
  if (!(HINT & 2)) { stg128(p, v); return; }
  asm volatile("st.global.L2::cache_hint.v4.b32 [%0], {%1,%2,%3,%4}, %5;" ::"l"(p), "r"(v.x), "r"(v.y), "r"(v.z), "r"(v.w), "l"(pol) : "memory");
}
__device__ __forceinline__ float bf_lo(uint32_t w) { return __uint_as_float(w << 16); }
__device__ __forceinline__ float bf_hi(uint32_t w) { return __uint_as_float(w & 0xffff0000u); }
__device__ __forceinline__ uint32_t pack_f16(float lo, float hi) { uint32_t d; asm("cvt.rn.f16x2.f32 %0, %1, %2;" : "=r"(d) : "f"(hi), "f"(lo)); return d; }
__device__ __forceinline__ uint32_t pack_f16_sat(float lo, float hi) { uint32_t d; asm("cvt.rn.satfinite.f16x2.f32 %0, %1, %2;" : "=r"(d) : "f"(hi), "f"(lo)); return d; }
__device__ __forceinline__ uint32_t pack_bf16(float lo, float hi) { uint32_t d; asm("cvt.rn.bf16x2.f32 %0, %1, %2;" : "=r"(d) : "f"(hi), "f"(lo)); return d; }
__device__ __forceinline__ uint32_t hadd2_bf16(uint32_t a, uint32_t b) { uint32_t d; asm("add.rn.bf16x2 %0, %1, %2;" : "=r"(d) : "r"(a), "r"(b)); return d; }
__device__ __forceinline__ uint32_t h2add(uint32_t a, uint32_t b) { uint32_t d; asm("add.rn.f16x2 %0, %1, %2;" : "=r"(d) : "r"(a), "r"(b)); return d; }
__device__ __forceinline__ uint32_t h2mul(uint32_t a, uint32_t b) { uint32_t d; asm("mul.rn.f16x2 %0, %1, %2;" : "=r"(d) : "r"(a), "r"(b)); return d; }
__device__ __forceinline__ uint32_t h2fma(uint32_t a, uint32_t b, uint32_t c) { uint32_t d; asm("fma.rn.f16x2 %0, %1, %2, %3;" : "=r"(d) : "r"(a), "r"(b), "r"(c)); return d; }
__device__ __forceinline__ uint32_t h2lo(uint32_t a) { uint32_t d; asm("{.reg .f16 l,h; mov.b32 {l,h}, %1; mov.b32 %0, {l,l};}" : "=r"(d) : "r"(a)); return d; }
__device__ __forceinline__ uint32_t h2hi(uint32_t a) { uint32_t d; asm("{.reg .f16 l,h; mov.b32 {l,h}, %1; mov.b32 %0, {h,h};}" : "=r"(d) : "r"(a)); return d; }
__device__ __forceinline__ float h_lo(uint32_t a) { float d; asm("{.reg .f16 l,h; mov.b32 {l,h}, %1; cvt.f32.f16 %0, l;}" : "=f"(d) : "r"(a)); return d; }
__device__ __forceinline__ float h_hi(uint32_t a) { float d; asm("{.reg .f16 l,h; mov.b32 {l,h}, %1; cvt.f32.f16 %0, h;}" : "=f"(d) : "r"(a)); return d; }
__device__ __forceinline__ uint32_t prmt(uint32_t a, uint32_t b, uint32_t s) { uint32_t d; asm("prmt.b32 %0, %1, %2, %3;" : "=r"(d) : "r"(a), "r"(b), "r"(s)); return d; }
__device__ __forceinline__ void mma_sp(float* d, const uint32_t* a, const uint32_t* b, const float* c, uint32_t e) {
  asm("mma.sp::ordered_metadata.sync.aligned.m16n8k32.row.col.f32.bf16.bf16.f32 {%0,%1,%2,%3}, {%4,%5,%6,%7}, {%8,%9,%10,%11}, {%12,%13,%14,%15}, %16, 0;"
      : "=f"(d[0]), "=f"(d[1]), "=f"(d[2]), "=f"(d[3])
      : "r"(a[0]), "r"(a[1]), "r"(a[2]), "r"(a[3]), "r"(b[0]), "r"(b[1]), "r"(b[2]), "r"(b[3]), "f"(c[0]), "f"(c[1]), "f"(c[2]), "f"(c[3]), "r"(e));
}
__device__ __forceinline__ uint32_t bf2_to_h2(uint32_t w, float s) { return pack_f16(bf_lo(w) * s, bf_hi(w) * s); }
__device__ __forceinline__ uint32_t bf2_to_h2(uint32_t w) { return pack_f16(bf_lo(w), bf_hi(w)); }

__device__ __forceinline__ uint32_t gelu_h2(uint32_t y) {
  uint32_t t, u, th, g;
  asm volatile("fma.rn.f16x2 %0, %1, %1, %2;" : "=r"(t) : "r"(y), "r"(GELU_A2));
  asm volatile("mul.rn.f16x2 %0, %1, %2;" : "=r"(u) : "r"(y), "r"(t));
  asm volatile("tanh.approx.f16x2 %0, %1;" : "=r"(th) : "r"(u));
  asm volatile("fma.rn.f16x2 %0, %1, %2, %1;" : "=r"(g) : "r"(y), "r"(th));
  return g;
}

__device__ __forceinline__ void copy_weights(uint32_t sb, int piece, const void* src) {
  asm volatile("{\n.reg .pred p;\nelect.sync _|p, 0xffffffff;\n@p mbarrier.init.shared::cta.b64 [%1], 1;\n@p fence.mbarrier_init.release.cluster;\n"
               "@p mbarrier.arrive.expect_tx.shared::cta.b64 _, [%1], 12288;\n"
               "@p cp.async.bulk.shared::cluster.global.mbarrier::complete_tx::bytes [%0], [%2], 12288, [%1];\n}"
               ::"r"(sb + piece * 12288), "r"(sb + WBAR + piece * 8), "l"(src) : "memory");
}
__device__ __forceinline__ void convert_weights(uint32_t sb, uint32_t wbar, int rot, int warp, int lane) {
  if (warp < 12) {
    const int l8 = lane & 7, q4 = lane >> 3;
    int s = (warp >> 1) + rot; if (s >= 6) s -= 6;
    const uint32_t base = sb + W1S + s * 12288 + (warp & 1) * 384;
    mbar_wait(wbar + s * 8, 0);
    uint32_t v[3][4][4];
#pragma unroll
    for (int r = 0; r < 4; r++)
#pragma unroll
      for (int i = 0; i < 3; i++) lds128(v[i][r], base + i * 128 + (4 * (l8 >> 1) + 2 * (r & 1) + (l8 & 1)) * 768 + ((l8 + q4 + 4 * (r >> 1)) & 7) * 16);
    __syncwarp();
#pragma unroll
    for (int r = 0; r < 4; r++)
#pragma unroll
      for (int i = 0; i < 3; i++)
        sts128(base + i * 128 + (2 * ((l8 + q4 + 4 * (r >> 1)) & 7) + (r & 1)) * 768 + l8 * 16,
               make_uint4(bf2_to_h2(v[i][r][0]), bf2_to_h2(v[i][r][1]), bf2_to_h2(v[i][r][2]), bf2_to_h2(v[i][r][3])));
  }
  PROF2_AT(lane == 0, 440 + warp);
  const int q = lane & 3, t = (lane >> 2) & 3, b = lane >> 4;
  int u = 3 * (warp ^ 15) + 8 * rot; if (u >= 48) u -= 48;
  uint32_t base[3], v[3][4][3];
#pragma unroll
  for (int i = 0; i < 3; i++) {
    const int ui = u + i >= 48 ? u + i - 48 : u + i;
    base[i] = sb + W2S + ui * 1536;
    if (i != 1) mbar_wait(wbar + 48 + (ui >> 3) * 8, 0);
  }
#pragma unroll
  for (int i = 0; i < 3; i++)
#pragma unroll
    for (int d = 0; d < 4; d++)
#pragma unroll
      for (int j = 0; j < 3; j++) v[i][d][j] = lds32(base[i] + (2 * ((q + d) & 3) + b) * 192 + j * 64 + t * 16 + q * 4);
  __syncwarp();
#pragma unroll
  for (int i = 0; i < 3; i++)
#pragma unroll
    for (int d = 0; d < 4; d++)
#pragma unroll
      for (int j = 0; j < 3; j++) sts32(base[i] + (4 * j + q) * 128 + (2 * ((q + d) & 3) + b) * 16 + t * 4, bf2_to_h2(v[i][d][j], 0.5f / GELU_C3));
}

__device__ __noinline__ void ln_wide(uint32_t ad) {
  float m[2], r[2];
#pragma unroll
  for (int hi = 0; hi < 2; hi++) {
    float sm = 0.f;
    for (int s = 0; s < 6; s++) { uint2 w = lds64(ad + s * 512 + hi * 8); sm += (h_lo(w.x) + h_hi(w.x)) + (h_lo(w.y) + h_hi(w.y)); }
    sm += __shfl_xor_sync(0xffffffffu, sm, 1); sm += __shfl_xor_sync(0xffffffffu, sm, 2);
    m[hi] = sm * (1.f / 96.f);
    float q = 0.f;
    for (int s = 0; s < 6; s++) {
      uint2 w = lds64(ad + s * 512 + hi * 8);
      float d0 = h_lo(w.x) - m[hi], d1 = h_hi(w.x) - m[hi], d2 = h_lo(w.y) - m[hi], d3 = h_hi(w.y) - m[hi];
      q += (d0 * d0 + d1 * d1) + (d2 * d2 + d3 * d3);
    }
    q += __shfl_xor_sync(0xffffffffu, q, 1); q += __shfl_xor_sync(0xffffffffu, q, 2);
    r[hi] = rsqrtf(fmaf(q, 1.f / 96.f, 1e-5f)) * GELU_C3;
  }
  for (int s = 0; s < 6; s++) {
    uint32_t w[4]; lds128(w, ad + s * 512);
    sts128(ad + s * 512, make_uint4(pack_f16((h_lo(w[0]) - m[0]) * r[0], (h_hi(w[0]) - m[0]) * r[0]), pack_f16((h_lo(w[2]) - m[1]) * r[1], (h_hi(w[2]) - m[1]) * r[1]),
                                    pack_f16((h_lo(w[1]) - m[0]) * r[0], (h_hi(w[1]) - m[0]) * r[0]), pack_f16((h_lo(w[3]) - m[1]) * r[1], (h_hi(w[3]) - m[1]) * r[1])));
  }
  asm volatile("fence.proxy.async.shared::cta;" ::: "memory");
}

__device__ __forceinline__ float rsqrt_fast(float v) { float r; asm("rsqrt.approx.ftz.f32 %0, %1;" : "=f"(r) : "f"(v)); return r; }
__device__ __forceinline__ uint32_t layer_norm(uint32_t (&raw)[6][4], uint32_t* a, uint32_t tag) {
  const uint32_t stale = ((raw[0][0] ^ tag) | (raw[1][0] ^ tag)) | ((raw[2][0] ^ tag) | (raw[3][0] ^ tag)) | ((raw[4][0] ^ tag) | (raw[5][0] ^ tag));
  uint32_t sm[2];
#pragma unroll
  for (int hi = 0; hi < 2; hi++) {
    uint32_t s0 = h2add(raw[0][2 * hi], raw[1][2 * hi]), s1 = h2add(raw[0][2 * hi + 1], raw[1][2 * hi + 1]);
    uint32_t s2 = h2add(raw[2][2 * hi], raw[3][2 * hi]), s3 = h2add(raw[2][2 * hi + 1], raw[3][2 * hi + 1]);
    uint32_t s4 = h2add(raw[4][2 * hi], raw[5][2 * hi]), s5 = h2add(raw[4][2 * hi + 1], raw[5][2 * hi + 1]);
    sm[hi] = h2add(h2add(h2add(s0, s1), h2add(s2, s3)), h2add(s4, s5));
  }
  uint32_t s = h2add(prmt(sm[0], sm[1], 0x5410), prmt(sm[0], sm[1], 0x7632));
  s = h2add(s, __shfl_xor_sync(0xffffffffu, s, 1));
  s = h2add(s, __shfl_xor_sync(0xffffffffu, s, 2));
  const uint32_t nm = h2mul(s, 0xA155A155u);
  uint32_t qq[2];
#pragma unroll
  for (int hi = 0; hi < 2; hi++) {
    const uint32_t m = hi ? h2hi(nm) : h2lo(nm);
    uint32_t q0 = 0, q1 = 0;
#pragma unroll
    for (int k = 0; k < 6; k++) {
      uint32_t d0 = h2add(raw[k][2 * hi], m), d1 = h2add(raw[k][2 * hi + 1], m);
      raw[k][2 * hi] = d0; raw[k][2 * hi + 1] = d1;
      q0 = k ? h2fma(d0, d0, q0) : h2mul(d0, d0);
      q1 = k ? h2fma(d1, d1, q1) : h2mul(d1, d1);
    }
    qq[hi] = h2add(q0, q1);
  }
  uint32_t q = h2add(prmt(qq[0], qq[1], 0x5410), prmt(qq[0], qq[1], 0x7632));
  q = h2add(q, __shfl_xor_sync(0xffffffffu, q, 1));
  q = h2add(q, __shfl_xor_sync(0xffffffffu, q, 2));
  constexpr float K1 = 1.f / (96.f * GELU_C3 * GELU_C3), K2 = 1e-5f / (GELU_C3 * GELU_C3);
  const float r0 = rsqrt_fast(fmaf(h_lo(q), K1, K2)), r1 = rsqrt_fast(fmaf(h_hi(q), K1, K2));
  const uint32_t r = pack_f16(r0, r1);
#pragma unroll
  for (int k = 0; k < 6; k++) {
    a[4 * k] = h2mul(raw[k][0], h2lo(r)); a[4 * k + 2] = h2mul(raw[k][1], h2lo(r));
    a[4 * k + 1] = h2mul(raw[k][2], h2hi(r)); a[4 * k + 3] = h2mul(raw[k][3], h2hi(r));
  }
  return (((q & 0x7c007c00u) + 0x04000400u) & 0x80008000u) | (stale & 1);
}

__device__ __forceinline__ void gemm1(uint32_t* p, const uint32_t* a, uint64_t d1, int c) {
  wgmma_n48_f16<0>(p, a, d1 + c * (1536 >> 4));
#pragma unroll
  for (int s = 1; s < 6; s++) wgmma_n48_f16<1>(p, a + 4 * s, d1 + c * (1536 >> 4) + s * (12288 >> 4));
}

__device__ __forceinline__ void gemm1_piece(uint32_t* p, const uint32_t* a, uint64_t d1, int c, int u) {
  if (u == 0) wgmma_n48_f16<0>(p, a, d1 + c * (1536 >> 4)); else wgmma_n48_f16<1>(p, a + 8 * u, d1 + c * (1536 >> 4) + 2 * u * (12288 >> 4));
  wgmma_n48_f16<1>(p, a + 8 * u + 4, d1 + c * (1536 >> 4) + (2 * u + 1) * (12288 >> 4));
}
__device__ __forceinline__ void fetch_a(uint32_t abuf, uint32_t bar, const unsigned char* src) {
  asm volatile("{\n.reg .pred p;\nelect.sync _|p, 0xffffffff;\n"
               "@p mbarrier.arrive.expect_tx.shared::cta.b64 _, [%1], 3072;\n"
               "@p cp.async.bulk.shared::cluster.global.mbarrier::complete_tx::bytes [%0], [%2], 3072, [%1];\n}"
               ::"r"(abuf), "r"(bar), "l"(src) : "memory");
}
__device__ __forceinline__ void fetch_a_if(uint32_t abuf, uint32_t bar, const unsigned char* src, uint32_t go) {
  asm volatile("{\n.reg .pred p, q;\nsetp.ne.u32 q, %3, 0;\nelect.sync _|p, 0xffffffff;\nand.pred p, p, q;\n"
               "@p mbarrier.arrive.expect_tx.shared::cta.b64 _, [%1], 3072;\n"
               "@p cp.async.bulk.shared::cluster.global.mbarrier::complete_tx::bytes [%0], [%2], 3072, [%1];\n}"
               ::"r"(abuf), "r"(bar), "l"(src), "r"(go) : "memory");
}
__device__ __forceinline__ bool mbar_test(uint32_t bar, uint32_t parity) {
  uint32_t r;
  asm volatile("{.reg .pred p; mbarrier.test_wait.parity.shared::cta.b64 p, [%1], %2; selp.u32 %0, 1, 0, p;}" : "=r"(r) : "r"(bar), "r"(parity) : "memory");
  return r;
}
__device__ __forceinline__ void fetch_x(uint32_t xbuf, uint32_t bar, const CUtensorMap* tm, uint32_t c0, uint32_t c12, uint64_t pol) {
  asm volatile("{\n.reg .pred p;\nelect.sync _|p, 0xffffffff;\n"
               "@p mbarrier.arrive.expect_tx.shared::cta.b64 _, [%1], 3072;\n"
               "@p cp.async.bulk.tensor.3d.shared::cluster.global.mbarrier::complete_tx::bytes.L2::cache_hint [%0], [%2, {%3, %4, %5}], [%1], %6;\n}"
               ::"r"(xbuf), "r"(bar), "l"(tm), "r"(c0), "r"(c12 & 255), "r"(c12 >> 8), "l"(pol) : "memory");
}
__device__ __forceinline__ void wait_ready(const uint32_t* p, uint32_t target) {
  int spins = 0;
  while (ld_relaxed(p) != target) { __nanosleep(32); if (++spins > SPIN_LIMIT) __trap(); }
}
__device__ __forceinline__ uint32_t slot_tag(int gm, int j, uint32_t epoch) {
  const int len = gm < 8 ? PLEN : LMID, writes = (len - (j & (RING - 1)) + RING - 1) / RING;
  return (epoch * writes + j / RING + 1) & 1;
}

__device__ __forceinline__ void build_tile_list(uint32_t sb, int k, int idx, bool tabled, bool is_conv, uint32_t epoch) {
  int n = -1;
  if (tabled) { if (k < 48) n = (int16_t)g_sched[idx][k]; }
  else if (!is_conv) {
    const int i = k * (gridDim.x - NCONV) + idx, r = i >> 2, full = LMID * NG;
    const int j = r < full ? r / NG : ((r - full) >> 3) + LMID, gm = r < full ? r % NG : (r - full) & 7;
    if (i < 4096) n = (gm * PLEN + j) * 4 + (i & 3);
  }
  const int q = n >> 2, gm = q / PLEN, j = q - gm * PLEN, seg = j / LM;
  const int strip = gm < 8 ? gm >> 1 : (gm - 8) * NSEG + seg, pair = gm < 8 ? ((gm & 1) ? 255 - j : j) : PLEN + j - seg * LM;
  sts128(sb + MISC + 512 + k * 16, make_uint4(q, (((j & (RING - 1)) * NG + gm) * 4 + (n & 3)) * TILEB + slot_tag(gm, j, epoch),
                                              (n & 2) * 384, (strip * 8 + (n & 1) * 4) | (pair << 9)));
  if (k == 0) sts32(sb + MISC + 256, epoch + 1);
}

__device__ __forceinline__ void mlp_setup(uint32_t sb, Globals* gs, int id, const __nv_bfloat16* __restrict__ w1, const __nv_bfloat16* __restrict__ w2,
                                          int idx, bool tabled, int warp, int lane) {
  const int rot = idx % 6;
  PROF2_AT(lane == 0, 400 + warp);
  if (warp < 12) {
    const int m = warp >= 6; int s = warp - 6 * m + rot; if (s >= 6) s -= 6;
    copy_weights(sb, 6 * m + s, (const char*)(m ? w2 : w1) + s * 12288);
  }
  __syncthreads();
  PROF2_AT(threadIdx.x == 0, 416);
  if (warp >= 12) build_tile_list(sb, threadIdx.x - 384, idx, tabled, false, ld_relaxed(&gs->epoch[id]));
  PROF2_AT(lane == 0, 420 + warp);
  convert_weights(sb, sb + WBAR, rot, warp, lane);
  PROF2_AT(lane == 0, 460 + warp);
  asm volatile("fence.proxy.async.shared::cta;" ::: "memory");
  __syncthreads();
  if (threadIdx.x == 480) {
    const uint32_t e1 = lds32(sb + MISC + 256);
    gs->epoch[id] = e1;
    if (idx < 24 && (idx & 1)) {
      asm volatile("cp.async.bulk.global.shared::cta.bulk_group [%0], [%1], 12288;\ncp.async.bulk.commit_group;\ncp.async.bulk.wait_group 0;\nfence.proxy.async.global;\n"
                   "red.release.gpu.global.add.u32 [%2], 1;" ::"l"(gs->wimg + (idx >> 1) * 12288), "r"(sb + (idx >> 1) * 12288), "l"(gs->wflag) : "memory");
    }
  }
  __syncwarp();
}

__device__ __forceinline__ void mlp_role(uint32_t sb, Globals* gs, const CUtensorMap* tmr, __nv_bfloat16* __restrict__ out) {
  uint32_t tid;
  asm volatile("mov.u32 %0, %%tid.x;" : "=r"(tid));
  const int warp = __shfl_sync(0xffffffffu, tid >> 5, 0), lane = tid & 31;
  const int wg = warp >> 2, w = warp & 3, g = lane >> 2, t = lane & 3;
  const uint32_t abuf = sb + ABUF + warp * 3072, xbuf = sb + XBUF + (warp & 7) * 3072;
  const uint32_t bar = sb + MISC + warp * 8, obar = sb + MISC + (warp ^ 8) * 8;
  const uint32_t tl = sb + MISC + 512;
  PROF_AT(threadIdx.x == 0, 1); PROF_VAL(threadIdx.x == 0, 8, clock64());
  const uint32_t rtarget = 3 * lds32(sb + MISC + 256);
  const uint64_t d1 = ((uint64_t)(768 >> 4) << 16) | ((uint64_t)(128 >> 4) << 32) | (uint64_t)(((sb + W1S) >> 4) & 0x3fff);
  const uint64_t d2 = ((uint64_t)(12288 >> 4) << 16) | ((uint64_t)(128 >> 4) << 32) | (uint64_t)(((sb + W2S) >> 4) & 0x3fff);
  const uint32_t ad = abuf + t * 128 + ((g ^ (2 * t)) << 4);
  const uint32_t xd = xbuf + g * 192 + t * 16;
  const int mybar = 1 + wg, nxtbar = 1 + ((wg + 1) & 3);
  const uint64_t pol = pol_evict_first();
  const unsigned char* const asrc = gs->scratch + w * 3072;
  uint32_t pha = 0, phx = 0, tp = tl + wg * 16;
  bool pending = true;
  uint32_t cur[4];
  lds128(cur, tp);
  while ((int)cur[0] >= 0) {
    PROF2_AT((threadIdx.x & 127) == 0, 16 + (tp - tl) / 4); PROF2_VAL((threadIdx.x & 127) == 0, 16 + (tp - tl) / 4 + 3, pending);
    uint32_t a[24], p[8][12], gg[8][12], acc[24], raw[6][4], xr[6][4], n2[4], n4[4];
    if (pending) {
      wait_ready(&gs->ready[cur[0]], rtarget);
      fetch_a(abuf, bar, asrc + (cur[1] & ~1u));
      if (tp < tl + 32) fetch_x(xbuf, bar + 128, tmr, cur[2] + w * 192, cur[3], pol);
    }
    mbar_wait(bar, pha); pha ^= 1;
    PROF2_AT((threadIdx.x & 127) == 0, 16 + (tp - tl) / 4 + 1);
#pragma unroll
    for (int k = 0; k < 6; k++) lds128(raw[k], ad + k * 512);
    const int sig = lds32(tp + 16);
    lds128(n4, tp + 64);
    uint32_t st = layer_norm(raw, a, cur[1]);
    if (__any_sync(0xffffffffu, st != 0)) {
      for (int tries = 0; __any_sync(0xffffffffu, st & 1); tries++) {
        if (tries > SPIN_LIMIT) __trap();
        fetch_a(abuf, bar, asrc + (cur[1] & ~1u));
        mbar_wait(bar, pha); pha ^= 1;
        st = 0;
#pragma unroll
        for (int k = 0; k < 6; k++) st |= lds32(ad + k * 512) ^ cur[1];
      }
      ln_wide(ad);
#pragma unroll
      for (int k = 0; k < 6; k++) lds128(a + 4 * k, ad + k * 512);
    }
    if (!LATERED) red_add_elect(&gs->cons[cur[0]]);
    if (tp != tl) asm volatile("bar.sync %0, 256;" ::"r"(mybar) : "memory");
    PROF2_AT((threadIdx.x & 127) == 0, 16 + (tp - tl) / 4 + 2);
    uint32_t rdy = 0;
    wg_fence();
    gemm1(p[0], a, d1, 0); wg_commit();
    if (SCHED == 9) { gemm1_piece(p[1], a, d1, 1, 0); wg_commit(); }
    if (LATERED) asm volatile("{.reg .pred p; setp.eq.u32 p, %1, 0; @p red.relaxed.gpu.global.add.u32 [%0], 1;}" ::"l"(&gs->cons[cur[0]] + lane), "r"(lane) : "memory");
#pragma unroll
    for (int j = 0; j < 24; j++) {
      const int c = j / 3, s = j % 3;
      if (j == JB) {
        rdy = ld_relaxed(&gs->ready[max((int)n4[0], 0)]);
        wg_wait<0>();
        mbar_wait(bar + 128, phx); phx ^= 1;
      } else if (SCHED == 9) wg_wait<1>(); else if (s == 0) wg_wait<0>();
      if (j == TRIG) asm volatile("{.reg .pred p; setp.ge.s32 p, %1, 0; @p bar.arrive %0, 256;}" ::"r"(nxtbar), "r"(sig) : "memory");
#pragma unroll
      for (int i = 0; i < 4; i++) gg[c][4 * s + i] = gelu_h2(p[c][4 * s + i]);
      wg_fence();
      if (j == 0) wgmma_n96_f16<0>(acc, gg[c], d2); else wgmma_n96_f16<1>(acc, &gg[c][4 * s], d2 + (16 * s + c) * (1536 >> 4));
      if (SCHED == 9) {
        if (j < 20) gemm1_piece(p[(j + 1) / 3 + 1], a, d1, (j + 1) / 3 + 1, (j + 1) % 3);
        wg_commit();
      } else if (s == 2) {
        if (c < 7) gemm1(p[c + 1], a, d1, c + 1);
        wg_commit();
      }
    }
    if (XEARLY) {
#pragma unroll
      for (int k = 0; k < 6; k++) lds128(xr[k], xd + (k / 3) * 1536 + (k % 3) * 64);
      lds128(n2, tp + 32);
    }
    pending = rdy != rtarget;
    if (FPRED) fetch_a_if(abuf, bar, asrc + (n4[1] & ~1u), !pending && (int)n4[0] >= 0);
    wg_wait<0>();
    if (!FPRED && !pending && (int)n4[0] >= 0) fetch_a(abuf, bar, asrc + (n4[1] & ~1u));
    char* const op = (char*)out + (size_t)(cur[3] >> 8) * (512 * 192) + ((cur[3] & 255) + (g >> 1)) * 3072 + cur[2] * 2 + (2 * w + (g & 1)) * 192 + t * 16;
    if (!XEARLY) lds128(n2, tp + 32);
#pragma unroll
    for (int k = 0; k < 6; k++) {
      const int hi = k / 3, j = k % 3;
      if (!XEARLY) lds128(xr[k], xd + hi * 1536 + j * 64);
      uint4 o;
      o.x = hadd2_bf16(xr[k][0], pack_bf16(h_lo(acc[8 * j + hi]), h_hi(acc[8 * j + hi])));
      o.y = hadd2_bf16(xr[k][1], pack_bf16(h_lo(acc[8 * j + 2 + hi]), h_hi(acc[8 * j + 2 + hi])));
      o.z = hadd2_bf16(xr[k][2], pack_bf16(h_lo(acc[8 * j + 4 + hi]), h_hi(acc[8 * j + 4 + hi])));
      o.w = hadd2_bf16(xr[k][3], pack_bf16(h_lo(acc[8 * j + 6 + hi]), h_hi(acc[8 * j + 6 + hi])));
      stg128_stream(op + hi * (512 * 192) + j * 64, o, pol);
    }
    __syncwarp();
    if ((int)n2[0] >= 0) fetch_x(xbuf, obar + 128, tmr, n2[2] + w * 192, n2[3], pol);
    tp += 64;
#pragma unroll
    for (int k = 0; k < 4; k++) cur[k] = n4[k];
  }
  PROF_AT((threadIdx.x & 127) == 0, 4 + wg); PROF_VAL(threadIdx.x == 0, 9, clock64());
}

__device__ __forceinline__ void conv_compute(uint32_t sb, Globals* gs, const __nv_bfloat16* __restrict__ dw, int third, int nit, int off, bool up, int warp, int lane) {
  const int g = lane >> 2, t = lane & 3;
  const uint32_t full = sb + CM;
  uint32_t A[4][4][4];
  {
    uint2 w[2][4][3];
#pragma unroll
    for (int h = 0; h < 2; h++) {
      const int j = (4 * h + t - g) & 7;
      const char* src = (const char*)(dw + j * 96 + third * 32 + warp * 4) + (up ? 5 : -1) * 1344;
#pragma unroll
      for (int u = 0; u < 4; u++) {
#pragma unroll
        for (int k = 0; k < 3; k++) {
          const bool edge = (u == 0 && k == 0) || (u == 3 && k == 2), edge_up = (u == 3 && k == 0) || (u == 0 && k == 2);
          const uint32_t ok = j < 7 && !(edge && !up) && !(edge_up && up);
          asm volatile("{.reg .pred p; setp.ne.u32 p, %3, 0; mov.b32 %0, 0; mov.b32 %1, 0; @p ld.global.nc.v2.b32 {%0,%1}, [%2];}"
                       : "=r"(w[h][u][k].x), "=r"(w[h][u][k].y) : "l"(src + k * 1344), "r"(ok) : "memory");
        }
        src += up ? -2688 : 2688;
      }
    }
    asm volatile("setmaxnreg.inc.sync.aligned.u32 %0;" ::"n"(CREGS));
    PROF2_AT(threadIdx.x == 0, 11);
#pragma unroll
    for (int u = 0; u < 4; u++)
#pragma unroll
      for (int r = 0; r < 4; r++) {
        const uint2 w0 = w[r >> 1][u][1 - (r & 1)], w1 = w[r >> 1][u][2 - (r & 1)];
        A[0][u][r] = prmt(w0.x, w1.x, 0x5410); A[1][u][r] = prmt(w0.x, w1.x, 0x7632);
        A[2][u][r] = prmt(w0.y, w1.y, 0x5410); A[3][u][r] = prmt(w0.y, w1.y, 0x7632);
      }
  }
  uint32_t meta = 0;
#pragma unroll
  for (int a = 0; a < 4; a++) meta |= ((4 * (t & 1) + a + 1 >= g) ? 0x80008u : 0xD000Du) << (4 * a);
  meta = __shfl_sync(0xffffffffu, meta, lane);
  float S[2][4][3][4];
#pragma unroll
  for (int s = 0; s < 2; s++)
#pragma unroll
    for (int c = 0; c < 4; c++)
#pragma unroll
      for (int i = 0; i < 3; i++)
#pragma unroll
        for (int k = 0; k < 4; k++) S[s][c][i][k] = 0.f;
  uint32_t aq[4];
#pragma unroll
  for (int q = 0; q < 4; q++) {
    const int pp = (g & 1) * 140 + (t & 1) * 70 + 16 * (g >> 1) + 2 * q + (t >> 1);
    aq[q] = __shfl_sync(0xffffffffu, sb + RBUF + pp * 64 + (((warp >> 1) ^ ((pp >> 1) & 3)) << 4) + (warp & 1) * 8, lane);
  }
  const int Q = third * 8 + warp;
  unsigned char* const obase = gs->scratch + (g >> 1) * 3072 + Q * 128 + (((2 * t + (g & 1)) ^ (2 * (Q & 3))) << 4);
  const float zero4[4] = {0.f, 0.f, 0.f, 0.f};
  uint32_t sofs = off * SLOTB, bar = full + off * 8, ph = 0;
  uint2 X[3][4];
  PROF_AT(threadIdx.x == 0, 12);
  asm volatile("bar.sync 0, 512;" ::: "memory");
  PROF2_AT(threadIdx.x == 0, 10);
  mbar_wait(bar, 0);
  PROF_AT(threadIdx.x == 0, 14);
#pragma unroll
  for (int j = 0; j < 2; j++)
#pragma unroll
    for (int q = 0; q < 4; q++) X[j][q] = lds64(aq[q] + sofs + j * 512);
  for (uint32_t ot = sb + CTAB; ot < sb + CTAB + nit * 16; ot += 16) {
    const uint2 oe = lds64(ot);
    unsigned char* const o = obase + oe.x;
    const uint32_t dbar = bar + 64;
#pragma unroll
    for (int s = 0; s < 2; s++) {
      uint32_t B[4][4];
      if (s == 1) {
        sofs += SLOTB; bar += 8;
        if (sofs == NSLOT * SLOTB) { sofs = 0; bar = full; ph ^= 1; }
        mbar_wait(bar, ph);
      }
#pragma unroll
      for (int c = 0; c < 4; c++)
#pragma unroll
        for (int q = 0; q < 4; q++) B[c][q] = prmt(c < 2 ? X[s][q].x : X[s][q].y, c < 2 ? X[s + 1][q].x : X[s + 1][q].y, (c & 1) ? 0x7632 : 0x5410);
      if (s == 0) {
#pragma unroll
        for (int q = 0; q < 4; q++) X[2][q] = lds64(aq[q] + sofs + 2 * 512);
      } else {
#pragma unroll
        for (int j = 0; j < 2; j++)
#pragma unroll
          for (int q = 0; q < 4; q++) X[j][q] = lds64(aq[q] + sofs + j * 512);
      }
      float T[4][4];
      if (CFN & 1) SCHED_FENCE();
#pragma unroll
      for (int c = 0; c < 4; c++) mma_sp(T[c], A[c][3], B[c], S[s][c][2], meta);
#pragma unroll
      for (int c = 0; c < 4; c++) mma_sp(S[s][c][2], A[c][2], B[c], S[s][c][1], meta);
      if (CFN & 2) SCHED_FENCE();
      stg128(o + (2 * s) * TILEB, make_uint4((pack_f16_sat(T[0][0], T[1][0]) & ~1u) | oe.y, pack_f16_sat(T[2][0], T[3][0]), pack_f16_sat(T[0][2], T[1][2]), pack_f16_sat(T[2][2], T[3][2])));
      stg128(o + (2 * s + 1) * TILEB, make_uint4((pack_f16_sat(T[0][1], T[1][1]) & ~1u) | oe.y, pack_f16_sat(T[2][1], T[3][1]), pack_f16_sat(T[0][3], T[1][3]), pack_f16_sat(T[2][3], T[3][3])));
      if (s == 1) mbar_arrive_elect(dbar);
      if (CFN & 4) SCHED_FENCE();
#pragma unroll
      for (int c = 0; c < 4; c++) mma_sp(S[s][c][1], A[c][1], B[c], S[s][c][0], meta);
#pragma unroll
      for (int c = 0; c < 4; c++) mma_sp(S[s][c][0], A[c][0], B[c], zero4, meta);
    }
  }
  PROF_AT(threadIdx.x == 0, 13);
}

__device__ __forceinline__ void conv_loader(uint32_t sb, Globals* gs, const CUtensorMap* tmx, int gm, int nit, int off, int cidx, int third, int k) {
  static_assert(AHEAD > 4 && AHEAD <= NSLOT && NCONV >= 24, "loader");
  const uint32_t full = sb + CM;
#pragma unroll
  for (int h = 0; h < 2; h++) {
    const int s = (k + off + 4 * h) & 7;
    asm volatile("{\n.reg .pred p, q;\nelect.sync _|p, 0xffffffff;\n@p mbarrier.init.shared::cta.b64 [%0], 2;\n@p mbarrier.init.shared::cta.b64 [%0+64], 8;\n"
                 "setp.ne.and.u32 q, %1, 0, p;\n@q mbarrier.arrive.shared::cta.b64 _, [%0], 2;\n@q mbarrier.arrive.shared::cta.b64 _, [%0+64], 8;\n}"
                 ::"r"(full + s * 8), "r"((uint32_t)(s < off)) : "memory");
  }
  if (k == 0) mbar_init_elect(sb + WBAR, 2);
  asm volatile("fence.mbarrier_init.release.cluster;" ::: "memory");
  bool synced = false;
#pragma unroll 1
  for (int it = k; it < nit + AHEAD; it += 4) {
    const int u = it + off, s = u & 7, seg = it / (LM + 3);
    const int st = gm < 8 ? gm >> 1 : (gm - 8) * NSEG + seg, J = gm < 8 ? ((gm & 1) ? 257 - it : it + 1) : PLEN + it - seg * (LM + 3);
    if (it >= AHEAD) {
      if (!synced) { asm volatile("bar.sync 0, 512;" ::: "memory"); synced = true; }
      const uint32_t ro = lds32(sb + CTAB + (it - AHEAD) * 16 + 8);
      mbar_wait(full + 64 + ((u - AHEAD) & 7) * 8, ((u - AHEAD) >> 3) & 1);
      red_add_elect((uint32_t*)((char*)gs + ro));
      PROF_AT((threadIdx.x & 31) == 0 && ((it - AHEAD) & (PROF > 1 ? 7 : 15)) == 0, 200 + it - AHEAD);
    }
    if (it <= nit)
      asm volatile("{\n.reg .pred p;\n.reg .s32 c2;\n.reg .u32 d2;\nelect.sync _|p, 0xffffffff;\nadd.s32 c2, %4, 64;\nadd.u32 d2, %0, 8960;\n"
                   "@p mbarrier.arrive.expect_tx.shared::cta.b64 _, [%2], 17920;\n"
                   "@p cp.async.bulk.tensor.3d.shared::cluster.global.mbarrier::complete_tx::bytes [%0], [%1, {%3, %4, %5}], [%2];\n"
                   "@p cp.async.bulk.tensor.3d.shared::cluster.global.mbarrier::complete_tx::bytes [d2], [%1, {%3, c2, %5}], [%2];\n}"
                   ::"r"(sb + RBUF + s * SLOTB), "l"(tmx), "r"(full + s * 8), "r"(third * 32), "r"(st * 128 - 3), "r"(2 * J - 3) : "memory");
    if (it >= nit - 16) {
      if (it < nit - 12) {
        wait_ready(gs->wflag, 12 * lds32(sb + MISC + 256));
        asm volatile("fence.acquire.gpu;\nfence.proxy.async.global;" ::: "memory");
        if (cidx < 24) asm volatile("{.reg .pred p; elect.sync _|p, 0xffffffff; @p cp.async.bulk.prefetch.L2.global [%0], 1536;}" ::"l"(gs->wimg + (cidx * 4 + k) * 1536) : "memory");
      }
      const int m = it == nit ? 0 : W2S;
      if (it == nit || it == nit + AHEAD - 4)
        asm volatile("{\n.reg .pred p;\nelect.sync _|p, 0xffffffff;\n@p mbarrier.arrive.expect_tx.shared::cta.b64 _, [%1], 73728;\n"
                     "@p cp.async.bulk.shared::cluster.global.mbarrier::complete_tx::bytes [%0], [%2], 73728, [%1];\n}"
                     ::"r"(sb + m), "r"(sb + WBAR), "l"(gs->wimg + m) : "memory");
    }
  }
}

__device__ __forceinline__ void conv_credit(uint32_t sb, Globals* gs, int P0, int nit, int off, uint32_t ctarget, int k) {
  const uint32_t full = sb + CM;
#pragma unroll 1
  for (int it = k + NSLOT; it <= nit; it += 4) {
    const int u = it + off, P = (int)lds32(sb + CTAB + it * 16 + 12) - RING;
    int spins = 0;
    mbar_wait(full + 64 + (u & 7) * 8, ((u >> 3) & 1) ^ 1);
    if (P >= P0) while (ld_relaxed(&gs->cons[P]) != ctarget) { __nanosleep(CSLEEP); if (++spins > SPIN_LIMIT) __trap(); }
    mbar_arrive_elect(full + (u & 7) * 8);
  }
}

__global__ void __launch_bounds__(512, 1) convnext_kernel(const __grid_constant__ CUtensorMap tmx, const __grid_constant__ CUtensorMap tmr, const __nv_bfloat16* __restrict__ dw,
                                                          const __nv_bfloat16* __restrict__ w1, const __nv_bfloat16* __restrict__ w2, __nv_bfloat16* __restrict__ out, Globals* gs) {
  extern __shared__ __align__(1024) unsigned char smem[];
  const uint32_t sb = smem_u32(smem);
  const int warp = __shfl_sync(0xffffffffu, threadIdx.x >> 5, 0), lane = threadIdx.x & 31;
  PROF_AT(threadIdx.x == 0, 0);
  if (threadIdx.x == 256) asm volatile("prefetch.tensormap [%0];" ::"l"(&tmx) : "memory");
  if (threadIdx.x == 288) asm volatile("prefetch.tensormap [%0];" ::"l"(&tmr) : "memory");
  uint32_t smid, nsmid;
  asm volatile("mov.u32 %0, %%smid;" : "=r"(smid));
  asm volatile("mov.u32 %0, %%nsmid;" : "=r"(nsmid));
  const bool tabled = TABLED && gridDim.x == 132 && nsmid == 132;
  const int id = tabled ? smid : blockIdx.x;
  int cidx, idx;
  int is_conv;
  if (tabled) {
    idx = smid;
    const int k = (smid - 60) / 14, r = smid - 60 - 14 * k;
    is_conv = smid < 48 ? !(smid & 1) : (smid >= 60 && smid <= 90 && (r & ~2) == 0);
    cidx = smid < 48 ? ((smid >> 1) & 7) * 3 + (smid >> 4) : 24 + (r >> 1) * 3 + k;
  } else {
    cidx = (blockIdx.x * NCONV) / gridDim.x;
    is_conv = ((blockIdx.x + 1) * NCONV) / gridDim.x != cidx;
    idx = blockIdx.x - cidx;
  }
  PROF_VAL(threadIdx.x == 0, 2, is_conv ? 1000 + cidx : idx);
  mbar_init_elect(sb + MISC + warp * 8, 1); mbar_init_elect(sb + MISC + 128 + warp * 8, 1);
  asm volatile("fence.mbarrier_init.release.cluster;" ::: "memory");
  if (is_conv) {
    const int gm = cidx / 3, third = cidx - gm * 3;
    const int P0 = gm * PLEN, nit = gm < 8 ? PLEN + 2 : NSEG * (LM + 3), off = (7 - nit) & 7;
    if (warp < 8) {
      conv_compute(sb, gs, dw, third, nit, off, gm < 8 && (gm & 1), warp, lane);
      asm volatile("setmaxnreg.dec.sync.aligned.u32 128;");
    } else if (warp >= 12) {
      asm volatile("setmaxnreg.dec.sync.aligned.u32 24;");
      const uint32_t epoch = ld_relaxed(&gs->epoch[id]);
#pragma unroll 1
      for (int it = threadIdx.x - 384; it <= nit; it += 128) {
        const int seg = it / (LM + 3), j = gm < 8 ? it - 2 : it - 3 * (seg + 1);
        const bool ok = it < nit && j >= (gm < 8 ? 0 : seg * LM);
        sts128(sb + CTAB + it * 16, make_uint4((ok ? (j & (RING - 1)) * NG + gm : RING * NG) * (4 * TILEB), slot_tag(gm, max(j, 0), epoch),
                                               offsetof(Globals, ready) + (ok ? P0 + j : NG * PLEN) * 4, ok ? P0 + j : -1));
      }
      asm volatile("bar.sync 0, 512;" ::: "memory");
      mbar_arrive_elect(sb + CM + ((((warp + 2) & 3) + off) & 7) * 8);
      mbar_arrive_elect(sb + CM + ((((warp + 2) & 3) + off + 4) & 7) * 8);
      build_tile_list(sb, threadIdx.x - 384, idx, tabled, true, epoch);
      if (threadIdx.x == 384) gs->epoch[id] = epoch + 1;
      conv_credit(sb, gs, P0, nit, off, 16 * (epoch + 1), (warp + 2) & 3);
      mbar_wait(sb + CM + 64 + 3 * 8, ((nit + off) >> 3) & 1);
      mbar_wait(sb + CM + 64 + 6 * 8, ((nit + off) >> 3) & 1);
      asm volatile("setmaxnreg.inc.sync.aligned.u32 128;");
    } else {
      asm volatile("setmaxnreg.dec.sync.aligned.u32 %0;" ::"n"(488 - 2 * CREGS));
      conv_loader(sb, gs, &tmx, gm, nit, off, cidx, third, warp & 3);
      mbar_wait(sb + CM + 64 + 3 * 8, ((nit + off) >> 3) & 1);
      mbar_wait(sb + CM + 64 + 6 * 8, ((nit + off) >> 3) & 1);
      asm volatile("setmaxnreg.inc.sync.aligned.u32 128;");
    }
    PROF2_AT((threadIdx.x & 31) == 0, 400 + (threadIdx.x >> 5));
    mbar_wait(sb + WBAR, 0);
    asm volatile("bar.sync 0, 512;" ::: "memory");
  } else {
    mlp_setup(sb, gs, id, w1, w2, idx, tabled, warp, lane);
  }
  mlp_role(sb, gs, &tmr, out);
}

typedef CUresult (*PFN_encodeTiled)(CUtensorMap*, CUtensorMapDataType, cuuint32_t, void*, const cuuint64_t*, const cuuint64_t*, const cuuint32_t*, const cuuint32_t*,
                                    CUtensorMapInterleave, CUtensorMapSwizzle, CUtensorMapL2promotion, CUtensorMapFloatOOBfill);

extern "C" void kernel_launch(void* const* d_in, const int* in_sizes, int n_in, void* d_out, int out_size) {
  const __nv_bfloat16* x = (const __nv_bfloat16*)d_in[0];
  const __nv_bfloat16* dw = (const __nv_bfloat16*)d_in[1];
  const __nv_bfloat16* w1 = (const __nv_bfloat16*)d_in[2];
  const __nv_bfloat16* w2 = (const __nv_bfloat16*)d_in[3];
  static PFN_encodeTiled encode = nullptr;
  static int nsm = 0;
  static Globals* gs = nullptr;
  if (!encode) {
    void* fn = nullptr; cudaDriverEntryPointQueryResult qr;
    cudaGetDriverEntryPoint("cuTensorMapEncodeTiled", &fn, cudaEnableDefault, &qr);
    encode = (PFN_encodeTiled)fn;
    cudaGetSymbolAddress((void**)&gs, g_state);
    int dev = 0; cudaGetDevice(&dev);
    cudaDeviceGetAttribute(&nsm, cudaDevAttrMultiProcessorCount, dev);
    cudaFuncSetAttribute(convnext_kernel, cudaFuncAttributeMaxDynamicSharedMemorySize, SMEM_BYTES);
  }
  CUtensorMap tm;
  cuuint64_t dims[3] = {96, 512, 512}, strides[2] = {192, 192 * 512};
  cuuint32_t box[3] = {32, 70, 2}, es[3] = {1, 1, 1};
  encode(&tm, CU_TENSOR_MAP_DATA_TYPE_BFLOAT16, 3, (void*)x, dims, strides, box, es, CU_TENSOR_MAP_INTERLEAVE_NONE, CU_TENSOR_MAP_SWIZZLE_64B,
         PROMO, CU_TENSOR_MAP_FLOAT_OOB_FILL_NONE);
  CUtensorMap tr;
  cuuint64_t dims2[3] = {1536, 32, 512}, strides2[2] = {3072, 192 * 512};
  cuuint32_t box2[3] = {192, 4, 2};
  encode(&tr, CU_TENSOR_MAP_DATA_TYPE_BFLOAT16, 3, (void*)x, dims2, strides2, box2, es, CU_TENSOR_MAP_INTERLEAVE_NONE, CU_TENSOR_MAP_SWIZZLE_NONE,
         CU_TENSOR_MAP_L2_PROMOTION_NONE, CU_TENSOR_MAP_FLOAT_OOB_FILL_NONE);
  convnext_kernel<<<nsm, 512, SMEM_BYTES>>>(tm, tr, dw, w1, w2, (__nv_bfloat16*)d_out, gs);
}
```

```cpp
#include <cuda_runtime.h>
#include <cuda_bf16.h>
#include <cuda.h>
#include <stdint.h>
#include <stddef.h>

template<int SCALE_D> __device__ __forceinline__ void wgmma_n48_f16(uint32_t* d, const uint32_t* a, uint64_t desc) {
  if (SCALE_D == 0) asm volatile("wgmma.mma_async.sync.aligned.m64n48k16.f16.f16.f16 {%0,%1,%2,%3,%4,%5,%6,%7,%8,%9,%10,%11}, {%12,%13,%14,%15}, %16, 0, 1, 1, 1;"
    : "=r"(d[0]),"=r"(d[1]),"=r"(d[2]),"=r"(d[3]),"=r"(d[4]),"=r"(d[5]),"=r"(d[6]),"=r"(d[7]),"=r"(d[8]),"=r"(d[9]),"=r"(d[10]),"=r"(d[11])
    : "r"(a[0]),"r"(a[1]),"r"(a[2]),"r"(a[3]),"l"(desc));
  if (SCALE_D == 1) asm volatile("wgmma.mma_async.sync.aligned.m64n48k16.f16.f16.f16 {%0,%1,%2,%3,%4,%5,%6,%7,%8,%9,%10,%11}, {%12,%13,%14,%15}, %16, 1, 1, 1, 1;"
    : "+r"(d[0]),"+r"(d[1]),"+r"(d[2]),"+r"(d[3]),"+r"(d[4]),"+r"(d[5]),"+r"(d[6]),"+r"(d[7]),"+r"(d[8]),"+r"(d[9]),"+r"(d[10]),"+r"(d[11])
    : "r"(a[0]),"r"(a[1]),"r"(a[2]),"r"(a[3]),"l"(desc));
}

template<int SCALE_D> __device__ __forceinline__ void wgmma_n96_f16(uint32_t* d, const uint32_t* a, uint64_t desc) {
  if (SCALE_D == 0) asm volatile("wgmma.mma_async.sync.aligned.m64n96k16.f16.f16.f16 {%0,%1,%2,%3,%4,%5,%6,%7,%8,%9,%10,%11,%12,%13,%14,%15,%16,%17,%18,%19,%20,%21,%22,%23}, {%24,%25,%26,%27}, %28, 0, 1, 1, 1;"
    : "=r"(d[0]),"=r"(d[1]),"=r"(d[2]),"=r"(d[3]),"=r"(d[4]),"=r"(d[5]),"=r"(d[6]),"=r"(d[7]),"=r"(d[8]),"=r"(d[9]),"=r"(d[10]),"=r"(d[11]),"=r"(d[12]),"=r"(d[13]),"=r"(d[14]),"=r"(d[15]),"=r"(d[16]),"=r"(d[17]),"=r"(d[18]),"=r"(d[19]),"=r"(d[20]),"=r"(d[21]),"=r"(d[22]),"=r"(d[23])
    : "r"(a[0]),"r"(a[1]),"r"(a[2]),"r"(a[3]),"l"(desc));
  if (SCALE_D == 1) asm volatile("wgmma.mma_async.sync.aligned.m64n96k16.f16.f16.f16 {%0,%1,%2,%3,%4,%5,%6,%7,%8,%9,%10,%11,%12,%13,%14,%15,%16,%17,%18,%19,%20,%21,%22,%23}, {%24,%25,%26,%27}, %28, 1, 1, 1, 1;"
    : "+r"(d[0]),"+r"(d[1]),"+r"(d[2]),"+r"(d[3]),"+r"(d[4]),"+r"(d[5]),"+r"(d[6]),"+r"(d[7]),"+r"(d[8]),"+r"(d[9]),"+r"(d[10]),"+r"(d[11]),"+r"(d[12]),"+r"(d[13]),"+r"(d[14]),"+r"(d[15]),"+r"(d[16]),"+r"(d[17]),"+r"(d[18]),"+r"(d[19]),"+r"(d[20]),"+r"(d[21]),"+r"(d[22]),"+r"(d[23])
    : "r"(a[0]),"r"(a[1]),"r"(a[2]),"r"(a[3]),"l"(desc));
}

#define SCHED_NG 10
#define SCHED_LE 103
__device__ const uint16_t g_sched[132][48] = {
{367,3260,389,403,65535,65535,65535,65535,65535,65535,65535,65535,65535,65535,65535,65535,65535,65535,65535,65535,65535,65535,65535,65535,65535,65535,65535,65535,65535,65535,65535,65535,65535,65535,65535,65535,65535,65535,65535,65535,65535,65535,65535,65535,65535,65535,65535,65535},
{0,2483,22,2915,2925,2935,3765,73,83,93,2986,3816,124,134,144,3037,3867,175,185,195,3088,218,3111,3121,3939,259,269,279,3172,3990,310,320,330,3223,4041,361,374,387,400,65535,65535,65535,65535,65535,65535,65535,65535,65535},
{2838,788,802,815,65535,65535,65535,65535,65535,65535,65535,65535,65535,65535,65535,65535,65535,65535,65535,65535,65535,65535,65535,65535,65535,65535,65535,65535,65535,65535,65535,65535,65535,65535,65535,65535,65535,65535,65535,65535,65535,65535,65535,65535,65535,65535,65535,65535},
{412,422,432,442,452,463,473,483,493,503,514,524,534,544,554,565,575,585,595,605,616,628,638,649,659,669,679,689,700,710,720,730,740,751,761,771,784,798,811,65535,65535,65535,65535,65535,65535,65535,65535,65535},
{3646,1199,1213,1226,65535,65535,65535,65535,65535,65535,65535,65535,65535,65535,65535,65535,65535,65535,65535,65535,65535,65535,65535,65535,65535,65535,65535,65535,65535,65535,65535,65535,65535,65535,65535,65535,65535,65535,65535,65535,65535,65535,65535,65535,65535,65535,65535,65535},
{824,834,845,855,865,876,886,896,906,917,927,937,947,957,968,978,988,998,1008,1019,1029,1041,1051,1062,1072,1082,1092,1103,1113,1123,1133,1143,1154,1164,1174,1184,1196,1210,1223,65535,65535,65535,65535,65535,65535,65535,65535,65535},
{1603,1612,1624,1638,65535,65535,65535,65535,65535,65535,65535,65535,65535,65535,65535,65535,65535,65535,65535,65535,65535,65535,65535,65535,65535,65535,65535,65535,65535,65535,65535,65535,65535,65535,65535,65535,65535,65535,65535,65535,65535,65535,65535,65535,65535,65535,65535,65535},
{1236,1247,1257,1267,1278,1288,1298,1308,1318,1329,1339,1349,1359,1369,1380,1390,1400,1410,1420,1431,1441,1453,1464,1474,1484,1494,1504,1515,1525,1535,1545,1555,1566,1576,1586,1596,1609,1622,1636,65535,65535,65535,65535,65535,65535,65535,65535,65535},
{2015,2024,2037,2050,65535,65535,65535,65535,65535,65535,65535,65535,65535,65535,65535,65535,65535,65535,65535,65535,65535,65535,65535,65535,65535,65535,65535,65535,65535,65535,65535,65535,65535,65535,65535,65535,65535,65535,65535,65535,65535,65535,65535,65535,65535,65535,65535,65535},
{1648,1659,1669,1680,1690,1700,1710,1720,1731,1741,1751,1761,1771,1782,1792,1802,1812,1822,1833,1843,1853,1865,1876,1886,1896,1906,1917,1927,1937,1947,1957,1968,1978,1988,1998,2008,2021,2035,2048,65535,65535,65535,65535,65535,65535,65535,65535,65535},
{4058,2436,2449,2462,65535,65535,65535,65535,65535,65535,65535,65535,65535,65535,65535,65535,65535,65535,65535,65535,65535,65535,65535,65535,65535,65535,65535,65535,65535,65535,65535,65535,65535,65535,65535,65535,65535,65535,65535,65535,65535,65535,65535,65535,65535,65535,65535,65535},
{2060,2071,2081,2092,2102,2112,2122,2132,2143,2153,2163,2173,2183,2194,2204,2214,2224,2234,2245,2255,2265,2277,2288,2298,2308,2318,2329,2339,2349,2359,2369,2380,2390,2400,2410,2420,2433,2447,2460,65535,65535,65535,65535,65535,65535,65535,65535,65535},
{2839,3656,2861,2874,65535,65535,65535,65535,65535,65535,65535,65535,65535,65535,65535,65535,65535,65535,65535,65535,65535,65535,65535,65535,65535,65535,65535,65535,65535,65535,65535,65535,65535,65535,65535,65535,65535,65535,65535,65535,65535,65535,65535,65535,65535,65535,65535,65535},
{2472,3303,3313,3323,3333,3343,2534,3364,3374,3384,3394,2585,3415,3425,3435,3445,2636,3466,3476,3486,2677,2690,3507,3517,2720,3538,3548,3558,3568,2771,3589,3599,3609,3619,2822,3640,3654,2859,2872,65535,65535,65535,65535,65535,65535,65535,65535,65535},
{3251,4068,3273,3286,65535,65535,65535,65535,65535,65535,65535,65535,65535,65535,65535,65535,65535,65535,65535,65535,65535,65535,65535,65535,65535,65535,65535,65535,65535,65535,65535,65535,65535,65535,65535,65535,65535,65535,65535,65535,65535,65535,65535,65535,65535,65535,65535,65535},
{2884,2895,2905,3735,3745,3755,2946,2956,2966,2976,3806,2997,3007,3017,3027,3857,3048,3058,3068,3078,3089,3909,3919,3929,3132,3142,3152,3162,3980,3183,3193,3203,3213,4031,3234,3244,4065,3270,4091,65535,65535,65535,65535,65535,65535,65535,65535,65535},
{368,378,390,3682,65535,65535,65535,65535,65535,65535,65535,65535,65535,65535,65535,65535,65535,65535,65535,65535,65535,65535,65535,65535,65535,65535,65535,65535,65535,65535,65535,65535,65535,65535,65535,65535,65535,65535,65535,65535,65535,65535,65535,65535,65535,65535,65535,65535},
{1,3715,3725,33,43,53,63,3776,3786,3796,104,114,3827,3837,3847,155,165,3878,3888,3898,206,219,229,239,249,3950,3960,3970,290,300,4001,4011,4021,341,351,4052,375,4078,401,65535,65535,65535,65535,65535,65535,65535,65535,65535},
{780,789,3669,4094,65535,65535,65535,65535,65535,65535,65535,65535,65535,65535,65535,65535,65535,65535,65535,65535,65535,65535,65535,65535,65535,65535,65535,65535,65535,65535,65535,65535,65535,65535,65535,65535,65535,65535,65535,65535,65535,65535,65535,65535,65535,65535,65535,65535},
{413,423,433,443,453,464,474,484,494,504,515,525,535,545,555,566,576,586,596,606,617,629,639,650,660,670,680,690,701,711,721,731,741,752,762,772,785,799,812,65535,65535,65535,65535,65535,65535,65535,65535,65535},
{1192,1200,1214,1227,65535,65535,65535,65535,65535,65535,65535,65535,65535,65535,65535,65535,65535,65535,65535,65535,65535,65535,65535,65535,65535,65535,65535,65535,65535,65535,65535,65535,65535,65535,65535,65535,65535,65535,65535,65535,65535,65535,65535,65535,65535,65535,65535,65535},
{825,835,846,856,866,877,887,897,907,918,928,938,948,958,969,979,989,999,1009,1020,1030,1042,1052,1063,1073,1083,1093,1104,1114,1124,1134,1144,1155,1165,1175,1185,1197,1211,1224,65535,65535,65535,65535,65535,65535,65535,65535,65535},
{1604,1613,1625,1639,65535,65535,65535,65535,65535,65535,65535,65535,65535,65535,65535,65535,65535,65535,65535,65535,65535,65535,65535,65535,65535,65535,65535,65535,65535,65535,65535,65535,65535,65535,65535,65535,65535,65535,65535,65535,65535,65535,65535,65535,65535,65535,65535,65535},
{1237,1248,1258,1268,1279,1289,1299,1309,1319,1330,1340,1350,1360,1370,1381,1391,1401,1411,1421,1432,1442,1454,1465,1475,1485,1495,1505,1516,1526,1536,1546,1556,1567,1577,1587,1597,1610,1623,1637,65535,65535,65535,65535,65535,65535,65535,65535,65535},
{2016,2025,2038,2051,65535,65535,65535,65535,65535,65535,65535,65535,65535,65535,65535,65535,65535,65535,65535,65535,65535,65535,65535,65535,65535,65535,65535,65535,65535,65535,65535,65535,65535,65535,65535,65535,65535,65535,65535,65535,65535,65535,65535,65535,65535,65535,65535,65535},
{1649,1660,1670,1681,1691,1701,1711,1721,1732,1742,1752,1762,1772,1783,1793,1803,1813,1823,1834,1844,1854,1866,1877,1887,1897,1907,1918,1928,1938,1948,1958,1969,1979,1989,1999,2009,2022,2036,2049,65535,65535,65535,65535,65535,65535,65535,65535,65535},
{2428,2437,2450,2463,65535,65535,65535,65535,65535,65535,65535,65535,65535,65535,65535,65535,65535,65535,65535,65535,65535,65535,65535,65535,65535,65535,65535,65535,65535,65535,65535,65535,65535,65535,65535,65535,65535,65535,65535,65535,65535,65535,65535,65535,65535,65535,65535,65535},
{2061,2072,2082,2093,2103,2113,2123,2133,2144,2154,2164,2174,2184,2195,2205,2215,2225,2235,2246,2256,2266,2278,2289,2299,2309,2319,2330,2340,2350,2360,2370,2381,2391,2401,2411,2421,2434,2448,2461,65535,65535,65535,65535,65535,65535,65535,65535,65535},
{3647,2849,2862,2875,65535,65535,65535,65535,65535,65535,65535,65535,65535,65535,65535,65535,65535,65535,65535,65535,65535,65535,65535,65535,65535,65535,65535,65535,65535,65535,65535,65535,65535,65535,65535,65535,65535,65535,65535,65535,65535,65535,65535,65535,65535,65535,65535,65535},
{2473,2484,2494,2504,3334,3344,2535,2545,2555,2565,3395,2586,2596,2606,2616,3446,2637,2647,2657,2667,2678,3498,3508,3518,2721,2731,2741,2751,3569,2772,2782,2792,2802,3620,2823,2833,2847,3667,3680,65535,65535,65535,65535,65535,65535,65535,65535,65535},
{4059,3261,4081,3287,65535,65535,65535,65535,65535,65535,65535,65535,65535,65535,65535,65535,65535,65535,65535,65535,65535,65535,65535,65535,65535,65535,65535,65535,65535,65535,65535,65535,65535,65535,65535,65535,65535,65535,65535,65535,65535,65535,65535,65535,65535,65535,65535,65535},
{2885,2896,2906,2916,2926,2936,3766,2957,2967,2977,2987,3817,3008,3018,3028,3038,3868,3059,3069,3079,3090,3910,3112,3122,3940,3143,3153,3163,3173,3991,3194,3204,3214,3224,4042,3245,4066,3271,4092,65535,65535,65535,65535,65535,65535,65535,65535,65535},
{369,3657,391,404,65535,65535,65535,65535,65535,65535,65535,65535,65535,65535,65535,65535,65535,65535,65535,65535,65535,65535,65535,65535,65535,65535,65535,65535,65535,65535,65535,65535,65535,65535,65535,65535,65535,65535,65535,65535,65535,65535,65535,65535,65535,65535,65535,65535},
{2,13,23,3324,3746,3756,64,3365,3375,3385,3807,115,3416,3426,3436,3858,166,3467,3477,3487,208,220,3920,3930,250,3539,3549,3559,3981,301,3590,3600,3610,4032,352,3641,376,4079,402,65535,65535,65535,65535,65535,65535,65535,65535,65535},
{781,790,803,816,65535,65535,65535,65535,65535,65535,65535,65535,65535,65535,65535,65535,65535,65535,65535,65535,65535,65535,65535,65535,65535,65535,65535,65535,65535,65535,65535,65535,65535,65535,65535,65535,65535,65535,65535,65535,65535,65535,65535,65535,65535,65535,65535,65535},
{414,424,434,444,454,465,475,485,495,505,516,526,536,546,556,567,577,587,597,607,618,630,640,651,661,671,681,691,702,712,722,732,742,753,763,773,786,800,813,65535,65535,65535,65535,65535,65535,65535,65535,65535},
{1193,1201,1215,1228,65535,65535,65535,65535,65535,65535,65535,65535,65535,65535,65535,65535,65535,65535,65535,65535,65535,65535,65535,65535,65535,65535,65535,65535,65535,65535,65535,65535,65535,65535,65535,65535,65535,65535,65535,65535,65535,65535,65535,65535,65535,65535,65535,65535},
{826,836,847,857,867,878,888,898,908,3797,929,939,949,959,3848,980,990,1000,1010,3899,1031,1043,1053,1064,1074,1084,1094,3971,1115,1125,1135,1145,4022,1166,1176,1186,1198,1212,1225,65535,65535,65535,65535,65535,65535,65535,65535,65535},
{1605,1614,1626,1640,65535,65535,65535,65535,65535,65535,65535,65535,65535,65535,65535,65535,65535,65535,65535,65535,65535,65535,65535,65535,65535,65535,65535,65535,65535,65535,65535,65535,65535,65535,65535,65535,65535,65535,65535,65535,65535,65535,65535,65535,65535,65535,65535,65535},
{1238,1249,1259,1269,1280,1290,1300,1310,1320,1331,1341,1351,1361,1371,1382,1392,1402,1412,1422,1433,1443,1455,1466,1476,1486,1496,1506,1517,1527,1537,1547,1557,1568,1578,1588,1598,1611,1627,1641,65535,65535,65535,65535,65535,65535,65535,65535,65535},
{2017,2026,2039,2052,65535,65535,65535,65535,65535,65535,65535,65535,65535,65535,65535,65535,65535,65535,65535,65535,65535,65535,65535,65535,65535,65535,65535,65535,65535,65535,65535,65535,65535,65535,65535,65535,65535,65535,65535,65535,65535,65535,65535,65535,65535,65535,65535,65535},
{1650,1661,1671,3736,1692,1702,1712,1722,1733,1743,1753,1763,1773,1784,1794,1804,1814,1824,1835,1845,1855,1867,1878,1888,1898,1908,1919,1929,1939,1949,1959,1970,1980,1990,2000,2010,2023,4082,2053,65535,65535,65535,65535,65535,65535,65535,65535,65535},
{2429,2438,2451,2464,65535,65535,65535,65535,65535,65535,65535,65535,65535,65535,65535,65535,65535,65535,65535,65535,65535,65535,65535,65535,65535,65535,65535,65535,65535,65535,65535,65535,65535,65535,65535,65535,65535,65535,65535,65535,65535,65535,65535,65535,65535,65535,65535,65535},
{2062,2073,2083,2094,2104,2114,2124,2134,2145,2155,2165,2175,2185,2196,2206,2216,2226,2236,2247,2257,2267,2279,2290,2300,2310,2320,2331,2341,2351,2361,2371,2382,2392,2402,2412,2422,2435,2452,2465,65535,65535,65535,65535,65535,65535,65535,65535,65535},
{2840,2850,3670,3683,65535,65535,65535,65535,65535,65535,65535,65535,65535,65535,65535,65535,65535,65535,65535,65535,65535,65535,65535,65535,65535,65535,65535,65535,65535,65535,65535,65535,65535,65535,65535,65535,65535,65535,65535,65535,65535,65535,65535,65535,65535,65535,65535,65535},
{2474,3304,3314,2505,2515,2525,3355,2546,2556,2566,2576,3406,2597,2607,2617,2627,3457,2648,2658,2668,2679,2691,2701,2711,3529,2732,2742,2752,2762,3580,2783,2793,2803,2813,3631,2834,3655,2860,2873,65535,65535,65535,65535,65535,65535,65535,65535,65535},
{3252,4069,3274,4095,65535,65535,65535,65535,65535,65535,65535,65535,65535,65535,65535,65535,65535,65535,65535,65535,65535,65535,65535,65535,65535,65535,65535,65535,65535,65535,65535,65535,65535,65535,65535,65535,65535,65535,65535,65535,65535,65535,65535,65535,65535,65535,65535,65535},
{2886,3716,3726,2917,2927,2937,2947,3777,3787,2978,2988,2998,3828,3838,3029,3039,3049,3879,3889,3080,3091,3103,3113,3123,3133,3951,3961,3164,3174,3184,4002,4012,3215,3225,3235,4053,3259,3272,3285,65535,65535,65535,65535,65535,65535,65535,65535,65535},
{3,14,24,35,45,55,2948,3778,3788,96,106,2999,3829,3839,147,157,3050,3880,3890,198,210,2692,231,241,3134,3952,3962,282,292,3185,4003,4013,333,343,3236,4054,379,2863,2876,65535,65535,65535,65535,65535,65535,65535,65535,65535},
{4,3305,3727,34,44,54,65,75,85,95,105,116,126,136,146,156,167,177,187,197,209,221,230,240,251,261,271,281,291,302,312,322,332,342,353,363,377,392,405,65535,65535,65535,65535,65535,65535,65535,65535,65535},
{415,425,435,445,455,466,476,486,496,506,517,527,537,547,557,568,578,588,598,608,619,631,641,652,662,672,682,692,703,713,723,733,743,754,764,774,787,801,814,65535,65535,65535,65535,65535,65535,65535,65535,65535},
{416,426,436,446,456,467,477,487,497,507,518,528,538,548,558,569,579,589,599,609,620,632,642,653,663,673,683,693,704,714,724,734,744,755,765,775,791,804,817,65535,65535,65535,65535,65535,65535,65535,65535,65535},
{827,837,848,858,868,879,889,899,909,919,930,940,950,960,970,981,991,1001,1011,1021,1032,1044,1054,1065,1075,1085,1095,1105,1116,1126,1136,1146,1156,1167,1177,1187,1202,1216,1229,65535,65535,65535,65535,65535,65535,65535,65535,65535},
{828,838,849,859,869,2526,3356,900,910,920,2577,3407,951,961,971,2628,3458,1002,1012,1022,1033,1045,1055,2712,3530,1086,1096,1106,2763,3581,1137,1147,1157,2814,3632,1188,1203,3275,3288,65535,65535,65535,65535,65535,65535,65535,65535,65535},
{1239,1250,1260,1270,1281,1291,1301,1311,1321,1332,1342,1352,1362,1372,1383,1393,1403,1413,1423,1434,1444,1456,1467,1477,1487,1497,1507,1518,1528,1538,1548,1558,1569,1579,1589,1599,1615,1628,3684,65535,65535,65535,65535,65535,65535,65535,65535,65535},
{1240,3717,1261,1271,2516,2938,3768,1312,1322,2567,2989,3819,1363,1373,2618,3040,3870,1414,1424,2669,1445,1457,2702,3124,3942,1498,1508,2753,3175,3993,1549,1559,2804,3226,4044,1600,3262,3671,4096,65535,65535,65535,65535,65535,65535,65535,65535,65535},
{1651,1662,1672,1682,1693,1703,1713,1723,1734,1744,1754,1764,1774,1785,1795,1805,1815,1825,1836,1846,1856,1868,1879,1889,1899,1909,1920,1930,1940,1950,1960,1971,1981,1991,2001,2011,2027,2040,2054,65535,65535,65535,65535,65535,65535,65535,65535,65535},
{1652,1663,1673,1683,2928,3346,1714,1724,2557,2979,3397,1765,1775,2608,3030,3448,1816,1826,2659,3081,1857,1869,3114,3520,1900,1910,2743,3165,3571,1951,1961,2794,3216,3622,2002,2012,3658,4083,2877,65535,65535,65535,65535,65535,65535,65535,65535,65535},
{2063,2074,2084,2095,2105,2115,2125,2135,2146,2156,2166,2176,2186,2197,2207,2217,2227,2237,2248,2258,2268,2280,2291,2301,2311,2321,2332,2342,2352,2362,2372,2383,2393,2403,2413,2423,2439,2453,2466,65535,65535,65535,65535,65535,65535,65535,65535,65535},
{2064,2075,2085,2506,3336,3758,2126,2136,2969,3387,3809,2177,2187,3020,3438,3860,2228,2238,3071,3489,2269,2281,3510,3932,2312,2322,3155,3561,3983,2363,2373,3206,3612,4034,2414,2424,4070,2864,3289,65535,65535,65535,65535,65535,65535,65535,65535,65535},
{2845,2854,2867,2880,65535,65535,65535,65535,65535,65535,65535,65535,65535,65535,65535,65535,65535,65535,65535,65535,65535,65535,65535,65535,65535,65535,65535,65535,65535,65535,65535,65535,65535,65535,65535,65535,65535,65535,65535,65535,65535,65535,65535,65535,65535,65535,65535,65535},
{2475,2485,2495,3325,3335,3345,2536,3366,3376,3386,3396,2587,3417,3427,3437,3447,2638,3468,3478,3488,2680,3499,3509,3519,2722,3540,3550,3560,3570,2773,3591,3601,3611,3621,2824,3642,2848,3668,3681,65535,65535,65535,65535,65535,65535,65535,65535,65535},
{3256,3266,4087,4100,65535,65535,65535,65535,65535,65535,65535,65535,65535,65535,65535,65535,65535,65535,65535,65535,65535,65535,65535,65535,65535,65535,65535,65535,65535,65535,65535,65535,65535,65535,65535,65535,65535,65535,65535,65535,65535,65535,65535,65535,65535,65535,65535,65535},
{2887,2897,2907,3737,3747,3757,3767,2958,2968,3798,3808,3818,3009,3019,3849,3859,3869,3060,3070,3900,3092,3911,3921,3931,3941,3144,3154,3972,3982,3992,3195,3205,4023,4033,4043,3246,4067,4080,4093,65535,65535,65535,65535,65535,65535,65535,65535,65535},
{417,427,437,447,457,468,478,488,498,508,519,529,539,549,559,570,580,590,600,610,621,633,643,654,664,674,684,694,705,715,725,735,745,756,766,776,792,805,818,65535,65535,65535,65535,65535,65535,65535,65535,65535},
{2476,2486,2496,2918,3748,2527,2537,2547,3377,3799,2578,2588,2598,3428,3850,2629,2639,2649,3479,3901,622,3104,3922,2713,2723,2733,3551,3973,2764,2774,2784,3602,4024,2815,2825,2835,2851,3276,3685,65535,65535,65535,65535,65535,65535,65535,65535,65535},
{829,839,2908,3326,870,880,890,2959,3789,921,931,941,3010,3840,972,982,992,3061,3891,1023,1034,3500,1056,1066,1076,3145,3963,1107,1117,1127,3196,4014,1158,1168,1178,3247,1204,1217,1230,65535,65535,65535,65535,65535,65535,65535,65535,65535},
{2888,2898,3316,3738,2517,2939,2949,3367,911,2568,2990,3000,3418,962,2619,3041,3051,3469,1013,2670,2681,3912,2703,3125,3135,3541,1097,2754,3176,3186,3592,1148,2805,3227,3237,3643,3263,3672,4097,65535,65535,65535,65535,65535,65535,65535,65535,65535},
{1241,1251,3728,1272,3749,1293,1303,1313,3378,3800,1344,1354,1364,3429,3851,1395,1405,1415,3480,3902,1447,3501,3923,1479,1489,1499,3552,3974,1530,1540,1550,3603,4025,1581,1591,1601,1617,1630,1643,65535,65535,65535,65535,65535,65535,65535,65535,65535},
{3296,3306,1262,2507,1282,1292,1302,3779,1323,1333,1343,1353,3830,1374,1384,1394,1404,3881,1425,1435,1446,1458,1468,1478,1488,3953,1509,1519,1529,1539,4004,1560,1570,1580,1590,4055,1616,1629,1642,65535,65535,65535,65535,65535,65535,65535,65535,65535},
{1653,3718,1674,1684,1694,1704,1715,1725,1735,1745,1755,1766,1776,1786,1796,1806,1817,1827,1837,1847,1858,1870,1880,1890,1901,1911,1921,1931,1941,1952,1962,1972,1982,1992,2003,2013,2028,2041,2055,65535,65535,65535,65535,65535,65535,65535,65535,65535},
{3708,1664,3317,3739,1695,1705,2538,3368,3790,1746,1756,2589,3419,3841,1797,1807,2640,3470,3892,1848,1859,3913,1881,1891,2724,3542,3964,1932,1942,2775,3593,4015,1983,1993,2826,3644,2029,2042,3686,65535,65535,65535,65535,65535,65535,65535,65535,65535},
{2065,2076,3729,2097,2107,2117,2950,3780,2148,2158,2168,3001,3831,2199,2209,2219,3052,3882,2250,2260,2271,2283,2293,2303,3136,3954,2334,2344,2354,3187,4005,2385,2395,2405,3238,4056,2441,3277,4098,65535,65535,65535,65535,65535,65535,65535,65535,65535},
{2066,2487,2086,2096,2106,2116,2127,2137,2147,2157,2167,2178,2188,2198,2208,2218,2229,2239,2249,2259,2270,2282,2292,2302,2313,2323,2333,2343,2353,2364,2374,2384,2394,2404,2415,2425,2440,2454,2467,65535,65535,65535,65535,65535,65535,65535,65535,65535},
{3653,3662,3675,3688,65535,65535,65535,65535,65535,65535,65535,65535,65535,65535,65535,65535,65535,65535,65535,65535,65535,65535,65535,65535,65535,65535,65535,65535,65535,65535,65535,65535,65535,65535,65535,65535,65535,65535,65535,65535,65535,65535,65535,65535,65535,65535,65535,65535},
{2477,3307,2497,3327,3337,3347,3357,2548,2558,3388,3398,3408,2599,2609,3439,3449,3459,2650,2660,3490,2682,2693,3511,3521,3531,2734,2744,3562,3572,3582,2785,2795,3613,3623,3633,2836,3659,2865,2878,65535,65535,65535,65535,65535,65535,65535,65535,65535},
{4064,4074,3280,3293,65535,65535,65535,65535,65535,65535,65535,65535,65535,65535,65535,65535,65535,65535,65535,65535,65535,65535,65535,65535,65535,65535,65535,65535,65535,65535,65535,65535,65535,65535,65535,65535,65535,65535,65535,65535,65535,65535,65535,65535,65535,65535,65535,65535},
{2889,2899,2909,2919,2929,3759,3769,2960,2970,2980,3810,3820,3011,3021,3031,3861,3871,3062,3072,3082,3093,3105,3115,3933,3943,3146,3156,3166,3984,3994,3197,3207,3217,4035,4045,3248,4071,4084,3290,65535,65535,65535,65535,65535,65535,65535,65535,65535},
{418,428,439,449,459,2528,3358,490,500,510,2579,3409,541,551,561,2630,3460,592,602,612,3094,635,645,2714,3532,676,686,696,2765,3583,727,737,747,2816,3634,778,2852,3673,820,65535,65535,65535,65535,65535,65535,65535,65535,65535},
{3297,3719,438,448,458,469,479,489,499,509,520,530,540,550,560,571,581,591,601,611,623,634,644,655,665,675,685,695,706,716,726,736,746,757,767,777,793,806,819,65535,65535,65535,65535,65535,65535,65535,65535,65535},
{830,840,850,860,871,881,891,901,912,922,932,942,952,963,973,983,993,1003,1014,1024,1035,1046,1057,1067,1077,1087,1098,1108,1118,1128,1138,1149,1159,1169,1179,1189,1205,1218,1231,65535,65535,65535,65535,65535,65535,65535,65535,65535},
{3709,841,851,861,2518,2940,3770,902,2559,2569,2991,3821,953,2610,2620,3042,3872,1004,2661,2671,1036,1047,2704,3126,3944,1088,2745,2755,3177,3995,1139,2796,2806,3228,4046,1190,3264,4085,1232,65535,65535,65535,65535,65535,65535,65535,65535,65535},
{1242,1252,1263,1273,1283,3348,1304,1314,1324,1334,3399,1355,1365,1375,1385,3450,1406,1416,1426,1436,1448,1459,1469,3522,1490,1500,1510,1520,3573,1541,1551,1561,1571,3624,1592,1602,3660,1631,1644,65535,65535,65535,65535,65535,65535,65535,65535,65535},
{1243,1253,2498,2508,2930,3760,2539,2549,2971,2981,3811,2590,2600,3022,3032,3862,2641,2651,3073,3083,2683,2694,3116,3934,2725,2735,3157,3167,3985,2776,2786,3208,3218,4036,2827,2837,4072,2866,2879,65535,65535,65535,65535,65535,65535,65535,65535,65535},
{1654,1665,1675,1685,3338,1706,1716,1726,1736,3389,1757,1767,1777,1787,3440,1808,1818,1828,1838,3491,1860,1871,3512,1892,1902,1912,1922,3563,1943,1953,1963,1973,3614,1994,2004,2014,2030,2043,2056,65535,65535,65535,65535,65535,65535,65535,65535,65535},
{1655,2488,2910,2920,3750,2529,2951,2961,3379,3801,2580,3002,3012,3430,3852,2631,3053,3063,3481,3903,3095,3106,3924,2715,3137,3147,3553,3975,2766,3188,3198,3604,4026,2817,3239,3249,2853,3278,3291,65535,65535,65535,65535,65535,65535,65535,65535,65535},
{2067,2077,2087,3328,2108,2119,2129,2139,2149,3390,2170,2180,2190,2200,3441,2221,2231,2241,2251,3492,2273,2284,3513,2305,2315,2325,2335,3564,2356,2366,2376,2386,3615,2407,2417,2427,2443,2456,2469,65535,65535,65535,65535,65535,65535,65535,65535,65535},
{2478,2900,3318,3740,2519,2118,2128,2138,3791,2159,2169,2179,2189,3842,2210,2220,2230,2240,3893,2261,2272,3502,2294,2304,2314,2324,3965,2345,2355,2365,2375,4016,2396,2406,2416,2426,2442,2455,2468,65535,65535,65535,65535,65535,65535,65535,65535,65535},
{2846,2855,2868,2881,65535,65535,65535,65535,65535,65535,65535,65535,65535,65535,65535,65535,65535,65535,65535,65535,65535,65535,65535,65535,65535,65535,65535,65535,65535,65535,65535,65535,65535,65535,65535,65535,65535,65535,65535,65535,65535,65535,65535,65535,65535,65535,65535,65535},
{3298,3308,2499,2509,3339,3349,3359,3369,2560,2570,3400,3410,3420,2611,2621,3451,3461,3471,2662,2672,2684,2695,2705,3523,3533,3543,2746,2756,3574,3584,3594,2797,2807,3625,3635,3645,3661,3674,3687,65535,65535,65535,65535,65535,65535,65535,65535,65535},
{3257,3267,4088,4101,65535,65535,65535,65535,65535,65535,65535,65535,65535,65535,65535,65535,65535,65535,65535,65535,65535,65535,65535,65535,65535,65535,65535,65535,65535,65535,65535,65535,65535,65535,65535,65535,65535,65535,65535,65535,65535,65535,65535,65535,65535,65535,65535,65535},
{2890,3720,3730,2921,2931,2941,3771,3781,2972,2982,2992,3822,3832,3023,3033,3043,3873,3883,3074,3084,3096,3914,3117,3127,3945,3955,3158,3168,3178,3996,4006,3209,3219,3229,4047,4057,3265,4086,4099,65535,65535,65535,65535,65535,65535,65535,65535,65535},
{419,429,440,3329,461,471,481,2550,3380,512,522,532,2601,3431,563,573,583,2652,3482,614,625,3503,647,657,667,2736,3554,698,708,718,2787,3605,749,759,769,3648,795,808,822,65535,65535,65535,65535,65535,65535,65535,65535,65535},
{3710,430,2911,450,460,470,480,491,501,511,521,531,542,552,562,572,582,593,603,613,624,636,646,656,666,677,687,697,707,717,728,738,748,758,768,779,794,807,821,65535,65535,65535,65535,65535,65535,65535,65535,65535},
{831,842,852,863,873,883,893,3370,914,924,934,944,3421,965,975,985,995,3472,1016,1026,1038,3915,1059,1069,1079,3544,1100,1110,1120,1130,3595,1151,1161,1171,1181,4060,1207,1220,1234,65535,65535,65535,65535,65535,65535,65535,65535,65535},
{832,2489,3319,862,872,882,892,903,913,923,933,943,954,964,974,984,994,1005,1015,1025,1037,1048,1058,1068,1078,1089,1099,1109,1119,1129,1140,1150,1160,1170,1180,1191,1206,1219,1233,65535,65535,65535,65535,65535,65535,65535,65535,65535},
{1244,3309,1265,1274,1284,1294,1305,1315,1325,1335,1345,1356,1366,1376,1386,1396,1407,1417,1427,1437,1449,1460,1470,1480,1491,1501,1511,1521,1531,1542,1552,1562,1572,1582,1593,1606,1618,1632,1645,65535,65535,65535,65535,65535,65535,65535,65535,65535},
{2479,1254,1264,1275,1285,1295,2540,3782,1326,1336,1346,2591,3833,1377,1387,1397,2642,3884,1428,1438,1450,1461,1471,1481,2726,3956,1512,1522,1532,2777,4007,1563,1573,1583,2828,2841,1619,1633,1646,65535,65535,65535,65535,65535,65535,65535,65535,65535},
{1656,3721,1677,1686,1696,1707,1717,1727,1737,1747,1758,1768,1778,1788,1798,1809,1819,1829,1839,1849,1861,1872,1882,1893,1903,1913,1923,1933,1944,1954,1964,1974,1984,1995,2005,2018,2031,2044,2057,65535,65535,65535,65535,65535,65535,65535,65535,65535},
{2891,1666,1676,1687,1697,2530,3360,1728,1738,1748,2581,3411,1779,1789,1799,2632,3462,1830,1840,1850,1862,1873,1883,2716,3534,1914,1924,1934,2767,3585,1965,1975,1985,2818,3636,3253,2032,2045,2058,65535,65535,65535,65535,65535,65535,65535,65535,65535},
{2068,2079,2089,2098,2109,2942,3772,2140,2150,2160,2993,3823,2191,2201,2211,3044,3874,2242,2252,2262,2274,2285,2295,3128,3946,2326,2336,2346,3179,3997,2377,2387,2397,3230,4048,2430,2444,2457,2470,65535,65535,65535,65535,65535,65535,65535,65535,65535},
{3299,2078,2088,2099,2520,3350,2130,2551,2561,2571,3401,2181,2602,2612,2622,3452,2232,2653,2663,2673,2685,2696,2706,3524,2316,2737,2747,2757,3575,2367,2788,2798,2808,3626,2418,3649,3663,3676,3689,65535,65535,65535,65535,65535,65535,65535,65535,65535},
{2480,2490,2500,2510,3340,2531,2541,3371,3381,3391,2582,2592,3422,3432,3442,2633,2643,3473,3483,3493,2686,3504,3514,2717,2727,3545,3555,3565,2768,2778,3596,3606,3616,2819,2829,2842,2856,2869,2882,65535,65535,65535,65535,65535,65535,65535,65535,65535},
{3300,3310,3320,3330,2521,3351,3361,2552,2562,2572,3402,3412,2603,2613,2623,3453,3463,2654,2664,2674,2687,2697,2707,3525,3535,2738,2748,2758,3576,3586,2789,2799,2809,3627,3637,3650,3664,3677,3690,65535,65535,65535,65535,65535,65535,65535,65535,65535},
{3711,2901,3731,3741,3751,3761,2952,2962,3792,3802,3812,3003,3013,3843,3853,3863,3054,3064,3894,3904,3097,3107,3925,3935,3138,3148,3966,3976,3986,3189,3199,4017,4027,4037,3240,3250,4073,3279,3292,65535,65535,65535,65535,65535,65535,65535,65535,65535},
{2892,2902,2912,2922,2932,3762,2953,2963,2973,2983,3813,3004,3014,3024,3034,3864,3055,3065,3075,3085,3098,3108,3118,3936,3139,3149,3159,3169,3987,3190,3200,3210,3220,4038,3241,4061,4075,3281,3294,65535,65535,65535,65535,65535,65535,65535,65535,65535},
{420,431,441,451,3752,472,482,492,502,3803,523,533,543,553,3854,574,584,594,604,3905,626,637,3926,658,668,678,688,3977,709,719,729,739,4028,760,770,782,796,809,823,65535,65535,65535,65535,65535,65535,65535,65535,65535},
{421,3722,3732,3742,462,2943,3773,3783,3793,513,2994,3824,3834,3844,564,3045,3875,3885,3895,615,627,3916,648,3129,3947,3957,3967,699,3180,3998,4008,4018,750,3231,4049,783,797,810,4102,65535,65535,65535,65535,65535,65535,65535,65535,65535},
{833,843,853,864,874,884,894,904,915,925,935,945,955,966,976,986,996,1006,1017,1027,1039,1049,1060,1070,1080,1090,1101,1111,1121,1131,1141,1152,1162,1172,1182,1194,1208,1221,1235,65535,65535,65535,65535,65535,65535,65535,65535,65535},
{3712,844,854,3331,875,885,895,905,916,926,936,946,956,967,977,987,997,1007,1018,1028,1040,1050,1061,1071,1081,1091,1102,1112,1122,1132,1142,1153,1163,1173,1183,1195,1209,1222,3691,65535,65535,65535,65535,65535,65535,65535,65535,65535},
{1245,1255,1266,1276,1286,1296,1306,1316,1327,1337,1347,1357,1367,1378,1388,1398,1408,1418,1429,1439,1451,1462,1472,1482,1492,1502,1513,1523,1533,1543,1553,1564,1574,1584,1594,1607,1620,1634,1647,65535,65535,65535,65535,65535,65535,65535,65535,65535},
{1246,1256,3321,1277,1287,1297,1307,1317,1328,1338,1348,1358,1368,1379,1389,1399,1409,1419,1430,1440,1452,1463,1473,1483,1493,1503,1514,1524,1534,1544,1554,1565,1575,1585,1595,1608,1621,1635,3692,65535,65535,65535,65535,65535,65535,65535,65535,65535},
{1657,1667,1678,1688,1698,1708,1718,1729,1739,1749,1759,1769,1780,1790,1800,1810,1820,1831,1841,1851,1863,1874,1884,1894,1904,1915,1925,1935,1945,1955,1966,1976,1986,1996,2006,2019,2033,2046,2059,65535,65535,65535,65535,65535,65535,65535,65535,65535},
{1658,1668,1679,1689,1699,1709,1719,1730,1740,1750,1760,1770,1781,1791,1801,1811,1821,1832,1842,1852,1864,1875,1885,1895,1905,1916,1926,1936,1946,1956,1967,1977,1987,1997,2007,2020,2034,2047,4104,65535,65535,65535,65535,65535,65535,65535,65535,65535},
{2069,2080,2091,2101,2111,2121,3362,2142,2152,2162,2172,3413,2193,2203,2213,2223,3464,2244,2254,2264,2276,2287,2297,2307,3536,2328,2338,2348,2358,3587,2379,2389,2399,2409,3638,2432,2446,2459,3693,65535,65535,65535,65535,65535,65535,65535,65535,65535},
{2070,2491,2090,2100,2110,2120,2131,2141,2151,2161,2171,2182,2192,2202,2212,2222,2233,2243,2253,2263,2275,2286,2296,2306,2317,2327,2337,2347,2357,2368,2378,2388,2398,2408,2419,2431,2445,2458,2471,65535,65535,65535,65535,65535,65535,65535,65535,65535},
{2481,3311,2501,2511,3341,2532,2542,3372,3382,3392,2583,2593,3423,3433,3443,2634,2644,3474,3484,3494,2688,3505,3515,2718,2728,3546,3556,3566,2769,2779,3597,3607,3617,2820,2830,2843,2857,2870,2883,65535,65535,65535,65535,65535,65535,65535,65535,65535},
{3301,2492,2502,2512,2522,3352,2543,2553,2563,2573,3403,2594,2604,2614,2624,3454,2645,2655,2665,2675,3496,2698,2708,3526,2729,2739,2749,2759,3577,2780,2790,2800,2810,3628,2831,3651,3665,3678,3694,65535,65535,65535,65535,65535,65535,65535,65535,65535},
{2893,2903,2913,2923,2933,3763,2954,2964,2974,2984,3814,3005,3015,3025,3035,3865,3056,3066,3076,3086,3099,3109,3119,3937,3140,3150,3160,3170,3988,3191,3201,3211,3221,4039,3242,3254,3268,4089,3295,65535,65535,65535,65535,65535,65535,65535,65535,65535},
{3713,3723,3733,3743,3753,2944,3774,3784,3794,3804,2995,3825,3835,3845,3855,3046,3876,3886,3896,3906,3100,3917,3927,3130,3948,3958,3968,3978,3181,3999,4009,4019,4029,3232,4050,4062,4076,3282,4103,65535,65535,65535,65535,65535,65535,65535,65535,65535},
{2482,3312,3322,3332,3342,2533,3363,3373,3383,3393,2584,3414,3424,3434,3444,2635,3465,3475,3485,3495,2689,3506,3516,2719,3537,3547,3557,3567,2770,3588,3598,3608,3618,2821,3639,2844,2858,2871,4105,65535,65535,65535,65535,65535,65535,65535,65535,65535},
{3302,2493,2503,2513,2523,3353,2544,2554,2564,2574,3404,2595,2605,2615,2625,3455,2646,2656,2666,2676,3497,2699,2709,3527,2730,2740,2750,2760,3578,2781,2791,2801,2811,3629,2832,3652,3666,3679,3695,65535,65535,65535,65535,65535,65535,65535,65535,65535},
{2894,2904,2914,2924,2934,3764,2955,2965,2975,2985,3815,3006,3016,3026,3036,3866,3057,3067,3077,3087,3908,3110,3120,3938,3141,3151,3161,3171,3989,3192,3202,3212,3222,4040,3243,3255,3269,4090,4106,65535,65535,65535,65535,65535,65535,65535,65535,65535},
{3714,3724,3734,3744,3754,2945,3775,3785,3795,3805,2996,3826,3836,3846,3856,3047,3877,3887,3897,3907,3101,3918,3928,3131,3949,3959,3969,3979,3182,4000,4010,4020,4030,3233,4051,4063,4077,3283,4107,65535,65535,65535,65535,65535,65535,65535,65535,65535},
{5,15,25,36,46,56,66,76,86,97,107,117,127,137,148,158,168,178,188,199,211,222,232,242,252,262,272,283,293,303,313,323,334,344,354,364,380,393,406,65535,65535,65535,65535,65535,65535,65535,65535,65535},
{6,16,26,37,47,57,67,77,87,98,108,118,128,138,149,159,169,179,189,200,212,223,233,243,253,263,273,284,294,304,314,324,335,345,355,365,381,394,407,65535,65535,65535,65535,65535,65535,65535,65535,65535},
{7,17,27,38,48,58,68,78,88,99,109,119,129,139,150,160,170,180,190,201,213,224,234,244,254,264,274,285,295,305,315,325,336,346,356,366,382,395,408,65535,65535,65535,65535,65535,65535,65535,65535,65535},
{8,18,28,39,49,59,69,79,89,100,110,120,130,140,151,161,171,181,191,202,214,225,235,245,255,265,275,286,296,306,316,326,337,347,357,370,383,396,409,65535,65535,65535,65535,65535,65535,65535,65535,65535},
{9,19,29,40,50,60,70,80,90,101,111,121,131,141,152,162,172,182,192,203,215,226,236,246,256,266,276,287,297,307,317,327,338,348,358,371,384,397,410,65535,65535,65535,65535,65535,65535,65535,65535,65535},
{10,20,30,41,51,61,71,81,91,102,112,122,132,142,153,163,173,183,193,204,216,227,237,247,257,267,277,288,298,308,318,328,339,349,359,372,385,398,411,65535,65535,65535,65535,65535,65535,65535,65535,65535},
{11,21,31,42,52,62,72,82,92,103,113,123,133,143,154,164,174,184,194,205,217,228,238,248,258,268,278,289,299,309,319,329,340,350,360,373,386,399,65535,65535,65535,65535,65535,65535,65535,65535,65535,65535},
{12,3315,32,2514,2524,3354,74,84,94,2575,3405,125,135,145,2626,3456,176,186,196,207,3102,2700,2710,3528,260,270,280,2761,3579,311,321,331,2812,3630,362,3258,388,3284,65535,65535,65535,65535,65535,65535,65535,65535,65535,65535},
};

#define NG SCHED_NG
#define RING 16
#define NSLOT 8
#define CFETCH 5
#define TABLED 1
#define PROMO CU_TENSOR_MAP_L2_PROMOTION_L2_128B
#define AHEAD 6
#define CF0 5
#define CFS 2
#define ABL 0
#define CX 5
#define PUBN 2
#define PUBE 8
#define SCHED 9
#define OUT_TMA 0
#define JB1 21
#define JB2 24
#define CVAR 2
#define CFN 0
#define CREGS 224
#define CSLEEP 200
#define JB 21
#define JF JB
#define JR 17
#define HOIST 1
#define XEARLY 0
#define FPRED 0
#define LATERED 1
#define WDELAY 0
#define WDELAY2 0
#define PFX 0
#define FIRST 3
#define NODUMP 1
#define TRIG 6
constexpr int NCONV = 3 * NG;
constexpr int PLEN = SCHED_LE, LM = 256 - 2 * PLEN, NSEG = 4 / (NG - 8), LMID = NSEG * LM;
static_assert(LMID <= PLEN && (NG == 9 || NG == 10), "geometry");
constexpr int TILEB = 12288;
constexpr int SLOTB = 280 * 64;
constexpr int W1S = 0, W2S = 73728, ABUF = 147456, XBUF = ABUF + 16 * 3072, MISC = XBUF + 8 * 3072;
constexpr int WBAR = MISC + 2560;
constexpr int RBUF = ABUF - 4 * SLOTB;
constexpr int CM = MISC + 2816, CTAB = CM + 256;
constexpr int SMEM_BYTES = CTAB + (PLEN + 16) * 16;
static_assert(RBUF % 512 == 0 && RBUF >= W2S && RBUF + NSLOT * SLOTB + 128 <= MISC && SMEM_BYTES <= 232448, "smem layout");

struct Globals {
  unsigned char scratch[(RING * NG + 1) * 4 * TILEB];
  unsigned char wimg[147456];
  uint32_t wflag[32];
  uint32_t ready[NG * PLEN + 1];
  uint32_t cons[NG * PLEN];
  uint32_t epoch[1024];
};
__device__ __align__(1024) Globals g_state;

#define PROF_AT(cond, idx)
#define PROF_VAL(cond, idx, v)
#define PROF2_AT(c, i)
#define PROF2_VAL(c, i, v)
#define PROFS(i)
#define GELU_C3 0.32920349f
#define GELU_A2 0x40d940d9u
#define SCHED_FENCE() asm volatile("pmevent 0;" ::: "memory")
#define SPIN_LIMIT 0x1000000

__device__ __forceinline__ uint32_t smem_u32(const void* p) { return (uint32_t)__cvta_generic_to_shared(p); }
__device__ __forceinline__ void wg_fence() { asm volatile("wgmma.fence.sync.aligned;" ::: "memory"); }
__device__ __forceinline__ void wg_commit() { asm volatile("wgmma.commit_group.sync.aligned;" ::: "memory"); }
template <int N> __device__ __forceinline__ void wg_wait() { asm volatile("wgmma.wait_group.sync.aligned %0;" ::"n"(N) : "memory"); }
__device__ __forceinline__ void mbar_init(uint32_t bar, uint32_t cnt) { asm volatile("mbarrier.init.shared::cta.b64 [%0], %1;" ::"r"(bar), "r"(cnt) : "memory"); }
__device__ __forceinline__ void mbar_expect_tx(uint32_t bar, uint32_t bytes) { asm volatile("mbarrier.arrive.expect_tx.shared::cta.b64 _, [%0], %1;" ::"r"(bar), "r"(bytes) : "memory"); }
__device__ __forceinline__ void mbar_arrive(uint32_t bar) { asm volatile("mbarrier.arrive.shared::cta.b64 _, [%0];" ::"r"(bar) : "memory"); }
__device__ __forceinline__ void mbar_wait(uint32_t bar, uint32_t parity) {
  asm volatile("{\n.reg .pred p;\n.reg .u32 c;\nmbarrier.try_wait.parity.shared::cta.b64 p, [%0], %1;\n@p bra DONE_%=;\nmov.u32 c, 0;\nWAIT_%=:\nmbarrier.try_wait.parity.shared::cta.b64 p, [%0], %1;\n@p bra DONE_%=;\n"
               "add.u32 c, c, 1;\nsetp.lt.u32 p, c, 0x1000000;\n@p bra WAIT_%=;\ntrap;\nDONE_%=:\n}" ::"r"(bar), "r"(parity) : "memory");
}
__device__ __forceinline__ void bulk_g2s(uint32_t dst, const void* src, uint32_t bytes, uint32_t bar) {
  asm volatile("cp.async.bulk.shared::cluster.global.mbarrier::complete_tx::bytes [%0], [%1], %2, [%3];" ::"r"(dst), "l"(src), "r"(bytes), "r"(bar) : "memory");
}
__device__ __forceinline__ uint32_t ld_relaxed(const uint32_t* p) { uint32_t v; asm volatile("ld.relaxed.gpu.global.u32 %0, [%1];" : "=r"(v) : "l"(p) : "memory"); return v; }
__device__ __forceinline__ void red_add_elect(uint32_t* p) { asm volatile("{.reg .pred p; elect.sync _|p, 0xffffffff; @p red.relaxed.gpu.global.add.u32 [%0], 1;}" ::"l"(p) : "memory"); }
__device__ __forceinline__ void mbar_arrive_elect(uint32_t bar) { asm volatile("{.reg .pred p; elect.sync _|p, 0xffffffff; @p mbarrier.arrive.shared::cta.b64 _, [%0];}" ::"r"(bar) : "memory"); }
__device__ __forceinline__ void mbar_init_elect(uint32_t bar, uint32_t cnt) { asm volatile("{.reg .pred p; elect.sync _|p, 0xffffffff; @p mbarrier.init.shared::cta.b64 [%0], %1;}" ::"r"(bar), "r"(cnt) : "memory"); }
__device__ __forceinline__ void lds128(uint32_t* r, uint32_t a) { asm volatile("ld.shared.v4.b32 {%0,%1,%2,%3}, [%4];" : "=r"(r[0]), "=r"(r[1]), "=r"(r[2]), "=r"(r[3]) : "r"(a) : "memory"); }
__device__ __forceinline__ uint2 lds64(uint32_t a) { uint2 v; asm volatile("ld.shared.v2.b32 {%0,%1}, [%2];" : "=r"(v.x), "=r"(v.y) : "r"(a) : "memory"); return v; }
__device__ __forceinline__ uint32_t lds32(uint32_t a) { uint32_t v; asm volatile("ld.shared.b32 %0, [%1];" : "=r"(v) : "r"(a) : "memory"); return v; }
__device__ __forceinline__ void sts32(uint32_t a, uint32_t v) { asm volatile("st.shared.b32 [%0], %1;" ::"r"(a), "r"(v) : "memory"); }
__device__ __forceinline__ void sts128(uint32_t a, uint4 v) { asm volatile("st.shared.v4.b32 [%0], {%1,%2,%3,%4};" ::"r"(a), "r"(v.x), "r"(v.y), "r"(v.z), "r"(v.w) : "memory"); }
__device__ __forceinline__ uint4 ldg128v(const void* p) { uint4 v; asm volatile("ld.global.nc.v4.b32 {%0,%1,%2,%3}, [%4];" : "=r"(v.x), "=r"(v.y), "=r"(v.z), "=r"(v.w) : "l"(p) : "memory"); return v; }
__device__ __forceinline__ void stg128(void* p, uint4 v) { asm volatile("st.global.v4.b32 [%0], {%1,%2,%3,%4};" ::"l"(p), "r"(v.x), "r"(v.y), "r"(v.z), "r"(v.w) : "memory"); }
#define HINT 3
__device__ __forceinline__ uint64_t pol_evict_first() { uint64_t p; asm("createpolicy.fractional.L2::evict_first.b64 %0, 1.0;" : "=l"(p)); return p; }
__device__ __forceinline__ uint4 ldg128_last(const void* p, uint64_t pol) {
  if (!(HINT & 1)) return ldg128v(p);
  uint4 v; asm volatile("ld.global.nc.L1::no_allocate.L2::cache_hint.v4.b32 {%0,%1,%2,%3}, [%4], %5;" : "=r"(v.x), "=r"(v.y), "=r"(v.z), "=r"(v.w) : "l"(p), "l"(pol) : "memory"); return v;
}
__device__ __forceinline__ void stg128_stream(void* p, uint4 v, uint64_t pol) {
  if (!(HINT & 2)) { stg128(p, v); return; }
  asm volatile("st.global.L2::cache_hint.v4.b32 [%0], {%1,%2,%3,%4}, %5;" ::"l"(p), "r"(v.x), "r"(v.y), "r"(v.z), "r"(v.w), "l"(pol) : "memory");
}
__device__ __forceinline__ float bf_lo(uint32_t w) { return __uint_as_float(w << 16); }
__device__ __forceinline__ float bf_hi(uint32_t w) { return __uint_as_float(w & 0xffff0000u); }
__device__ __forceinline__ uint32_t pack_f16(float lo, float hi) { uint32_t d; asm("cvt.rn.f16x2.f32 %0, %1, %2;" : "=r"(d) : "f"(hi), "f"(lo)); return d; }
__device__ __forceinline__ uint32_t pack_f16_sat(float lo, float hi) { uint32_t d; asm("cvt.rn.satfinite.f16x2.f32 %0, %1, %2;" : "=r"(d) : "f"(hi), "f"(lo)); return d; }
__device__ __forceinline__ uint32_t pack_bf16(float lo, float hi) { uint32_t d; asm("cvt.rn.bf16x2.f32 %0, %1, %2;" : "=r"(d) : "f"(hi), "f"(lo)); return d; }
__device__ __forceinline__ uint32_t hadd2_bf16(uint32_t a, uint32_t b) { uint32_t d; asm("add.rn.bf16x2 %0, %1, %2;" : "=r"(d) : "r"(a), "r"(b)); return d; }
__device__ __forceinline__ uint32_t h2add(uint32_t a, uint32_t b) { uint32_t d; asm("add.rn.f16x2 %0, %1, %2;" : "=r"(d) : "r"(a), "r"(b)); return d; }
__device__ __forceinline__ uint32_t h2mul(uint32_t a, uint32_t b) { uint32_t d; asm("mul.rn.f16x2 %0, %1, %2;" : "=r"(d) : "r"(a), "r"(b)); return d; }
__device__ __forceinline__ uint32_t h2fma(uint32_t a, uint32_t b, uint32_t c) { uint32_t d; asm("fma.rn.f16x2 %0, %1, %2, %3;" : "=r"(d) : "r"(a), "r"(b), "r"(c)); return d; }
__device__ __forceinline__ uint32_t h2lo(uint32_t a) { uint32_t d; asm("{.reg .f16 l,h; mov.b32 {l,h}, %1; mov.b32 %0, {l,l};}" : "=r"(d) : "r"(a)); return d; }
__device__ __forceinline__ uint32_t h2hi(uint32_t a) { uint32_t d; asm("{.reg .f16 l,h; mov.b32 {l,h}, %1; mov.b32 %0, {h,h};}" : "=r"(d) : "r"(a)); return d; }
__device__ __forceinline__ float h_lo(uint32_t a) { float d; asm("{.reg .f16 l,h; mov.b32 {l,h}, %1; cvt.f32.f16 %0, l;}" : "=f"(d) : "r"(a)); return d; }
__device__ __forceinline__ float h_hi(uint32_t a) { float d; asm("{.reg .f16 l,h; mov.b32 {l,h}, %1; cvt.f32.f16 %0, h;}" : "=f"(d) : "r"(a)); return d; }
__device__ __forceinline__ uint32_t prmt(uint32_t a, uint32_t b, uint32_t s) { uint32_t d; asm("prmt.b32 %0, %1, %2, %3;" : "=r"(d) : "r"(a), "r"(b), "r"(s)); return d; }
__device__ __forceinline__ void mma_sp(float* d, const uint32_t* a, const uint32_t* b, const float* c, uint32_t e) {
  asm("mma.sp::ordered_metadata.sync.aligned.m16n8k32.row.col.f32.bf16.bf16.f32 {%0,%1,%2,%3}, {%4,%5,%6,%7}, {%8,%9,%10,%11}, {%12,%13,%14,%15}, %16, 0;"
      : "=f"(d[0]), "=f"(d[1]), "=f"(d[2]), "=f"(d[3])
      : "r"(a[0]), "r"(a[1]), "r"(a[2]), "r"(a[3]), "r"(b[0]), "r"(b[1]), "r"(b[2]), "r"(b[3]), "f"(c[0]), "f"(c[1]), "f"(c[2]), "f"(c[3]), "r"(e));
}
__device__ __forceinline__ uint32_t bf2_to_h2(uint32_t w, float s) { return pack_f16(bf_lo(w) * s, bf_hi(w) * s); }
__device__ __forceinline__ uint32_t bf2_to_h2(uint32_t w) { return pack_f16(bf_lo(w), bf_hi(w)); }

__device__ __forceinline__ uint32_t gelu_h2(uint32_t y) {
  uint32_t t, u, th, g;
  asm volatile("fma.rn.f16x2 %0, %1, %1, %2;" : "=r"(t) : "r"(y), "r"(GELU_A2));
  asm volatile("mul.rn.f16x2 %0, %1, %2;" : "=r"(u) : "r"(y), "r"(t));
  asm volatile("tanh.approx.f16x2 %0, %1;" : "=r"(th) : "r"(u));
  asm volatile("fma.rn.f16x2 %0, %1, %2, %1;" : "=r"(g) : "r"(y), "r"(th));
  return g;
}

__device__ __forceinline__ void copy_weights(uint32_t sb, int piece, const void* src) {
  asm volatile("{\n.reg .pred p;\nelect.sync _|p, 0xffffffff;\n@p mbarrier.init.shared::cta.b64 [%1], 1;\n@p fence.mbarrier_init.release.cluster;\n"
               "@p mbarrier.arrive.expect_tx.shared::cta.b64 _, [%1], 12288;\n"
               "@p cp.async.bulk.shared::cluster.global.mbarrier::complete_tx::bytes [%0], [%2], 12288, [%1];\n}"
               ::"r"(sb + piece * 12288), "r"(sb + WBAR + piece * 8), "l"(src) : "memory");
}
__device__ __forceinline__ void convert_weights(uint32_t sb, uint32_t wbar, int rot, int warp, int lane) {
  if (warp < 12) {
    const int l8 = lane & 7, q4 = lane >> 3;
    int s = (warp >> 1) + rot; if (s >= 6) s -= 6;
    const uint32_t base = sb + W1S + s * 12288 + (warp & 1) * 384;
    mbar_wait(wbar + s * 8, 0);
    uint32_t v[3][4][4];
#pragma unroll
    for (int r = 0; r < 4; r++)
#pragma unroll
      for (int i = 0; i < 3; i++) lds128(v[i][r], base + i * 128 + (4 * (l8 >> 1) + 2 * (r & 1) + (l8 & 1)) * 768 + ((l8 + q4 + 4 * (r >> 1)) & 7) * 16);
    __syncwarp();
#pragma unroll
    for (int r = 0; r < 4; r++)
#pragma unroll
      for (int i = 0; i < 3; i++)
        sts128(base + i * 128 + (2 * ((l8 + q4 + 4 * (r >> 1)) & 7) + (r & 1)) * 768 + l8 * 16,
               make_uint4(bf2_to_h2(v[i][r][0]), bf2_to_h2(v[i][r][1]), bf2_to_h2(v[i][r][2]), bf2_to_h2(v[i][r][3])));
  }
  PROF2_AT(lane == 0, 440 + warp);
  const int q = lane & 3, t = (lane >> 2) & 3, b = lane >> 4;
  int u = 3 * (warp ^ 15) + 8 * rot; if (u >= 48) u -= 48;
  uint32_t base[3], v[3][4][3];
#pragma unroll
  for (int i = 0; i < 3; i++) {
    const int ui = u + i >= 48 ? u + i - 48 : u + i;
    base[i] = sb + W2S + ui * 1536;
    if (i != 1) mbar_wait(wbar + 48 + (ui >> 3) * 8, 0);
  }
#pragma unroll
  for (int i = 0; i < 3; i++)
#pragma unroll
    for (int d = 0; d < 4; d++)
#pragma unroll
      for (int j = 0; j < 3; j++) v[i][d][j] = lds32(base[i] + (2 * ((q + d) & 3) + b) * 192 + j * 64 + t * 16 + q * 4);
  __syncwarp();
#pragma unroll
  for (int i = 0; i < 3; i++)
#pragma unroll
    for (int d = 0; d < 4; d++)
#pragma unroll
      for (int j = 0; j < 3; j++) sts32(base[i] + (4 * j + q) * 128 + (2 * ((q + d) & 3) + b) * 16 + t * 4, bf2_to_h2(v[i][d][j], 0.5f / GELU_C3));
}

__device__ __noinline__ void ln_wide(uint32_t ad) {
  float m[2], r[2];
#pragma unroll
  for (int hi = 0; hi < 2; hi++) {
    float sm = 0.f;
    for (int s = 0; s < 6; s++) { uint2 w = lds64(ad + s * 512 + hi * 8); sm += (h_lo(w.x) + h_hi(w.x)) + (h_lo(w.y) + h_hi(w.y)); }
    sm += __shfl_xor_sync(0xffffffffu, sm, 1); sm += __shfl_xor_sync(0xffffffffu, sm, 2);
    m[hi] = sm * (1.f / 96.f);
    float q = 0.f;
    for (int s = 0; s < 6; s++) {
      uint2 w = lds64(ad + s * 512 + hi * 8);
      float d0 = h_lo(w.x) - m[hi], d1 = h_hi(w.x) - m[hi], d2 = h_lo(w.y) - m[hi], d3 = h_hi(w.y) - m[hi];
      q += (d0 * d0 + d1 * d1) + (d2 * d2 + d3 * d3);
    }
    q += __shfl_xor_sync(0xffffffffu, q, 1); q += __shfl_xor_sync(0xffffffffu, q, 2);
    r[hi] = rsqrtf(fmaf(q, 1.f / 96.f, 1e-5f)) * GELU_C3;
  }
  for (int s = 0; s < 6; s++) {
    uint32_t w[4]; lds128(w, ad + s * 512);
    sts128(ad + s * 512, make_uint4(pack_f16((h_lo(w[0]) - m[0]) * r[0], (h_hi(w[0]) - m[0]) * r[0]), pack_f16((h_lo(w[2]) - m[1]) * r[1], (h_hi(w[2]) - m[1]) * r[1]),
                                    pack_f16((h_lo(w[1]) - m[0]) * r[0], (h_hi(w[1]) - m[0]) * r[0]), pack_f16((h_lo(w[3]) - m[1]) * r[1], (h_hi(w[3]) - m[1]) * r[1])));
  }
  asm volatile("fence.proxy.async.shared::cta;" ::: "memory");
}

__device__ __forceinline__ float rsqrt_fast(float v) { float r; asm("rsqrt.approx.ftz.f32 %0, %1;" : "=f"(r) : "f"(v)); return r; }
__device__ __forceinline__ uint32_t layer_norm(uint32_t (&raw)[6][4], uint32_t* a, uint32_t tag) {
  const uint32_t stale = ((raw[0][0] ^ tag) | (raw[1][0] ^ tag)) | ((raw[2][0] ^ tag) | (raw[3][0] ^ tag)) | ((raw[4][0] ^ tag) | (raw[5][0] ^ tag));
  uint32_t sm[2];
#pragma unroll
  for (int hi = 0; hi < 2; hi++) {
    uint32_t s0 = h2add(raw[0][2 * hi], raw[1][2 * hi]), s1 = h2add(raw[0][2 * hi + 1], raw[1][2 * hi + 1]);
    uint32_t s2 = h2add(raw[2][2 * hi], raw[3][2 * hi]), s3 = h2add(raw[2][2 * hi + 1], raw[3][2 * hi + 1]);
    uint32_t s4 = h2add(raw[4][2 * hi], raw[5][2 * hi]), s5 = h2add(raw[4][2 * hi + 1], raw[5][2 * hi + 1]);
    sm[hi] = h2add(h2add(h2add(s0, s1), h2add(s2, s3)), h2add(s4, s5));
  }
  uint32_t s = h2add(prmt(sm[0], sm[1], 0x5410), prmt(sm[0], sm[1], 0x7632));
  s = h2add(s, __shfl_xor_sync(0xffffffffu, s, 1));
  s = h2add(s, __shfl_xor_sync(0xffffffffu, s, 2));
  const uint32_t nm = h2mul(s, 0xA155A155u);
  uint32_t qq[2];
#pragma unroll
  for (int hi = 0; hi < 2; hi++) {
    const uint32_t m = hi ? h2hi(nm) : h2lo(nm);
    uint32_t q0 = 0, q1 = 0;
#pragma unroll
    for (int k = 0; k < 6; k++) {
      uint32_t d0 = h2add(raw[k][2 * hi], m), d1 = h2add(raw[k][2 * hi + 1], m);
      raw[k][2 * hi] = d0; raw[k][2 * hi + 1] = d1;
      q0 = k ? h2fma(d0, d0, q0) : h2mul(d0, d0);
      q1 = k ? h2fma(d1, d1, q1) : h2mul(d1, d1);
    }
    qq[hi] = h2add(q0, q1);
  }
  uint32_t q = h2add(prmt(qq[0], qq[1], 0x5410), prmt(qq[0], qq[1], 0x7632));
  q = h2add(q, __shfl_xor_sync(0xffffffffu, q, 1));
  q = h2add(q, __shfl_xor_sync(0xffffffffu, q, 2));
  constexpr float K1 = 1.f / (96.f * GELU_C3 * GELU_C3), K2 = 1e-5f / (GELU_C3 * GELU_C3);
  const float r0 = rsqrt_fast(fmaf(h_lo(q), K1, K2)), r1 = rsqrt_fast(fmaf(h_hi(q), K1, K2));
  const uint32_t r = pack_f16(r0, r1);
#pragma unroll
  for (int k = 0; k < 6; k++) {
    a[4 * k] = h2mul(raw[k][0], h2lo(r)); a[4 * k + 2] = h2mul(raw[k][1], h2lo(r));
    a[4 * k + 1] = h2mul(raw[k][2], h2hi(r)); a[4 * k + 3] = h2mul(raw[k][3], h2hi(r));
  }
  return (((q & 0x7c007c00u) + 0x04000400u) & 0x80008000u) | (stale & 1);
}

__device__ __forceinline__ void gemm1(uint32_t* p, const uint32_t* a, uint64_t d1, int c) {
  wgmma_n48_f16<0>(p, a, d1 + c * (1536 >> 4));
#pragma unroll
  for (int s = 1; s < 6; s++) wgmma_n48_f16<1>(p, a + 4 * s, d1 + c * (1536 >> 4) + s * (12288 >> 4));
}

__device__ __forceinline__ void gemm1_piece(uint32_t* p, const uint32_t* a, uint64_t d1, int c, int u) {
  if (u == 0) wgmma_n48_f16<0>(p, a, d1 + c * (1536 >> 4)); else wgmma_n48_f16<1>(p, a + 8 * u, d1 + c * (1536 >> 4) + 2 * u * (12288 >> 4));
  wgmma_n48_f16<1>(p, a + 8 * u + 4, d1 + c * (1536 >> 4) + (2 * u + 1) * (12288 >> 4));
}
__device__ __forceinline__ void fetch_a(uint32_t abuf, uint32_t bar, const unsigned char* src) {
  asm volatile("{\n.reg .pred p;\nelect.sync _|p, 0xffffffff;\n"
               "@p mbarrier.arrive.expect_tx.shared::cta.b64 _, [%1], 3072;\n"
               "@p cp.async.bulk.shared::cluster.global.mbarrier::complete_tx::bytes [%0], [%2], 3072, [%1];\n}"
               ::"r"(abuf), "r"(bar), "l"(src) : "memory");
}
__device__ __forceinline__ void fetch_a_if(uint32_t abuf, uint32_t bar, const unsigned char* src, uint32_t go) {
  asm volatile("{\n.reg .pred p, q;\nsetp.ne.u32 q, %3, 0;\nelect.sync _|p, 0xffffffff;\nand.pred p, p, q;\n"
               "@p mbarrier.arrive.expect_tx.shared::cta.b64 _, [%1], 3072;\n"
               "@p cp.async.bulk.shared::cluster.global.mbarrier::complete_tx::bytes [%0], [%2], 3072, [%1];\n}"
               ::"r"(abuf), "r"(bar), "l"(src), "r"(go) : "memory");
}
__device__ __forceinline__ bool mbar_test(uint32_t bar, uint32_t parity) {
  uint32_t r;
  asm volatile("{.reg .pred p; mbarrier.test_wait.parity.shared::cta.b64 p, [%1], %2; selp.u32 %0, 1, 0, p;}" : "=r"(r) : "r"(bar), "r"(parity) : "memory");
  return r;
}
__device__ __forceinline__ void fetch_x(uint32_t xbuf, uint32_t bar, const CUtensorMap* tm, uint32_t c0, uint32_t c12, uint64_t pol) {
  asm volatile("{\n.reg .pred p;\nelect.sync _|p, 0xffffffff;\n"
               "@p mbarrier.arrive.expect_tx.shared::cta.b64 _, [%1], 3072;\n"
               "@p cp.async.bulk.tensor.3d.shared::cluster.global.mbarrier::complete_tx::bytes.L2::cache_hint [%0], [%2, {%3, %4, %5}], [%1], %6;\n}"
               ::"r"(xbuf), "r"(bar), "l"(tm), "r"(c0), "r"(c12 & 255), "r"(c12 >> 8), "l"(pol) : "memory");
}
__device__ __forceinline__ void wait_ready(const uint32_t* p, uint32_t target) {
  int spins = 0;
  while (ld_relaxed(p) != target) { __nanosleep(32); if (++spins > SPIN_LIMIT) __trap(); }
}
__device__ __forceinline__ uint32_t slot_tag(int gm, int j, uint32_t epoch) {
  const int len = gm < 8 ? PLEN : LMID, writes = (len - (j & (RING - 1)) + RING - 1) / RING;
  return (epoch * writes + j / RING + 1) & 1;
}

__device__ __forceinline__ void build_tile_list(uint32_t sb, int k, int idx, bool tabled, bool is_conv, uint32_t epoch) {
  int n = -1;
  if (tabled) { if (k < 48) n = (int16_t)g_sched[idx][k]; }
  else if (!is_conv) {
    const int i = k * (gridDim.x - NCONV) + idx, r = i >> 2, full = LMID * NG;
    const int j = r < full ? r / NG : ((r - full) >> 3) + LMID, gm = r < full ? r % NG : (r - full) & 7;
    if (i < 4096) n = (gm * PLEN + j) * 4 + (i & 3);
  }
  const int q = n >> 2, gm = q / PLEN, j = q - gm * PLEN, seg = j / LM;
  const int strip = gm < 8 ? gm >> 1 : (gm - 8) * NSEG + seg, pair = gm < 8 ? ((gm & 1) ? 255 - j : j) : PLEN + j - seg * LM;
  sts128(sb + MISC + 512 + k * 16, make_uint4(q, (((j & (RING - 1)) * NG + gm) * 4 + (n & 3)) * TILEB + slot_tag(gm, j, epoch),
                                              (n & 2) * 384, (strip * 8 + (n & 1) * 4) | (pair << 9)));
  if (k == 0) sts32(sb + MISC + 256, epoch + 1);
}

__device__ __forceinline__ void mlp_setup(uint32_t sb, Globals* gs, int id, const __nv_bfloat16* __restrict__ w1, const __nv_bfloat16* __restrict__ w2,
                                          int idx, bool tabled, int warp, int lane) {
  const int rot = idx % 6;
  PROF2_AT(lane == 0, 400 + warp);
  if (warp < 12) {
    const int m = warp >= 6; int s = warp - 6 * m + rot; if (s >= 6) s -= 6;
    if (WDELAY) __nanosleep(WDELAY + m * WDELAY2);
    copy_weights(sb, 6 * m + s, (const char*)(m ? w2 : w1) + s * 12288);
  }
  __syncthreads();
  PROF2_AT(threadIdx.x == 0, 416);
  if (warp >= 12) build_tile_list(sb, threadIdx.x - 384, idx, tabled, false, ld_relaxed(&gs->epoch[id]));
  PROF2_AT(lane == 0, 420 + warp);
  convert_weights(sb, sb + WBAR, rot, warp, lane);
  PROF2_AT(lane == 0, 460 + warp);
  asm volatile("fence.proxy.async.shared::cta;" ::: "memory");
  __syncthreads();
  if (threadIdx.x == 480) {
    const uint32_t e1 = lds32(sb + MISC + 256);
    gs->epoch[id] = e1;
    if (idx < 24 && (idx & 1)) {
      asm volatile("cp.async.bulk.global.shared::cta.bulk_group [%0], [%1], 12288;\ncp.async.bulk.commit_group;\ncp.async.bulk.wait_group 0;\nfence.proxy.async.global;\n"
                   "red.release.gpu.global.add.u32 [%2], 1;" ::"l"(gs->wimg + (idx >> 1) * 12288), "r"(sb + (idx >> 1) * 12288), "l"(gs->wflag) : "memory");
    }
  }
  __syncwarp();
}

__device__ __forceinline__ void mlp_role(uint32_t sb, Globals* gs, const CUtensorMap* tmr, __nv_bfloat16* __restrict__ out) {
  uint32_t tid;
  asm volatile("mov.u32 %0, %%tid.x;" : "=r"(tid));
  const int warp = __shfl_sync(0xffffffffu, tid >> 5, 0), lane = tid & 31;
  const int wg = warp >> 2, w = warp & 3, g = lane >> 2, t = lane & 3;
  const uint32_t abuf = sb + ABUF + warp * 3072, xbuf = sb + XBUF + (warp & 7) * 3072;
  const uint32_t bar = sb + MISC + warp * 8, obar = sb + MISC + (warp ^ 8) * 8;
  const uint32_t tl = sb + MISC + 512;
  PROF_AT(threadIdx.x == 0, 1); PROF_VAL(threadIdx.x == 0, 8, clock64());
  const uint32_t rtarget = 3 * lds32(sb + MISC + 256);
  const uint64_t d1 = ((uint64_t)(768 >> 4) << 16) | ((uint64_t)(128 >> 4) << 32) | (uint64_t)(((sb + W1S) >> 4) & 0x3fff);
  const uint64_t d2 = ((uint64_t)(12288 >> 4) << 16) | ((uint64_t)(128 >> 4) << 32) | (uint64_t)(((sb + W2S) >> 4) & 0x3fff);
  const uint32_t ad = abuf + t * 128 + ((g ^ (2 * t)) << 4);
  const uint32_t xd = xbuf + g * 192 + t * 16;
  const int mybar = 1 + wg, nxtbar = 1 + ((wg + 1) & 3);
  const uint64_t pol = pol_evict_first();
  const unsigned char* const asrc = gs->scratch + w * 3072;
  uint32_t pha = 0, phx = 0, tp = tl + wg * 16;
  bool pending = true;
  uint32_t cur[4];
  lds128(cur, tp);
  while ((int)cur[0] >= 0) {
    PROF2_AT((threadIdx.x & 127) == 0, 16 + (tp - tl) / 4); PROF2_VAL((threadIdx.x & 127) == 0, 16 + (tp - tl) / 4 + 3, pending);
    uint32_t a[24], p[8][12], gg[8][12], acc[24], raw[6][4], xr[6][4], n2[4], n4[4];
    if (pending) {
      wait_ready(&gs->ready[cur[0]], rtarget);
      fetch_a(abuf, bar, asrc + (cur[1] & ~1u));
      if (tp < tl + 32) fetch_x(xbuf, bar + 128, tmr, cur[2] + w * 192, cur[3], pol);
    }
    mbar_wait(bar, pha); pha ^= 1;
    PROF2_AT((threadIdx.x & 127) == 0, 16 + (tp - tl) / 4 + 1);
#pragma unroll
    for (int k = 0; k < 6; k++) lds128(raw[k], ad + k * 512);
    const int sig = lds32(tp + 16);
    lds128(n4, tp + 64);
    uint32_t st = layer_norm(raw, a, cur[1]);
    if (__any_sync(0xffffffffu, st != 0)) {
      for (int tries = 0; __any_sync(0xffffffffu, st & 1); tries++) {
        if (tries > SPIN_LIMIT) __trap();
        fetch_a(abuf, bar, asrc + (cur[1] & ~1u));
        mbar_wait(bar, pha); pha ^= 1;
        st = 0;
#pragma unroll
        for (int k = 0; k < 6; k++) st |= lds32(ad + k * 512) ^ cur[1];
      }
      ln_wide(ad);
#pragma unroll
      for (int k = 0; k < 6; k++) lds128(a + 4 * k, ad + k * 512);
    }
    if (!LATERED) red_add_elect(&gs->cons[cur[0]]);
    if (tp != tl) asm volatile("bar.sync %0, 256;" ::"r"(mybar) : "memory");
    PROF2_AT((threadIdx.x & 127) == 0, 16 + (tp - tl) / 4 + 2);
    uint32_t rdy = 0;
    wg_fence();
    gemm1(p[0], a, d1, 0); wg_commit();
    if (SCHED == 9) { gemm1_piece(p[1], a, d1, 1, 0); wg_commit(); }
    if (LATERED) asm volatile("{.reg .pred p; setp.eq.u32 p, %1, 0; @p red.relaxed.gpu.global.add.u32 [%0], 1;}" ::"l"(&gs->cons[cur[0]] + lane), "r"(lane) : "memory");
#pragma unroll
    for (int j = 0; j < 24; j++) {
      const int c = j / 3, s = j % 3;
      if (j == JB) {
        rdy = ld_relaxed(&gs->ready[max((int)n4[0], 0)]);
        wg_wait<0>();
        mbar_wait(bar + 128, phx); phx ^= 1;
      } else if (SCHED == 9) wg_wait<1>(); else if (s == 0) wg_wait<0>();
      if (j == TRIG) asm volatile("{.reg .pred p; setp.ge.s32 p, %1, 0; @p bar.arrive %0, 256;}" ::"r"(nxtbar), "r"(sig) : "memory");
#pragma unroll
      for (int i = 0; i < 4; i++) gg[c][4 * s + i] = gelu_h2(p[c][4 * s + i]);
      wg_fence();
      if (j == 0) wgmma_n96_f16<0>(acc, gg[c], d2); else wgmma_n96_f16<1>(acc, &gg[c][4 * s], d2 + (16 * s + c) * (1536 >> 4));
      if (SCHED == 9) {
        if (j < 20) gemm1_piece(p[(j + 1) / 3 + 1], a, d1, (j + 1) / 3 + 1, (j + 1) % 3);
        wg_commit();
      } else if (s == 2) {
        if (c < 7) gemm1(p[c + 1], a, d1, c + 1);
        wg_commit();
      }
    }
    if (XEARLY) {
#pragma unroll
      for (int k = 0; k < 6; k++) lds128(xr[k], xd + (k / 3) * 1536 + (k % 3) * 64);
      lds128(n2, tp + 32);
    }
    pending = rdy != rtarget;
    if (FPRED) fetch_a_if(abuf, bar, asrc + (n4[1] & ~1u), !pending && (int)n4[0] >= 0);
    wg_wait<0>();
    if (!FPRED && !pending && (int)n4[0] >= 0) fetch_a(abuf, bar, asrc + (n4[1] & ~1u));
    char* const op = (char*)out + (size_t)(cur[3] >> 8) * (512 * 192) + ((cur[3] & 255) + (g >> 1)) * 3072 + cur[2] * 2 + (2 * w + (g & 1)) * 192 + t * 16;
    if (!XEARLY) lds128(n2, tp + 32);
#pragma unroll
    for (int k = 0; k < 6; k++) {
      const int hi = k / 3, j = k % 3;
      if (!XEARLY) lds128(xr[k], xd + hi * 1536 + j * 64);
      uint4 o;
      o.x = hadd2_bf16(xr[k][0], pack_bf16(h_lo(acc[8 * j + hi]), h_hi(acc[8 * j + hi])));
      o.y = hadd2_bf16(xr[k][1], pack_bf16(h_lo(acc[8 * j + 2 + hi]), h_hi(acc[8 * j + 2 + hi])));
      o.z = hadd2_bf16(xr[k][2], pack_bf16(h_lo(acc[8 * j + 4 + hi]), h_hi(acc[8 * j + 4 + hi])));
      o.w = hadd2_bf16(xr[k][3], pack_bf16(h_lo(acc[8 * j + 6 + hi]), h_hi(acc[8 * j + 6 + hi])));
      stg128_stream(op + hi * (512 * 192) + j * 64, o, pol);
    }
    __syncwarp();
    if ((int)n2[0] >= 0) fetch_x(xbuf, obar + 128, tmr, n2[2] + w * 192, n2[3], pol);
    tp += 64;
#pragma unroll
    for (int k = 0; k < 4; k++) cur[k] = n4[k];
  }
  PROF_AT((threadIdx.x & 127) == 0, 4 + wg); PROF_VAL(threadIdx.x == 0, 9, clock64());
}

__device__ __forceinline__ void stg128_if(uint32_t ofs, void* p, uint4 v) {
  if (NODUMP) asm volatile("{.reg .pred q; setp.ge.s32 q, %5, 0; @q st.global.v4.b32 [%0], {%1,%2,%3,%4};}" ::"l"(p), "r"(v.x), "r"(v.y), "r"(v.z), "r"(v.w), "r"(ofs) : "memory");
  else stg128(p, v);
}
__device__ __forceinline__ void conv_compute(uint32_t sb, Globals* gs, int third, int nit, int off, bool up, int warp, int lane) {
  const int g = lane >> 2, t = lane & 3;
  const uint32_t full = sb + CM;
  PROFS(0);
  const uint32_t wt = sb + 16384 + warp * 1024;
  sts128(wt + lane * 16, make_uint4(0, 0, 0, 0));
  if (lane < 4) sts128(wt + 512 + lane * 16, make_uint4(0, 0, 0, 0));
  asm volatile("setmaxnreg.inc.sync.aligned.u32 %0;" ::"n"(CREGS));
  PROFS(1);
  uint32_t meta = 0;
#pragma unroll
  for (int a = 0; a < 4; a++) meta |= ((4 * (t & 1) + a + 1 >= g) ? 0x80008u : 0xD000Du) << (4 * a);
  meta = __shfl_sync(0xffffffffu, meta, lane);
  uint32_t aq[4];
#pragma unroll
  for (int q = 0; q < 4; q++) {
    const int pp = (g & 1) * 140 + (t & 1) * 70 + 16 * (g >> 1) + 2 * q + (t >> 1);
    aq[q] = __shfl_sync(0xffffffffu, sb + RBUF + pp * 64 + (((warp >> 1) ^ ((pp >> 1) & 3)) << 4) + (warp & 1) * 8, lane);
  }
  const int Q = third * 8 + warp;
  unsigned char* const obase = gs->scratch + (g >> 1) * 3072 + Q * 128 + (((2 * t + (g & 1)) ^ (2 * (Q & 3))) << 4);
  const float zero4[4] = {0.f, 0.f, 0.f, 0.f};
  {
    uint32_t A[4][4][4];
    PROFS(2);
    asm volatile("bar.sync 5, 288;" ::: "memory");
    mbar_wait(sb + WBAR + 8, 0);
    PROFS(3);
    {
#pragma unroll
      for (int k = 0; k < 2; k++) {
        const int tap = lane + 32 * k, i = tap / 7;
        if (tap < 49) { const uint2 v = lds64(sb + tap * 192 + third * 64 + warp * 8); asm volatile("st.shared.v2.b32 [%0], {%1,%2};" ::"r"(wt + (tap + i + 8) * 8), "r"(v.x), "r"(v.y) : "memory"); }
      }
      __syncwarp();
      uint2 w[2][4][3];
#pragma unroll
      for (int h = 0; h < 2; h++) {
        uint32_t src = wt + ((4 * h + t - g) & 7) * 8 + (up ? 384 : 0);
#pragma unroll
        for (int u = 0; u < 4; u++) {
#pragma unroll
          for (int k = 0; k < 3; k++) w[h][u][k] = lds64(src + k * 64);
          src += up ? -128 : 128;
        }
      }
#pragma unroll
      for (int u = 0; u < 4; u++)
#pragma unroll
        for (int r = 0; r < 4; r++) {
          const uint2 w0 = w[r >> 1][u][1 - (r & 1)], w1 = w[r >> 1][u][2 - (r & 1)];
          A[0][u][r] = prmt(w0.x, w1.x, 0x5410); A[1][u][r] = prmt(w0.x, w1.x, 0x7632);
          A[2][u][r] = prmt(w0.y, w1.y, 0x5410); A[3][u][r] = prmt(w0.y, w1.y, 0x7632);
        }
    }
    float S[2][4][3][4];
#pragma unroll
    for (int s = 0; s < 2; s++)
#pragma unroll
      for (int c = 0; c < 4; c++)
#pragma unroll
        for (int i = 0; i < 3; i++)
#pragma unroll
          for (int k = 0; k < 4; k++) S[s][c][i][k] = 0.f;
    uint32_t sofs = off * SLOTB, bar = full + off * 8, ph = 0, ot = sb + CTAB;
    const uint32_t oend = ot + nit * 16;
    PROF_AT(threadIdx.x == 0, 12);
    PROFS(4);
    asm volatile("bar.sync 0, 512;" ::: "memory");
    PROFS(5);
    mbar_wait(bar, 0);
    PROF_AT(threadIdx.x == 0, 14);
    PROFS(6);
    uint2 X[3][4];
#pragma unroll
    for (int j = 0; j < 2; j++)
#pragma unroll
      for (int q = 0; q < 4; q++) X[j][q] = lds64(aq[q] + sofs + j * 512);
#pragma unroll 1
    do {
      const uint2 oe = lds64(ot);
      unsigned char* const o = obase + oe.x;
      const uint32_t dbar = bar + 64;
#pragma unroll
      for (int s = 0; s < 2; s++) {
        uint32_t B[4][4];
        if (s == 1) {
          sofs += SLOTB; bar += 8;
          if (sofs == NSLOT * SLOTB) { sofs = 0; bar = full; ph ^= 1; }
          mbar_wait(bar, ph);
        }
#pragma unroll
        for (int c = 0; c < 4; c++)
#pragma unroll
          for (int q = 0; q < 4; q++) B[c][q] = prmt(c < 2 ? X[s][q].x : X[s][q].y, c < 2 ? X[s + 1][q].x : X[s + 1][q].y, (c & 1) ? 0x7632 : 0x5410);
        if (s == 0) {
#pragma unroll
          for (int q = 0; q < 4; q++) X[2][q] = lds64(aq[q] + sofs + 2 * 512);
        } else {
#pragma unroll
          for (int j = 0; j < 2; j++)
#pragma unroll
            for (int q = 0; q < 4; q++) X[j][q] = lds64(aq[q] + sofs + j * 512);
        }
        float T[4][4];
        if (CFN & 1) SCHED_FENCE();
#pragma unroll
        for (int c = 0; c < 4; c++) mma_sp(T[c], A[c][3], B[c], S[s][c][2], meta);
#pragma unroll
        for (int c = 0; c < 4; c++) mma_sp(S[s][c][2], A[c][2], B[c], S[s][c][1], meta);
        if (CFN & 2) SCHED_FENCE();
        stg128_if(oe.x, o + (2 * s) * TILEB, make_uint4((pack_f16_sat(T[0][0], T[1][0]) & ~1u) | oe.y, pack_f16_sat(T[2][0], T[3][0]), pack_f16_sat(T[0][2], T[1][2]), pack_f16_sat(T[2][2], T[3][2])));
        stg128_if(oe.x, o + (2 * s + 1) * TILEB, make_uint4((pack_f16_sat(T[0][1], T[1][1]) & ~1u) | oe.y, pack_f16_sat(T[2][1], T[3][1]), pack_f16_sat(T[0][3], T[1][3]), pack_f16_sat(T[2][3], T[3][3])));
        if (s == 1) mbar_arrive_elect(dbar);
        if (CFN & 4) SCHED_FENCE();
#pragma unroll
        for (int c = 0; c < 4; c++) mma_sp(S[s][c][1], A[c][1], B[c], S[s][c][0], meta);
#pragma unroll
        for (int c = 0; c < 4; c++) mma_sp(S[s][c][0], A[c][0], B[c], zero4, meta);
      }
      ot += 16;
    } while (ot != oend);
  }
  PROF_AT(threadIdx.x == 0, 13);
}

__device__ __forceinline__ void load_step(uint32_t sb, const CUtensorMap* tmx, int gm, int third, int it, int s) {
  const int seg = it / (LM + 3);
  const int st = gm < 8 ? gm >> 1 : (gm - 8) * NSEG + seg, J = gm < 8 ? ((gm & 1) ? 257 - it : it + 1) : PLEN + it - seg * (LM + 3);
  asm volatile("{\n.reg .pred p;\n.reg .s32 c2;\n.reg .u32 d2;\nelect.sync _|p, 0xffffffff;\nadd.s32 c2, %4, 64;\nadd.u32 d2, %0, 8960;\n"
               "@p mbarrier.arrive.expect_tx.shared::cta.b64 _, [%2], 17920;\n"
               "@p cp.async.bulk.tensor.3d.shared::cluster.global.mbarrier::complete_tx::bytes [%0], [%1, {%3, %4, %5}], [%2];\n"
               "@p cp.async.bulk.tensor.3d.shared::cluster.global.mbarrier::complete_tx::bytes [d2], [%1, {%3, c2, %5}], [%2];\n}"
               ::"r"(sb + RBUF + s * SLOTB), "l"(tmx), "r"(sb + CM + s * 8), "r"(third * 32), "r"(st * 128 - 3), "r"(2 * J - 3) : "memory");
}
__device__ __forceinline__ void ring_bar_init(uint32_t bar, uint32_t cnt, bool ahead) {
  asm volatile("{\n.reg .pred p, q;\nelect.sync _|p, 0xffffffff;\n@p mbarrier.init.shared::cta.b64 [%0], %1;\n"
               "setp.ne.and.u32 q, %2, 0, p;\n@q mbarrier.arrive.shared::cta.b64 _, [%0], %1;\n@p fence.mbarrier_init.release.cluster;\n}" ::"r"(bar), "r"(cnt), "r"((uint32_t)ahead) : "memory");
}
__device__ __forceinline__ void conv_loader(uint32_t sb, Globals* gs, const CUtensorMap* tmx, int gm, int nit, int off, int cidx, int third, int k) {
  static_assert(AHEAD > 4 && AHEAD <= NSLOT && NCONV >= 24, "loader");
  const uint32_t full = sb + CM;
  asm volatile("bar.sync 0, 512;" ::: "memory");
  if (FIRST + k < AHEAD) load_step(sb, tmx, gm, third, FIRST + k, (FIRST + k + off) & 7);
#pragma unroll 1
  for (int it = AHEAD + k; it < nit + AHEAD; it += 4) {
    const int u = it + off;
    const uint32_t ro = lds32(sb + CTAB + (it - AHEAD) * 16 + 8);
    mbar_wait(full + 64 + ((u - AHEAD) & 7) * 8, ((u - AHEAD) >> 3) & 1);
    red_add_elect((uint32_t*)((char*)gs + ro));
    PROF_AT((threadIdx.x & 31) == 0 && (((it - AHEAD) & (PROF > 1 ? 7 : 15)) == 0 || it - AHEAD < 6), 200 + it - AHEAD);
    if (it <= nit) load_step(sb, tmx, gm, third, it, u & 7);
    if (it >= nit - 16) {
      if (it < nit - 12) {
        wait_ready(gs->wflag, 12 * lds32(sb + MISC + 256));
        asm volatile("fence.acquire.gpu;\nfence.proxy.async.global;" ::: "memory");
        if (cidx < 24) asm volatile("{.reg .pred p; elect.sync _|p, 0xffffffff; @p cp.async.bulk.prefetch.L2.global [%0], 1536;}" ::"l"(gs->wimg + (cidx * 4 + k) * 1536) : "memory");
      }
      const int m = it == nit ? 0 : W2S;
      if (it == nit || it == nit + AHEAD - 4)
        asm volatile("{\n.reg .pred p;\nelect.sync _|p, 0xffffffff;\n@p mbarrier.arrive.expect_tx.shared::cta.b64 _, [%1], 73728;\n"
                     "@p cp.async.bulk.shared::cluster.global.mbarrier::complete_tx::bytes [%0], [%2], 73728, [%1];\n}"
                     ::"r"(sb + m), "r"(sb + WBAR), "l"(gs->wimg + m) : "memory");
    }
  }
}

__device__ __forceinline__ void conv_credit(uint32_t sb, Globals* gs, int P0, int nit, int off, uint32_t ctarget, int k) {
  const uint32_t full = sb + CM;
#pragma unroll 1
  for (int it = k + NSLOT; it <= nit; it += 4) {
    const int u = it + off, P = (int)lds32(sb + CTAB + it * 16 + 12) - RING;
    int spins = 0;
    mbar_wait(full + 64 + (u & 7) * 8, ((u >> 3) & 1) ^ 1);
    if (P >= P0) while (ld_relaxed(&gs->cons[P]) != ctarget) { __nanosleep(CSLEEP); if (++spins > SPIN_LIMIT) __trap(); }
    mbar_arrive_elect(full + (u & 7) * 8);
  }
}

__global__ void __launch_bounds__(512, 1) convnext_kernel(const __grid_constant__ CUtensorMap tmx, const __grid_constant__ CUtensorMap tmr, const __nv_bfloat16* __restrict__ dw,
                                                          const __nv_bfloat16* __restrict__ w1, const __nv_bfloat16* __restrict__ w2, __nv_bfloat16* __restrict__ out, Globals* gs) {
  extern __shared__ __align__(1024) unsigned char smem[];
  const uint32_t sb = smem_u32(smem);
  const int warp = __shfl_sync(0xffffffffu, threadIdx.x >> 5, 0), lane = threadIdx.x & 31;
  PROF_AT(threadIdx.x == 0, 0);
  if (PFX && threadIdx.x == 320) asm volatile("prefetch.tensormap [%0];" ::"l"(&tmx) : "memory");
  if (threadIdx.x == 288) asm volatile("prefetch.tensormap [%0];" ::"l"(&tmr) : "memory");
  uint32_t smid, nsmid;
  asm volatile("mov.u32 %0, %%smid;" : "=r"(smid));
  asm volatile("mov.u32 %0, %%nsmid;" : "=r"(nsmid));
  const bool tabled = TABLED && gridDim.x == 132 && nsmid == 132;
  const int id = tabled ? smid : blockIdx.x;
  int cidx, idx;
  int is_conv;
  if (tabled) {
    idx = smid;
    const int k = (smid - 60) / 14, r = smid - 60 - 14 * k;
    is_conv = smid < 48 ? !(smid & 1) : (smid >= 60 && smid <= 90 && (r & ~2) == 0);
    cidx = smid < 48 ? ((smid >> 1) & 7) * 3 + (smid >> 4) : 24 + (r >> 1) * 3 + k;
  } else {
    cidx = (blockIdx.x * NCONV) / gridDim.x;
    is_conv = ((blockIdx.x + 1) * NCONV) / gridDim.x != cidx;
    idx = blockIdx.x - cidx;
  }
  PROF_VAL(threadIdx.x == 0, 2, is_conv ? 1000 + cidx : idx);
  const int gm = cidx / 3, third = cidx - gm * 3;
  const int P0 = gm * PLEN, nit = gm < 8 ? PLEN + 2 : NSEG * (LM + 3), off = (7 - nit) & 7;
  if (is_conv && warp == 8) {
    asm volatile("{\n.reg .pred p;\nelect.sync _|p, 0xffffffff;\n@p mbarrier.init.shared::cta.b64 [%1], 1;\n@p fence.mbarrier_init.release.cluster;\n"
                 "@p mbarrier.arrive.expect_tx.shared::cta.b64 _, [%1], 9408;\n"
                 "@p cp.async.bulk.shared::cluster.global.mbarrier::complete_tx::bytes [%0], [%2], 9408, [%1];\nbar.arrive 5, 288;\n}"
                 ::"r"(sb), "r"(sb + WBAR + 8), "l"(dw) : "memory");
#pragma unroll 1
    for (int it = 0; it < NSLOT; it++) {
      const int s = (it + off) & 7;
      ring_bar_init(sb + CM + s * 8, 2, s < off);
      PROF_AT(it == 0 && (threadIdx.x & 31) == 0, 15);
      if (it < FIRST) load_step(sb, &tmx, gm, third, it, s);
    }
  }
  mbar_init_elect(sb + MISC + warp * 8, 1); mbar_init_elect(sb + MISC + 128 + warp * 8, 1);
  asm volatile("fence.mbarrier_init.release.cluster;" ::: "memory");
  if (is_conv) {
    if (warp >= 8) ring_bar_init(sb + CM + warp * 8, 8, warp - 8 < off);
    if (warp == 9) mbar_init_elect(sb + WBAR, 2);
    if (warp < 8) {
      conv_compute(sb, gs, third, nit, off, gm < 8 && (gm & 1), warp, lane);
      asm volatile("setmaxnreg.dec.sync.aligned.u32 128;");
    } else if (warp >= 12) {
      asm volatile("setmaxnreg.dec.sync.aligned.u32 24;");
      const uint32_t epoch = ld_relaxed(&gs->epoch[id]);
#pragma unroll 1
      for (int it = threadIdx.x - 384; it <= nit; it += 128) {
        const int seg = it / (LM + 3), j = gm < 8 ? it - 2 : it - 3 * (seg + 1);
        const bool ok = it < nit && j >= (gm < 8 ? 0 : seg * LM);
        sts128(sb + CTAB + it * 16, make_uint4((ok ? (j & (RING - 1)) * NG + gm : NODUMP ? -1 : RING * NG) * (4 * TILEB), slot_tag(gm, max(j, 0), epoch),
                                               offsetof(Globals, ready) + (ok ? P0 + j : NG * PLEN) * 4, ok ? P0 + j : -1));
      }
      asm volatile("bar.sync 0, 512;" ::: "memory");
      mbar_arrive_elect(sb + CM + ((((warp + 2) & 3) + off) & 7) * 8);
      mbar_arrive_elect(sb + CM + ((((warp + 2) & 3) + off + 4) & 7) * 8);
      build_tile_list(sb, threadIdx.x - 384, idx, tabled, true, epoch);
      if (threadIdx.x == 384) gs->epoch[id] = epoch + 1;
      conv_credit(sb, gs, P0, nit, off, 16 * (epoch + 1), (warp + 2) & 3);
      mbar_wait(sb + CM + 64 + 3 * 8, ((nit + off) >> 3) & 1);
      mbar_wait(sb + CM + 64 + 6 * 8, ((nit + off) >> 3) & 1);
      asm volatile("setmaxnreg.inc.sync.aligned.u32 128;");
    } else {
      asm volatile("setmaxnreg.dec.sync.aligned.u32 %0;" ::"n"(488 - 2 * CREGS));
      conv_loader(sb, gs, &tmx, gm, nit, off, cidx, third, warp & 3);
      mbar_wait(sb + CM + 64 + 3 * 8, ((nit + off) >> 3) & 1);
      mbar_wait(sb + CM + 64 + 6 * 8, ((nit + off) >> 3) & 1);
      asm volatile("setmaxnreg.inc.sync.aligned.u32 128;");
    }
    PROF2_AT((threadIdx.x & 31) == 0, 400 + (threadIdx.x >> 5));
    mbar_wait(sb + WBAR, 0);
    asm volatile("bar.sync 0, 512;" ::: "memory");
  } else {
    mlp_setup(sb, gs, id, w1, w2, idx, tabled, warp, lane);
  }
  mlp_role(sb, gs, &tmr, out);
}

typedef CUresult (*PFN_encodeTiled)(CUtensorMap*, CUtensorMapDataType, cuuint32_t, void*, const cuuint64_t*, const cuuint64_t*, const cuuint32_t*, const cuuint32_t*,
                                    CUtensorMapInterleave, CUtensorMapSwizzle, CUtensorMapL2promotion, CUtensorMapFloatOOBfill);

extern "C" void kernel_launch(void* const* d_in, const int* in_sizes, int n_in, void* d_out, int out_size) {
  const __nv_bfloat16* x = (const __nv_bfloat16*)d_in[0];
  const __nv_bfloat16* dw = (const __nv_bfloat16*)d_in[1];
  const __nv_bfloat16* w1 = (const __nv_bfloat16*)d_in[2];
  const __nv_bfloat16* w2 = (const __nv_bfloat16*)d_in[3];
  static PFN_encodeTiled encode = nullptr;
  static int nsm = 0;
  static Globals* gs = nullptr;
  if (!encode) {
    void* fn = nullptr; cudaDriverEntryPointQueryResult qr;
    cudaGetDriverEntryPoint("cuTensorMapEncodeTiled", &fn, cudaEnableDefault, &qr);
    encode = (PFN_encodeTiled)fn;
    cudaGetSymbolAddress((void**)&gs, g_state);
    int dev = 0; cudaGetDevice(&dev);
    cudaDeviceGetAttribute(&nsm, cudaDevAttrMultiProcessorCount, dev);
    cudaFuncSetAttribute(convnext_kernel, cudaFuncAttributeMaxDynamicSharedMemorySize, SMEM_BYTES);
  }
  CUtensorMap tm;
  cuuint64_t dims[3] = {96, 512, 512}, strides[2] = {192, 192 * 512};
  cuuint32_t box[3] = {32, 70, 2}, es[3] = {1, 1, 1};
  encode(&tm, CU_TENSOR_MAP_DATA_TYPE_BFLOAT16, 3, (void*)x, dims, strides, box, es, CU_TENSOR_MAP_INTERLEAVE_NONE, CU_TENSOR_MAP_SWIZZLE_64B,
         PROMO, CU_TENSOR_MAP_FLOAT_OOB_FILL_NONE);
  CUtensorMap tr;
  cuuint64_t dims2[3] = {1536, 32, 512}, strides2[2] = {3072, 192 * 512};
  cuuint32_t box2[3] = {192, 4, 2};
  encode(&tr, CU_TENSOR_MAP_DATA_TYPE_BFLOAT16, 3, (void*)x, dims2, strides2, box2, es, CU_TENSOR_MAP_INTERLEAVE_NONE, CU_TENSOR_MAP_SWIZZLE_NONE,
         CU_TENSOR_MAP_L2_PROMOTION_NONE, CU_TENSOR_MAP_FLOAT_OOB_FILL_NONE);
  convnext_kernel<<<nsm, 512, SMEM_BYTES>>>(tm, tr, dw, w1, w2, (__nv_bfloat16*)d_out, gs);
}
```

```cpp
#include <cuda_runtime.h>
#include <cuda_bf16.h>
#include <cuda.h>
#include <stdint.h>
#include <stddef.h>

template<int SCALE_D> __device__ __forceinline__ void wgmma_n32_f16(uint32_t* d, const uint32_t* a, uint64_t desc) {
  if (SCALE_D == 0) asm volatile("wgmma.mma_async.sync.aligned.m64n32k16.f16.f16.f16 {%0,%1,%2,%3,%4,%5,%6,%7}, {%8,%9,%10,%11}, %12, 0, 1, 1, 1;"
    : "=r"(d[0]),"=r"(d[1]),"=r"(d[2]),"=r"(d[3]),"=r"(d[4]),"=r"(d[5]),"=r"(d[6]),"=r"(d[7])
    : "r"(a[0]),"r"(a[1]),"r"(a[2]),"r"(a[3]),"l"(desc));
  if (SCALE_D == 1) asm volatile("wgmma.mma_async.sync.aligned.m64n32k16.f16.f16.f16 {%0,%1,%2,%3,%4,%5,%6,%7}, {%8,%9,%10,%11}, %12, 1, 1, 1, 1;"
    : "+r"(d[0]),"+r"(d[1]),"+r"(d[2]),"+r"(d[3]),"+r"(d[4]),"+r"(d[5]),"+r"(d[6]),"+r"(d[7])
    : "r"(a[0]),"r"(a[1]),"r"(a[2]),"r"(a[3]),"l"(desc));
}

template<int SCALE_D> __device__ __forceinline__ void wgmma_n48_f16(uint32_t* d, const uint32_t* a, uint64_t desc) {
  if (SCALE_D == 0) asm volatile("wgmma.mma_async.sync.aligned.m64n48k16.f16.f16.f16 {%0,%1,%2,%3,%4,%5,%6,%7,%8,%9,%10,%11}, {%12,%13,%14,%15}, %16, 0, 1, 1, 1;"
    : "=r"(d[0]),"=r"(d[1]),"=r"(d[2]),"=r"(d[3]),"=r"(d[4]),"=r"(d[5]),"=r"(d[6]),"=r"(d[7]),"=r"(d[8]),"=r"(d[9]),"=r"(d[10]),"=r"(d[11])
    : "r"(a[0]),"r"(a[1]),"r"(a[2]),"r"(a[3]),"l"(desc));
  if (SCALE_D == 1) asm volatile("wgmma.mma_async.sync.aligned.m64n48k16.f16.f16.f16 {%0,%1,%2,%3,%4,%5,%6,%7,%8,%9,%10,%11}, {%12,%13,%14,%15}, %16, 1, 1, 1, 1;"
    : "+r"(d[0]),"+r"(d[1]),"+r"(d[2]),"+r"(d[3]),"+r"(d[4]),"+r"(d[5]),"+r"(d[6]),"+r"(d[7]),"+r"(d[8]),"+r"(d[9]),"+r"(d[10]),"+r"(d[11])
    : "r"(a[0]),"r"(a[1]),"r"(a[2]),"r"(a[3]),"l"(desc));
}

template<int SCALE_D> __device__ __forceinline__ void wgmma_n64_f16(uint32_t* d, const uint32_t* a, uint64_t desc) {
  if (SCALE_D == 0) asm volatile("wgmma.mma_async.sync.aligned.m64n64k16.f16.f16.f16 {%0,%1,%2,%3,%4,%5,%6,%7,%8,%9,%10,%11,%12,%13,%14,%15}, {%16,%17,%18,%19}, %20, 0, 1, 1, 1;"
    : "=r"(d[0]),"=r"(d[1]),"=r"(d[2]),"=r"(d[3]),"=r"(d[4]),"=r"(d[5]),"=r"(d[6]),"=r"(d[7]),"=r"(d[8]),"=r"(d[9]),"=r"(d[10]),"=r"(d[11]),"=r"(d[12]),"=r"(d[13]),"=r"(d[14]),"=r"(d[15])
    : "r"(a[0]),"r"(a[1]),"r"(a[2]),"r"(a[3]),"l"(desc));
  if (SCALE_D == 1) asm volatile("wgmma.mma_async.sync.aligned.m64n64k16.f16.f16.f16 {%0,%1,%2,%3,%4,%5,%6,%7,%8,%9,%10,%11,%12,%13,%14,%15}, {%16,%17,%18,%19}, %20, 1, 1, 1, 1;"
    : "+r"(d[0]),"+r"(d[1]),"+r"(d[2]),"+r"(d[3]),"+r"(d[4]),"+r"(d[5]),"+r"(d[6]),"+r"(d[7]),"+r"(d[8]),"+r"(d[9]),"+r"(d[10]),"+r"(d[11]),"+r"(d[12]),"+r"(d[13]),"+r"(d[14]),"+r"(d[15])
    : "r"(a[0]),"r"(a[1]),"r"(a[2]),"r"(a[3]),"l"(desc));
}

template<int SCALE_D> __device__ __forceinline__ void wgmma_n96_f16(uint32_t* d, const uint32_t* a, uint64_t desc) {
  if (SCALE_D == 0) asm volatile("wgmma.mma_async.sync.aligned.m64n96k16.f16.f16.f16 {%0,%1,%2,%3,%4,%5,%6,%7,%8,%9,%10,%11,%12,%13,%14,%15,%16,%17,%18,%19,%20,%21,%22,%23}, {%24,%25,%26,%27}, %28, 0, 1, 1, 1;"
    : "=r"(d[0]),"=r"(d[1]),"=r"(d[2]),"=r"(d[3]),"=r"(d[4]),"=r"(d[5]),"=r"(d[6]),"=r"(d[7]),"=r"(d[8]),"=r"(d[9]),"=r"(d[10]),"=r"(d[11]),"=r"(d[12]),"=r"(d[13]),"=r"(d[14]),"=r"(d[15]),"=r"(d[16]),"=r"(d[17]),"=r"(d[18]),"=r"(d[19]),"=r"(d[20]),"=r"(d[21]),"=r"(d[22]),"=r"(d[23])
    : "r"(a[0]),"r"(a[1]),"r"(a[2]),"r"(a[3]),"l"(desc));
  if (SCALE_D == 1) asm volatile("wgmma.mma_async.sync.aligned.m64n96k16.f16.f16.f16 {%0,%1,%2,%3,%4,%5,%6,%7,%8,%9,%10,%11,%12,%13,%14,%15,%16,%17,%18,%19,%20,%21,%22,%23}, {%24,%25,%26,%27}, %28, 1, 1, 1, 1;"
    : "+r"(d[0]),"+r"(d[1]),"+r"(d[2]),"+r"(d[3]),"+r"(d[4]),"+r"(d[5]),"+r"(d[6]),"+r"(d[7]),"+r"(d[8]),"+r"(d[9]),"+r"(d[10]),"+r"(d[11]),"+r"(d[12]),"+r"(d[13]),"+r"(d[14]),"+r"(d[15]),"+r"(d[16]),"+r"(d[17]),"+r"(d[18]),"+r"(d[19]),"+r"(d[20]),"+r"(d[21]),"+r"(d[22]),"+r"(d[23])
    : "r"(a[0]),"r"(a[1]),"r"(a[2]),"r"(a[3]),"l"(desc));
}

#define SCHED_NG 10
#define SCHED_LE 103
__device__ const uint16_t g_sched[132][48] = {
{367,3260,389,403,65535,65535,65535,65535,65535,65535,65535,65535,65535,65535,65535,65535,65535,65535,65535,65535,65535,65535,65535,65535,65535,65535,65535,65535,65535,65535,65535,65535,65535,65535,65535,65535,65535,65535,65535,65535,65535,65535,65535,65535,65535,65535,65535,65535},
{0,2483,22,2915,2925,2935,3765,73,83,93,2986,3816,124,134,144,3037,3867,175,185,195,3088,218,3111,3121,3939,259,269,279,3172,3990,310,320,330,3223,4041,361,374,387,400,65535,65535,65535,65535,65535,65535,65535,65535,65535},
{2838,788,802,815,65535,65535,65535,65535,65535,65535,65535,65535,65535,65535,65535,65535,65535,65535,65535,65535,65535,65535,65535,65535,65535,65535,65535,65535,65535,65535,65535,65535,65535,65535,65535,65535,65535,65535,65535,65535,65535,65535,65535,65535,65535,65535,65535,65535},
{412,422,432,442,452,463,473,483,493,503,514,524,534,544,554,565,575,585,595,605,616,628,638,649,659,669,679,689,700,710,720,730,740,751,761,771,784,798,811,65535,65535,65535,65535,65535,65535,65535,65535,65535},
{3646,1199,1213,1226,65535,65535,65535,65535,65535,65535,65535,65535,65535,65535,65535,65535,65535,65535,65535,65535,65535,65535,65535,65535,65535,65535,65535,65535,65535,65535,65535,65535,65535,65535,65535,65535,65535,65535,65535,65535,65535,65535,65535,65535,65535,65535,65535,65535},
{824,834,845,855,865,876,886,896,906,917,927,937,947,957,968,978,988,998,1008,1019,1029,1041,1051,1062,1072,1082,1092,1103,1113,1123,1133,1143,1154,1164,1174,1184,1196,1210,1223,65535,65535,65535,65535,65535,65535,65535,65535,65535},
{1603,1612,1624,1638,65535,65535,65535,65535,65535,65535,65535,65535,65535,65535,65535,65535,65535,65535,65535,65535,65535,65535,65535,65535,65535,65535,65535,65535,65535,65535,65535,65535,65535,65535,65535,65535,65535,65535,65535,65535,65535,65535,65535,65535,65535,65535,65535,65535},
{1236,1247,1257,1267,1278,1288,1298,1308,1318,1329,1339,1349,1359,1369,1380,1390,1400,1410,1420,1431,1441,1453,1464,1474,1484,1494,1504,1515,1525,1535,1545,1555,1566,1576,1586,1596,1609,1622,1636,65535,65535,65535,65535,65535,65535,65535,65535,65535},
{2015,2024,2037,2050,65535,65535,65535,65535,65535,65535,65535,65535,65535,65535,65535,65535,65535,65535,65535,65535,65535,65535,65535,65535,65535,65535,65535,65535,65535,65535,65535,65535,65535,65535,65535,65535,65535,65535,65535,65535,65535,65535,65535,65535,65535,65535,65535,65535},
{1648,1659,1669,1680,1690,1700,1710,1720,1731,1741,1751,1761,1771,1782,1792,1802,1812,1822,1833,1843,1853,1865,1876,1886,1896,1906,1917,1927,1937,1947,1957,1968,1978,1988,1998,2008,2021,2035,2048,65535,65535,65535,65535,65535,65535,65535,65535,65535},
{4058,2436,2449,2462,65535,65535,65535,65535,65535,65535,65535,65535,65535,65535,65535,65535,65535,65535,65535,65535,65535,65535,65535,65535,65535,65535,65535,65535,65535,65535,65535,65535,65535,65535,65535,65535,65535,65535,65535,65535,65535,65535,65535,65535,65535,65535,65535,65535},
{2060,2071,2081,2092,2102,2112,2122,2132,2143,2153,2163,2173,2183,2194,2204,2214,2224,2234,2245,2255,2265,2277,2288,2298,2308,2318,2329,2339,2349,2359,2369,2380,2390,2400,2410,2420,2433,2447,2460,65535,65535,65535,65535,65535,65535,65535,65535,65535},
{2839,3656,2861,2874,65535,65535,65535,65535,65535,65535,65535,65535,65535,65535,65535,65535,65535,65535,65535,65535,65535,65535,65535,65535,65535,65535,65535,65535,65535,65535,65535,65535,65535,65535,65535,65535,65535,65535,65535,65535,65535,65535,65535,65535,65535,65535,65535,65535},
{2472,3303,3313,3323,3333,3343,2534,3364,3374,3384,3394,2585,3415,3425,3435,3445,2636,3466,3476,3486,2677,2690,3507,3517,2720,3538,3548,3558,3568,2771,3589,3599,3609,3619,2822,3640,3654,2859,2872,65535,65535,65535,65535,65535,65535,65535,65535,65535},
{3251,4068,3273,3286,65535,65535,65535,65535,65535,65535,65535,65535,65535,65535,65535,65535,65535,65535,65535,65535,65535,65535,65535,65535,65535,65535,65535,65535,65535,65535,65535,65535,65535,65535,65535,65535,65535,65535,65535,65535,65535,65535,65535,65535,65535,65535,65535,65535},
{2884,2895,2905,3735,3745,3755,2946,2956,2966,2976,3806,2997,3007,3017,3027,3857,3048,3058,3068,3078,3089,3909,3919,3929,3132,3142,3152,3162,3980,3183,3193,3203,3213,4031,3234,3244,4065,3270,4091,65535,65535,65535,65535,65535,65535,65535,65535,65535},
{368,378,390,3682,65535,65535,65535,65535,65535,65535,65535,65535,65535,65535,65535,65535,65535,65535,65535,65535,65535,65535,65535,65535,65535,65535,65535,65535,65535,65535,65535,65535,65535,65535,65535,65535,65535,65535,65535,65535,65535,65535,65535,65535,65535,65535,65535,65535},
{1,3715,3725,33,43,53,63,3776,3786,3796,104,114,3827,3837,3847,155,165,3878,3888,3898,206,219,229,239,249,3950,3960,3970,290,300,4001,4011,4021,341,351,4052,375,4078,401,65535,65535,65535,65535,65535,65535,65535,65535,65535},
{780,789,3669,4094,65535,65535,65535,65535,65535,65535,65535,65535,65535,65535,65535,65535,65535,65535,65535,65535,65535,65535,65535,65535,65535,65535,65535,65535,65535,65535,65535,65535,65535,65535,65535,65535,65535,65535,65535,65535,65535,65535,65535,65535,65535,65535,65535,65535},
{413,423,433,443,453,464,474,484,494,504,515,525,535,545,555,566,576,586,596,606,617,629,639,650,660,670,680,690,701,711,721,731,741,752,762,772,785,799,812,65535,65535,65535,65535,65535,65535,65535,65535,65535},
{1192,1200,1214,1227,65535,65535,65535,65535,65535,65535,65535,65535,65535,65535,65535,65535,65535,65535,65535,65535,65535,65535,65535,65535,65535,65535,65535,65535,65535,65535,65535,65535,65535,65535,65535,65535,65535,65535,65535,65535,65535,65535,65535,65535,65535,65535,65535,65535},
{825,835,846,856,866,877,887,897,907,918,928,938,948,958,969,979,989,999,1009,1020,1030,1042,1052,1063,1073,1083,1093,1104,1114,1124,1134,1144,1155,1165,1175,1185,1197,1211,1224,65535,65535,65535,65535,65535,65535,65535,65535,65535},
{1604,1613,1625,1639,65535,65535,65535,65535,65535,65535,65535,65535,65535,65535,65535,65535,65535,65535,65535,65535,65535,65535,65535,65535,65535,65535,65535,65535,65535,65535,65535,65535,65535,65535,65535,65535,65535,65535,65535,65535,65535,65535,65535,65535,65535,65535,65535,65535},
{1237,1248,1258,1268,1279,1289,1299,1309,1319,1330,1340,1350,1360,1370,1381,1391,1401,1411,1421,1432,1442,1454,1465,1475,1485,1495,1505,1516,1526,1536,1546,1556,1567,1577,1587,1597,1610,1623,1637,65535,65535,65535,65535,65535,65535,65535,65535,65535},
{2016,2025,2038,2051,65535,65535,65535,65535,65535,65535,65535,65535,65535,65535,65535,65535,65535,65535,65535,65535,65535,65535,65535,65535,65535,65535,65535,65535,65535,65535,65535,65535,65535,65535,65535,65535,65535,65535,65535,65535,65535,65535,65535,65535,65535,65535,65535,65535},
{1649,1660,1670,1681,1691,1701,1711,1721,1732,1742,1752,1762,1772,1783,1793,1803,1813,1823,1834,1844,1854,1866,1877,1887,1897,1907,1918,1928,1938,1948,1958,1969,1979,1989,1999,2009,2022,2036,2049,65535,65535,65535,65535,65535,65535,65535,65535,65535},
{2428,2437,2450,2463,65535,65535,65535,65535,65535,65535,65535,65535,65535,65535,65535,65535,65535,65535,65535,65535,65535,65535,65535,65535,65535,65535,65535,65535,65535,65535,65535,65535,65535,65535,65535,65535,65535,65535,65535,65535,65535,65535,65535,65535,65535,65535,65535,65535},
{2061,2072,2082,2093,2103,2113,2123,2133,2144,2154,2164,2174,2184,2195,2205,2215,2225,2235,2246,2256,2266,2278,2289,2299,2309,2319,2330,2340,2350,2360,2370,2381,2391,2401,2411,2421,2434,2448,2461,65535,65535,65535,65535,65535,65535,65535,65535,65535},
{3647,2849,2862,2875,65535,65535,65535,65535,65535,65535,65535,65535,65535,65535,65535,65535,65535,65535,65535,65535,65535,65535,65535,65535,65535,65535,65535,65535,65535,65535,65535,65535,65535,65535,65535,65535,65535,65535,65535,65535,65535,65535,65535,65535,65535,65535,65535,65535},
{2473,2484,2494,2504,3334,3344,2535,2545,2555,2565,3395,2586,2596,2606,2616,3446,2637,2647,2657,2667,2678,3498,3508,3518,2721,2731,2741,2751,3569,2772,2782,2792,2802,3620,2823,2833,2847,3667,3680,65535,65535,65535,65535,65535,65535,65535,65535,65535},
{4059,3261,4081,3287,65535,65535,65535,65535,65535,65535,65535,65535,65535,65535,65535,65535,65535,65535,65535,65535,65535,65535,65535,65535,65535,65535,65535,65535,65535,65535,65535,65535,65535,65535,65535,65535,65535,65535,65535,65535,65535,65535,65535,65535,65535,65535,65535,65535},
{2885,2896,2906,2916,2926,2936,3766,2957,2967,2977,2987,3817,3008,3018,3028,3038,3868,3059,3069,3079,3090,3910,3112,3122,3940,3143,3153,3163,3173,3991,3194,3204,3214,3224,4042,3245,4066,3271,4092,65535,65535,65535,65535,65535,65535,65535,65535,65535},
{369,3657,391,404,65535,65535,65535,65535,65535,65535,65535,65535,65535,65535,65535,65535,65535,65535,65535,65535,65535,65535,65535,65535,65535,65535,65535,65535,65535,65535,65535,65535,65535,65535,65535,65535,65535,65535,65535,65535,65535,65535,65535,65535,65535,65535,65535,65535},
{2,13,23,3324,3746,3756,64,3365,3375,3385,3807,115,3416,3426,3436,3858,166,3467,3477,3487,208,220,3920,3930,250,3539,3549,3559,3981,301,3590,3600,3610,4032,352,3641,376,4079,402,65535,65535,65535,65535,65535,65535,65535,65535,65535},
{781,790,803,816,65535,65535,65535,65535,65535,65535,65535,65535,65535,65535,65535,65535,65535,65535,65535,65535,65535,65535,65535,65535,65535,65535,65535,65535,65535,65535,65535,65535,65535,65535,65535,65535,65535,65535,65535,65535,65535,65535,65535,65535,65535,65535,65535,65535},
{414,424,434,444,454,465,475,485,495,505,516,526,536,546,556,567,577,587,597,607,618,630,640,651,661,671,681,691,702,712,722,732,742,753,763,773,786,800,813,65535,65535,65535,65535,65535,65535,65535,65535,65535},
{1193,1201,1215,1228,65535,65535,65535,65535,65535,65535,65535,65535,65535,65535,65535,65535,65535,65535,65535,65535,65535,65535,65535,65535,65535,65535,65535,65535,65535,65535,65535,65535,65535,65535,65535,65535,65535,65535,65535,65535,65535,65535,65535,65535,65535,65535,65535,65535},
{826,836,847,857,867,878,888,898,908,3797,929,939,949,959,3848,980,990,1000,1010,3899,1031,1043,1053,1064,1074,1084,1094,3971,1115,1125,1135,1145,4022,1166,1176,1186,1198,1212,1225,65535,65535,65535,65535,65535,65535,65535,65535,65535},
{1605,1614,1626,1640,65535,65535,65535,65535,65535,65535,65535,65535,65535,65535,65535,65535,65535,65535,65535,65535,65535,65535,65535,65535,65535,65535,65535,65535,65535,65535,65535,65535,65535,65535,65535,65535,65535,65535,65535,65535,65535,65535,65535,65535,65535,65535,65535,65535},
{1238,1249,1259,1269,1280,1290,1300,1310,1320,1331,1341,1351,1361,1371,1382,1392,1402,1412,1422,1433,1443,1455,1466,1476,1486,1496,1506,1517,1527,1537,1547,1557,1568,1578,1588,1598,1611,1627,1641,65535,65535,65535,65535,65535,65535,65535,65535,65535},
{2017,2026,2039,2052,65535,65535,65535,65535,65535,65535,65535,65535,65535,65535,65535,65535,65535,65535,65535,65535,65535,65535,65535,65535,65535,65535,65535,65535,65535,65535,65535,65535,65535,65535,65535,65535,65535,65535,65535,65535,65535,65535,65535,65535,65535,65535,65535,65535},
{1650,1661,1671,3736,1692,1702,1712,1722,1733,1743,1753,1763,1773,1784,1794,1804,1814,1824,1835,1845,1855,1867,1878,1888,1898,1908,1919,1929,1939,1949,1959,1970,1980,1990,2000,2010,2023,4082,2053,65535,65535,65535,65535,65535,65535,65535,65535,65535},
{2429,2438,2451,2464,65535,65535,65535,65535,65535,65535,65535,65535,65535,65535,65535,65535,65535,65535,65535,65535,65535,65535,65535,65535,65535,65535,65535,65535,65535,65535,65535,65535,65535,65535,65535,65535,65535,65535,65535,65535,65535,65535,65535,65535,65535,65535,65535,65535},
{2062,2073,2083,2094,2104,2114,2124,2134,2145,2155,2165,2175,2185,2196,2206,2216,2226,2236,2247,2257,2267,2279,2290,2300,2310,2320,2331,2341,2351,2361,2371,2382,2392,2402,2412,2422,2435,2452,2465,65535,65535,65535,65535,65535,65535,65535,65535,65535},
{2840,2850,3670,3683,65535,65535,65535,65535,65535,65535,65535,65535,65535,65535,65535,65535,65535,65535,65535,65535,65535,65535,65535,65535,65535,65535,65535,65535,65535,65535,65535,65535,65535,65535,65535,65535,65535,65535,65535,65535,65535,65535,65535,65535,65535,65535,65535,65535},
{2474,3304,3314,2505,2515,2525,3355,2546,2556,2566,2576,3406,2597,2607,2617,2627,3457,2648,2658,2668,2679,2691,2701,2711,3529,2732,2742,2752,2762,3580,2783,2793,2803,2813,3631,2834,3655,2860,2873,65535,65535,65535,65535,65535,65535,65535,65535,65535},
{3252,4069,3274,4095,65535,65535,65535,65535,65535,65535,65535,65535,65535,65535,65535,65535,65535,65535,65535,65535,65535,65535,65535,65535,65535,65535,65535,65535,65535,65535,65535,65535,65535,65535,65535,65535,65535,65535,65535,65535,65535,65535,65535,65535,65535,65535,65535,65535},
{2886,3716,3726,2917,2927,2937,2947,3777,3787,2978,2988,2998,3828,3838,3029,3039,3049,3879,3889,3080,3091,3103,3113,3123,3133,3951,3961,3164,3174,3184,4002,4012,3215,3225,3235,4053,3259,3272,3285,65535,65535,65535,65535,65535,65535,65535,65535,65535},
{3,14,24,35,45,55,2948,3778,3788,96,106,2999,3829,3839,147,157,3050,3880,3890,198,210,2692,231,241,3134,3952,3962,282,292,3185,4003,4013,333,343,3236,4054,379,2863,2876,65535,65535,65535,65535,65535,65535,65535,65535,65535},
{4,3305,3727,34,44,54,65,75,85,95,105,116,126,136,146,156,167,177,187,197,209,221,230,240,251,261,271,281,291,302,312,322,332,342,353,363,377,392,405,65535,65535,65535,65535,65535,65535,65535,65535,65535},
{415,425,435,445,455,466,476,486,496,506,517,527,537,547,557,568,578,588,598,608,619,631,641,652,662,672,682,692,703,713,723,733,743,754,764,774,787,801,814,65535,65535,65535,65535,65535,65535,65535,65535,65535},
{416,426,436,446,456,467,477,487,497,507,518,528,538,548,558,569,579,589,599,609,620,632,642,653,663,673,683,693,704,714,724,734,744,755,765,775,791,804,817,65535,65535,65535,65535,65535,65535,65535,65535,65535},
{827,837,848,858,868,879,889,899,909,919,930,940,950,960,970,981,991,1001,1011,1021,1032,1044,1054,1065,1075,1085,1095,1105,1116,1126,1136,1146,1156,1167,1177,1187,1202,1216,1229,65535,65535,65535,65535,65535,65535,65535,65535,65535},
{828,838,849,859,869,2526,3356,900,910,920,2577,3407,951,961,971,2628,3458,1002,1012,1022,1033,1045,1055,2712,3530,1086,1096,1106,2763,3581,1137,1147,1157,2814,3632,1188,1203,3275,3288,65535,65535,65535,65535,65535,65535,65535,65535,65535},
{1239,1250,1260,1270,1281,1291,1301,1311,1321,1332,1342,1352,1362,1372,1383,1393,1403,1413,1423,1434,1444,1456,1467,1477,1487,1497,1507,1518,1528,1538,1548,1558,1569,1579,1589,1599,1615,1628,3684,65535,65535,65535,65535,65535,65535,65535,65535,65535},
{1240,3717,1261,1271,2516,2938,3768,1312,1322,2567,2989,3819,1363,1373,2618,3040,3870,1414,1424,2669,1445,1457,2702,3124,3942,1498,1508,2753,3175,3993,1549,1559,2804,3226,4044,1600,3262,3671,4096,65535,65535,65535,65535,65535,65535,65535,65535,65535},
{1651,1662,1672,1682,1693,1703,1713,1723,1734,1744,1754,1764,1774,1785,1795,1805,1815,1825,1836,1846,1856,1868,1879,1889,1899,1909,1920,1930,1940,1950,1960,1971,1981,1991,2001,2011,2027,2040,2054,65535,65535,65535,65535,65535,65535,65535,65535,65535},
{1652,1663,1673,1683,2928,3346,1714,1724,2557,2979,3397,1765,1775,2608,3030,3448,1816,1826,2659,3081,1857,1869,3114,3520,1900,1910,2743,3165,3571,1951,1961,2794,3216,3622,2002,2012,3658,4083,2877,65535,65535,65535,65535,65535,65535,65535,65535,65535},
{2063,2074,2084,2095,2105,2115,2125,2135,2146,2156,2166,2176,2186,2197,2207,2217,2227,2237,2248,2258,2268,2280,2291,2301,2311,2321,2332,2342,2352,2362,2372,2383,2393,2403,2413,2423,2439,2453,2466,65535,65535,65535,65535,65535,65535,65535,65535,65535},
{2064,2075,2085,2506,3336,3758,2126,2136,2969,3387,3809,2177,2187,3020,3438,3860,2228,2238,3071,3489,2269,2281,3510,3932,2312,2322,3155,3561,3983,2363,2373,3206,3612,4034,2414,2424,4070,2864,3289,65535,65535,65535,65535,65535,65535,65535,65535,65535},
{2845,2854,2867,2880,65535,65535,65535,65535,65535,65535,65535,65535,65535,65535,65535,65535,65535,65535,65535,65535,65535,65535,65535,65535,65535,65535,65535,65535,65535,65535,65535,65535,65535,65535,65535,65535,65535,65535,65535,65535,65535,65535,65535,65535,65535,65535,65535,65535},
{2475,2485,2495,3325,3335,3345,2536,3366,3376,3386,3396,2587,3417,3427,3437,3447,2638,3468,3478,3488,2680,3499,3509,3519,2722,3540,3550,3560,3570,2773,3591,3601,3611,3621,2824,3642,2848,3668,3681,65535,65535,65535,65535,65535,65535,65535,65535,65535},
{3256,3266,4087,4100,65535,65535,65535,65535,65535,65535,65535,65535,65535,65535,65535,65535,65535,65535,65535,65535,65535,65535,65535,65535,65535,65535,65535,65535,65535,65535,65535,65535,65535,65535,65535,65535,65535,65535,65535,65535,65535,65535,65535,65535,65535,65535,65535,65535},
{2887,2897,2907,3737,3747,3757,3767,2958,2968,3798,3808,3818,3009,3019,3849,3859,3869,3060,3070,3900,3092,3911,3921,3931,3941,3144,3154,3972,3982,3992,3195,3205,4023,4033,4043,3246,4067,4080,4093,65535,65535,65535,65535,65535,65535,65535,65535,65535},
{417,427,437,447,457,468,478,488,498,508,519,529,539,549,559,570,580,590,600,610,621,633,643,654,664,674,684,694,705,715,725,735,745,756,766,776,792,805,818,65535,65535,65535,65535,65535,65535,65535,65535,65535},
{2476,2486,2496,2918,3748,2527,2537,2547,3377,3799,2578,2588,2598,3428,3850,2629,2639,2649,3479,3901,622,3104,3922,2713,2723,2733,3551,3973,2764,2774,2784,3602,4024,2815,2825,2835,2851,3276,3685,65535,65535,65535,65535,65535,65535,65535,65535,65535},
{829,839,2908,3326,870,880,890,2959,3789,921,931,941,3010,3840,972,982,992,3061,3891,1023,1034,3500,1056,1066,1076,3145,3963,1107,1117,1127,3196,4014,1158,1168,1178,3247,1204,1217,1230,65535,65535,65535,65535,65535,65535,65535,65535,65535},
{2888,2898,3316,3738,2517,2939,2949,3367,911,2568,2990,3000,3418,962,2619,3041,3051,3469,1013,2670,2681,3912,2703,3125,3135,3541,1097,2754,3176,3186,3592,1148,2805,3227,3237,3643,3263,3672,4097,65535,65535,65535,65535,65535,65535,65535,65535,65535},
{1241,1251,3728,1272,3749,1293,1303,1313,3378,3800,1344,1354,1364,3429,3851,1395,1405,1415,3480,3902,1447,3501,3923,1479,1489,1499,3552,3974,1530,1540,1550,3603,4025,1581,1591,1601,1617,1630,1643,65535,65535,65535,65535,65535,65535,65535,65535,65535},
{3296,3306,1262,2507,1282,1292,1302,3779,1323,1333,1343,1353,3830,1374,1384,1394,1404,3881,1425,1435,1446,1458,1468,1478,1488,3953,1509,1519,1529,1539,4004,1560,1570,1580,1590,4055,1616,1629,1642,65535,65535,65535,65535,65535,65535,65535,65535,65535},
{1653,3718,1674,1684,1694,1704,1715,1725,1735,1745,1755,1766,1776,1786,1796,1806,1817,1827,1837,1847,1858,1870,1880,1890,1901,1911,1921,1931,1941,1952,1962,1972,1982,1992,2003,2013,2028,2041,2055,65535,65535,65535,65535,65535,65535,65535,65535,65535},
{3708,1664,3317,3739,1695,1705,2538,3368,3790,1746,1756,2589,3419,3841,1797,1807,2640,3470,3892,1848,1859,3913,1881,1891,2724,3542,3964,1932,1942,2775,3593,4015,1983,1993,2826,3644,2029,2042,3686,65535,65535,65535,65535,65535,65535,65535,65535,65535},
{2065,2076,3729,2097,2107,2117,2950,3780,2148,2158,2168,3001,3831,2199,2209,2219,3052,3882,2250,2260,2271,2283,2293,2303,3136,3954,2334,2344,2354,3187,4005,2385,2395,2405,3238,4056,2441,3277,4098,65535,65535,65535,65535,65535,65535,65535,65535,65535},
{2066,2487,2086,2096,2106,2116,2127,2137,2147,2157,2167,2178,2188,2198,2208,2218,2229,2239,2249,2259,2270,2282,2292,2302,2313,2323,2333,2343,2353,2364,2374,2384,2394,2404,2415,2425,2440,2454,2467,65535,65535,65535,65535,65535,65535,65535,65535,65535},
{3653,3662,3675,3688,65535,65535,65535,65535,65535,65535,65535,65535,65535,65535,65535,65535,65535,65535,65535,65535,65535,65535,65535,65535,65535,65535,65535,65535,65535,65535,65535,65535,65535,65535,65535,65535,65535,65535,65535,65535,65535,65535,65535,65535,65535,65535,65535,65535},
{2477,3307,2497,3327,3337,3347,3357,2548,2558,3388,3398,3408,2599,2609,3439,3449,3459,2650,2660,3490,2682,2693,3511,3521,3531,2734,2744,3562,3572,3582,2785,2795,3613,3623,3633,2836,3659,2865,2878,65535,65535,65535,65535,65535,65535,65535,65535,65535},
{4064,4074,3280,3293,65535,65535,65535,65535,65535,65535,65535,65535,65535,65535,65535,65535,65535,65535,65535,65535,65535,65535,65535,65535,65535,65535,65535,65535,65535,65535,65535,65535,65535,65535,65535,65535,65535,65535,65535,65535,65535,65535,65535,65535,65535,65535,65535,65535},
{2889,2899,2909,2919,2929,3759,3769,2960,2970,2980,3810,3820,3011,3021,3031,3861,3871,3062,3072,3082,3093,3105,3115,3933,3943,3146,3156,3166,3984,3994,3197,3207,3217,4035,4045,3248,4071,4084,3290,65535,65535,65535,65535,65535,65535,65535,65535,65535},
{418,428,439,449,459,2528,3358,490,500,510,2579,3409,541,551,561,2630,3460,592,602,612,3094,635,645,2714,3532,676,686,696,2765,3583,727,737,747,2816,3634,778,2852,3673,820,65535,65535,65535,65535,65535,65535,65535,65535,65535},
{3297,3719,438,448,458,469,479,489,499,509,520,530,540,550,560,571,581,591,601,611,623,634,644,655,665,675,685,695,706,716,726,736,746,757,767,777,793,806,819,65535,65535,65535,65535,65535,65535,65535,65535,65535},
{830,840,850,860,871,881,891,901,912,922,932,942,952,963,973,983,993,1003,1014,1024,1035,1046,1057,1067,1077,1087,1098,1108,1118,1128,1138,1149,1159,1169,1179,1189,1205,1218,1231,65535,65535,65535,65535,65535,65535,65535,65535,65535},
{3709,841,851,861,2518,2940,3770,902,2559,2569,2991,3821,953,2610,2620,3042,3872,1004,2661,2671,1036,1047,2704,3126,3944,1088,2745,2755,3177,3995,1139,2796,2806,3228,4046,1190,3264,4085,1232,65535,65535,65535,65535,65535,65535,65535,65535,65535},
{1242,1252,1263,1273,1283,3348,1304,1314,1324,1334,3399,1355,1365,1375,1385,3450,1406,1416,1426,1436,1448,1459,1469,3522,1490,1500,1510,1520,3573,1541,1551,1561,1571,3624,1592,1602,3660,1631,1644,65535,65535,65535,65535,65535,65535,65535,65535,65535},
{1243,1253,2498,2508,2930,3760,2539,2549,2971,2981,3811,2590,2600,3022,3032,3862,2641,2651,3073,3083,2683,2694,3116,3934,2725,2735,3157,3167,3985,2776,2786,3208,3218,4036,2827,2837,4072,2866,2879,65535,65535,65535,65535,65535,65535,65535,65535,65535},
{1654,1665,1675,1685,3338,1706,1716,1726,1736,3389,1757,1767,1777,1787,3440,1808,1818,1828,1838,3491,1860,1871,3512,1892,1902,1912,1922,3563,1943,1953,1963,1973,3614,1994,2004,2014,2030,2043,2056,65535,65535,65535,65535,65535,65535,65535,65535,65535},
{1655,2488,2910,2920,3750,2529,2951,2961,3379,3801,2580,3002,3012,3430,3852,2631,3053,3063,3481,3903,3095,3106,3924,2715,3137,3147,3553,3975,2766,3188,3198,3604,4026,2817,3239,3249,2853,3278,3291,65535,65535,65535,65535,65535,65535,65535,65535,65535},
{2067,2077,2087,3328,2108,2119,2129,2139,2149,3390,2170,2180,2190,2200,3441,2221,2231,2241,2251,3492,2273,2284,3513,2305,2315,2325,2335,3564,2356,2366,2376,2386,3615,2407,2417,2427,2443,2456,2469,65535,65535,65535,65535,65535,65535,65535,65535,65535},
{2478,2900,3318,3740,2519,2118,2128,2138,3791,2159,2169,2179,2189,3842,2210,2220,2230,2240,3893,2261,2272,3502,2294,2304,2314,2324,3965,2345,2355,2365,2375,4016,2396,2406,2416,2426,2442,2455,2468,65535,65535,65535,65535,65535,65535,65535,65535,65535},
{2846,2855,2868,2881,65535,65535,65535,65535,65535,65535,65535,65535,65535,65535,65535,65535,65535,65535,65535,65535,65535,65535,65535,65535,65535,65535,65535,65535,65535,65535,65535,65535,65535,65535,65535,65535,65535,65535,65535,65535,65535,65535,65535,65535,65535,65535,65535,65535},
{3298,3308,2499,2509,3339,3349,3359,3369,2560,2570,3400,3410,3420,2611,2621,3451,3461,3471,2662,2672,2684,2695,2705,3523,3533,3543,2746,2756,3574,3584,3594,2797,2807,3625,3635,3645,3661,3674,3687,65535,65535,65535,65535,65535,65535,65535,65535,65535},
{3257,3267,4088,4101,65535,65535,65535,65535,65535,65535,65535,65535,65535,65535,65535,65535,65535,65535,65535,65535,65535,65535,65535,65535,65535,65535,65535,65535,65535,65535,65535,65535,65535,65535,65535,65535,65535,65535,65535,65535,65535,65535,65535,65535,65535,65535,65535,65535},
{2890,3720,3730,2921,2931,2941,3771,3781,2972,2982,2992,3822,3832,3023,3033,3043,3873,3883,3074,3084,3096,3914,3117,3127,3945,3955,3158,3168,3178,3996,4006,3209,3219,3229,4047,4057,3265,4086,4099,65535,65535,65535,65535,65535,65535,65535,65535,65535},
{419,429,440,3329,461,471,481,2550,3380,512,522,532,2601,3431,563,573,583,2652,3482,614,625,3503,647,657,667,2736,3554,698,708,718,2787,3605,749,759,769,3648,795,808,822,65535,65535,65535,65535,65535,65535,65535,65535,65535},
{3710,430,2911,450,460,470,480,491,501,511,521,531,542,552,562,572,582,593,603,613,624,636,646,656,666,677,687,697,707,717,728,738,748,758,768,779,794,807,821,65535,65535,65535,65535,65535,65535,65535,65535,65535},
{831,842,852,863,873,883,893,3370,914,924,934,944,3421,965,975,985,995,3472,1016,1026,1038,3915,1059,1069,1079,3544,1100,1110,1120,1130,3595,1151,1161,1171,1181,4060,1207,1220,1234,65535,65535,65535,65535,65535,65535,65535,65535,65535},
{832,2489,3319,862,872,882,892,903,913,923,933,943,954,964,974,984,994,1005,1015,1025,1037,1048,1058,1068,1078,1089,1099,1109,1119,1129,1140,1150,1160,1170,1180,1191,1206,1219,1233,65535,65535,65535,65535,65535,65535,65535,65535,65535},
{1244,3309,1265,1274,1284,1294,1305,1315,1325,1335,1345,1356,1366,1376,1386,1396,1407,1417,1427,1437,1449,1460,1470,1480,1491,1501,1511,1521,1531,1542,1552,1562,1572,1582,1593,1606,1618,1632,1645,65535,65535,65535,65535,65535,65535,65535,65535,65535},
{2479,1254,1264,1275,1285,1295,2540,3782,1326,1336,1346,2591,3833,1377,1387,1397,2642,3884,1428,1438,1450,1461,1471,1481,2726,3956,1512,1522,1532,2777,4007,1563,1573,1583,2828,2841,1619,1633,1646,65535,65535,65535,65535,65535,65535,65535,65535,65535},
{1656,3721,1677,1686,1696,1707,1717,1727,1737,1747,1758,1768,1778,1788,1798,1809,1819,1829,1839,1849,1861,1872,1882,1893,1903,1913,1923,1933,1944,1954,1964,1974,1984,1995,2005,2018,2031,2044,2057,65535,65535,65535,65535,65535,65535,65535,65535,65535},
{2891,1666,1676,1687,1697,2530,3360,1728,1738,1748,2581,3411,1779,1789,1799,2632,3462,1830,1840,1850,1862,1873,1883,2716,3534,1914,1924,1934,2767,3585,1965,1975,1985,2818,3636,3253,2032,2045,2058,65535,65535,65535,65535,65535,65535,65535,65535,65535},
{2068,2079,2089,2098,2109,2942,3772,2140,2150,2160,2993,3823,2191,2201,2211,3044,3874,2242,2252,2262,2274,2285,2295,3128,3946,2326,2336,2346,3179,3997,2377,2387,2397,3230,4048,2430,2444,2457,2470,65535,65535,65535,65535,65535,65535,65535,65535,65535},
{3299,2078,2088,2099,2520,3350,2130,2551,2561,2571,3401,2181,2602,2612,2622,3452,2232,2653,2663,2673,2685,2696,2706,3524,2316,2737,2747,2757,3575,2367,2788,2798,2808,3626,2418,3649,3663,3676,3689,65535,65535,65535,65535,65535,65535,65535,65535,65535},
{2480,2490,2500,2510,3340,2531,2541,3371,3381,3391,2582,2592,3422,3432,3442,2633,2643,3473,3483,3493,2686,3504,3514,2717,2727,3545,3555,3565,2768,2778,3596,3606,3616,2819,2829,2842,2856,2869,2882,65535,65535,65535,65535,65535,65535,65535,65535,65535},
{3300,3310,3320,3330,2521,3351,3361,2552,2562,2572,3402,3412,2603,2613,2623,3453,3463,2654,2664,2674,2687,2697,2707,3525,3535,2738,2748,2758,3576,3586,2789,2799,2809,3627,3637,3650,3664,3677,3690,65535,65535,65535,65535,65535,65535,65535,65535,65535},
{3711,2901,3731,3741,3751,3761,2952,2962,3792,3802,3812,3003,3013,3843,3853,3863,3054,3064,3894,3904,3097,3107,3925,3935,3138,3148,3966,3976,3986,3189,3199,4017,4027,4037,3240,3250,4073,3279,3292,65535,65535,65535,65535,65535,65535,65535,65535,65535},
{2892,2902,2912,2922,2932,3762,2953,2963,2973,2983,3813,3004,3014,3024,3034,3864,3055,3065,3075,3085,3098,3108,3118,3936,3139,3149,3159,3169,3987,3190,3200,3210,3220,4038,3241,4061,4075,3281,3294,65535,65535,65535,65535,65535,65535,65535,65535,65535},
{420,431,441,451,3752,472,482,492,502,3803,523,533,543,553,3854,574,584,594,604,3905,626,637,3926,658,668,678,688,3977,709,719,729,739,4028,760,770,782,796,809,823,65535,65535,65535,65535,65535,65535,65535,65535,65535},
{421,3722,3732,3742,462,2943,3773,3783,3793,513,2994,3824,3834,3844,564,3045,3875,3885,3895,615,627,3916,648,3129,3947,3957,3967,699,3180,3998,4008,4018,750,3231,4049,783,797,810,4102,65535,65535,65535,65535,65535,65535,65535,65535,65535},
{833,843,853,864,874,884,894,904,915,925,935,945,955,966,976,986,996,1006,1017,1027,1039,1049,1060,1070,1080,1090,1101,1111,1121,1131,1141,1152,1162,1172,1182,1194,1208,1221,1235,65535,65535,65535,65535,65535,65535,65535,65535,65535},
{3712,844,854,3331,875,885,895,905,916,926,936,946,956,967,977,987,997,1007,1018,1028,1040,1050,1061,1071,1081,1091,1102,1112,1122,1132,1142,1153,1163,1173,1183,1195,1209,1222,3691,65535,65535,65535,65535,65535,65535,65535,65535,65535},
{1245,1255,1266,1276,1286,1296,1306,1316,1327,1337,1347,1357,1367,1378,1388,1398,1408,1418,1429,1439,1451,1462,1472,1482,1492,1502,1513,1523,1533,1543,1553,1564,1574,1584,1594,1607,1620,1634,1647,65535,65535,65535,65535,65535,65535,65535,65535,65535},
{1246,1256,3321,1277,1287,1297,1307,1317,1328,1338,1348,1358,1368,1379,1389,1399,1409,1419,1430,1440,1452,1463,1473,1483,1493,1503,1514,1524,1534,1544,1554,1565,1575,1585,1595,1608,1621,1635,3692,65535,65535,65535,65535,65535,65535,65535,65535,65535},
{1657,1667,1678,1688,1698,1708,1718,1729,1739,1749,1759,1769,1780,1790,1800,1810,1820,1831,1841,1851,1863,1874,1884,1894,1904,1915,1925,1935,1945,1955,1966,1976,1986,1996,2006,2019,2033,2046,2059,65535,65535,65535,65535,65535,65535,65535,65535,65535},
{1658,1668,1679,1689,1699,1709,1719,1730,1740,1750,1760,1770,1781,1791,1801,1811,1821,1832,1842,1852,1864,1875,1885,1895,1905,1916,1926,1936,1946,1956,1967,1977,1987,1997,2007,2020,2034,2047,4104,65535,65535,65535,65535,65535,65535,65535,65535,65535},
{2069,2080,2091,2101,2111,2121,3362,2142,2152,2162,2172,3413,2193,2203,2213,2223,3464,2244,2254,2264,2276,2287,2297,2307,3536,2328,2338,2348,2358,3587,2379,2389,2399,2409,3638,2432,2446,2459,3693,65535,65535,65535,65535,65535,65535,65535,65535,65535},
{2070,2491,2090,2100,2110,2120,2131,2141,2151,2161,2171,2182,2192,2202,2212,2222,2233,2243,2253,2263,2275,2286,2296,2306,2317,2327,2337,2347,2357,2368,2378,2388,2398,2408,2419,2431,2445,2458,2471,65535,65535,65535,65535,65535,65535,65535,65535,65535},
{2481,3311,2501,2511,3341,2532,2542,3372,3382,3392,2583,2593,3423,3433,3443,2634,2644,3474,3484,3494,2688,3505,3515,2718,2728,3546,3556,3566,2769,2779,3597,3607,3617,2820,2830,2843,2857,2870,2883,65535,65535,65535,65535,65535,65535,65535,65535,65535},
{3301,2492,2502,2512,2522,3352,2543,2553,2563,2573,3403,2594,2604,2614,2624,3454,2645,2655,2665,2675,3496,2698,2708,3526,2729,2739,2749,2759,3577,2780,2790,2800,2810,3628,2831,3651,3665,3678,3694,65535,65535,65535,65535,65535,65535,65535,65535,65535},
{2893,2903,2913,2923,2933,3763,2954,2964,2974,2984,3814,3005,3015,3025,3035,3865,3056,3066,3076,3086,3099,3109,3119,3937,3140,3150,3160,3170,3988,3191,3201,3211,3221,4039,3242,3254,3268,4089,3295,65535,65535,65535,65535,65535,65535,65535,65535,65535},
{3713,3723,3733,3743,3753,2944,3774,3784,3794,3804,2995,3825,3835,3845,3855,3046,3876,3886,3896,3906,3100,3917,3927,3130,3948,3958,3968,3978,3181,3999,4009,4019,4029,3232,4050,4062,4076,3282,4103,65535,65535,65535,65535,65535,65535,65535,65535,65535},
{2482,3312,3322,3332,3342,2533,3363,3373,3383,3393,2584,3414,3424,3434,3444,2635,3465,3475,3485,3495,2689,3506,3516,2719,3537,3547,3557,3567,2770,3588,3598,3608,3618,2821,3639,2844,2858,2871,4105,65535,65535,65535,65535,65535,65535,65535,65535,65535},
{3302,2493,2503,2513,2523,3353,2544,2554,2564,2574,3404,2595,2605,2615,2625,3455,2646,2656,2666,2676,3497,2699,2709,3527,2730,2740,2750,2760,3578,2781,2791,2801,2811,3629,2832,3652,3666,3679,3695,65535,65535,65535,65535,65535,65535,65535,65535,65535},
{2894,2904,2914,2924,2934,3764,2955,2965,2975,2985,3815,3006,3016,3026,3036,3866,3057,3067,3077,3087,3908,3110,3120,3938,3141,3151,3161,3171,3989,3192,3202,3212,3222,4040,3243,3255,3269,4090,4106,65535,65535,65535,65535,65535,65535,65535,65535,65535},
{3714,3724,3734,3744,3754,2945,3775,3785,3795,3805,2996,3826,3836,3846,3856,3047,3877,3887,3897,3907,3101,3918,3928,3131,3949,3959,3969,3979,3182,4000,4010,4020,4030,3233,4051,4063,4077,3283,4107,65535,65535,65535,65535,65535,65535,65535,65535,65535},
{5,15,25,36,46,56,66,76,86,97,107,117,127,137,148,158,168,178,188,199,211,222,232,242,252,262,272,283,293,303,313,323,334,344,354,364,380,393,406,65535,65535,65535,65535,65535,65535,65535,65535,65535},
{6,16,26,37,47,57,67,77,87,98,108,118,128,138,149,159,169,179,189,200,212,223,233,243,253,263,273,284,294,304,314,324,335,345,355,365,381,394,407,65535,65535,65535,65535,65535,65535,65535,65535,65535},
{7,17,27,38,48,58,68,78,88,99,109,119,129,139,150,160,170,180,190,201,213,224,234,244,254,264,274,285,295,305,315,325,336,346,356,366,382,395,408,65535,65535,65535,65535,65535,65535,65535,65535,65535},
{8,18,28,39,49,59,69,79,89,100,110,120,130,140,151,161,171,181,191,202,214,225,235,245,255,265,275,286,296,306,316,326,337,347,357,370,383,396,409,65535,65535,65535,65535,65535,65535,65535,65535,65535},
{9,19,29,40,50,60,70,80,90,101,111,121,131,141,152,162,172,182,192,203,215,226,236,246,256,266,276,287,297,307,317,327,338,348,358,371,384,397,410,65535,65535,65535,65535,65535,65535,65535,65535,65535},
{10,20,30,41,51,61,71,81,91,102,112,122,132,142,153,163,173,183,193,204,216,227,237,247,257,267,277,288,298,308,318,328,339,349,359,372,385,398,411,65535,65535,65535,65535,65535,65535,65535,65535,65535},
{11,21,31,42,52,62,72,82,92,103,113,123,133,143,154,164,174,184,194,205,217,228,238,248,258,268,278,289,299,309,319,329,340,350,360,373,386,399,65535,65535,65535,65535,65535,65535,65535,65535,65535,65535},
{12,3315,32,2514,2524,3354,74,84,94,2575,3405,125,135,145,2626,3456,176,186,196,207,3102,2700,2710,3528,260,270,280,2761,3579,311,321,331,2812,3630,362,3258,388,3284,65535,65535,65535,65535,65535,65535,65535,65535,65535,65535},
};

#define NG SCHED_NG
#define RING 16
#define NSLOT 8
#define CFETCH 5
#define TABLED 1
#define PROMO CU_TENSOR_MAP_L2_PROMOTION_L2_128B
#define AHEAD 6
#define CF0 5
#define CFS 2
#define ABL 0
#define CX 5
#define PUBN 2
#define PUBE 8
#define SCHED 9
#define OUT_TMA 0
#define JB1 21
#define JB2 24
#define CVAR 2
#define CFN 0
#define CREGS 224
#define CSLEEP 200
#define JB 20
#define JF 24
#define JR 17
#define HOIST 1
#define XEARLY 0
#define FPRED 1
#define LATERED 1
#define WDELAY 0
#define WDELAY2 0
#define PFX 0
#define FIRST 3
#define NODUMP 1
#define CH 64
#define NOJB 3
#define JFF 0
#define XPRED 0
#define TRIG0 -1
#define NEARLY 3
#define NLATE 0
#define TRIG 8
constexpr int NCONV = 3 * NG;
constexpr int PLEN = SCHED_LE, LM = 256 - 2 * PLEN, NSEG = 4 / (NG - 8), LMID = NSEG * LM;
static_assert(LMID <= PLEN && (NG == 9 || NG == 10), "geometry");
constexpr int TILEB = 12288;
constexpr int SLOTB = 280 * 64;
constexpr int W1S = 0, W2S = 73728, ABUF = 147456, XBUF = ABUF + 16 * 3072, MISC = XBUF + 8 * 3072;
constexpr int WBAR = MISC + 2560;
constexpr int RBUF = ABUF - 4 * SLOTB;
constexpr int CM = MISC + 2816, CTAB = CM + 256;
constexpr int SMEM_BYTES = CTAB + (PLEN + 16) * 16;
static_assert(RBUF % 512 == 0 && RBUF >= W2S && RBUF + NSLOT * SLOTB + 128 <= MISC && SMEM_BYTES <= 232448, "smem layout");

struct Globals {
  unsigned char scratch[(RING * NG + 1) * 4 * TILEB];
  unsigned char wimg[147456];
  uint32_t wflag[32];
  uint32_t ready[NG * PLEN + 1];
  uint32_t cons[NG * PLEN];
  uint32_t epoch[1024];
};
__device__ __align__(1024) Globals g_state;

#define PROF_AT(cond, idx)
#define PROF_VAL(cond, idx, v)
#define PROF2_AT(c, i)
#define PROF2_VAL(c, i, v)
#define PROFS(i)
#define GELU_C3 0.32920349f
#define GELU_A2 0x40d940d9u
#define SCHED_FENCE() asm volatile("pmevent 0;" ::: "memory")
#define SPIN_LIMIT 0x1000000

__device__ __forceinline__ uint32_t smem_u32(const void* p) { return (uint32_t)__cvta_generic_to_shared(p); }
__device__ __forceinline__ void wg_fence() { asm volatile("wgmma.fence.sync.aligned;" ::: "memory"); }
__device__ __forceinline__ void wg_commit() { asm volatile("wgmma.commit_group.sync.aligned;" ::: "memory"); }
template <int N> __device__ __forceinline__ void wg_wait() { asm volatile("wgmma.wait_group.sync.aligned %0;" ::"n"(N) : "memory"); }
__device__ __forceinline__ void mbar_init(uint32_t bar, uint32_t cnt) { asm volatile("mbarrier.init.shared::cta.b64 [%0], %1;" ::"r"(bar), "r"(cnt) : "memory"); }
__device__ __forceinline__ void mbar_expect_tx(uint32_t bar, uint32_t bytes) { asm volatile("mbarrier.arrive.expect_tx.shared::cta.b64 _, [%0], %1;" ::"r"(bar), "r"(bytes) : "memory"); }
__device__ __forceinline__ void mbar_arrive(uint32_t bar) { asm volatile("mbarrier.arrive.shared::cta.b64 _, [%0];" ::"r"(bar) : "memory"); }
__device__ __forceinline__ void mbar_wait(uint32_t bar, uint32_t parity) {
  asm volatile("{\n.reg .pred p;\n.reg .u32 c;\nmbarrier.try_wait.parity.shared::cta.b64 p, [%0], %1;\n@p bra DONE_%=;\nmov.u32 c, 0;\nWAIT_%=:\nmbarrier.try_wait.parity.shared::cta.b64 p, [%0], %1;\n@p bra DONE_%=;\n"
               "add.u32 c, c, 1;\nsetp.lt.u32 p, c, 0x1000000;\n@p bra WAIT_%=;\ntrap;\nDONE_%=:\n}" ::"r"(bar), "r"(parity) : "memory");
}
__device__ __forceinline__ void bulk_g2s(uint32_t dst, const void* src, uint32_t bytes, uint32_t bar) {
  asm volatile("cp.async.bulk.shared::cluster.global.mbarrier::complete_tx::bytes [%0], [%1], %2, [%3];" ::"r"(dst), "l"(src), "r"(bytes), "r"(bar) : "memory");
}
__device__ __forceinline__ uint32_t ld_relaxed(const uint32_t* p) { uint32_t v; asm volatile("ld.relaxed.gpu.global.u32 %0, [%1];" : "=r"(v) : "l"(p) : "memory"); return v; }
__device__ __forceinline__ void red_add_elect(uint32_t* p) { asm volatile("{.reg .pred p; elect.sync _|p, 0xffffffff; @p red.relaxed.gpu.global.add.u32 [%0], 1;}" ::"l"(p) : "memory"); }
__device__ __forceinline__ void mbar_arrive_elect(uint32_t bar) { asm volatile("{.reg .pred p; elect.sync _|p, 0xffffffff; @p mbarrier.arrive.shared::cta.b64 _, [%0];}" ::"r"(bar) : "memory"); }
__device__ __forceinline__ void mbar_init_elect(uint32_t bar, uint32_t cnt) { asm volatile("{.reg .pred p; elect.sync _|p, 0xffffffff; @p mbarrier.init.shared::cta.b64 [%0], %1;}" ::"r"(bar), "r"(cnt) : "memory"); }
__device__ __forceinline__ void lds128(uint32_t* r, uint32_t a) { asm volatile("ld.shared.v4.b32 {%0,%1,%2,%3}, [%4];" : "=r"(r[0]), "=r"(r[1]), "=r"(r[2]), "=r"(r[3]) : "r"(a) : "memory"); }
__device__ __forceinline__ uint2 lds64(uint32_t a) { uint2 v; asm volatile("ld.shared.v2.b32 {%0,%1}, [%2];" : "=r"(v.x), "=r"(v.y) : "r"(a) : "memory"); return v; }
__device__ __forceinline__ uint32_t lds32(uint32_t a) { uint32_t v; asm volatile("ld.shared.b32 %0, [%1];" : "=r"(v) : "r"(a) : "memory"); return v; }
__device__ __forceinline__ void sts32(uint32_t a, uint32_t v) { asm volatile("st.shared.b32 [%0], %1;" ::"r"(a), "r"(v) : "memory"); }
__device__ __forceinline__ void sts128(uint32_t a, uint4 v) { asm volatile("st.shared.v4.b32 [%0], {%1,%2,%3,%4};" ::"r"(a), "r"(v.x), "r"(v.y), "r"(v.z), "r"(v.w) : "memory"); }
__device__ __forceinline__ uint4 ldg128v(const void* p) { uint4 v; asm volatile("ld.global.nc.v4.b32 {%0,%1,%2,%3}, [%4];" : "=r"(v.x), "=r"(v.y), "=r"(v.z), "=r"(v.w) : "l"(p) : "memory"); return v; }
__device__ __forceinline__ void stg128(void* p, uint4 v) { asm volatile("st.global.v4.b32 [%0], {%1,%2,%3,%4};" ::"l"(p), "r"(v.x), "r"(v.y), "r"(v.z), "r"(v.w) : "memory"); }
#define HINT 3
__device__ __forceinline__ uint64_t pol_evict_first() { uint64_t p; asm("createpolicy.fractional.L2::evict_first.b64 %0, 1.0;" : "=l"(p)); return p; }
__device__ __forceinline__ uint4 ldg128_last(const void* p, uint64_t pol) {
  if (!(HINT & 1)) return ldg128v(p);
  uint4 v; asm volatile("ld.global.nc.L1::no_allocate.L2::cache_hint.v4.b32 {%0,%1,%2,%3}, [%4], %5;" : "=r"(v.x), "=r"(v.y), "=r"(v.z), "=r"(v.w) : "l"(p), "l"(pol) : "memory"); return v;
}
__device__ __forceinline__ void stg128_stream(void* p, uint4 v, uint64_t pol) {
  if (!(HINT & 2)) { stg128(p, v); return; }
  asm volatile("st.global.L2::cache_hint.v4.b32 [%0], {%1,%2,%3,%4}, %5;" ::"l"(p), "r"(v.x), "r"(v.y), "r"(v.z), "r"(v.w), "l"(pol) : "memory");
}
__device__ __forceinline__ float bf_lo(uint32_t w) { return __uint_as_float(w << 16); }
__device__ __forceinline__ float bf_hi(uint32_t w) { return __uint_as_float(w & 0xffff0000u); }
__device__ __forceinline__ uint32_t pack_f16(float lo, float hi) { uint32_t d; asm("cvt.rn.f16x2.f32 %0, %1, %2;" : "=r"(d) : "f"(hi), "f"(lo)); return d; }
__device__ __forceinline__ uint32_t pack_f16_sat(float lo, float hi) { uint32_t d; asm("cvt.rn.satfinite.f16x2.f32 %0, %1, %2;" : "=r"(d) : "f"(hi), "f"(lo)); return d; }
__device__ __forceinline__ uint32_t pack_bf16(float lo, float hi) { uint32_t d; asm("cvt.rn.bf16x2.f32 %0, %1, %2;" : "=r"(d) : "f"(hi), "f"(lo)); return d; }
__device__ __forceinline__ uint32_t hadd2_bf16(uint32_t a, uint32_t b) { uint32_t d; asm("add.rn.bf16x2 %0, %1, %2;" : "=r"(d) : "r"(a), "r"(b)); return d; }
__device__ __forceinline__ uint32_t h2add(uint32_t a, uint32_t b) { uint32_t d; asm("add.rn.f16x2 %0, %1, %2;" : "=r"(d) : "r"(a), "r"(b)); return d; }
__device__ __forceinline__ uint32_t h2mul(uint32_t a, uint32_t b) { uint32_t d; asm("mul.rn.f16x2 %0, %1, %2;" : "=r"(d) : "r"(a), "r"(b)); return d; }
__device__ __forceinline__ uint32_t h2fma(uint32_t a, uint32_t b, uint32_t c) { uint32_t d; asm("fma.rn.f16x2 %0, %1, %2, %3;" : "=r"(d) : "r"(a), "r"(b), "r"(c)); return d; }
__device__ __forceinline__ uint32_t h2lo(uint32_t a) { uint32_t d; asm("{.reg .f16 l,h; mov.b32 {l,h}, %1; mov.b32 %0, {l,l};}" : "=r"(d) : "r"(a)); return d; }
__device__ __forceinline__ uint32_t h2hi(uint32_t a) { uint32_t d; asm("{.reg .f16 l,h; mov.b32 {l,h}, %1; mov.b32 %0, {h,h};}" : "=r"(d) : "r"(a)); return d; }
__device__ __forceinline__ float h_lo(uint32_t a) { float d; asm("{.reg .f16 l,h; mov.b32 {l,h}, %1; cvt.f32.f16 %0, l;}" : "=f"(d) : "r"(a)); return d; }
__device__ __forceinline__ float h_hi(uint32_t a) { float d; asm("{.reg .f16 l,h; mov.b32 {l,h}, %1; cvt.f32.f16 %0, h;}" : "=f"(d) : "r"(a)); return d; }
__device__ __forceinline__ uint32_t prmt(uint32_t a, uint32_t b, uint32_t s) { uint32_t d; asm("prmt.b32 %0, %1, %2, %3;" : "=r"(d) : "r"(a), "r"(b), "r"(s)); return d; }
__device__ __forceinline__ void mma_sp(float* d, const uint32_t* a, const uint32_t* b, const float* c, uint32_t e) {
  asm("mma.sp::ordered_metadata.sync.aligned.m16n8k32.row.col.f32.bf16.bf16.f32 {%0,%1,%2,%3}, {%4,%5,%6,%7}, {%8,%9,%10,%11}, {%12,%13,%14,%15}, %16, 0;"
      : "=f"(d[0]), "=f"(d[1]), "=f"(d[2]), "=f"(d[3])
      : "r"(a[0]), "r"(a[1]), "r"(a[2]), "r"(a[3]), "r"(b[0]), "r"(b[1]), "r"(b[2]), "r"(b[3]), "f"(c[0]), "f"(c[1]), "f"(c[2]), "f"(c[3]), "r"(e));
}
__device__ __forceinline__ uint32_t bf2_to_h2(uint32_t w, float s) { return pack_f16(bf_lo(w) * s, bf_hi(w) * s); }
__device__ __forceinline__ uint32_t bf2_to_h2(uint32_t w) { return pack_f16(bf_lo(w), bf_hi(w)); }

__device__ __forceinline__ uint32_t gelu_h2(uint32_t y) {
  uint32_t t, u, th, g;
  asm volatile("fma.rn.f16x2 %0, %1, %1, %2;" : "=r"(t) : "r"(y), "r"(GELU_A2));
  asm volatile("mul.rn.f16x2 %0, %1, %2;" : "=r"(u) : "r"(y), "r"(t));
  asm volatile("tanh.approx.f16x2 %0, %1;" : "=r"(th) : "r"(u));
  asm volatile("fma.rn.f16x2 %0, %1, %2, %1;" : "=r"(g) : "r"(y), "r"(th));
  return g;
}

__device__ __forceinline__ void copy_weights(uint32_t sb, int piece, const void* src) {
  asm volatile("{\n.reg .pred p;\nelect.sync _|p, 0xffffffff;\n@p mbarrier.init.shared::cta.b64 [%1], 1;\n@p fence.mbarrier_init.release.cluster;\n"
               "@p mbarrier.arrive.expect_tx.shared::cta.b64 _, [%1], 12288;\n"
               "@p cp.async.bulk.shared::cluster.global.mbarrier::complete_tx::bytes [%0], [%2], 12288, [%1];\n}"
               ::"r"(sb + piece * 12288), "r"(sb + WBAR + piece * 8), "l"(src) : "memory");
}
__device__ __forceinline__ void convert_weights(uint32_t sb, uint32_t wbar, int rot, int warp, int lane) {
  if (warp < 12) {
    const int l8 = lane & 7, q4 = lane >> 3;
    int s = (warp >> 1) + rot; if (s >= 6) s -= 6;
    const uint32_t base = sb + W1S + s * 12288 + (warp & 1) * 384;
    mbar_wait(wbar + s * 8, 0);
    uint32_t v[3][4][4];
#pragma unroll
    for (int r = 0; r < 4; r++)
#pragma unroll
      for (int i = 0; i < 3; i++) lds128(v[i][r], base + i * 128 + (4 * (l8 >> 1) + 2 * (r & 1) + (l8 & 1)) * 768 + ((l8 + q4 + 4 * (r >> 1)) & 7) * 16);
    __syncwarp();
#pragma unroll
    for (int r = 0; r < 4; r++)
#pragma unroll
      for (int i = 0; i < 3; i++)
        sts128(base + i * 128 + (((l8 + q4 + 4 * (r >> 1)) & 7) + 8 * (r & 1)) * 768 + l8 * 16,
               make_uint4(bf2_to_h2(v[i][r][0]), bf2_to_h2(v[i][r][1]), bf2_to_h2(v[i][r][2]), bf2_to_h2(v[i][r][3])));
  }
  PROF2_AT(lane == 0, 440 + warp);
  const int q = lane & 3, t = (lane >> 2) & 3, b = lane >> 4;
  int u = 3 * (warp ^ 15) + 8 * rot; if (u >= 48) u -= 48;
  uint32_t base[3], v[3][4][3];
#pragma unroll
  for (int i = 0; i < 3; i++) {
    const int ui = u + i >= 48 ? u + i - 48 : u + i;
    base[i] = sb + W2S + ui * 1536;
    if (i != 1) mbar_wait(wbar + 48 + (ui >> 3) * 8, 0);
  }
#pragma unroll
  for (int i = 0; i < 3; i++)
#pragma unroll
    for (int d = 0; d < 4; d++)
#pragma unroll
      for (int j = 0; j < 3; j++) v[i][d][j] = lds32(base[i] + (2 * ((q + d) & 3) + b) * 192 + j * 64 + t * 16 + q * 4);
  __syncwarp();
#pragma unroll
  for (int i = 0; i < 3; i++)
#pragma unroll
    for (int d = 0; d < 4; d++)
#pragma unroll
      for (int j = 0; j < 3; j++) sts32(base[i] + (4 * j + q) * 128 + (2 * ((q + d) & 3) + b) * 16 + t * 4, bf2_to_h2(v[i][d][j], 0.5f / GELU_C3));
}

__device__ __noinline__ void ln_wide(uint32_t ad) {
  float m[2], r[2];
#pragma unroll
  for (int hi = 0; hi < 2; hi++) {
    float sm = 0.f;
    for (int s = 0; s < 6; s++) { uint2 w = lds64(ad + s * 512 + hi * 8); sm += (h_lo(w.x) + h_hi(w.x)) + (h_lo(w.y) + h_hi(w.y)); }
    sm += __shfl_xor_sync(0xffffffffu, sm, 1); sm += __shfl_xor_sync(0xffffffffu, sm, 2);
    m[hi] = sm * (1.f / 96.f);
    float q = 0.f;
    for (int s = 0; s < 6; s++) {
      uint2 w = lds64(ad + s * 512 + hi * 8);
      float d0 = h_lo(w.x) - m[hi], d1 = h_hi(w.x) - m[hi], d2 = h_lo(w.y) - m[hi], d3 = h_hi(w.y) - m[hi];
      q += (d0 * d0 + d1 * d1) + (d2 * d2 + d3 * d3);
    }
    q += __shfl_xor_sync(0xffffffffu, q, 1); q += __shfl_xor_sync(0xffffffffu, q, 2);
    r[hi] = rsqrtf(fmaf(q, 1.f / 96.f, 1e-5f)) * GELU_C3;
  }
  for (int s = 0; s < 6; s++) {
    uint32_t w[4]; lds128(w, ad + s * 512);
    sts128(ad + s * 512, make_uint4(pack_f16((h_lo(w[0]) - m[0]) * r[0], (h_hi(w[0]) - m[0]) * r[0]), pack_f16((h_lo(w[2]) - m[1]) * r[1], (h_hi(w[2]) - m[1]) * r[1]),
                                    pack_f16((h_lo(w[1]) - m[0]) * r[0], (h_hi(w[1]) - m[0]) * r[0]), pack_f16((h_lo(w[3]) - m[1]) * r[1], (h_hi(w[3]) - m[1]) * r[1])));
  }
  asm volatile("fence.proxy.async.shared::cta;" ::: "memory");
}

__device__ __forceinline__ float rsqrt_fast(float v) { float r; asm("rsqrt.approx.ftz.f32 %0, %1;" : "=f"(r) : "f"(v)); return r; }
__device__ __forceinline__ uint32_t layer_norm(uint32_t (&raw)[6][4], uint32_t* a, uint32_t tag) {
  const uint32_t stale = ((raw[0][0] ^ tag) | (raw[1][0] ^ tag)) | ((raw[2][0] ^ tag) | (raw[3][0] ^ tag)) | ((raw[4][0] ^ tag) | (raw[5][0] ^ tag));
  uint32_t sm[2];
#pragma unroll
  for (int hi = 0; hi < 2; hi++) {
    uint32_t s0 = h2add(raw[0][2 * hi], raw[1][2 * hi]), s1 = h2add(raw[0][2 * hi + 1], raw[1][2 * hi + 1]);
    uint32_t s2 = h2add(raw[2][2 * hi], raw[3][2 * hi]), s3 = h2add(raw[2][2 * hi + 1], raw[3][2 * hi + 1]);
    uint32_t s4 = h2add(raw[4][2 * hi], raw[5][2 * hi]), s5 = h2add(raw[4][2 * hi + 1], raw[5][2 * hi + 1]);
    sm[hi] = h2add(h2add(h2add(s0, s1), h2add(s2, s3)), h2add(s4, s5));
  }
  uint32_t s = h2add(prmt(sm[0], sm[1], 0x5410), prmt(sm[0], sm[1], 0x7632));
  s = h2add(s, __shfl_xor_sync(0xffffffffu, s, 1));
  s = h2add(s, __shfl_xor_sync(0xffffffffu, s, 2));
  const uint32_t nm = h2mul(s, 0xA155A155u);
  uint32_t qq[2];
#pragma unroll
  for (int hi = 0; hi < 2; hi++) {
    const uint32_t m = hi ? h2hi(nm) : h2lo(nm);
    uint32_t q0 = 0, q1 = 0;
#pragma unroll
    for (int k = 0; k < 6; k++) {
      uint32_t d0 = h2add(raw[k][2 * hi], m), d1 = h2add(raw[k][2 * hi + 1], m);
      raw[k][2 * hi] = d0; raw[k][2 * hi + 1] = d1;
      q0 = k ? h2fma(d0, d0, q0) : h2mul(d0, d0);
      q1 = k ? h2fma(d1, d1, q1) : h2mul(d1, d1);
    }
    qq[hi] = h2add(q0, q1);
  }
  uint32_t q = h2add(prmt(qq[0], qq[1], 0x5410), prmt(qq[0], qq[1], 0x7632));
  q = h2add(q, __shfl_xor_sync(0xffffffffu, q, 1));
  q = h2add(q, __shfl_xor_sync(0xffffffffu, q, 2));
  constexpr float K1 = 1.f / (96.f * GELU_C3 * GELU_C3), K2 = 1e-5f / (GELU_C3 * GELU_C3);
  const float r0 = rsqrt_fast(fmaf(h_lo(q), K1, K2)), r1 = rsqrt_fast(fmaf(h_hi(q), K1, K2));
  const uint32_t r = pack_f16(r0, r1);
#pragma unroll
  for (int k = 0; k < 6; k++) {
    a[4 * k] = h2mul(raw[k][0], h2lo(r)); a[4 * k + 2] = h2mul(raw[k][1], h2lo(r));
    a[4 * k + 1] = h2mul(raw[k][2], h2hi(r)); a[4 * k + 3] = h2mul(raw[k][3], h2hi(r));
  }
  return (((q & 0x7c007c00u) + 0x04000400u) & 0x80008000u) | (stale & 1);
}

constexpr int KS = CH / 16, NC = 384 / CH;
#define WG1_(n) wgmma_n##n##_f16
#define WG1(n) WG1_(n)
__device__ __forceinline__ void gemm1(uint32_t* p, const uint32_t* a, uint64_t d1, int c, int k0 = 0, int k1 = 6) {
#pragma unroll
  for (int s = 0; s < 6; s++)
    if (s >= k0 && s < k1) {
      if (s == 0) WG1(CH)<0>(p, a, d1 + c * CH); else WG1(CH)<1>(p, a + 4 * s, d1 + c * CH + s * (12288 >> 4));
    }
}
__device__ __forceinline__ void fetch_a(uint32_t abuf, uint32_t bar, const unsigned char* src) {
  asm volatile("{\n.reg .pred p;\nelect.sync _|p, 0xffffffff;\n"
               "@p mbarrier.arrive.expect_tx.shared::cta.b64 _, [%1], 3072;\n"
               "@p cp.async.bulk.shared::cluster.global.mbarrier::complete_tx::bytes [%0], [%2], 3072, [%1];\n}"
               ::"r"(abuf), "r"(bar), "l"(src) : "memory");
}
__device__ __forceinline__ void fetch_a_if(uint32_t abuf, uint32_t bar, const unsigned char* src, uint32_t go) {
  asm volatile("{\n.reg .pred p, q;\nsetp.ne.u32 q, %3, 0;\nelect.sync _|p, 0xffffffff;\nand.pred p, p, q;\n"
               "@p mbarrier.arrive.expect_tx.shared::cta.b64 _, [%1], 3072;\n"
               "@p cp.async.bulk.shared::cluster.global.mbarrier::complete_tx::bytes [%0], [%2], 3072, [%1];\n}"
               ::"r"(abuf), "r"(bar), "l"(src), "r"(go) : "memory");
}
__device__ __forceinline__ bool mbar_test(uint32_t bar, uint32_t parity) {
  uint32_t r;
  asm volatile("{.reg .pred p; mbarrier.test_wait.parity.shared::cta.b64 p, [%1], %2; selp.u32 %0, 1, 0, p;}" : "=r"(r) : "r"(bar), "r"(parity) : "memory");
  return r;
}
__device__ __forceinline__ void fetch_x(uint32_t xbuf, uint32_t bar, const CUtensorMap* tm, uint32_t c0, uint32_t c12, uint64_t pol, int go = 0) {
  asm volatile("{\n.reg .pred p, q;\nsetp.ge.s32 q, %7, 0;\nelect.sync _|p, 0xffffffff;\nand.pred p, p, q;\n"
               "@p mbarrier.arrive.expect_tx.shared::cta.b64 _, [%1], 3072;\n"
               "@p cp.async.bulk.tensor.3d.shared::cluster.global.mbarrier::complete_tx::bytes.L2::cache_hint [%0], [%2, {%3, %4, %5}], [%1], %6;\n}"
               ::"r"(xbuf), "r"(bar), "l"(tm), "r"(c0), "r"(c12 & 255), "r"(c12 >> 8), "l"(pol), "r"(go) : "memory");
}
__device__ __forceinline__ void wait_ready(const uint32_t* p, uint32_t target) {
  int spins = 0;
  while (ld_relaxed(p) != target) { __nanosleep(32); if (++spins > SPIN_LIMIT) __trap(); }
}
__device__ __forceinline__ uint32_t slot_tag(int gm, int j, uint32_t epoch) {
  const int len = gm < 8 ? PLEN : LMID, writes = (len - (j & (RING - 1)) + RING - 1) / RING;
  return (epoch * writes + j / RING + 1) & 1;
}

__device__ __forceinline__ void build_tile_list(uint32_t sb, int k, int idx, bool tabled, bool is_conv, uint32_t epoch) {
  int n = -1;
  if (tabled) { if (k < 48) n = (int16_t)g_sched[idx][k]; }
  else if (!is_conv) {
    const int i = k * (gridDim.x - NCONV) + idx, r = i >> 2, full = LMID * NG;
    const int j = r < full ? r / NG : ((r - full) >> 3) + LMID, gm = r < full ? r % NG : (r - full) & 7;
    if (i < 4096) n = (gm * PLEN + j) * 4 + (i & 3);
  }
  const int q = n >> 2, gm = q / PLEN, j = q - gm * PLEN, seg = j / LM;
  const int strip = gm < 8 ? gm >> 1 : (gm - 8) * NSEG + seg, pair = gm < 8 ? ((gm & 1) ? 255 - j : j) : PLEN + j - seg * LM;
  sts128(sb + MISC + 512 + k * 16, make_uint4(q, (((j & (RING - 1)) * NG + gm) * 4 + (n & 3)) * TILEB + slot_tag(gm, j, epoch),
                                              (n & 2) * 384, (strip * 8 + (n & 1) * 4) | (pair << 9)));
  if (k == 0) sts32(sb + MISC + 256, epoch + 1);
}

__device__ __forceinline__ void mlp_setup(uint32_t sb, Globals* gs, int id, const __nv_bfloat16* __restrict__ w1, const __nv_bfloat16* __restrict__ w2,
                                          int idx, bool tabled, int warp, int lane) {
  const int rot = idx % 6;
  PROF2_AT(lane == 0, 400 + warp);
  if (warp < 12) {
    const int m = warp >= 6; int s = warp - 6 * m + rot; if (s >= 6) s -= 6;
    if (WDELAY) __nanosleep(WDELAY + m * WDELAY2);
    copy_weights(sb, 6 * m + s, (const char*)(m ? w2 : w1) + s * 12288);
  }
  __syncthreads();
  PROF2_AT(threadIdx.x == 0, 416);
  if (warp >= 12) build_tile_list(sb, threadIdx.x - 384, idx, tabled, false, ld_relaxed(&gs->epoch[id]));
  PROF2_AT(lane == 0, 420 + warp);
  convert_weights(sb, sb + WBAR, rot, warp, lane);
  PROF2_AT(lane == 0, 460 + warp);
  asm volatile("fence.proxy.async.shared::cta;" ::: "memory");
  __syncthreads();
  if (threadIdx.x == 480) {
    const uint32_t e1 = lds32(sb + MISC + 256);
    gs->epoch[id] = e1;
    if (idx < 24 && (idx & 1)) {
      asm volatile("cp.async.bulk.global.shared::cta.bulk_group [%0], [%1], 12288;\ncp.async.bulk.commit_group;\ncp.async.bulk.wait_group 0;\nfence.proxy.async.global;\n"
                   "red.release.gpu.global.add.u32 [%2], 1;" ::"l"(gs->wimg + (idx >> 1) * 12288), "r"(sb + (idx >> 1) * 12288), "l"(gs->wflag) : "memory");
    }
  }
  __syncwarp();
}

__device__ __forceinline__ void mlp_role(uint32_t sb, Globals* gs, const CUtensorMap* tmr, __nv_bfloat16* __restrict__ out) {
  uint32_t tid;
  asm volatile("mov.u32 %0, %%tid.x;" : "=r"(tid));
  const int warp = __shfl_sync(0xffffffffu, tid >> 5, 0), lane = tid & 31;
  const int wg = warp >> 2, w = warp & 3, g = lane >> 2, t = lane & 3;
  const uint32_t abuf = sb + ABUF + warp * 3072, xbuf = sb + XBUF + (warp & 7) * 3072;
  const uint32_t bar = sb + MISC + warp * 8, obar = sb + MISC + (warp ^ 8) * 8;
  const uint32_t tl = sb + MISC + 512;
  PROF_AT(threadIdx.x == 0, 1); PROF_VAL(threadIdx.x == 0, 8, clock64());
  const uint32_t rtarget = 3 * lds32(sb + MISC + 256);
  const uint64_t d1 = ((uint64_t)(6144 >> 4) << 16) | ((uint64_t)(128 >> 4) << 32) | (uint64_t)(((sb + W1S) >> 4) & 0x3fff);
  const uint64_t d2 = ((uint64_t)(12288 >> 4) << 16) | ((uint64_t)(128 >> 4) << 32) | (uint64_t)(((sb + W2S) >> 4) & 0x3fff);
  const uint32_t ad = abuf + t * 128 + ((g ^ (2 * t)) << 4);
  const uint32_t xd = xbuf + g * 192 + t * 16;
  const int mybar = 1 + wg, nxtbar = 1 + ((wg + 1) & 3);
  const uint64_t pol = pol_evict_first();
  const unsigned char* const asrc = gs->scratch + w * 3072;
  uint32_t pha = 0, phx = 0, tp = tl + wg * 16;
  bool pending = true;
  uint32_t cur[4];
  lds128(cur, tp);
  while ((int)cur[0] >= 0) {
    PROF2_AT((threadIdx.x & 127) == 0, 16 + (tp - tl) / 4); PROF2_VAL((threadIdx.x & 127) == 0, 16 + (tp - tl) / 4 + 3, pending);
    uint32_t a[24], p[NC][CH / 4], gg[24][4], acc[24], raw[6][4], xr[6][4], n2[4], n4[4];
    if (pending) {
      wait_ready(&gs->ready[cur[0]], rtarget);
      fetch_a(abuf, bar, asrc + (cur[1] & ~1u));
      if (tp < tl + 32) fetch_x(xbuf, bar + 128, tmr, cur[2] + w * 192, cur[3], pol);
    }
    mbar_wait(bar, pha); pha ^= 1;
    PROF2_AT((threadIdx.x & 127) == 0, 16 + (tp - tl) / 4 + 1);
#pragma unroll
    for (int k = 0; k < 6; k++) lds128(raw[k], ad + k * 512);
    int sig = (int)lds32(tp + 16) >> 31;
    if (TRIG0 >= 0 && sig == 0) sig = tp < tl + 16 * NEARLY || (NLATE && (int)lds32(tp + 16 + 16 * NLATE) < 0);
    lds128(n4, tp + 64);
    uint32_t st = layer_norm(raw, a, cur[1]);
    if (__any_sync(0xffffffffu, st != 0)) {
      for (int tries = 0; __any_sync(0xffffffffu, st & 1); tries++) {
        if (tries > SPIN_LIMIT) __trap();
        fetch_a(abuf, bar, asrc + (cur[1] & ~1u));
        mbar_wait(bar, pha); pha ^= 1;
        st = 0;
#pragma unroll
        for (int k = 0; k < 6; k++) st |= lds32(ad + k * 512) ^ cur[1];
      }
      ln_wide(ad);
#pragma unroll
      for (int k = 0; k < 6; k++) lds128(a + 4 * k, ad + k * 512);
    }
    if (!LATERED) red_add_elect(&gs->cons[cur[0]]);
    if (tp != tl) asm volatile("bar.sync %0, 256;" ::"r"(mybar) : "memory");
    PROF2_AT((threadIdx.x & 127) == 0, 16 + (tp - tl) / 4 + 2);
    uint32_t rdy = 0;
    wg_fence();
    gemm1(p[0], a, d1, 0); wg_commit();
    if (SCHED == 9) { gemm1(p[1], a, d1, 1, 0, 6 / KS); wg_commit(); }
    if (LATERED) asm volatile("{.reg .pred p; setp.eq.u32 p, %1, 0; @p red.relaxed.gpu.global.add.u32 [%0], 1;}" ::"l"(&gs->cons[cur[0]] + lane), "r"(lane) : "memory");
#pragma unroll
    for (int j = 0; j < 24; j++) {
      const int c = j / KS, s = j % KS;
      if (NOJB && j == JB) { if (NOJB == 2) SCHED_FENCE(); rdy = ld_relaxed(&gs->ready[max((int)n4[0], 0)]); if (NOJB == 3) SCHED_FENCE(); }
      if (!NOJB && j == JB) {
        rdy = ld_relaxed(&gs->ready[max((int)n4[0], 0)]);
        if (SCHED != 9 && s) wg_commit();
        wg_wait<0>();
        mbar_wait(bar + 128, phx); phx ^= 1;
      } else if (SCHED == 9) wg_wait<1>(); else if (s == 0) wg_wait<0>();
      if (j == JF) { pending = rdy != rtarget; fetch_a_if(abuf, bar, asrc + (n4[1] & ~1u), !pending && (int)n4[0] >= 0); if (JFF) SCHED_FENCE(); }
      if (j == TRIG0) asm volatile("{.reg .pred p; setp.eq.s32 p, %1, 1; @p bar.arrive %0, 256;}" ::"r"(nxtbar), "r"(sig) : "memory");
      if (j == TRIG) asm volatile("{.reg .pred p; setp.eq.s32 p, %1, 0; @p bar.arrive %0, 256;}" ::"r"(nxtbar), "r"(sig) : "memory");
#pragma unroll
      for (int i = 0; i < 4; i++) gg[j][i] = gelu_h2(p[c][4 * s + i]);
      wg_fence();
      if (j == 0) wgmma_n96_f16<0>(acc, gg[j], d2); else wgmma_n96_f16<1>(acc, gg[j], d2 + (16 * (j % 3) + j / 3) * (1536 >> 4));
      if (SCHED == 9) {
        const int c1 = (j + 1) / KS + 1, u = (j + 1) % KS;
        if (c1 < NC) gemm1(p[c1], a, d1, c1, (6 * u) / KS, (6 * (u + 1)) / KS);
        wg_commit();
      } else if (s == KS - 1) {
        if (c + 1 < NC) gemm1(p[c + 1], a, d1, c + 1);
        wg_commit();
      }
    }
    if (XEARLY) {
#pragma unroll
      for (int k = 0; k < 6; k++) lds128(xr[k], xd + (k / 3) * 1536 + (k % 3) * 64);
      lds128(n2, tp + 32);
    }
    pending = rdy != rtarget;
    if (FPRED && JF == 24) fetch_a_if(abuf, bar, asrc + (n4[1] & ~1u), !pending && (int)n4[0] >= 0);
    wg_wait<0>();
    if (!FPRED && !pending && (int)n4[0] >= 0) fetch_a(abuf, bar, asrc + (n4[1] & ~1u));
    if (NOJB) { mbar_wait(bar + 128, phx); phx ^= 1; }
    char* const op = (char*)out + (size_t)(cur[3] >> 8) * (512 * 192) + ((cur[3] & 255) + (g >> 1)) * 3072 + cur[2] * 2 + (2 * w + (g & 1)) * 192 + t * 16;
    if (!XEARLY) lds128(n2, tp + 32);
#pragma unroll
    for (int k = 0; k < 6; k++) {
      const int hi = k / 3, j = k % 3;
      if (!XEARLY) lds128(xr[k], xd + hi * 1536 + j * 64);
      uint4 o;
      o.x = hadd2_bf16(xr[k][0], pack_bf16(h_lo(acc[8 * j + hi]), h_hi(acc[8 * j + hi])));
      o.y = hadd2_bf16(xr[k][1], pack_bf16(h_lo(acc[8 * j + 2 + hi]), h_hi(acc[8 * j + 2 + hi])));
      o.z = hadd2_bf16(xr[k][2], pack_bf16(h_lo(acc[8 * j + 4 + hi]), h_hi(acc[8 * j + 4 + hi])));
      o.w = hadd2_bf16(xr[k][3], pack_bf16(h_lo(acc[8 * j + 6 + hi]), h_hi(acc[8 * j + 6 + hi])));
      stg128_stream(op + hi * (512 * 192) + j * 64, o, pol);
    }
    __syncwarp();
    if (XPRED) fetch_x(xbuf, obar + 128, tmr, n2[2] + w * 192, n2[3], pol, n2[0]);
    else if ((int)n2[0] >= 0) fetch_x(xbuf, obar + 128, tmr, n2[2] + w * 192, n2[3], pol);
    tp += 64;
#pragma unroll
    for (int k = 0; k < 4; k++) cur[k] = n4[k];
  }
  PROF_AT((threadIdx.x & 127) == 0, 4 + wg); PROF_VAL(threadIdx.x == 0, 9, clock64());
}

__device__ __forceinline__ void stg128_if(uint32_t ofs, void* p, uint4 v) {
  if (NODUMP) asm volatile("{.reg .pred q; setp.ge.s32 q, %5, 0; @q st.global.v4.b32 [%0], {%1,%2,%3,%4};}" ::"l"(p), "r"(v.x), "r"(v.y), "r"(v.z), "r"(v.w), "r"(ofs) : "memory");
  else stg128(p, v);
}
__device__ __forceinline__ void conv_compute(uint32_t sb, Globals* gs, int third, int nit, int off, bool up, int warp, int lane) {
  const int g = lane >> 2, t = lane & 3;
  const uint32_t full = sb + CM;
  PROFS(0);
  const uint32_t wt = sb + 16384 + warp * 1024;
  sts128(wt + lane * 16, make_uint4(0, 0, 0, 0));
  if (lane < 4) sts128(wt + 512 + lane * 16, make_uint4(0, 0, 0, 0));
  asm volatile("setmaxnreg.inc.sync.aligned.u32 %0;" ::"n"(CREGS));
  PROFS(1);
  uint32_t meta = 0;
#pragma unroll
  for (int a = 0; a < 4; a++) meta |= ((4 * (t & 1) + a + 1 >= g) ? 0x80008u : 0xD000Du) << (4 * a);
  meta = __shfl_sync(0xffffffffu, meta, lane);
  uint32_t aq[4];
#pragma unroll
  for (int q = 0; q < 4; q++) {
    const int pp = (g & 1) * 140 + (t & 1) * 70 + 16 * (g >> 1) + 2 * q + (t >> 1);
    aq[q] = __shfl_sync(0xffffffffu, sb + RBUF + pp * 64 + (((warp >> 1) ^ ((pp >> 1) & 3)) << 4) + (warp & 1) * 8, lane);
  }
  const int Q = third * 8 + warp;
  unsigned char* const obase = gs->scratch + (g >> 1) * 3072 + Q * 128 + (((2 * t + (g & 1)) ^ (2 * (Q & 3))) << 4);
  const float zero4[4] = {0.f, 0.f, 0.f, 0.f};
  {
    uint32_t A[4][4][4];
    PROFS(2);
    asm volatile("bar.sync 5, 288;" ::: "memory");
    mbar_wait(sb + WBAR + 8, 0);
    PROFS(3);
    {
#pragma unroll
      for (int k = 0; k < 2; k++) {
        const int tap = lane + 32 * k, i = tap / 7;
        if (tap < 49) { const uint2 v = lds64(sb + tap * 192 + third * 64 + warp * 8); asm volatile("st.shared.v2.b32 [%0], {%1,%2};" ::"r"(wt + (tap + i + 8) * 8), "r"(v.x), "r"(v.y) : "memory"); }
      }
      __syncwarp();
      uint2 w[2][4][3];
#pragma unroll
      for (int h = 0; h < 2; h++) {
        uint32_t src = wt + ((4 * h + t - g) & 7) * 8 + (up ? 384 : 0);
#pragma unroll
        for (int u = 0; u < 4; u++) {
#pragma unroll
          for (int k = 0; k < 3; k++) w[h][u][k] = lds64(src + k * 64);
          src += up ? -128 : 128;
        }
      }
#pragma unroll
      for (int u = 0; u < 4; u++)
#pragma unroll
        for (int r = 0; r < 4; r++) {
          const uint2 w0 = w[r >> 1][u][1 - (r & 1)], w1 = w[r >> 1][u][2 - (r & 1)];
          A[0][u][r] = prmt(w0.x, w1.x, 0x5410); A[1][u][r] = prmt(w0.x, w1.x, 0x7632);
          A[2][u][r] = prmt(w0.y, w1.y, 0x5410); A[3][u][r] = prmt(w0.y, w1.y, 0x7632);
        }
    }
    float S[2][4][3][4];
#pragma unroll
    for (int s = 0; s < 2; s++)
#pragma unroll
      for (int c = 0; c < 4; c++)
#pragma unroll
        for (int i = 0; i < 3; i++)
#pragma unroll
          for (int k = 0; k < 4; k++) S[s][c][i][k] = 0.f;
    uint32_t sofs = off * SLOTB, bar = full + off * 8, ph = 0, ot = sb + CTAB;
    const uint32_t oend = ot + nit * 16;
    PROF_AT(threadIdx.x == 0, 12);
    PROFS(4);
    asm volatile("bar.sync 0, 512;" ::: "memory");
    PROFS(5);
    mbar_wait(bar, 0);
    PROF_AT(threadIdx.x == 0, 14);
    PROFS(6);
    uint2 X[3][4];
#pragma unroll
    for (int j = 0; j < 2; j++)
#pragma unroll
      for (int q = 0; q < 4; q++) X[j][q] = lds64(aq[q] + sofs + j * 512);
#pragma unroll 1
    do {
      const uint2 oe = lds64(ot);
      unsigned char* const o = obase + oe.x;
      const uint32_t dbar = bar + 64;
#pragma unroll
      for (int s = 0; s < 2; s++) {
        uint32_t B[4][4];
        if (s == 1) {
          sofs += SLOTB; bar += 8;
          if (sofs == NSLOT * SLOTB) { sofs = 0; bar = full; ph ^= 1; }
          mbar_wait(bar, ph);
        }
#pragma unroll
        for (int c = 0; c < 4; c++)
#pragma unroll
          for (int q = 0; q < 4; q++) B[c][q] = prmt(c < 2 ? X[s][q].x : X[s][q].y, c < 2 ? X[s + 1][q].x : X[s + 1][q].y, (c & 1) ? 0x7632 : 0x5410);
        if (s == 0) {
#pragma unroll
          for (int q = 0; q < 4; q++) X[2][q] = lds64(aq[q] + sofs + 2 * 512);
        } else {
#pragma unroll
          for (int j = 0; j < 2; j++)
#pragma unroll
            for (int q = 0; q < 4; q++) X[j][q] = lds64(aq[q] + sofs + j * 512);
        }
        float T[4][4];
        if (CFN & 1) SCHED_FENCE();
#pragma unroll
        for (int c = 0; c < 4; c++) mma_sp(T[c], A[c][3], B[c], S[s][c][2], meta);
#pragma unroll
        for (int c = 0; c < 4; c++) mma_sp(S[s][c][2], A[c][2], B[c], S[s][c][1], meta);
        if (CFN & 2) SCHED_FENCE();
        stg128_if(oe.x, o + (2 * s) * TILEB, make_uint4((pack_f16_sat(T[0][0], T[1][0]) & ~1u) | oe.y, pack_f16_sat(T[2][0], T[3][0]), pack_f16_sat(T[0][2], T[1][2]), pack_f16_sat(T[2][2], T[3][2])));
        stg128_if(oe.x, o + (2 * s + 1) * TILEB, make_uint4((pack_f16_sat(T[0][1], T[1][1]) & ~1u) | oe.y, pack_f16_sat(T[2][1], T[3][1]), pack_f16_sat(T[0][3], T[1][3]), pack_f16_sat(T[2][3], T[3][3])));
        if (s == 1) mbar_arrive_elect(dbar);
        if (CFN & 4) SCHED_FENCE();
#pragma unroll
        for (int c = 0; c < 4; c++) mma_sp(S[s][c][1], A[c][1], B[c], S[s][c][0], meta);
#pragma unroll
        for (int c = 0; c < 4; c++) mma_sp(S[s][c][0], A[c][0], B[c], zero4, meta);
      }
      ot += 16;
    } while (ot != oend);
  }
  PROF_AT(threadIdx.x == 0, 13);
}

__device__ __forceinline__ void load_step(uint32_t sb, const CUtensorMap* tmx, int gm, int third, int it, int s) {
  const int seg = it / (LM + 3);
  const int st = gm < 8 ? gm >> 1 : (gm - 8) * NSEG + seg, J = gm < 8 ? ((gm & 1) ? 257 - it : it + 1) : PLEN + it - seg * (LM + 3);
  asm volatile("{\n.reg .pred p;\n.reg .s32 c2;\n.reg .u32 d2;\nelect.sync _|p, 0xffffffff;\nadd.s32 c2, %4, 64;\nadd.u32 d2, %0, 8960;\n"
               "@p mbarrier.arrive.expect_tx.shared::cta.b64 _, [%2], 17920;\n"
               "@p cp.async.bulk.tensor.3d.shared::cluster.global.mbarrier::complete_tx::bytes [%0], [%1, {%3, %4, %5}], [%2];\n"
               "@p cp.async.bulk.tensor.3d.shared::cluster.global.mbarrier::complete_tx::bytes [d2], [%1, {%3, c2, %5}], [%2];\n}"
               ::"r"(sb + RBUF + s * SLOTB), "l"(tmx), "r"(sb + CM + s * 8), "r"(third * 32), "r"(st * 128 - 3), "r"(2 * J - 3) : "memory");
}
__device__ __forceinline__ void ring_bar_init(uint32_t bar, uint32_t cnt, bool ahead) {
  asm volatile("{\n.reg .pred p, q;\nelect.sync _|p, 0xffffffff;\n@p mbarrier.init.shared::cta.b64 [%0], %1;\n"
               "setp.ne.and.u32 q, %2, 0, p;\n@q mbarrier.arrive.shared::cta.b64 _, [%0], %1;\n@p fence.mbarrier_init.release.cluster;\n}" ::"r"(bar), "r"(cnt), "r"((uint32_t)ahead) : "memory");
}
__device__ __forceinline__ void conv_loader(uint32_t sb, Globals* gs, const CUtensorMap* tmx, int gm, int nit, int off, int cidx, int third, int k) {
  static_assert(AHEAD > 4 && AHEAD <= NSLOT && NCONV >= 24, "loader");
  const uint32_t full = sb + CM;
  asm volatile("bar.sync 0, 512;" ::: "memory");
  if (FIRST + k < AHEAD) load_step(sb, tmx, gm, third, FIRST + k, (FIRST + k + off) & 7);
#pragma unroll 1
  for (int it = AHEAD + k; it < nit + AHEAD; it += 4) {
    const int u = it + off;
    const uint32_t ro = lds32(sb + CTAB + (it - AHEAD) * 16 + 8);
    mbar_wait(full + 64 + ((u - AHEAD) & 7) * 8, ((u - AHEAD) >> 3) & 1);
    red_add_elect((uint32_t*)((char*)gs + ro));
    PROF_AT((threadIdx.x & 31) == 0 && (((it - AHEAD) & (PROF > 1 ? 7 : 15)) == 0 || it - AHEAD < 6), 200 + it - AHEAD);
    if (it <= nit) load_step(sb, tmx, gm, third, it, u & 7);
    if (it >= nit - 16) {
      if (it < nit - 12) {
        wait_ready(gs->wflag, 12 * lds32(sb + MISC + 256));
        asm volatile("fence.acquire.gpu;\nfence.proxy.async.global;" ::: "memory");
        if (cidx < 24) asm volatile("{.reg .pred p; elect.sync _|p, 0xffffffff; @p cp.async.bulk.prefetch.L2.global [%0], 1536;}" ::"l"(gs->wimg + (cidx * 4 + k) * 1536) : "memory");
      }
      const int m = it == nit ? 0 : W2S;
      if (it == nit || it == nit + AHEAD - 4)
        asm volatile("{\n.reg .pred p;\nelect.sync _|p, 0xffffffff;\n@p mbarrier.arrive.expect_tx.shared::cta.b64 _, [%1], 73728;\n"
                     "@p cp.async.bulk.shared::cluster.global.mbarrier::complete_tx::bytes [%0], [%2], 73728, [%1];\n}"
                     ::"r"(sb + m), "r"(sb + WBAR), "l"(gs->wimg + m) : "memory");
    }
  }
}

__device__ __forceinline__ void conv_credit(uint32_t sb, Globals* gs, int P0, int nit, int off, uint32_t ctarget, int k) {
  const uint32_t full = sb + CM;
#pragma unroll 1
  for (int it = k + NSLOT; it <= nit; it += 4) {
    const int u = it + off, P = (int)lds32(sb + CTAB + it * 16 + 12) - RING;
    int spins = 0;
    mbar_wait(full + 64 + (u & 7) * 8, ((u >> 3) & 1) ^ 1);
    if (P >= P0) while (ld_relaxed(&gs->cons[P]) != ctarget) { __nanosleep(CSLEEP); if (++spins > SPIN_LIMIT) __trap(); }
    mbar_arrive_elect(full + (u & 7) * 8);
  }
}

__global__ void __launch_bounds__(512, 1) convnext_kernel(const __grid_constant__ CUtensorMap tmx, const __grid_constant__ CUtensorMap tmr, const __nv_bfloat16* __restrict__ dw,
                                                          const __nv_bfloat16* __restrict__ w1, const __nv_bfloat16* __restrict__ w2, __nv_bfloat16* __restrict__ out, Globals* gs) {
  extern __shared__ __align__(1024) unsigned char smem[];
  const uint32_t sb = smem_u32(smem);
  const int warp = __shfl_sync(0xffffffffu, threadIdx.x >> 5, 0), lane = threadIdx.x & 31;
  PROF_AT(threadIdx.x == 0, 0);
  if (PFX && threadIdx.x == 320) asm volatile("prefetch.tensormap [%0];" ::"l"(&tmx) : "memory");
  if (threadIdx.x == 288) asm volatile("prefetch.tensormap [%0];" ::"l"(&tmr) : "memory");
  uint32_t smid, nsmid;
  asm volatile("mov.u32 %0, %%smid;" : "=r"(smid));
  asm volatile("mov.u32 %0, %%nsmid;" : "=r"(nsmid));
  const bool tabled = TABLED && gridDim.x == 132 && nsmid == 132;
  const int id = tabled ? smid : blockIdx.x;
  int cidx, idx;
  int is_conv;
  if (tabled) {
    idx = smid;
    const int k = (smid - 60) / 14, r = smid - 60 - 14 * k;
    is_conv = smid < 48 ? !(smid & 1) : (smid >= 60 && smid <= 90 && (r & ~2) == 0);
    cidx = smid < 48 ? ((smid >> 1) & 7) * 3 + (smid >> 4) : 24 + (r >> 1) * 3 + k;
  } else {
    cidx = (blockIdx.x * NCONV) / gridDim.x;
    is_conv = ((blockIdx.x + 1) * NCONV) / gridDim.x != cidx;
    idx = blockIdx.x - cidx;
  }
  PROF_VAL(threadIdx.x == 0, 2, is_conv ? 1000 + cidx : idx);
  const int gm = cidx / 3, third = cidx - gm * 3;
  const int P0 = gm * PLEN, nit = gm < 8 ? PLEN + 2 : NSEG * (LM + 3), off = (7 - nit) & 7;
  if (is_conv && warp == 8) {
    asm volatile("{\n.reg .pred p;\nelect.sync _|p, 0xffffffff;\n@p mbarrier.init.shared::cta.b64 [%1], 1;\n@p fence.mbarrier_init.release.cluster;\n"
                 "@p mbarrier.arrive.expect_tx.shared::cta.b64 _, [%1], 9408;\n"
                 "@p cp.async.bulk.shared::cluster.global.mbarrier::complete_tx::bytes [%0], [%2], 9408, [%1];\nbar.arrive 5, 288;\n}"
                 ::"r"(sb), "r"(sb + WBAR + 8), "l"(dw) : "memory");
#pragma unroll 1
    for (int it = 0; it < NSLOT; it++) {
      const int s = (it + off) & 7;
      ring_bar_init(sb + CM + s * 8, 2, s < off);
      PROF_AT(it == 0 && (threadIdx.x & 31) == 0, 15);
      if (it < FIRST) load_step(sb, &tmx, gm, third, it, s);
    }
  }
  mbar_init_elect(sb + MISC + warp * 8, 1); mbar_init_elect(sb + MISC + 128 + warp * 8, 1);
  asm volatile("fence.mbarrier_init.release.cluster;" ::: "memory");
  if (is_conv) {
    if (warp >= 8) ring_bar_init(sb + CM + warp * 8, 8, warp - 8 < off);
    if (warp == 9) mbar_init_elect(sb + WBAR, 2);
    if (warp < 8) {
      conv_compute(sb, gs, third, nit, off, gm < 8 && (gm & 1), warp, lane);
      asm volatile("setmaxnreg.dec.sync.aligned.u32 128;");
    } else if (warp >= 12) {
      asm volatile("setmaxnreg.dec.sync.aligned.u32 24;");
      const uint32_t epoch = ld_relaxed(&gs->epoch[id]);
#pragma unroll 1
      for (int it = threadIdx.x - 384; it <= nit; it += 128) {
        const int seg = it / (LM + 3), j = gm < 8 ? it - 2 : it - 3 * (seg + 1);
        const bool ok = it < nit && j >= (gm < 8 ? 0 : seg * LM);
        sts128(sb + CTAB + it * 16, make_uint4((ok ? (j & (RING - 1)) * NG + gm : NODUMP ? -1 : RING * NG) * (4 * TILEB), slot_tag(gm, max(j, 0), epoch),
                                               offsetof(Globals, ready) + (ok ? P0 + j : NG * PLEN) * 4, ok ? P0 + j : -1));
      }
      asm volatile("bar.sync 0, 512;" ::: "memory");
      mbar_arrive_elect(sb + CM + ((((warp + 2) & 3) + off) & 7) * 8);
      mbar_arrive_elect(sb + CM + ((((warp + 2) & 3) + off + 4) & 7) * 8);
      build_tile_list(sb, threadIdx.x - 384, idx, tabled, true, epoch);
      if (threadIdx.x == 384) gs->epoch[id] = epoch + 1;
      conv_credit(sb, gs, P0, nit, off, 16 * (epoch + 1), (warp + 2) & 3);
      mbar_wait(sb + CM + 64 + 3 * 8, ((nit + off) >> 3) & 1);
      mbar_wait(sb + CM + 64 + 6 * 8, ((nit + off) >> 3) & 1);
      asm volatile("setmaxnreg.inc.sync.aligned.u32 128;");
    } else {
      asm volatile("setmaxnreg.dec.sync.aligned.u32 %0;" ::"n"(488 - 2 * CREGS));
      conv_loader(sb, gs, &tmx, gm, nit, off, cidx, third, warp & 3);
      mbar_wait(sb + CM + 64 + 3 * 8, ((nit + off) >> 3) & 1);
      mbar_wait(sb + CM + 64 + 6 * 8, ((nit + off) >> 3) & 1);
      asm volatile("setmaxnreg.inc.sync.aligned.u32 128;");
    }
    PROF2_AT((threadIdx.x & 31) == 0, 400 + (threadIdx.x >> 5));
    mbar_wait(sb + WBAR, 0);
    asm volatile("bar.sync 0, 512;" ::: "memory");
  } else {
    mlp_setup(sb, gs, id, w1, w2, idx, tabled, warp, lane);
  }
  mlp_role(sb, gs, &tmr, out);
}

typedef CUresult (*PFN_encodeTiled)(CUtensorMap*, CUtensorMapDataType, cuuint32_t, void*, const cuuint64_t*, const cuuint64_t*, const cuuint32_t*, const cuuint32_t*,
                                    CUtensorMapInterleave, CUtensorMapSwizzle, CUtensorMapL2promotion, CUtensorMapFloatOOBfill);

extern "C" void kernel_launch(void* const* d_in, const int* in_sizes, int n_in, void* d_out, int out_size) {
  const __nv_bfloat16* x = (const __nv_bfloat16*)d_in[0];
  const __nv_bfloat16* dw = (const __nv_bfloat16*)d_in[1];
  const __nv_bfloat16* w1 = (const __nv_bfloat16*)d_in[2];
  const __nv_bfloat16* w2 = (const __nv_bfloat16*)d_in[3];
  static PFN_encodeTiled encode = nullptr;
  static int nsm = 0;
  static Globals* gs = nullptr;
  if (!encode) {
    void* fn = nullptr; cudaDriverEntryPointQueryResult qr;
    cudaGetDriverEntryPoint("cuTensorMapEncodeTiled", &fn, cudaEnableDefault, &qr);
    encode = (PFN_encodeTiled)fn;
    cudaGetSymbolAddress((void**)&gs, g_state);
    int dev = 0; cudaGetDevice(&dev);
    cudaDeviceGetAttribute(&nsm, cudaDevAttrMultiProcessorCount, dev);
    cudaFuncSetAttribute(convnext_kernel, cudaFuncAttributeMaxDynamicSharedMemorySize, SMEM_BYTES);
  }
  CUtensorMap tm;
  cuuint64_t dims[3] = {96, 512, 512}, strides[2] = {192, 192 * 512};
  cuuint32_t box[3] = {32, 70, 2}, es[3] = {1, 1, 1};
  encode(&tm, CU_TENSOR_MAP_DATA_TYPE_BFLOAT16, 3, (void*)x, dims, strides, box, es, CU_TENSOR_MAP_INTERLEAVE_NONE, CU_TENSOR_MAP_SWIZZLE_64B,
         PROMO, CU_TENSOR_MAP_FLOAT_OOB_FILL_NONE);
  CUtensorMap tr;
  cuuint64_t dims2[3] = {1536, 32, 512}, strides2[2] = {3072, 192 * 512};
  cuuint32_t box2[3] = {192, 4, 2};
  encode(&tr, CU_TENSOR_MAP_DATA_TYPE_BFLOAT16, 3, (void*)x, dims2, strides2, box2, es, CU_TENSOR_MAP_INTERLEAVE_NONE, CU_TENSOR_MAP_SWIZZLE_NONE,
         CU_TENSOR_MAP_L2_PROMOTION_NONE, CU_TENSOR_MAP_FLOAT_OOB_FILL_NONE);
  convnext_kernel<<<nsm, 512, SMEM_BYTES>>>(tm, tr, dw, w1, w2, (__nv_bfloat16*)d_out, gs);
}
```

```cpp
#include <cuda_runtime.h>
#include <cuda_bf16.h>
#include <cuda.h>
#include <stdint.h>
#include <stddef.h>

template<int SCALE_D> __device__ __forceinline__ void wgmma_n32_f16(uint32_t* d, const uint32_t* a, uint64_t desc) {
  if (SCALE_D == 0) asm volatile("wgmma.mma_async.sync.aligned.m64n32k16.f16.f16.f16 {%0,%1,%2,%3,%4,%5,%6,%7}, {%8,%9,%10,%11}, %12, 0, 1, 1, 1;"
    : "=r"(d[0]),"=r"(d[1]),"=r"(d[2]),"=r"(d[3]),"=r"(d[4]),"=r"(d[5]),"=r"(d[6]),"=r"(d[7])
    : "r"(a[0]),"r"(a[1]),"r"(a[2]),"r"(a[3]),"l"(desc));
  if (SCALE_D == 1) asm volatile("wgmma.mma_async.sync.aligned.m64n32k16.f16.f16.f16 {%0,%1,%2,%3,%4,%5,%6,%7}, {%8,%9,%10,%11}, %12, 1, 1, 1, 1;"
    : "+r"(d[0]),"+r"(d[1]),"+r"(d[2]),"+r"(d[3]),"+r"(d[4]),"+r"(d[5]),"+r"(d[6]),"+r"(d[7])
    : "r"(a[0]),"r"(a[1]),"r"(a[2]),"r"(a[3]),"l"(desc));
}

template<int SCALE_D> __device__ __forceinline__ void wgmma_n48_f16(uint32_t* d, const uint32_t* a, uint64_t desc) {
  if (SCALE_D == 0) asm volatile("wgmma.mma_async.sync.aligned.m64n48k16.f16.f16.f16 {%0,%1,%2,%3,%4,%5,%6,%7,%8,%9,%10,%11}, {%12,%13,%14,%15}, %16, 0, 1, 1, 1;"
    : "=r"(d[0]),"=r"(d[1]),"=r"(d[2]),"=r"(d[3]),"=r"(d[4]),"=r"(d[5]),"=r"(d[6]),"=r"(d[7]),"=r"(d[8]),"=r"(d[9]),"=r"(d[10]),"=r"(d[11])
    : "r"(a[0]),"r"(a[1]),"r"(a[2]),"r"(a[3]),"l"(desc));
  if (SCALE_D == 1) asm volatile("wgmma.mma_async.sync.aligned.m64n48k16.f16.f16.f16 {%0,%1,%2,%3,%4,%5,%6,%7,%8,%9,%10,%11}, {%12,%13,%14,%15}, %16, 1, 1, 1, 1;"
    : "+r"(d[0]),"+r"(d[1]),"+r"(d[2]),"+r"(d[3]),"+r"(d[4]),"+r"(d[5]),"+r"(d[6]),"+r"(d[7]),"+r"(d[8]),"+r"(d[9]),"+r"(d[10]),"+r"(d[11])
    : "r"(a[0]),"r"(a[1]),"r"(a[2]),"r"(a[3]),"l"(desc));
}

template<int SCALE_D> __device__ __forceinline__ void wgmma_n64_f16(uint32_t* d, const uint32_t* a, uint64_t desc) {
  if (SCALE_D == 0) asm volatile("wgmma.mma_async.sync.aligned.m64n64k16.f16.f16.f16 {%0,%1,%2,%3,%4,%5,%6,%7,%8,%9,%10,%11,%12,%13,%14,%15}, {%16,%17,%18,%19}, %20, 0, 1, 1, 1;"
    : "=r"(d[0]),"=r"(d[1]),"=r"(d[2]),"=r"(d[3]),"=r"(d[4]),"=r"(d[5]),"=r"(d[6]),"=r"(d[7]),"=r"(d[8]),"=r"(d[9]),"=r"(d[10]),"=r"(d[11]),"=r"(d[12]),"=r"(d[13]),"=r"(d[14]),"=r"(d[15])
    : "r"(a[0]),"r"(a[1]),"r"(a[2]),"r"(a[3]),"l"(desc));
  if (SCALE_D == 1) asm volatile("wgmma.mma_async.sync.aligned.m64n64k16.f16.f16.f16 {%0,%1,%2,%3,%4,%5,%6,%7,%8,%9,%10,%11,%12,%13,%14,%15}, {%16,%17,%18,%19}, %20, 1, 1, 1, 1;"
    : "+r"(d[0]),"+r"(d[1]),"+r"(d[2]),"+r"(d[3]),"+r"(d[4]),"+r"(d[5]),"+r"(d[6]),"+r"(d[7]),"+r"(d[8]),"+r"(d[9]),"+r"(d[10]),"+r"(d[11]),"+r"(d[12]),"+r"(d[13]),"+r"(d[14]),"+r"(d[15])
    : "r"(a[0]),"r"(a[1]),"r"(a[2]),"r"(a[3]),"l"(desc));
}

template<int SCALE_D> __device__ __forceinline__ void wgmma_n96_f16(uint32_t* d, const uint32_t* a, uint64_t desc) {
  if (SCALE_D == 0) asm volatile("wgmma.mma_async.sync.aligned.m64n96k16.f16.f16.f16 {%0,%1,%2,%3,%4,%5,%6,%7,%8,%9,%10,%11,%12,%13,%14,%15,%16,%17,%18,%19,%20,%21,%22,%23}, {%24,%25,%26,%27}, %28, 0, 1, 1, 1;"
    : "=r"(d[0]),"=r"(d[1]),"=r"(d[2]),"=r"(d[3]),"=r"(d[4]),"=r"(d[5]),"=r"(d[6]),"=r"(d[7]),"=r"(d[8]),"=r"(d[9]),"=r"(d[10]),"=r"(d[11]),"=r"(d[12]),"=r"(d[13]),"=r"(d[14]),"=r"(d[15]),"=r"(d[16]),"=r"(d[17]),"=r"(d[18]),"=r"(d[19]),"=r"(d[20]),"=r"(d[21]),"=r"(d[22]),"=r"(d[23])
    : "r"(a[0]),"r"(a[1]),"r"(a[2]),"r"(a[3]),"l"(desc));
  if (SCALE_D == 1) asm volatile("wgmma.mma_async.sync.aligned.m64n96k16.f16.f16.f16 {%0,%1,%2,%3,%4,%5,%6,%7,%8,%9,%10,%11,%12,%13,%14,%15,%16,%17,%18,%19,%20,%21,%22,%23}, {%24,%25,%26,%27}, %28, 1, 1, 1, 1;"
    : "+r"(d[0]),"+r"(d[1]),"+r"(d[2]),"+r"(d[3]),"+r"(d[4]),"+r"(d[5]),"+r"(d[6]),"+r"(d[7]),"+r"(d[8]),"+r"(d[9]),"+r"(d[10]),"+r"(d[11]),"+r"(d[12]),"+r"(d[13]),"+r"(d[14]),"+r"(d[15]),"+r"(d[16]),"+r"(d[17]),"+r"(d[18]),"+r"(d[19]),"+r"(d[20]),"+r"(d[21]),"+r"(d[22]),"+r"(d[23])
    : "r"(a[0]),"r"(a[1]),"r"(a[2]),"r"(a[3]),"l"(desc));
}

#define SCHED_NG 10
#define SCHED_LE 103
__device__ const uint16_t g_sched[132][48] = {
{367,3260,389,403,65535,65535,65535,65535,65535,65535,65535,65535,65535,65535,65535,65535,65535,65535,65535,65535,65535,65535,65535,65535,65535,65535,65535,65535,65535,65535,65535,65535,65535,65535,65535,65535,65535,65535,65535,65535,65535,65535,65535,65535,65535,65535,65535,65535},
{0,2483,22,2915,2925,2935,3765,73,83,93,2986,3816,124,134,144,3037,3867,175,185,195,3088,218,3111,3121,3939,259,269,279,3172,3990,310,320,330,3223,4041,361,374,387,400,65535,65535,65535,65535,65535,65535,65535,65535,65535},
{2838,788,802,815,65535,65535,65535,65535,65535,65535,65535,65535,65535,65535,65535,65535,65535,65535,65535,65535,65535,65535,65535,65535,65535,65535,65535,65535,65535,65535,65535,65535,65535,65535,65535,65535,65535,65535,65535,65535,65535,65535,65535,65535,65535,65535,65535,65535},
{412,422,432,442,452,463,473,483,493,503,514,524,534,544,554,565,575,585,595,605,616,628,638,649,659,669,679,689,700,710,720,730,740,751,761,771,784,798,811,65535,65535,65535,65535,65535,65535,65535,65535,65535},
{3646,1199,1213,1226,65535,65535,65535,65535,65535,65535,65535,65535,65535,65535,65535,65535,65535,65535,65535,65535,65535,65535,65535,65535,65535,65535,65535,65535,65535,65535,65535,65535,65535,65535,65535,65535,65535,65535,65535,65535,65535,65535,65535,65535,65535,65535,65535,65535},
{824,834,845,855,865,876,886,896,906,917,927,937,947,957,968,978,988,998,1008,1019,1029,1041,1051,1062,1072,1082,1092,1103,1113,1123,1133,1143,1154,1164,1174,1184,1196,1210,1223,65535,65535,65535,65535,65535,65535,65535,65535,65535},
{1603,1612,1624,1638,65535,65535,65535,65535,65535,65535,65535,65535,65535,65535,65535,65535,65535,65535,65535,65535,65535,65535,65535,65535,65535,65535,65535,65535,65535,65535,65535,65535,65535,65535,65535,65535,65535,65535,65535,65535,65535,65535,65535,65535,65535,65535,65535,65535},
{1236,1247,1257,1267,1278,1288,1298,1308,1318,1329,1339,1349,1359,1369,1380,1390,1400,1410,1420,1431,1441,1453,1464,1474,1484,1494,1504,1515,1525,1535,1545,1555,1566,1576,1586,1596,1609,1622,1636,65535,65535,65535,65535,65535,65535,65535,65535,65535},
{2015,2024,2037,2050,65535,65535,65535,65535,65535,65535,65535,65535,65535,65535,65535,65535,65535,65535,65535,65535,65535,65535,65535,65535,65535,65535,65535,65535,65535,65535,65535,65535,65535,65535,65535,65535,65535,65535,65535,65535,65535,65535,65535,65535,65535,65535,65535,65535},
{1648,1659,1669,1680,1690,1700,1710,1720,1731,1741,1751,1761,1771,1782,1792,1802,1812,1822,1833,1843,1853,1865,1876,1886,1896,1906,1917,1927,1937,1947,1957,1968,1978,1988,1998,2008,2021,2035,2048,65535,65535,65535,65535,65535,65535,65535,65535,65535},
{4058,2436,2449,2462,65535,65535,65535,65535,65535,65535,65535,65535,65535,65535,65535,65535,65535,65535,65535,65535,65535,65535,65535,65535,65535,65535,65535,65535,65535,65535,65535,65535,65535,65535,65535,65535,65535,65535,65535,65535,65535,65535,65535,65535,65535,65535,65535,65535},
{2060,2071,2081,2092,2102,2112,2122,2132,2143,2153,2163,2173,2183,2194,2204,2214,2224,2234,2245,2255,2265,2277,2288,2298,2308,2318,2329,2339,2349,2359,2369,2380,2390,2400,2410,2420,2433,2447,2460,65535,65535,65535,65535,65535,65535,65535,65535,65535},
{2839,3656,2861,2874,65535,65535,65535,65535,65535,65535,65535,65535,65535,65535,65535,65535,65535,65535,65535,65535,65535,65535,65535,65535,65535,65535,65535,65535,65535,65535,65535,65535,65535,65535,65535,65535,65535,65535,65535,65535,65535,65535,65535,65535,65535,65535,65535,65535},
{2472,3303,3313,3323,3333,3343,2534,3364,3374,3384,3394,2585,3415,3425,3435,3445,2636,3466,3476,3486,2677,2690,3507,3517,2720,3538,3548,3558,3568,2771,3589,3599,3609,3619,2822,3640,3654,2859,2872,65535,65535,65535,65535,65535,65535,65535,65535,65535},
{3251,4068,3273,3286,65535,65535,65535,65535,65535,65535,65535,65535,65535,65535,65535,65535,65535,65535,65535,65535,65535,65535,65535,65535,65535,65535,65535,65535,65535,65535,65535,65535,65535,65535,65535,65535,65535,65535,65535,65535,65535,65535,65535,65535,65535,65535,65535,65535},
{2884,2895,2905,3735,3745,3755,2946,2956,2966,2976,3806,2997,3007,3017,3027,3857,3048,3058,3068,3078,3089,3909,3919,3929,3132,3142,3152,3162,3980,3183,3193,3203,3213,4031,3234,3244,4065,3270,4091,65535,65535,65535,65535,65535,65535,65535,65535,65535},
{368,378,390,3682,65535,65535,65535,65535,65535,65535,65535,65535,65535,65535,65535,65535,65535,65535,65535,65535,65535,65535,65535,65535,65535,65535,65535,65535,65535,65535,65535,65535,65535,65535,65535,65535,65535,65535,65535,65535,65535,65535,65535,65535,65535,65535,65535,65535},
{1,3715,3725,33,43,53,63,3776,3786,3796,104,114,3827,3837,3847,155,165,3878,3888,3898,206,219,229,239,249,3950,3960,3970,290,300,4001,4011,4021,341,351,4052,375,4078,401,65535,65535,65535,65535,65535,65535,65535,65535,65535},
{780,789,3669,4094,65535,65535,65535,65535,65535,65535,65535,65535,65535,65535,65535,65535,65535,65535,65535,65535,65535,65535,65535,65535,65535,65535,65535,65535,65535,65535,65535,65535,65535,65535,65535,65535,65535,65535,65535,65535,65535,65535,65535,65535,65535,65535,65535,65535},
{413,423,433,443,453,464,474,484,494,504,515,525,535,545,555,566,576,586,596,606,617,629,639,650,660,670,680,690,701,711,721,731,741,752,762,772,785,799,812,65535,65535,65535,65535,65535,65535,65535,65535,65535},
{1192,1200,1214,1227,65535,65535,65535,65535,65535,65535,65535,65535,65535,65535,65535,65535,65535,65535,65535,65535,65535,65535,65535,65535,65535,65535,65535,65535,65535,65535,65535,65535,65535,65535,65535,65535,65535,65535,65535,65535,65535,65535,65535,65535,65535,65535,65535,65535},
{825,835,846,856,866,877,887,897,907,918,928,938,948,958,969,979,989,999,1009,1020,1030,1042,1052,1063,1073,1083,1093,1104,1114,1124,1134,1144,1155,1165,1175,1185,1197,1211,1224,65535,65535,65535,65535,65535,65535,65535,65535,65535},
{1604,1613,1625,1639,65535,65535,65535,65535,65535,65535,65535,65535,65535,65535,65535,65535,65535,65535,65535,65535,65535,65535,65535,65535,65535,65535,65535,65535,65535,65535,65535,65535,65535,65535,65535,65535,65535,65535,65535,65535,65535,65535,65535,65535,65535,65535,65535,65535},
{1237,1248,1258,1268,1279,1289,1299,1309,1319,1330,1340,1350,1360,1370,1381,1391,1401,1411,1421,1432,1442,1454,1465,1475,1485,1495,1505,1516,1526,1536,1546,1556,1567,1577,1587,1597,1610,1623,1637,65535,65535,65535,65535,65535,65535,65535,65535,65535},
{2016,2025,2038,2051,65535,65535,65535,65535,65535,65535,65535,65535,65535,65535,65535,65535,65535,65535,65535,65535,65535,65535,65535,65535,65535,65535,65535,65535,65535,65535,65535,65535,65535,65535,65535,65535,65535,65535,65535,65535,65535,65535,65535,65535,65535,65535,65535,65535},
{1649,1660,1670,1681,1691,1701,1711,1721,1732,1742,1752,1762,1772,1783,1793,1803,1813,1823,1834,1844,1854,1866,1877,1887,1897,1907,1918,1928,1938,1948,1958,1969,1979,1989,1999,2009,2022,2036,2049,65535,65535,65535,65535,65535,65535,65535,65535,65535},
{2428,2437,2450,2463,65535,65535,65535,65535,65535,65535,65535,65535,65535,65535,65535,65535,65535,65535,65535,65535,65535,65535,65535,65535,65535,65535,65535,65535,65535,65535,65535,65535,65535,65535,65535,65535,65535,65535,65535,65535,65535,65535,65535,65535,65535,65535,65535,65535},
{2061,2072,2082,2093,2103,2113,2123,2133,2144,2154,2164,2174,2184,2195,2205,2215,2225,2235,2246,2256,2266,2278,2289,2299,2309,2319,2330,2340,2350,2360,2370,2381,2391,2401,2411,2421,2434,2448,2461,65535,65535,65535,65535,65535,65535,65535,65535,65535},
{3647,2849,2862,2875,65535,65535,65535,65535,65535,65535,65535,65535,65535,65535,65535,65535,65535,65535,65535,65535,65535,65535,65535,65535,65535,65535,65535,65535,65535,65535,65535,65535,65535,65535,65535,65535,65535,65535,65535,65535,65535,65535,65535,65535,65535,65535,65535,65535},
{2473,2484,2494,2504,3334,3344,2535,2545,2555,2565,3395,2586,2596,2606,2616,3446,2637,2647,2657,2667,2678,3498,3508,3518,2721,2731,2741,2751,3569,2772,2782,2792,2802,3620,2823,2833,2847,3667,3680,65535,65535,65535,65535,65535,65535,65535,65535,65535},
{4059,3261,4081,3287,65535,65535,65535,65535,65535,65535,65535,65535,65535,65535,65535,65535,65535,65535,65535,65535,65535,65535,65535,65535,65535,65535,65535,65535,65535,65535,65535,65535,65535,65535,65535,65535,65535,65535,65535,65535,65535,65535,65535,65535,65535,65535,65535,65535},
{2885,2896,2906,2916,2926,2936,3766,2957,2967,2977,2987,3817,3008,3018,3028,3038,3868,3059,3069,3079,3090,3910,3112,3122,3940,3143,3153,3163,3173,3991,3194,3204,3214,3224,4042,3245,4066,3271,4092,65535,65535,65535,65535,65535,65535,65535,65535,65535},
{369,3657,391,404,65535,65535,65535,65535,65535,65535,65535,65535,65535,65535,65535,65535,65535,65535,65535,65535,65535,65535,65535,65535,65535,65535,65535,65535,65535,65535,65535,65535,65535,65535,65535,65535,65535,65535,65535,65535,65535,65535,65535,65535,65535,65535,65535,65535},
{2,13,23,3324,3746,3756,64,3365,3375,3385,3807,115,3416,3426,3436,3858,166,3467,3477,3487,208,220,3920,3930,250,3539,3549,3559,3981,301,3590,3600,3610,4032,352,3641,376,4079,402,65535,65535,65535,65535,65535,65535,65535,65535,65535},
{781,790,803,816,65535,65535,65535,65535,65535,65535,65535,65535,65535,65535,65535,65535,65535,65535,65535,65535,65535,65535,65535,65535,65535,65535,65535,65535,65535,65535,65535,65535,65535,65535,65535,65535,65535,65535,65535,65535,65535,65535,65535,65535,65535,65535,65535,65535},
{414,424,434,444,454,465,475,485,495,505,516,526,536,546,556,567,577,587,597,607,618,630,640,651,661,671,681,691,702,712,722,732,742,753,763,773,786,800,813,65535,65535,65535,65535,65535,65535,65535,65535,65535},
{1193,1201,1215,1228,65535,65535,65535,65535,65535,65535,65535,65535,65535,65535,65535,65535,65535,65535,65535,65535,65535,65535,65535,65535,65535,65535,65535,65535,65535,65535,65535,65535,65535,65535,65535,65535,65535,65535,65535,65535,65535,65535,65535,65535,65535,65535,65535,65535},
{826,836,847,857,867,878,888,898,908,3797,929,939,949,959,3848,980,990,1000,1010,3899,1031,1043,1053,1064,1074,1084,1094,3971,1115,1125,1135,1145,4022,1166,1176,1186,1198,1212,1225,65535,65535,65535,65535,65535,65535,65535,65535,65535},
{1605,1614,1626,1640,65535,65535,65535,65535,65535,65535,65535,65535,65535,65535,65535,65535,65535,65535,65535,65535,65535,65535,65535,65535,65535,65535,65535,65535,65535,65535,65535,65535,65535,65535,65535,65535,65535,65535,65535,65535,65535,65535,65535,65535,65535,65535,65535,65535},
{1238,1249,1259,1269,1280,1290,1300,1310,1320,1331,1341,1351,1361,1371,1382,1392,1402,1412,1422,1433,1443,1455,1466,1476,1486,1496,1506,1517,1527,1537,1547,1557,1568,1578,1588,1598,1611,1627,1641,65535,65535,65535,65535,65535,65535,65535,65535,65535},
{2017,2026,2039,2052,65535,65535,65535,65535,65535,65535,65535,65535,65535,65535,65535,65535,65535,65535,65535,65535,65535,65535,65535,65535,65535,65535,65535,65535,65535,65535,65535,65535,65535,65535,65535,65535,65535,65535,65535,65535,65535,65535,65535,65535,65535,65535,65535,65535},
{1650,1661,1671,3736,1692,1702,1712,1722,1733,1743,1753,1763,1773,1784,1794,1804,1814,1824,1835,1845,1855,1867,1878,1888,1898,1908,1919,1929,1939,1949,1959,1970,1980,1990,2000,2010,2023,4082,2053,65535,65535,65535,65535,65535,65535,65535,65535,65535},
{2429,2438,2451,2464,65535,65535,65535,65535,65535,65535,65535,65535,65535,65535,65535,65535,65535,65535,65535,65535,65535,65535,65535,65535,65535,65535,65535,65535,65535,65535,65535,65535,65535,65535,65535,65535,65535,65535,65535,65535,65535,65535,65535,65535,65535,65535,65535,65535},
{2062,2073,2083,2094,2104,2114,2124,2134,2145,2155,2165,2175,2185,2196,2206,2216,2226,2236,2247,2257,2267,2279,2290,2300,2310,2320,2331,2341,2351,2361,2371,2382,2392,2402,2412,2422,2435,2452,2465,65535,65535,65535,65535,65535,65535,65535,65535,65535},
{2840,2850,3670,3683,65535,65535,65535,65535,65535,65535,65535,65535,65535,65535,65535,65535,65535,65535,65535,65535,65535,65535,65535,65535,65535,65535,65535,65535,65535,65535,65535,65535,65535,65535,65535,65535,65535,65535,65535,65535,65535,65535,65535,65535,65535,65535,65535,65535},
{2474,3304,3314,2505,2515,2525,3355,2546,2556,2566,2576,3406,2597,2607,2617,2627,3457,2648,2658,2668,2679,2691,2701,2711,3529,2732,2742,2752,2762,3580,2783,2793,2803,2813,3631,2834,3655,2860,2873,65535,65535,65535,65535,65535,65535,65535,65535,65535},
{3252,4069,3274,4095,65535,65535,65535,65535,65535,65535,65535,65535,65535,65535,65535,65535,65535,65535,65535,65535,65535,65535,65535,65535,65535,65535,65535,65535,65535,65535,65535,65535,65535,65535,65535,65535,65535,65535,65535,65535,65535,65535,65535,65535,65535,65535,65535,65535},
{2886,3716,3726,2917,2927,2937,2947,3777,3787,2978,2988,2998,3828,3838,3029,3039,3049,3879,3889,3080,3091,3103,3113,3123,3133,3951,3961,3164,3174,3184,4002,4012,3215,3225,3235,4053,3259,3272,3285,65535,65535,65535,65535,65535,65535,65535,65535,65535},
{3,14,24,35,45,55,2948,3778,3788,96,106,2999,3829,3839,147,157,3050,3880,3890,198,210,2692,231,241,3134,3952,3962,282,292,3185,4003,4013,333,343,3236,4054,379,2863,2876,65535,65535,65535,65535,65535,65535,65535,65535,65535},
{4,3305,3727,34,44,54,65,75,85,95,105,116,126,136,146,156,167,177,187,197,209,221,230,240,251,261,271,281,291,302,312,322,332,342,353,363,377,392,405,65535,65535,65535,65535,65535,65535,65535,65535,65535},
{415,425,435,445,455,466,476,486,496,506,517,527,537,547,557,568,578,588,598,608,619,631,641,652,662,672,682,692,703,713,723,733,743,754,764,774,787,801,814,65535,65535,65535,65535,65535,65535,65535,65535,65535},
{416,426,436,446,456,467,477,487,497,507,518,528,538,548,558,569,579,589,599,609,620,632,642,653,663,673,683,693,704,714,724,734,744,755,765,775,791,804,817,65535,65535,65535,65535,65535,65535,65535,65535,65535},
{827,837,848,858,868,879,889,899,909,919,930,940,950,960,970,981,991,1001,1011,1021,1032,1044,1054,1065,1075,1085,1095,1105,1116,1126,1136,1146,1156,1167,1177,1187,1202,1216,1229,65535,65535,65535,65535,65535,65535,65535,65535,65535},
{828,838,849,859,869,2526,3356,900,910,920,2577,3407,951,961,971,2628,3458,1002,1012,1022,1033,1045,1055,2712,3530,1086,1096,1106,2763,3581,1137,1147,1157,2814,3632,1188,1203,3275,3288,65535,65535,65535,65535,65535,65535,65535,65535,65535},
{1239,1250,1260,1270,1281,1291,1301,1311,1321,1332,1342,1352,1362,1372,1383,1393,1403,1413,1423,1434,1444,1456,1467,1477,1487,1497,1507,1518,1528,1538,1548,1558,1569,1579,1589,1599,1615,1628,3684,65535,65535,65535,65535,65535,65535,65535,65535,65535},
{1240,3717,1261,1271,2516,2938,3768,1312,1322,2567,2989,3819,1363,1373,2618,3040,3870,1414,1424,2669,1445,1457,2702,3124,3942,1498,1508,2753,3175,3993,1549,1559,2804,3226,4044,1600,3262,3671,4096,65535,65535,65535,65535,65535,65535,65535,65535,65535},
{1651,1662,1672,1682,1693,1703,1713,1723,1734,1744,1754,1764,1774,1785,1795,1805,1815,1825,1836,1846,1856,1868,1879,1889,1899,1909,1920,1930,1940,1950,1960,1971,1981,1991,2001,2011,2027,2040,2054,65535,65535,65535,65535,65535,65535,65535,65535,65535},
{1652,1663,1673,1683,2928,3346,1714,1724,2557,2979,3397,1765,1775,2608,3030,3448,1816,1826,2659,3081,1857,1869,3114,3520,1900,1910,2743,3165,3571,1951,1961,2794,3216,3622,2002,2012,3658,4083,2877,65535,65535,65535,65535,65535,65535,65535,65535,65535},
{2063,2074,2084,2095,2105,2115,2125,2135,2146,2156,2166,2176,2186,2197,2207,2217,2227,2237,2248,2258,2268,2280,2291,2301,2311,2321,2332,2342,2352,2362,2372,2383,2393,2403,2413,2423,2439,2453,2466,65535,65535,65535,65535,65535,65535,65535,65535,65535},
{2064,2075,2085,2506,3336,3758,2126,2136,2969,3387,3809,2177,2187,3020,3438,3860,2228,2238,3071,3489,2269,2281,3510,3932,2312,2322,3155,3561,3983,2363,2373,3206,3612,4034,2414,2424,4070,2864,3289,65535,65535,65535,65535,65535,65535,65535,65535,65535},
{2845,2854,2867,2880,65535,65535,65535,65535,65535,65535,65535,65535,65535,65535,65535,65535,65535,65535,65535,65535,65535,65535,65535,65535,65535,65535,65535,65535,65535,65535,65535,65535,65535,65535,65535,65535,65535,65535,65535,65535,65535,65535,65535,65535,65535,65535,65535,65535},
{2475,2485,2495,3325,3335,3345,2536,3366,3376,3386,3396,2587,3417,3427,3437,3447,2638,3468,3478,3488,2680,3499,3509,3519,2722,3540,3550,3560,3570,2773,3591,3601,3611,3621,2824,3642,2848,3668,3681,65535,65535,65535,65535,65535,65535,65535,65535,65535},
{3256,3266,4087,4100,65535,65535,65535,65535,65535,65535,65535,65535,65535,65535,65535,65535,65535,65535,65535,65535,65535,65535,65535,65535,65535,65535,65535,65535,65535,65535,65535,65535,65535,65535,65535,65535,65535,65535,65535,65535,65535,65535,65535,65535,65535,65535,65535,65535},
{2887,2897,2907,3737,3747,3757,3767,2958,2968,3798,3808,3818,3009,3019,3849,3859,3869,3060,3070,3900,3092,3911,3921,3931,3941,3144,3154,3972,3982,3992,3195,3205,4023,4033,4043,3246,4067,4080,4093,65535,65535,65535,65535,65535,65535,65535,65535,65535},
{417,427,437,447,457,468,478,488,498,508,519,529,539,549,559,570,580,590,600,610,621,633,643,654,664,674,684,694,705,715,725,735,745,756,766,776,792,805,818,65535,65535,65535,65535,65535,65535,65535,65535,65535},
{2476,2486,2496,2918,3748,2527,2537,2547,3377,3799,2578,2588,2598,3428,3850,2629,2639,2649,3479,3901,622,3104,3922,2713,2723,2733,3551,3973,2764,2774,2784,3602,4024,2815,2825,2835,2851,3276,3685,65535,65535,65535,65535,65535,65535,65535,65535,65535},
{829,839,2908,3326,870,880,890,2959,3789,921,931,941,3010,3840,972,982,992,3061,3891,1023,1034,3500,1056,1066,1076,3145,3963,1107,1117,1127,3196,4014,1158,1168,1178,3247,1204,1217,1230,65535,65535,65535,65535,65535,65535,65535,65535,65535},
{2888,2898,3316,3738,2517,2939,2949,3367,911,2568,2990,3000,3418,962,2619,3041,3051,3469,1013,2670,2681,3912,2703,3125,3135,3541,1097,2754,3176,3186,3592,1148,2805,3227,3237,3643,3263,3672,4097,65535,65535,65535,65535,65535,65535,65535,65535,65535},
{1241,1251,3728,1272,3749,1293,1303,1313,3378,3800,1344,1354,1364,3429,3851,1395,1405,1415,3480,3902,1447,3501,3923,1479,1489,1499,3552,3974,1530,1540,1550,3603,4025,1581,1591,1601,1617,1630,1643,65535,65535,65535,65535,65535,65535,65535,65535,65535},
{3296,3306,1262,2507,1282,1292,1302,3779,1323,1333,1343,1353,3830,1374,1384,1394,1404,3881,1425,1435,1446,1458,1468,1478,1488,3953,1509,1519,1529,1539,4004,1560,1570,1580,1590,4055,1616,1629,1642,65535,65535,65535,65535,65535,65535,65535,65535,65535},
{1653,3718,1674,1684,1694,1704,1715,1725,1735,1745,1755,1766,1776,1786,1796,1806,1817,1827,1837,1847,1858,1870,1880,1890,1901,1911,1921,1931,1941,1952,1962,1972,1982,1992,2003,2013,2028,2041,2055,65535,65535,65535,65535,65535,65535,65535,65535,65535},
{3708,1664,3317,3739,1695,1705,2538,3368,3790,1746,1756,2589,3419,3841,1797,1807,2640,3470,3892,1848,1859,3913,1881,1891,2724,3542,3964,1932,1942,2775,3593,4015,1983,1993,2826,3644,2029,2042,3686,65535,65535,65535,65535,65535,65535,65535,65535,65535},
{2065,2076,3729,2097,2107,2117,2950,3780,2148,2158,2168,3001,3831,2199,2209,2219,3052,3882,2250,2260,2271,2283,2293,2303,3136,3954,2334,2344,2354,3187,4005,2385,2395,2405,3238,4056,2441,3277,4098,65535,65535,65535,65535,65535,65535,65535,65535,65535},
{2066,2487,2086,2096,2106,2116,2127,2137,2147,2157,2167,2178,2188,2198,2208,2218,2229,2239,2249,2259,2270,2282,2292,2302,2313,2323,2333,2343,2353,2364,2374,2384,2394,2404,2415,2425,2440,2454,2467,65535,65535,65535,65535,65535,65535,65535,65535,65535},
{3653,3662,3675,3688,65535,65535,65535,65535,65535,65535,65535,65535,65535,65535,65535,65535,65535,65535,65535,65535,65535,65535,65535,65535,65535,65535,65535,65535,65535,65535,65535,65535,65535,65535,65535,65535,65535,65535,65535,65535,65535,65535,65535,65535,65535,65535,65535,65535},
{2477,3307,2497,3327,3337,3347,3357,2548,2558,3388,3398,3408,2599,2609,3439,3449,3459,2650,2660,3490,2682,2693,3511,3521,3531,2734,2744,3562,3572,3582,2785,2795,3613,3623,3633,2836,3659,2865,2878,65535,65535,65535,65535,65535,65535,65535,65535,65535},
{4064,4074,3280,3293,65535,65535,65535,65535,65535,65535,65535,65535,65535,65535,65535,65535,65535,65535,65535,65535,65535,65535,65535,65535,65535,65535,65535,65535,65535,65535,65535,65535,65535,65535,65535,65535,65535,65535,65535,65535,65535,65535,65535,65535,65535,65535,65535,65535},
{2889,2899,2909,2919,2929,3759,3769,2960,2970,2980,3810,3820,3011,3021,3031,3861,3871,3062,3072,3082,3093,3105,3115,3933,3943,3146,3156,3166,3984,3994,3197,3207,3217,4035,4045,3248,4071,4084,3290,65535,65535,65535,65535,65535,65535,65535,65535,65535},
{418,428,439,449,459,2528,3358,490,500,510,2579,3409,541,551,561,2630,3460,592,602,612,3094,635,645,2714,3532,676,686,696,2765,3583,727,737,747,2816,3634,778,2852,3673,820,65535,65535,65535,65535,65535,65535,65535,65535,65535},
{3297,3719,438,448,458,469,479,489,499,509,520,530,540,550,560,571,581,591,601,611,623,634,644,655,665,675,685,695,706,716,726,736,746,757,767,777,793,806,819,65535,65535,65535,65535,65535,65535,65535,65535,65535},
{830,840,850,860,871,881,891,901,912,922,932,942,952,963,973,983,993,1003,1014,1024,1035,1046,1057,1067,1077,1087,1098,1108,1118,1128,1138,1149,1159,1169,1179,1189,1205,1218,1231,65535,65535,65535,65535,65535,65535,65535,65535,65535},
{3709,841,851,861,2518,2940,3770,902,2559,2569,2991,3821,953,2610,2620,3042,3872,1004,2661,2671,1036,1047,2704,3126,3944,1088,2745,2755,3177,3995,1139,2796,2806,3228,4046,1190,3264,4085,1232,65535,65535,65535,65535,65535,65535,65535,65535,65535},
{1242,1252,1263,1273,1283,3348,1304,1314,1324,1334,3399,1355,1365,1375,1385,3450,1406,1416,1426,1436,1448,1459,1469,3522,1490,1500,1510,1520,3573,1541,1551,1561,1571,3624,1592,1602,3660,1631,1644,65535,65535,65535,65535,65535,65535,65535,65535,65535},
{1243,1253,2498,2508,2930,3760,2539,2549,2971,2981,3811,2590,2600,3022,3032,3862,2641,2651,3073,3083,2683,2694,3116,3934,2725,2735,3157,3167,3985,2776,2786,3208,3218,4036,2827,2837,4072,2866,2879,65535,65535,65535,65535,65535,65535,65535,65535,65535},
{1654,1665,1675,1685,3338,1706,1716,1726,1736,3389,1757,1767,1777,1787,3440,1808,1818,1828,1838,3491,1860,1871,3512,1892,1902,1912,1922,3563,1943,1953,1963,1973,3614,1994,2004,2014,2030,2043,2056,65535,65535,65535,65535,65535,65535,65535,65535,65535},
{1655,2488,2910,2920,3750,2529,2951,2961,3379,3801,2580,3002,3012,3430,3852,2631,3053,3063,3481,3903,3095,3106,3924,2715,3137,3147,3553,3975,2766,3188,3198,3604,4026,2817,3239,3249,2853,3278,3291,65535,65535,65535,65535,65535,65535,65535,65535,65535},
{2067,2077,2087,3328,2108,2119,2129,2139,2149,3390,2170,2180,2190,2200,3441,2221,2231,2241,2251,3492,2273,2284,3513,2305,2315,2325,2335,3564,2356,2366,2376,2386,3615,2407,2417,2427,2443,2456,2469,65535,65535,65535,65535,65535,65535,65535,65535,65535},
{2478,2900,3318,3740,2519,2118,2128,2138,3791,2159,2169,2179,2189,3842,2210,2220,2230,2240,3893,2261,2272,3502,2294,2304,2314,2324,3965,2345,2355,2365,2375,4016,2396,2406,2416,2426,2442,2455,2468,65535,65535,65535,65535,65535,65535,65535,65535,65535},
{2846,2855,2868,2881,65535,65535,65535,65535,65535,65535,65535,65535,65535,65535,65535,65535,65535,65535,65535,65535,65535,65535,65535,65535,65535,65535,65535,65535,65535,65535,65535,65535,65535,65535,65535,65535,65535,65535,65535,65535,65535,65535,65535,65535,65535,65535,65535,65535},
{3298,3308,2499,2509,3339,3349,3359,3369,2560,2570,3400,3410,3420,2611,2621,3451,3461,3471,2662,2672,2684,2695,2705,3523,3533,3543,2746,2756,3574,3584,3594,2797,2807,3625,3635,3645,3661,3674,3687,65535,65535,65535,65535,65535,65535,65535,65535,65535},
{3257,3267,4088,4101,65535,65535,65535,65535,65535,65535,65535,65535,65535,65535,65535,65535,65535,65535,65535,65535,65535,65535,65535,65535,65535,65535,65535,65535,65535,65535,65535,65535,65535,65535,65535,65535,65535,65535,65535,65535,65535,65535,65535,65535,65535,65535,65535,65535},
{2890,3720,3730,2921,2931,2941,3771,3781,2972,2982,2992,3822,3832,3023,3033,3043,3873,3883,3074,3084,3096,3914,3117,3127,3945,3955,3158,3168,3178,3996,4006,3209,3219,3229,4047,4057,3265,4086,4099,65535,65535,65535,65535,65535,65535,65535,65535,65535},
{419,429,440,3329,461,471,481,2550,3380,512,522,532,2601,3431,563,573,583,2652,3482,614,625,3503,647,657,667,2736,3554,698,708,718,2787,3605,749,759,769,3648,795,808,822,65535,65535,65535,65535,65535,65535,65535,65535,65535},
{3710,430,2911,450,460,470,480,491,501,511,521,531,542,552,562,572,582,593,603,613,624,636,646,656,666,677,687,697,707,717,728,738,748,758,768,779,794,807,821,65535,65535,65535,65535,65535,65535,65535,65535,65535},
{831,842,852,863,873,883,893,3370,914,924,934,944,3421,965,975,985,995,3472,1016,1026,1038,3915,1059,1069,1079,3544,1100,1110,1120,1130,3595,1151,1161,1171,1181,4060,1207,1220,1234,65535,65535,65535,65535,65535,65535,65535,65535,65535},
{832,2489,3319,862,872,882,892,903,913,923,933,943,954,964,974,984,994,1005,1015,1025,1037,1048,1058,1068,1078,1089,1099,1109,1119,1129,1140,1150,1160,1170,1180,1191,1206,1219,1233,65535,65535,65535,65535,65535,65535,65535,65535,65535},
{1244,3309,1265,1274,1284,1294,1305,1315,1325,1335,1345,1356,1366,1376,1386,1396,1407,1417,1427,1437,1449,1460,1470,1480,1491,1501,1511,1521,1531,1542,1552,1562,1572,1582,1593,1606,1618,1632,1645,65535,65535,65535,65535,65535,65535,65535,65535,65535},
{2479,1254,1264,1275,1285,1295,2540,3782,1326,1336,1346,2591,3833,1377,1387,1397,2642,3884,1428,1438,1450,1461,1471,1481,2726,3956,1512,1522,1532,2777,4007,1563,1573,1583,2828,2841,1619,1633,1646,65535,65535,65535,65535,65535,65535,65535,65535,65535},
{1656,3721,1677,1686,1696,1707,1717,1727,1737,1747,1758,1768,1778,1788,1798,1809,1819,1829,1839,1849,1861,1872,1882,1893,1903,1913,1923,1933,1944,1954,1964,1974,1984,1995,2005,2018,2031,2044,2057,65535,65535,65535,65535,65535,65535,65535,65535,65535},
{2891,1666,1676,1687,1697,2530,3360,1728,1738,1748,2581,3411,1779,1789,1799,2632,3462,1830,1840,1850,1862,1873,1883,2716,3534,1914,1924,1934,2767,3585,1965,1975,1985,2818,3636,3253,2032,2045,2058,65535,65535,65535,65535,65535,65535,65535,65535,65535},
{2068,2079,2089,2098,2109,2942,3772,2140,2150,2160,2993,3823,2191,2201,2211,3044,3874,2242,2252,2262,2274,2285,2295,3128,3946,2326,2336,2346,3179,3997,2377,2387,2397,3230,4048,2430,2444,2457,2470,65535,65535,65535,65535,65535,65535,65535,65535,65535},
{3299,2078,2088,2099,2520,3350,2130,2551,2561,2571,3401,2181,2602,2612,2622,3452,2232,2653,2663,2673,2685,2696,2706,3524,2316,2737,2747,2757,3575,2367,2788,2798,2808,3626,2418,3649,3663,3676,3689,65535,65535,65535,65535,65535,65535,65535,65535,65535},
{2480,2490,2500,2510,3340,2531,2541,3371,3381,3391,2582,2592,3422,3432,3442,2633,2643,3473,3483,3493,2686,3504,3514,2717,2727,3545,3555,3565,2768,2778,3596,3606,3616,2819,2829,2842,2856,2869,2882,65535,65535,65535,65535,65535,65535,65535,65535,65535},
{3300,3310,3320,3330,2521,3351,3361,2552,2562,2572,3402,3412,2603,2613,2623,3453,3463,2654,2664,2674,2687,2697,2707,3525,3535,2738,2748,2758,3576,3586,2789,2799,2809,3627,3637,3650,3664,3677,3690,65535,65535,65535,65535,65535,65535,65535,65535,65535},
{3711,2901,3731,3741,3751,3761,2952,2962,3792,3802,3812,3003,3013,3843,3853,3863,3054,3064,3894,3904,3097,3107,3925,3935,3138,3148,3966,3976,3986,3189,3199,4017,4027,4037,3240,3250,4073,3279,3292,65535,65535,65535,65535,65535,65535,65535,65535,65535},
{2892,2902,2912,2922,2932,3762,2953,2963,2973,2983,3813,3004,3014,3024,3034,3864,3055,3065,3075,3085,3098,3108,3118,3936,3139,3149,3159,3169,3987,3190,3200,3210,3220,4038,3241,4061,4075,3281,3294,65535,65535,65535,65535,65535,65535,65535,65535,65535},
{420,431,441,451,3752,472,482,492,502,3803,523,533,543,553,3854,574,584,594,604,3905,626,637,3926,658,668,678,688,3977,709,719,729,739,4028,760,770,782,796,809,823,65535,65535,65535,65535,65535,65535,65535,65535,65535},
{421,3722,3732,3742,462,2943,3773,3783,3793,513,2994,3824,3834,3844,564,3045,3875,3885,3895,615,627,3916,648,3129,3947,3957,3967,699,3180,3998,4008,4018,750,3231,4049,783,797,810,4102,65535,65535,65535,65535,65535,65535,65535,65535,65535},
{833,843,853,864,874,884,894,904,915,925,935,945,955,966,976,986,996,1006,1017,1027,1039,1049,1060,1070,1080,1090,1101,1111,1121,1131,1141,1152,1162,1172,1182,1194,1208,1221,1235,65535,65535,65535,65535,65535,65535,65535,65535,65535},
{3712,844,854,3331,875,885,895,905,916,926,936,946,956,967,977,987,997,1007,1018,1028,1040,1050,1061,1071,1081,1091,1102,1112,1122,1132,1142,1153,1163,1173,1183,1195,1209,1222,3691,65535,65535,65535,65535,65535,65535,65535,65535,65535},
{1245,1255,1266,1276,1286,1296,1306,1316,1327,1337,1347,1357,1367,1378,1388,1398,1408,1418,1429,1439,1451,1462,1472,1482,1492,1502,1513,1523,1533,1543,1553,1564,1574,1584,1594,1607,1620,1634,1647,65535,65535,65535,65535,65535,65535,65535,65535,65535},
{1246,1256,3321,1277,1287,1297,1307,1317,1328,1338,1348,1358,1368,1379,1389,1399,1409,1419,1430,1440,1452,1463,1473,1483,1493,1503,1514,1524,1534,1544,1554,1565,1575,1585,1595,1608,1621,1635,3692,65535,65535,65535,65535,65535,65535,65535,65535,65535},
{1657,1667,1678,1688,1698,1708,1718,1729,1739,1749,1759,1769,1780,1790,1800,1810,1820,1831,1841,1851,1863,1874,1884,1894,1904,1915,1925,1935,1945,1955,1966,1976,1986,1996,2006,2019,2033,2046,2059,65535,65535,65535,65535,65535,65535,65535,65535,65535},
{1658,1668,1679,1689,1699,1709,1719,1730,1740,1750,1760,1770,1781,1791,1801,1811,1821,1832,1842,1852,1864,1875,1885,1895,1905,1916,1926,1936,1946,1956,1967,1977,1987,1997,2007,2020,2034,2047,4104,65535,65535,65535,65535,65535,65535,65535,65535,65535},
{2069,2080,2091,2101,2111,2121,3362,2142,2152,2162,2172,3413,2193,2203,2213,2223,3464,2244,2254,2264,2276,2287,2297,2307,3536,2328,2338,2348,2358,3587,2379,2389,2399,2409,3638,2432,2446,2459,3693,65535,65535,65535,65535,65535,65535,65535,65535,65535},
{2070,2491,2090,2100,2110,2120,2131,2141,2151,2161,2171,2182,2192,2202,2212,2222,2233,2243,2253,2263,2275,2286,2296,2306,2317,2327,2337,2347,2357,2368,2378,2388,2398,2408,2419,2431,2445,2458,2471,65535,65535,65535,65535,65535,65535,65535,65535,65535},
{2481,3311,2501,2511,3341,2532,2542,3372,3382,3392,2583,2593,3423,3433,3443,2634,2644,3474,3484,3494,2688,3505,3515,2718,2728,3546,3556,3566,2769,2779,3597,3607,3617,2820,2830,2843,2857,2870,2883,65535,65535,65535,65535,65535,65535,65535,65535,65535},
{3301,2492,2502,2512,2522,3352,2543,2553,2563,2573,3403,2594,2604,2614,2624,3454,2645,2655,2665,2675,3496,2698,2708,3526,2729,2739,2749,2759,3577,2780,2790,2800,2810,3628,2831,3651,3665,3678,3694,65535,65535,65535,65535,65535,65535,65535,65535,65535},
{2893,2903,2913,2923,2933,3763,2954,2964,2974,2984,3814,3005,3015,3025,3035,3865,3056,3066,3076,3086,3099,3109,3119,3937,3140,3150,3160,3170,3988,3191,3201,3211,3221,4039,3242,3254,3268,4089,3295,65535,65535,65535,65535,65535,65535,65535,65535,65535},
{3713,3723,3733,3743,3753,2944,3774,3784,3794,3804,2995,3825,3835,3845,3855,3046,3876,3886,3896,3906,3100,3917,3927,3130,3948,3958,3968,3978,3181,3999,4009,4019,4029,3232,4050,4062,4076,3282,4103,65535,65535,65535,65535,65535,65535,65535,65535,65535},
{2482,3312,3322,3332,3342,2533,3363,3373,3383,3393,2584,3414,3424,3434,3444,2635,3465,3475,3485,3495,2689,3506,3516,2719,3537,3547,3557,3567,2770,3588,3598,3608,3618,2821,3639,2844,2858,2871,4105,65535,65535,65535,65535,65535,65535,65535,65535,65535},
{3302,2493,2503,2513,2523,3353,2544,2554,2564,2574,3404,2595,2605,2615,2625,3455,2646,2656,2666,2676,3497,2699,2709,3527,2730,2740,2750,2760,3578,2781,2791,2801,2811,3629,2832,3652,3666,3679,3695,65535,65535,65535,65535,65535,65535,65535,65535,65535},
{2894,2904,2914,2924,2934,3764,2955,2965,2975,2985,3815,3006,3016,3026,3036,3866,3057,3067,3077,3087,3908,3110,3120,3938,3141,3151,3161,3171,3989,3192,3202,3212,3222,4040,3243,3255,3269,4090,4106,65535,65535,65535,65535,65535,65535,65535,65535,65535},
{3714,3724,3734,3744,3754,2945,3775,3785,3795,3805,2996,3826,3836,3846,3856,3047,3877,3887,3897,3907,3101,3918,3928,3131,3949,3959,3969,3979,3182,4000,4010,4020,4030,3233,4051,4063,4077,3283,4107,65535,65535,65535,65535,65535,65535,65535,65535,65535},
{5,15,25,36,46,56,66,76,86,97,107,117,127,137,148,158,168,178,188,199,211,222,232,242,252,262,272,283,293,303,313,323,334,344,354,364,380,393,406,65535,65535,65535,65535,65535,65535,65535,65535,65535},
{6,16,26,37,47,57,67,77,87,98,108,118,128,138,149,159,169,179,189,200,212,223,233,243,253,263,273,284,294,304,314,324,335,345,355,365,381,394,407,65535,65535,65535,65535,65535,65535,65535,65535,65535},
{7,17,27,38,48,58,68,78,88,99,109,119,129,139,150,160,170,180,190,201,213,224,234,244,254,264,274,285,295,305,315,325,336,346,356,366,382,395,408,65535,65535,65535,65535,65535,65535,65535,65535,65535},
{8,18,28,39,49,59,69,79,89,100,110,120,130,140,151,161,171,181,191,202,214,225,235,245,255,265,275,286,296,306,316,326,337,347,357,370,383,396,409,65535,65535,65535,65535,65535,65535,65535,65535,65535},
{9,19,29,40,50,60,70,80,90,101,111,121,131,141,152,162,172,182,192,203,215,226,236,246,256,266,276,287,297,307,317,327,338,348,358,371,384,397,410,65535,65535,65535,65535,65535,65535,65535,65535,65535},
{10,20,30,41,51,61,71,81,91,102,112,122,132,142,153,163,173,183,193,204,216,227,237,247,257,267,277,288,298,308,318,328,339,349,359,372,385,398,411,65535,65535,65535,65535,65535,65535,65535,65535,65535},
{11,21,31,42,52,62,72,82,92,103,113,123,133,143,154,164,174,184,194,205,217,228,238,248,258,268,278,289,299,309,319,329,340,350,360,373,386,399,65535,65535,65535,65535,65535,65535,65535,65535,65535,65535},
{12,3315,32,2514,2524,3354,74,84,94,2575,3405,125,135,145,2626,3456,176,186,196,207,3102,2700,2710,3528,260,270,280,2761,3579,311,321,331,2812,3630,362,3258,388,3284,65535,65535,65535,65535,65535,65535,65535,65535,65535,65535},
};

#define NG SCHED_NG
#define RING 16
#define NSLOT 8
#define CFETCH 5
#define TABLED 1
#define PROMO CU_TENSOR_MAP_L2_PROMOTION_L2_128B
#define AHEAD 6
#define CF0 5
#define CFS 2
#define ABL 0
#define CX 5
#define PUBN 2
#define PUBE 8
#define SCHED 9
#define OUT_TMA 0
#define JB1 21
#define JB2 24
#define CVAR 2
#define CFN 0
#define CREGS 224
#define CSLEEP 200
#define JB 18
#define JF 24
#define JR 17
#define HOIST 1
#define XEARLY 0
#define FPRED 1
#define LATERED 1
#define WDELAY 0
#define WDELAY2 0
#define PFX 0
#define FIRST 3
#define NODUMP 1
#define CH 64
#define NOJB 3
#define JFF 0
#define XPRED 0
#define W2X 2
#define RETRY 0
#define HMASK 0
#define GMASK 0
#define TRIG0 -1
#define NEARLY 3
#define NLATE 0
#define TRIG 8
constexpr int NCONV = 3 * NG;
constexpr int PLEN = SCHED_LE, LM = 256 - 2 * PLEN, NSEG = 4 / (NG - 8), LMID = NSEG * LM;
static_assert(LMID <= PLEN && (NG == 9 || NG == 10), "geometry");
constexpr int TILEB = 12288;
constexpr int SLOTB = 280 * 64;
constexpr int W1S = 0, W2S = 73728, ABUF = 147456, XBUF = ABUF + 16 * 3072, MISC = XBUF + 8 * 3072;
constexpr int WBAR = MISC + 2560;
constexpr int RBUF = ABUF - 4 * SLOTB;
constexpr int CM = MISC + 2816, CTAB = CM + 256;
constexpr int SMEM_BYTES = CTAB + (PLEN + 16) * 16;
static_assert(RBUF % 512 == 0 && RBUF >= W2S && RBUF + NSLOT * SLOTB + 128 <= MISC && SMEM_BYTES <= 232448, "smem layout");

struct Globals {
  unsigned char scratch[(RING * NG + 1) * 4 * TILEB];
  unsigned char wimg[147456];
  uint32_t wflag[32];
  uint32_t ready[NG * PLEN + 1];
  uint32_t cons[NG * PLEN];
  uint32_t epoch[1024];
};
__device__ __align__(1024) Globals g_state;

#define PROF_AT(cond, idx)
#define PROF_VAL(cond, idx, v)
#define PROF2_AT(c, i)
#define PROF2_VAL(c, i, v)
#define PROFS(i)
#define GELU_C3 0.32920349f
#define GELU_A2 0x40d940d9u
#define SCHED_FENCE() asm volatile("pmevent 0;" ::: "memory")
#define SPIN_LIMIT 0x1000000

__device__ __forceinline__ uint32_t smem_u32(const void* p) { return (uint32_t)__cvta_generic_to_shared(p); }
__device__ __forceinline__ void wg_fence() { asm volatile("wgmma.fence.sync.aligned;" ::: "memory"); }
__device__ __forceinline__ void wg_commit() { asm volatile("wgmma.commit_group.sync.aligned;" ::: "memory"); }
template <int N> __device__ __forceinline__ void wg_wait() { asm volatile("wgmma.wait_group.sync.aligned %0;" ::"n"(N) : "memory"); }
__device__ __forceinline__ void mbar_init(uint32_t bar, uint32_t cnt) { asm volatile("mbarrier.init.shared::cta.b64 [%0], %1;" ::"r"(bar), "r"(cnt) : "memory"); }
__device__ __forceinline__ void mbar_expect_tx(uint32_t bar, uint32_t bytes) { asm volatile("mbarrier.arrive.expect_tx.shared::cta.b64 _, [%0], %1;" ::"r"(bar), "r"(bytes) : "memory"); }
__device__ __forceinline__ void mbar_arrive(uint32_t bar) { asm volatile("mbarrier.arrive.shared::cta.b64 _, [%0];" ::"r"(bar) : "memory"); }
__device__ __forceinline__ void mbar_wait(uint32_t bar, uint32_t parity) {
  asm volatile("{\n.reg .pred p;\n.reg .u32 c;\nmbarrier.try_wait.parity.shared::cta.b64 p, [%0], %1;\n@p bra DONE_%=;\nmov.u32 c, 0;\nWAIT_%=:\nmbarrier.try_wait.parity.shared::cta.b64 p, [%0], %1;\n@p bra DONE_%=;\n"
               "add.u32 c, c, 1;\nsetp.lt.u32 p, c, 0x1000000;\n@p bra WAIT_%=;\ntrap;\nDONE_%=:\n}" ::"r"(bar), "r"(parity) : "memory");
}
__device__ __forceinline__ void bulk_g2s(uint32_t dst, const void* src, uint32_t bytes, uint32_t bar) {
  asm volatile("cp.async.bulk.shared::cluster.global.mbarrier::complete_tx::bytes [%0], [%1], %2, [%3];" ::"r"(dst), "l"(src), "r"(bytes), "r"(bar) : "memory");
}
__device__ __forceinline__ uint32_t ld_relaxed(const uint32_t* p) { uint32_t v; asm volatile("ld.relaxed.gpu.global.u32 %0, [%1];" : "=r"(v) : "l"(p) : "memory"); return v; }
__device__ __forceinline__ void red_add_elect(uint32_t* p) { asm volatile("{.reg .pred p; elect.sync _|p, 0xffffffff; @p red.relaxed.gpu.global.add.u32 [%0], 1;}" ::"l"(p) : "memory"); }
__device__ __forceinline__ void mbar_arrive_elect(uint32_t bar) { asm volatile("{.reg .pred p; elect.sync _|p, 0xffffffff; @p mbarrier.arrive.shared::cta.b64 _, [%0];}" ::"r"(bar) : "memory"); }
__device__ __forceinline__ void mbar_init_elect(uint32_t bar, uint32_t cnt) { asm volatile("{.reg .pred p; elect.sync _|p, 0xffffffff; @p mbarrier.init.shared::cta.b64 [%0], %1;}" ::"r"(bar), "r"(cnt) : "memory"); }
__device__ __forceinline__ void lds128(uint32_t* r, uint32_t a) { asm volatile("ld.shared.v4.b32 {%0,%1,%2,%3}, [%4];" : "=r"(r[0]), "=r"(r[1]), "=r"(r[2]), "=r"(r[3]) : "r"(a) : "memory"); }
__device__ __forceinline__ uint2 lds64(uint32_t a) { uint2 v; asm volatile("ld.shared.v2.b32 {%0,%1}, [%2];" : "=r"(v.x), "=r"(v.y) : "r"(a) : "memory"); return v; }
__device__ __forceinline__ uint32_t lds32(uint32_t a) { uint32_t v; asm volatile("ld.shared.b32 %0, [%1];" : "=r"(v) : "r"(a) : "memory"); return v; }
__device__ __forceinline__ void sts32(uint32_t a, uint32_t v) { asm volatile("st.shared.b32 [%0], %1;" ::"r"(a), "r"(v) : "memory"); }
__device__ __forceinline__ void sts128(uint32_t a, uint4 v) { asm volatile("st.shared.v4.b32 [%0], {%1,%2,%3,%4};" ::"r"(a), "r"(v.x), "r"(v.y), "r"(v.z), "r"(v.w) : "memory"); }
__device__ __forceinline__ uint4 ldg128v(const void* p) { uint4 v; asm volatile("ld.global.nc.v4.b32 {%0,%1,%2,%3}, [%4];" : "=r"(v.x), "=r"(v.y), "=r"(v.z), "=r"(v.w) : "l"(p) : "memory"); return v; }
__device__ __forceinline__ void stg128(void* p, uint4 v) { asm volatile("st.global.v4.b32 [%0], {%1,%2,%3,%4};" ::"l"(p), "r"(v.x), "r"(v.y), "r"(v.z), "r"(v.w) : "memory"); }
#define HINT 3
__device__ __forceinline__ uint64_t pol_evict_first() { uint64_t p; asm("createpolicy.fractional.L2::evict_first.b64 %0, 1.0;" : "=l"(p)); return p; }
__device__ __forceinline__ uint4 ldg128_last(const void* p, uint64_t pol) {
  if (!(HINT & 1)) return ldg128v(p);
  uint4 v; asm volatile("ld.global.nc.L1::no_allocate.L2::cache_hint.v4.b32 {%0,%1,%2,%3}, [%4], %5;" : "=r"(v.x), "=r"(v.y), "=r"(v.z), "=r"(v.w) : "l"(p), "l"(pol) : "memory"); return v;
}
__device__ __forceinline__ void stg128_stream(void* p, uint4 v, uint64_t pol) {
  if (!(HINT & 2)) { stg128(p, v); return; }
  asm volatile("st.global.L2::cache_hint.v4.b32 [%0], {%1,%2,%3,%4}, %5;" ::"l"(p), "r"(v.x), "r"(v.y), "r"(v.z), "r"(v.w), "l"(pol) : "memory");
}
__device__ __forceinline__ float bf_lo(uint32_t w) { return __uint_as_float(w << 16); }
__device__ __forceinline__ float bf_hi(uint32_t w) { return __uint_as_float(w & 0xffff0000u); }
__device__ __forceinline__ uint32_t pack_f16(float lo, float hi) { uint32_t d; asm("cvt.rn.f16x2.f32 %0, %1, %2;" : "=r"(d) : "f"(hi), "f"(lo)); return d; }
__device__ __forceinline__ uint32_t pack_f16_sat(float lo, float hi) { uint32_t d; asm("cvt.rn.satfinite.f16x2.f32 %0, %1, %2;" : "=r"(d) : "f"(hi), "f"(lo)); return d; }
__device__ __forceinline__ uint32_t pack_bf16(float lo, float hi) { uint32_t d; asm("cvt.rn.bf16x2.f32 %0, %1, %2;" : "=r"(d) : "f"(hi), "f"(lo)); return d; }
__device__ __forceinline__ uint32_t hadd2_bf16(uint32_t a, uint32_t b) { uint32_t d; asm("add.rn.bf16x2 %0, %1, %2;" : "=r"(d) : "r"(a), "r"(b)); return d; }
__device__ __forceinline__ uint32_t h2add(uint32_t a, uint32_t b) { uint32_t d; asm("add.rn.f16x2 %0, %1, %2;" : "=r"(d) : "r"(a), "r"(b)); return d; }
__device__ __forceinline__ uint32_t h2mul(uint32_t a, uint32_t b) { uint32_t d; asm("mul.rn.f16x2 %0, %1, %2;" : "=r"(d) : "r"(a), "r"(b)); return d; }
__device__ __forceinline__ uint32_t h2fma(uint32_t a, uint32_t b, uint32_t c) { uint32_t d; asm("fma.rn.f16x2 %0, %1, %2, %3;" : "=r"(d) : "r"(a), "r"(b), "r"(c)); return d; }
__device__ __forceinline__ uint32_t h2lo(uint32_t a) { uint32_t d; asm("{.reg .f16 l,h; mov.b32 {l,h}, %1; mov.b32 %0, {l,l};}" : "=r"(d) : "r"(a)); return d; }
__device__ __forceinline__ uint32_t h2hi(uint32_t a) { uint32_t d; asm("{.reg .f16 l,h; mov.b32 {l,h}, %1; mov.b32 %0, {h,h};}" : "=r"(d) : "r"(a)); return d; }
__device__ __forceinline__ float h_lo(uint32_t a) { float d; asm("{.reg .f16 l,h; mov.b32 {l,h}, %1; cvt.f32.f16 %0, l;}" : "=f"(d) : "r"(a)); return d; }
__device__ __forceinline__ float h_hi(uint32_t a) { float d; asm("{.reg .f16 l,h; mov.b32 {l,h}, %1; cvt.f32.f16 %0, h;}" : "=f"(d) : "r"(a)); return d; }
__device__ __forceinline__ uint32_t prmt(uint32_t a, uint32_t b, uint32_t s) { uint32_t d; asm("prmt.b32 %0, %1, %2, %3;" : "=r"(d) : "r"(a), "r"(b), "r"(s)); return d; }
__device__ __forceinline__ void mma_sp(float* d, const uint32_t* a, const uint32_t* b, const float* c, uint32_t e) {
  asm("mma.sp::ordered_metadata.sync.aligned.m16n8k32.row.col.f32.bf16.bf16.f32 {%0,%1,%2,%3}, {%4,%5,%6,%7}, {%8,%9,%10,%11}, {%12,%13,%14,%15}, %16, 0;"
      : "=f"(d[0]), "=f"(d[1]), "=f"(d[2]), "=f"(d[3])
      : "r"(a[0]), "r"(a[1]), "r"(a[2]), "r"(a[3]), "r"(b[0]), "r"(b[1]), "r"(b[2]), "r"(b[3]), "f"(c[0]), "f"(c[1]), "f"(c[2]), "f"(c[3]), "r"(e));
}
__device__ __forceinline__ uint32_t bf2_to_h2(uint32_t w, float s) { return pack_f16(bf_lo(w) * s, bf_hi(w) * s); }
__device__ __forceinline__ uint32_t bf2_to_h2(uint32_t w) { return pack_f16(bf_lo(w), bf_hi(w)); }

__device__ __forceinline__ uint32_t gelu_h2(uint32_t y) {
  uint32_t t, u, th, g;
  asm volatile("fma.rn.f16x2 %0, %1, %1, %2;" : "=r"(t) : "r"(y), "r"(GELU_A2));
  asm volatile("mul.rn.f16x2 %0, %1, %2;" : "=r"(u) : "r"(y), "r"(t));
  asm volatile("tanh.approx.f16x2 %0, %1;" : "=r"(th) : "r"(u));
  asm volatile("fma.rn.f16x2 %0, %1, %2, %1;" : "=r"(g) : "r"(y), "r"(th));
  return GMASK ? g & GMASK : g;
}

__device__ __forceinline__ void copy_weights(uint32_t sb, int piece, const void* src) {
  asm volatile("{\n.reg .pred p;\nelect.sync _|p, 0xffffffff;\n@p mbarrier.init.shared::cta.b64 [%1], 1;\n@p fence.mbarrier_init.release.cluster;\n"
               "@p mbarrier.arrive.expect_tx.shared::cta.b64 _, [%1], 12288;\n"
               "@p cp.async.bulk.shared::cluster.global.mbarrier::complete_tx::bytes [%0], [%2], 12288, [%1];\n}"
               ::"r"(sb + piece * 12288), "r"(sb + WBAR + piece * 8), "l"(src) : "memory");
}
__device__ __forceinline__ void convert_weights(uint32_t sb, uint32_t wbar, int rot, int warp, int lane) {
  if (warp < 12) {
    const int l8 = lane & 7, q4 = lane >> 3;
    int s = (warp >> 1) + rot; if (s >= 6) s -= 6;
    const uint32_t base = sb + W1S + s * 12288 + (warp & 1) * 384;
    mbar_wait(wbar + s * 8, 0);
    uint32_t v[3][4][4];
#pragma unroll
    for (int r = 0; r < 4; r++)
#pragma unroll
      for (int i = 0; i < 3; i++) lds128(v[i][r], base + i * 128 + (4 * (l8 >> 1) + 2 * (r & 1) + (l8 & 1)) * 768 + ((l8 + q4 + 4 * (r >> 1)) & 7) * 16);
    __syncwarp();
#pragma unroll
    for (int r = 0; r < 4; r++)
#pragma unroll
      for (int i = 0; i < 3; i++)
        sts128(base + i * 128 + (((l8 + q4 + 4 * (r >> 1)) & 7) + 8 * (r & 1)) * 768 + l8 * 16,
               make_uint4(bf2_to_h2(v[i][r][0]), bf2_to_h2(v[i][r][1]), bf2_to_h2(v[i][r][2]), bf2_to_h2(v[i][r][3])));
  }
  PROF2_AT(lane == 0, 440 + warp);
  const int q = lane & 3, t = (lane >> 2) & 3, b = lane >> 4;
  int u = 3 * (warp ^ 15) + 8 * rot; if (u >= 48) u -= 48;
  uint32_t base[3], v[3][4][3];
#pragma unroll
  for (int i = 0; i < 3; i++) {
    const int ui = u + i >= 48 ? u + i - 48 : u + i;
    base[i] = sb + W2S + ui * 1536;
    if (i != 1) mbar_wait(wbar + 48 + (ui >> 3) * 8, 0);
  }
#pragma unroll
  for (int i = 0; i < 3; i++)
#pragma unroll
    for (int d = 0; d < 4; d++)
#pragma unroll
      for (int j = 0; j < 3; j++) v[i][d][j] = lds32(base[i] + (2 * ((q + d) & 3) + b) * 192 + j * 64 + t * 16 + q * 4);
  __syncwarp();
#pragma unroll
  for (int i = 0; i < 3; i++)
#pragma unroll
    for (int d = 0; d < 4; d++)
#pragma unroll
      for (int j = 0; j < 3; j++) sts32(base[i] + (4 * j + q) * 128 + (2 * ((q + d) & 3) + b) * 16 + t * 4, W2X ? bf2_to_h2(v[i][d][j]) : bf2_to_h2(v[i][d][j], 0.5f / GELU_C3));
}

__device__ __noinline__ void ln_wide(uint32_t ad) {
  float m[2], r[2];
#pragma unroll
  for (int hi = 0; hi < 2; hi++) {
    float sm = 0.f;
    for (int s = 0; s < 6; s++) { uint2 w = lds64(ad + s * 512 + hi * 8); sm += (h_lo(w.x) + h_hi(w.x)) + (h_lo(w.y) + h_hi(w.y)); }
    sm += __shfl_xor_sync(0xffffffffu, sm, 1); sm += __shfl_xor_sync(0xffffffffu, sm, 2);
    m[hi] = sm * (1.f / 96.f);
    float q = 0.f;
    for (int s = 0; s < 6; s++) {
      uint2 w = lds64(ad + s * 512 + hi * 8);
      float d0 = h_lo(w.x) - m[hi], d1 = h_hi(w.x) - m[hi], d2 = h_lo(w.y) - m[hi], d3 = h_hi(w.y) - m[hi];
      q += (d0 * d0 + d1 * d1) + (d2 * d2 + d3 * d3);
    }
    q += __shfl_xor_sync(0xffffffffu, q, 1); q += __shfl_xor_sync(0xffffffffu, q, 2);
    r[hi] = rsqrtf(fmaf(q, 1.f / 96.f, 1e-5f)) * GELU_C3;
  }
  for (int s = 0; s < 6; s++) {
    uint32_t w[4]; lds128(w, ad + s * 512);
    sts128(ad + s * 512, make_uint4(pack_f16((h_lo(w[0]) - m[0]) * r[0], (h_hi(w[0]) - m[0]) * r[0]), pack_f16((h_lo(w[2]) - m[1]) * r[1], (h_hi(w[2]) - m[1]) * r[1]),
                                    pack_f16((h_lo(w[1]) - m[0]) * r[0], (h_hi(w[1]) - m[0]) * r[0]), pack_f16((h_lo(w[3]) - m[1]) * r[1], (h_hi(w[3]) - m[1]) * r[1])));
  }
  asm volatile("fence.proxy.async.shared::cta;" ::: "memory");
}

__device__ __forceinline__ float rsqrt_fast(float v) { float r; asm("rsqrt.approx.ftz.f32 %0, %1;" : "=f"(r) : "f"(v)); return r; }
__device__ __forceinline__ uint32_t layer_norm(uint32_t (&raw)[6][4], uint32_t* a, uint32_t tag) {
  const uint32_t stale = ((raw[0][0] ^ tag) | (raw[1][0] ^ tag)) | ((raw[2][0] ^ tag) | (raw[3][0] ^ tag)) | ((raw[4][0] ^ tag) | (raw[5][0] ^ tag));
  uint32_t sm[2];
#pragma unroll
  for (int hi = 0; hi < 2; hi++) {
    uint32_t s0 = h2add(raw[0][2 * hi], raw[1][2 * hi]), s1 = h2add(raw[0][2 * hi + 1], raw[1][2 * hi + 1]);
    uint32_t s2 = h2add(raw[2][2 * hi], raw[3][2 * hi]), s3 = h2add(raw[2][2 * hi + 1], raw[3][2 * hi + 1]);
    uint32_t s4 = h2add(raw[4][2 * hi], raw[5][2 * hi]), s5 = h2add(raw[4][2 * hi + 1], raw[5][2 * hi + 1]);
    sm[hi] = h2add(h2add(h2add(s0, s1), h2add(s2, s3)), h2add(s4, s5));
  }
  uint32_t s = h2add(prmt(sm[0], sm[1], 0x5410), prmt(sm[0], sm[1], 0x7632));
  s = h2add(s, __shfl_xor_sync(0xffffffffu, s, 1));
  s = h2add(s, __shfl_xor_sync(0xffffffffu, s, 2));
  const uint32_t nm = h2mul(s, 0xA155A155u);
  uint32_t qq[2];
#pragma unroll
  for (int hi = 0; hi < 2; hi++) {
    const uint32_t m = hi ? h2hi(nm) : h2lo(nm);
    uint32_t q0 = 0, q1 = 0;
#pragma unroll
    for (int k = 0; k < 6; k++) {
      uint32_t d0 = h2add(raw[k][2 * hi], m), d1 = h2add(raw[k][2 * hi + 1], m);
      raw[k][2 * hi] = d0; raw[k][2 * hi + 1] = d1;
      q0 = k ? h2fma(d0, d0, q0) : h2mul(d0, d0);
      q1 = k ? h2fma(d1, d1, q1) : h2mul(d1, d1);
    }
    qq[hi] = h2add(q0, q1);
  }
  uint32_t q = h2add(prmt(qq[0], qq[1], 0x5410), prmt(qq[0], qq[1], 0x7632));
  q = h2add(q, __shfl_xor_sync(0xffffffffu, q, 1));
  q = h2add(q, __shfl_xor_sync(0xffffffffu, q, 2));
  constexpr float K1 = 1.f / (96.f * GELU_C3 * GELU_C3), K2 = 1e-5f / (GELU_C3 * GELU_C3);
  const float r0 = rsqrt_fast(fmaf(h_lo(q), K1, K2)), r1 = rsqrt_fast(fmaf(h_hi(q), K1, K2));
  const uint32_t r = pack_f16(r0, r1);
#pragma unroll
  for (int k = 0; k < 6; k++) {
    a[4 * k] = h2mul(raw[k][0], h2lo(r)); a[4 * k + 2] = h2mul(raw[k][1], h2lo(r));
    a[4 * k + 1] = h2mul(raw[k][2], h2hi(r)); a[4 * k + 3] = h2mul(raw[k][3], h2hi(r));
  }
  if (HMASK) {
#pragma unroll
    for (int k = 0; k < 24; k++) a[k] &= HMASK;
  }
  return (((q & 0x7c007c00u) + 0x04000400u) & 0x80008000u) | (stale & 1);
}

constexpr int KS = CH / 16, NC = 384 / CH;
#define WG1_(n) wgmma_n##n##_f16
#define WG1(n) WG1_(n)
__device__ __forceinline__ void gemm1(uint32_t* p, const uint32_t* a, uint64_t d1, int c, int k0 = 0, int k1 = 6) {
#pragma unroll
  for (int s = 0; s < 6; s++)
    if (s >= k0 && s < k1) {
      if (s == 0) WG1(CH)<0>(p, a, d1 + c * CH); else WG1(CH)<1>(p, a + 4 * s, d1 + c * CH + s * (12288 >> 4));
    }
}
__device__ __forceinline__ void fetch_a(uint32_t abuf, uint32_t bar, const unsigned char* src) {
  asm volatile("{\n.reg .pred p;\nelect.sync _|p, 0xffffffff;\n"
               "@p mbarrier.arrive.expect_tx.shared::cta.b64 _, [%1], 3072;\n"
               "@p cp.async.bulk.shared::cluster.global.mbarrier::complete_tx::bytes [%0], [%2], 3072, [%1];\n}"
               ::"r"(abuf), "r"(bar), "l"(src) : "memory");
}
__device__ __forceinline__ void fetch_a_if(uint32_t abuf, uint32_t bar, const unsigned char* src, uint32_t go) {
  asm volatile("{\n.reg .pred p, q;\nsetp.ne.u32 q, %3, 0;\nelect.sync _|p, 0xffffffff;\nand.pred p, p, q;\n"
               "@p mbarrier.arrive.expect_tx.shared::cta.b64 _, [%1], 3072;\n"
               "@p cp.async.bulk.shared::cluster.global.mbarrier::complete_tx::bytes [%0], [%2], 3072, [%1];\n}"
               ::"r"(abuf), "r"(bar), "l"(src), "r"(go) : "memory");
}
__device__ __forceinline__ bool mbar_test(uint32_t bar, uint32_t parity) {
  uint32_t r;
  asm volatile("{.reg .pred p; mbarrier.test_wait.parity.shared::cta.b64 p, [%1], %2; selp.u32 %0, 1, 0, p;}" : "=r"(r) : "r"(bar), "r"(parity) : "memory");
  return r;
}
__device__ __forceinline__ void fetch_x(uint32_t xbuf, uint32_t bar, const CUtensorMap* tm, uint32_t c0, uint32_t c12, uint64_t pol, int go = 0) {
  asm volatile("{\n.reg .pred p, q;\nsetp.ge.s32 q, %7, 0;\nelect.sync _|p, 0xffffffff;\nand.pred p, p, q;\n"
               "@p mbarrier.arrive.expect_tx.shared::cta.b64 _, [%1], 3072;\n"
               "@p cp.async.bulk.tensor.3d.shared::cluster.global.mbarrier::complete_tx::bytes.L2::cache_hint [%0], [%2, {%3, %4, %5}], [%1], %6;\n}"
               ::"r"(xbuf), "r"(bar), "l"(tm), "r"(c0), "r"(c12 & 255), "r"(c12 >> 8), "l"(pol), "r"(go) : "memory");
}
__device__ __forceinline__ void wait_ready(const uint32_t* p, uint32_t target) {
  int spins = 0;
  while (ld_relaxed(p) != target) { __nanosleep(32); if (++spins > SPIN_LIMIT) __trap(); }
}
__device__ __forceinline__ uint32_t slot_tag(int gm, int j, uint32_t epoch) {
  const int len = gm < 8 ? PLEN : LMID, writes = (len - (j & (RING - 1)) + RING - 1) / RING;
  return (epoch * writes + j / RING + 1) & 1;
}

__device__ __forceinline__ void build_tile_list(uint32_t sb, int k, int idx, bool tabled, bool is_conv, uint32_t epoch) {
  int n = -1;
  if (tabled) { if (k < 48) n = (int16_t)g_sched[idx][k]; }
  else if (!is_conv) {
    const int i = k * (gridDim.x - NCONV) + idx, r = i >> 2, full = LMID * NG;
    const int j = r < full ? r / NG : ((r - full) >> 3) + LMID, gm = r < full ? r % NG : (r - full) & 7;
    if (i < 4096) n = (gm * PLEN + j) * 4 + (i & 3);
  }
  const int q = n >> 2, gm = q / PLEN, j = q - gm * PLEN, seg = j / LM;
  const int strip = gm < 8 ? gm >> 1 : (gm - 8) * NSEG + seg, pair = gm < 8 ? ((gm & 1) ? 255 - j : j) : PLEN + j - seg * LM;
  sts128(sb + MISC + 512 + k * 16, make_uint4(q, (((j & (RING - 1)) * NG + gm) * 4 + (n & 3)) * TILEB + slot_tag(gm, j, epoch),
                                              (n & 2) * 384, (strip * 8 + (n & 1) * 4) | (pair << 9)));
  if (k == 0) sts32(sb + MISC + 256, epoch + 1);
}

__device__ __forceinline__ void mlp_setup(uint32_t sb, Globals* gs, int id, const __nv_bfloat16* __restrict__ w1, const __nv_bfloat16* __restrict__ w2,
                                          int idx, bool tabled, int warp, int lane) {
  const int rot = idx % 6;
  PROF2_AT(lane == 0, 400 + warp);
  if (warp < 12) {
    const int m = warp >= 6; int s = warp - 6 * m + rot; if (s >= 6) s -= 6;
    if (WDELAY) __nanosleep(WDELAY + m * WDELAY2);
    copy_weights(sb, 6 * m + s, (const char*)(m ? w2 : w1) + s * 12288);
  }
  __syncthreads();
  PROF2_AT(threadIdx.x == 0, 416);
  if (warp >= 12) build_tile_list(sb, threadIdx.x - 384, idx, tabled, false, ld_relaxed(&gs->epoch[id]));
  PROF2_AT(lane == 0, 420 + warp);
  convert_weights(sb, sb + WBAR, rot, warp, lane);
  PROF2_AT(lane == 0, 460 + warp);
  asm volatile("fence.proxy.async.shared::cta;" ::: "memory");
  __syncthreads();
  if (threadIdx.x == 480) {
    const uint32_t e1 = lds32(sb + MISC + 256);
    gs->epoch[id] = e1;
    if (idx < 24 && (idx & 1)) {
      asm volatile("cp.async.bulk.global.shared::cta.bulk_group [%0], [%1], 12288;\ncp.async.bulk.commit_group;\ncp.async.bulk.wait_group 0;\nfence.proxy.async.global;\n"
                   "red.release.gpu.global.add.u32 [%2], 1;" ::"l"(gs->wimg + (idx >> 1) * 12288), "r"(sb + (idx >> 1) * 12288), "l"(gs->wflag) : "memory");
    }
  }
  __syncwarp();
}

__device__ __forceinline__ void mlp_role(uint32_t sb, Globals* gs, const CUtensorMap* tmr, __nv_bfloat16* __restrict__ out) {
  uint32_t tid;
  asm volatile("mov.u32 %0, %%tid.x;" : "=r"(tid));
  const int warp = __shfl_sync(0xffffffffu, tid >> 5, 0), lane = tid & 31;
  const int wg = warp >> 2, w = warp & 3, g = lane >> 2, t = lane & 3;
  const uint32_t abuf = sb + ABUF + warp * 3072, xbuf = sb + XBUF + (warp & 7) * 3072;
  const uint32_t bar = sb + MISC + warp * 8, obar = sb + MISC + (warp ^ 8) * 8;
  const uint32_t tl = sb + MISC + 512;
  PROF_AT(threadIdx.x == 0, 1); PROF_VAL(threadIdx.x == 0, 8, clock64());
  const uint32_t rtarget = 3 * lds32(sb + MISC + 256);
  const uint64_t d1 = ((uint64_t)(6144 >> 4) << 16) | ((uint64_t)(128 >> 4) << 32) | (uint64_t)(((sb + W1S) >> 4) & 0x3fff);
  const uint64_t d2 = ((uint64_t)(12288 >> 4) << 16) | ((uint64_t)(128 >> 4) << 32) | (uint64_t)(((sb + W2S) >> 4) & 0x3fff);
  const uint32_t ad = abuf + t * 128 + ((g ^ (2 * t)) << 4);
  const uint32_t xd = xbuf + g * 192 + t * 16;
  const int mybar = 1 + wg, nxtbar = 1 + ((wg + 1) & 3);
  const uint64_t pol = pol_evict_first();
  const unsigned char* const asrc = gs->scratch + w * 3072;
  uint32_t pha = 0, phx = 0, tp = tl + wg * 16;
  bool pending = true;
  uint32_t cur[4];
  lds128(cur, tp);
  while ((int)cur[0] >= 0) {
    PROF2_AT((threadIdx.x & 127) == 0, 16 + (tp - tl) / 4); PROF2_VAL((threadIdx.x & 127) == 0, 16 + (tp - tl) / 4 + 3, pending);
    uint32_t a[24], p[NC][CH / 4], gg[24][4], acc[24], raw[6][4], xr[6][4], n2[4], n4[4];
    if (pending) {
      wait_ready(&gs->ready[cur[0]], rtarget);
      fetch_a(abuf, bar, asrc + (cur[1] & ~1u));
      if (tp < tl + 32) fetch_x(xbuf, bar + 128, tmr, cur[2] + w * 192, cur[3], pol);
    }
    mbar_wait(bar, pha); pha ^= 1;
    PROF2_AT((threadIdx.x & 127) == 0, 16 + (tp - tl) / 4 + 1);
#pragma unroll
    for (int k = 0; k < 6; k++) lds128(raw[k], ad + k * 512);
    int sig = (int)lds32(tp + 16) >> 31;
    if (TRIG0 >= 0 && sig == 0) sig = tp < tl + 16 * NEARLY || (NLATE && (int)lds32(tp + 16 + 16 * NLATE) < 0);
    lds128(n4, tp + 64);
    uint32_t st = layer_norm(raw, a, cur[1]);
    if (__any_sync(0xffffffffu, st != 0)) {
      for (int tries = 0; __any_sync(0xffffffffu, st & 1); tries++) {
        if (tries > SPIN_LIMIT) __trap();
        fetch_a(abuf, bar, asrc + (cur[1] & ~1u));
        mbar_wait(bar, pha); pha ^= 1;
        st = 0;
#pragma unroll
        for (int k = 0; k < 6; k++) st |= lds32(ad + k * 512) ^ cur[1];
      }
      ln_wide(ad);
#pragma unroll
      for (int k = 0; k < 6; k++) lds128(a + 4 * k, ad + k * 512);
    }
    if (!LATERED) red_add_elect(&gs->cons[cur[0]]);
    if (tp != tl) asm volatile("bar.sync %0, 256;" ::"r"(mybar) : "memory");
    PROF2_AT((threadIdx.x & 127) == 0, 16 + (tp - tl) / 4 + 2);
    uint32_t rdy = 0;
    wg_fence();
    gemm1(p[0], a, d1, 0); wg_commit();
    if (SCHED == 9) { gemm1(p[1], a, d1, 1, 0, 6 / KS); wg_commit(); }
    if (LATERED) asm volatile("{.reg .pred p; setp.eq.u32 p, %1, 0; @p red.relaxed.gpu.global.add.u32 [%0], 1;}" ::"l"(&gs->cons[cur[0]] + lane), "r"(lane) : "memory");
#pragma unroll
    for (int j = 0; j < 24; j++) {
      const int c = j / KS, s = j % KS;
      if (NOJB && j == JB) { if (NOJB == 2) SCHED_FENCE(); rdy = ld_relaxed(&gs->ready[max((int)n4[0], 0)]); if (NOJB == 3) SCHED_FENCE(); }
      if (!NOJB && j == JB) {
        rdy = ld_relaxed(&gs->ready[max((int)n4[0], 0)]);
        if (SCHED != 9 && s) wg_commit();
        wg_wait<0>();
        mbar_wait(bar + 128, phx); phx ^= 1;
      } else if (SCHED == 9) wg_wait<1>(); else if (s == 0) wg_wait<0>();
      if (j == JF) { pending = rdy != rtarget; fetch_a_if(abuf, bar, asrc + (n4[1] & ~1u), !pending && (int)n4[0] >= 0); if (JFF) SCHED_FENCE(); }
      if (j == TRIG0) asm volatile("{.reg .pred p; setp.eq.s32 p, %1, 1; @p bar.arrive %0, 256;}" ::"r"(nxtbar), "r"(sig) : "memory");
      if (j == TRIG) asm volatile("{.reg .pred p; setp.eq.s32 p, %1, 0; @p bar.arrive %0, 256;}" ::"r"(nxtbar), "r"(sig) : "memory");
#pragma unroll
      for (int i = 0; i < 4; i++) gg[j][i] = gelu_h2(p[c][4 * s + i]);
      wg_fence();
      if (j == 0) wgmma_n96_f16<0>(acc, gg[j], d2); else wgmma_n96_f16<1>(acc, gg[j], d2 + (16 * (j % 3) + j / 3) * (1536 >> 4));
      if (SCHED == 9) {
        const int c1 = (j + 1) / KS + 1, u = (j + 1) % KS;
        if (c1 < NC) gemm1(p[c1], a, d1, c1, (6 * u) / KS, (6 * (u + 1)) / KS);
        wg_commit();
      } else if (s == KS - 1) {
        if (c + 1 < NC) gemm1(p[c + 1], a, d1, c + 1);
        wg_commit();
      }
    }
    if (XEARLY) {
#pragma unroll
      for (int k = 0; k < 6; k++) lds128(xr[k], xd + (k / 3) * 1536 + (k % 3) * 64);
      lds128(n2, tp + 32);
    }
    pending = rdy != rtarget;
    if (FPRED && JF == 24) fetch_a_if(abuf, bar, asrc + (n4[1] & ~1u), !pending && (int)n4[0] >= 0);
    wg_wait<0>();
    if (!FPRED && !pending && (int)n4[0] >= 0) fetch_a(abuf, bar, asrc + (n4[1] & ~1u));
    if (NOJB) { mbar_wait(bar + 128, phx); phx ^= 1; }
    if (W2X == 2) {
#pragma unroll
      for (int k = 0; k < 24; k++) acc[k] = h2mul(acc[k], 0x3E133E13u);
    }
    uint32_t rdy2 = 0;
    if (RETRY) rdy2 = ld_relaxed(&gs->ready[max((int)n4[0], 0)]);
    char* const op = (char*)out + (size_t)(cur[3] >> 8) * (512 * 192) + ((cur[3] & 255) + (g >> 1)) * 3072 + cur[2] * 2 + (2 * w + (g & 1)) * 192 + t * 16;
    if (!XEARLY) lds128(n2, tp + 32);
#pragma unroll
    for (int k = 0; k < 6; k++) {
      const int hi = k / 3, j = k % 3;
      if (!XEARLY) lds128(xr[k], xd + hi * 1536 + j * 64);
      uint4 o;
      o.x = hadd2_bf16(xr[k][0], pack_bf16(h_lo(acc[8 * j + hi]), h_hi(acc[8 * j + hi])));
      o.y = hadd2_bf16(xr[k][1], pack_bf16(h_lo(acc[8 * j + 2 + hi]), h_hi(acc[8 * j + 2 + hi])));
      o.z = hadd2_bf16(xr[k][2], pack_bf16(h_lo(acc[8 * j + 4 + hi]), h_hi(acc[8 * j + 4 + hi])));
      o.w = hadd2_bf16(xr[k][3], pack_bf16(h_lo(acc[8 * j + 6 + hi]), h_hi(acc[8 * j + 6 + hi])));
      stg128_stream(op + hi * (512 * 192) + j * 64, o, pol);
    }
    __syncwarp();
    if (XPRED) fetch_x(xbuf, obar + 128, tmr, n2[2] + w * 192, n2[3], pol, n2[0]);
    else if ((int)n2[0] >= 0) fetch_x(xbuf, obar + 128, tmr, n2[2] + w * 192, n2[3], pol);
    if (RETRY && pending && rdy2 == rtarget && (int)n4[0] >= 0) { pending = false; fetch_a(abuf, bar, asrc + (n4[1] & ~1u)); }
    tp += 64;
#pragma unroll
    for (int k = 0; k < 4; k++) cur[k] = n4[k];
  }
  PROF_AT((threadIdx.x & 127) == 0, 4 + wg); PROF_VAL(threadIdx.x == 0, 9, clock64());
}

__device__ __forceinline__ void stg128_if(uint32_t ofs, void* p, uint4 v) {
  if (NODUMP) asm volatile("{.reg .pred q; setp.ge.s32 q, %5, 0; @q st.global.v4.b32 [%0], {%1,%2,%3,%4};}" ::"l"(p), "r"(v.x), "r"(v.y), "r"(v.z), "r"(v.w), "r"(ofs) : "memory");
  else stg128(p, v);
}
__device__ __forceinline__ void conv_compute(uint32_t sb, Globals* gs, int third, int nit, int off, bool up, int warp, int lane) {
  const int g = lane >> 2, t = lane & 3;
  const uint32_t full = sb + CM;
  PROFS(0);
  const uint32_t wt = sb + 16384 + warp * 1024;
  sts128(wt + lane * 16, make_uint4(0, 0, 0, 0));
  if (lane < 4) sts128(wt + 512 + lane * 16, make_uint4(0, 0, 0, 0));
  asm volatile("setmaxnreg.inc.sync.aligned.u32 %0;" ::"n"(CREGS));
  PROFS(1);
  uint32_t meta = 0;
#pragma unroll
  for (int a = 0; a < 4; a++) meta |= ((4 * (t & 1) + a + 1 >= g) ? 0x80008u : 0xD000Du) << (4 * a);
  meta = __shfl_sync(0xffffffffu, meta, lane);
  uint32_t aq[4];
#pragma unroll
  for (int q = 0; q < 4; q++) {
    const int pp = (g & 1) * 140 + (t & 1) * 70 + 16 * (g >> 1) + 2 * q + (t >> 1);
    aq[q] = __shfl_sync(0xffffffffu, sb + RBUF + pp * 64 + (((warp >> 1) ^ ((pp >> 1) & 3)) << 4) + (warp & 1) * 8, lane);
  }
  const int Q = third * 8 + warp;
  unsigned char* const obase = gs->scratch + (g >> 1) * 3072 + Q * 128 + (((2 * t + (g & 1)) ^ (2 * (Q & 3))) << 4);
  const float zero4[4] = {0.f, 0.f, 0.f, 0.f};
  {
    uint32_t A[4][4][4];
    PROFS(2);
    asm volatile("bar.sync 5, 288;" ::: "memory");
    mbar_wait(sb + WBAR + 8, 0);
    PROFS(3);
    {
#pragma unroll
      for (int k = 0; k < 2; k++) {
        const int tap = lane + 32 * k, i = tap / 7;
        if (tap < 49) { const uint2 v = lds64(sb + tap * 192 + third * 64 + warp * 8); asm volatile("st.shared.v2.b32 [%0], {%1,%2};" ::"r"(wt + (tap + i + 8) * 8), "r"(v.x), "r"(v.y) : "memory"); }
      }
      __syncwarp();
      uint2 w[2][4][3];
#pragma unroll
      for (int h = 0; h < 2; h++) {
        uint32_t src = wt + ((4 * h + t - g) & 7) * 8 + (up ? 384 : 0);
#pragma unroll
        for (int u = 0; u < 4; u++) {
#pragma unroll
          for (int k = 0; k < 3; k++) w[h][u][k] = lds64(src + k * 64);
          src += up ? -128 : 128;
        }
      }
#pragma unroll
      for (int u = 0; u < 4; u++)
#pragma unroll
        for (int r = 0; r < 4; r++) {
          const uint2 w0 = w[r >> 1][u][1 - (r & 1)], w1 = w[r >> 1][u][2 - (r & 1)];
          A[0][u][r] = prmt(w0.x, w1.x, 0x5410); A[1][u][r] = prmt(w0.x, w1.x, 0x7632);
          A[2][u][r] = prmt(w0.y, w1.y, 0x5410); A[3][u][r] = prmt(w0.y, w1.y, 0x7632);
        }
    }
    float S[2][4][3][4];
#pragma unroll
    for (int s = 0; s < 2; s++)
#pragma unroll
      for (int c = 0; c < 4; c++)
#pragma unroll
        for (int i = 0; i < 3; i++)
#pragma unroll
          for (int k = 0; k < 4; k++) S[s][c][i][k] = 0.f;
    uint32_t sofs = off * SLOTB, bar = full + off * 8, ph = 0, ot = sb + CTAB;
    const uint32_t oend = ot + nit * 16;
    PROF_AT(threadIdx.x == 0, 12);
    PROFS(4);
    asm volatile("bar.sync 0, 512;" ::: "memory");
    PROFS(5);
    mbar_wait(bar, 0);
    PROF_AT(threadIdx.x == 0, 14);
    PROFS(6);
    uint2 X[3][4];
#pragma unroll
    for (int j = 0; j < 2; j++)
#pragma unroll
      for (int q = 0; q < 4; q++) X[j][q] = lds64(aq[q] + sofs + j * 512);
#pragma unroll 1
    do {
      const uint2 oe = lds64(ot);
      unsigned char* const o = obase + oe.x;
      const uint32_t dbar = bar + 64;
#pragma unroll
      for (int s = 0; s < 2; s++) {
        uint32_t B[4][4];
        if (s == 1) {
          sofs += SLOTB; bar += 8;
          if (sofs == NSLOT * SLOTB) { sofs = 0; bar = full; ph ^= 1; }
          mbar_wait(bar, ph);
        }
#pragma unroll
        for (int c = 0; c < 4; c++)
#pragma unroll
          for (int q = 0; q < 4; q++) B[c][q] = prmt(c < 2 ? X[s][q].x : X[s][q].y, c < 2 ? X[s + 1][q].x : X[s + 1][q].y, (c & 1) ? 0x7632 : 0x5410);
        if (s == 0) {
#pragma unroll
          for (int q = 0; q < 4; q++) X[2][q] = lds64(aq[q] + sofs + 2 * 512);
        } else {
#pragma unroll
          for (int j = 0; j < 2; j++)
#pragma unroll
            for (int q = 0; q < 4; q++) X[j][q] = lds64(aq[q] + sofs + j * 512);
        }
        float T[4][4];
        if (CFN & 1) SCHED_FENCE();
#pragma unroll
        for (int c = 0; c < 4; c++) mma_sp(T[c], A[c][3], B[c], S[s][c][2], meta);
#pragma unroll
        for (int c = 0; c < 4; c++) mma_sp(S[s][c][2], A[c][2], B[c], S[s][c][1], meta);
        if (CFN & 2) SCHED_FENCE();
        stg128_if(oe.x, o + (2 * s) * TILEB, make_uint4((pack_f16_sat(T[0][0], T[1][0]) & ~1u) | oe.y, pack_f16_sat(T[2][0], T[3][0]), pack_f16_sat(T[0][2], T[1][2]), pack_f16_sat(T[2][2], T[3][2])));
        stg128_if(oe.x, o + (2 * s + 1) * TILEB, make_uint4((pack_f16_sat(T[0][1], T[1][1]) & ~1u) | oe.y, pack_f16_sat(T[2][1], T[3][1]), pack_f16_sat(T[0][3], T[1][3]), pack_f16_sat(T[2][3], T[3][3])));
        if (s == 1) mbar_arrive_elect(dbar);
        if (CFN & 4) SCHED_FENCE();
#pragma unroll
        for (int c = 0; c < 4; c++) mma_sp(S[s][c][1], A[c][1], B[c], S[s][c][0], meta);
#pragma unroll
        for (int c = 0; c < 4; c++) mma_sp(S[s][c][0], A[c][0], B[c], zero4, meta);
      }
      ot += 16;
    } while (ot != oend);
  }
  PROF_AT(threadIdx.x == 0, 13);
}

__device__ __forceinline__ void load_step(uint32_t sb, const CUtensorMap* tmx, int gm, int third, int it, int s) {
  const int seg = it / (LM + 3);
  const int st = gm < 8 ? gm >> 1 : (gm - 8) * NSEG + seg, J = gm < 8 ? ((gm & 1) ? 257 - it : it + 1) : PLEN + it - seg * (LM + 3);
  asm volatile("{\n.reg .pred p;\n.reg .s32 c2;\n.reg .u32 d2;\nelect.sync _|p, 0xffffffff;\nadd.s32 c2, %4, 64;\nadd.u32 d2, %0, 8960;\n"
               "@p mbarrier.arrive.expect_tx.shared::cta.b64 _, [%2], 17920;\n"
               "@p cp.async.bulk.tensor.3d.shared::cluster.global.mbarrier::complete_tx::bytes [%0], [%1, {%3, %4, %5}], [%2];\n"
               "@p cp.async.bulk.tensor.3d.shared::cluster.global.mbarrier::complete_tx::bytes [d2], [%1, {%3, c2, %5}], [%2];\n}"
               ::"r"(sb + RBUF + s * SLOTB), "l"(tmx), "r"(sb + CM + s * 8), "r"(third * 32), "r"(st * 128 - 3), "r"(2 * J - 3) : "memory");
}
__device__ __forceinline__ void ring_bar_init(uint32_t bar, uint32_t cnt, bool ahead) {
  asm volatile("{\n.reg .pred p, q;\nelect.sync _|p, 0xffffffff;\n@p mbarrier.init.shared::cta.b64 [%0], %1;\n"
               "setp.ne.and.u32 q, %2, 0, p;\n@q mbarrier.arrive.shared::cta.b64 _, [%0], %1;\n@p fence.mbarrier_init.release.cluster;\n}" ::"r"(bar), "r"(cnt), "r"((uint32_t)ahead) : "memory");
}
__device__ __forceinline__ void conv_loader(uint32_t sb, Globals* gs, const CUtensorMap* tmx, int gm, int nit, int off, int cidx, int third, int k) {
  static_assert(AHEAD > 4 && AHEAD <= NSLOT && NCONV >= 24, "loader");
  const uint32_t full = sb + CM;
  asm volatile("bar.sync 0, 512;" ::: "memory");
  if (FIRST + k < AHEAD) load_step(sb, tmx, gm, third, FIRST + k, (FIRST + k + off) & 7);
#pragma unroll 1
  for (int it = AHEAD + k; it < nit + AHEAD; it += 4) {
    const int u = it + off;
    const uint32_t ro = lds32(sb + CTAB + (it - AHEAD) * 16 + 8);
    mbar_wait(full + 64 + ((u - AHEAD) & 7) * 8, ((u - AHEAD) >> 3) & 1);
    red_add_elect((uint32_t*)((char*)gs + ro));
    PROF_AT((threadIdx.x & 31) == 0 && (((it - AHEAD) & (PROF > 1 ? 7 : 15)) == 0 || it - AHEAD < 6), 200 + it - AHEAD);
    if (it <= nit) load_step(sb, tmx, gm, third, it, u & 7);
    if (it >= nit - 16) {
      if (it < nit - 12) {
        wait_ready(gs->wflag, 12 * lds32(sb + MISC + 256));
        asm volatile("fence.acquire.gpu;\nfence.proxy.async.global;" ::: "memory");
        if (cidx < 24) asm volatile("{.reg .pred p; elect.sync _|p, 0xffffffff; @p cp.async.bulk.prefetch.L2.global [%0], 1536;}" ::"l"(gs->wimg + (cidx * 4 + k) * 1536) : "memory");
      }
      const int m = it == nit ? 0 : W2S;
      if (it == nit || it == nit + AHEAD - 4)
        asm volatile("{\n.reg .pred p;\nelect.sync _|p, 0xffffffff;\n@p mbarrier.arrive.expect_tx.shared::cta.b64 _, [%1], 73728;\n"
                     "@p cp.async.bulk.shared::cluster.global.mbarrier::complete_tx::bytes [%0], [%2], 73728, [%1];\n}"
                     ::"r"(sb + m), "r"(sb + WBAR), "l"(gs->wimg + m) : "memory");
    }
  }
}

__device__ __forceinline__ void conv_credit(uint32_t sb, Globals* gs, int P0, int nit, int off, uint32_t ctarget, int k) {
  const uint32_t full = sb + CM;
#pragma unroll 1
  for (int it = k + NSLOT; it <= nit; it += 4) {
    const int u = it + off, P = (int)lds32(sb + CTAB + it * 16 + 12) - RING;
    int spins = 0;
    mbar_wait(full + 64 + (u & 7) * 8, ((u >> 3) & 1) ^ 1);
    if (P >= P0) while (ld_relaxed(&gs->cons[P]) != ctarget) { __nanosleep(CSLEEP); if (++spins > SPIN_LIMIT) __trap(); }
    mbar_arrive_elect(full + (u & 7) * 8);
  }
}

__global__ void __launch_bounds__(512, 1) convnext_kernel(const __grid_constant__ CUtensorMap tmx, const __grid_constant__ CUtensorMap tmr, const __nv_bfloat16* __restrict__ dw,
                                                          const __nv_bfloat16* __restrict__ w1, const __nv_bfloat16* __restrict__ w2, __nv_bfloat16* __restrict__ out, Globals* gs) {
  extern __shared__ __align__(1024) unsigned char smem[];
  const uint32_t sb = smem_u32(smem);
  const int warp = __shfl_sync(0xffffffffu, threadIdx.x >> 5, 0), lane = threadIdx.x & 31;
  PROF_AT(threadIdx.x == 0, 0);
  if (PFX && threadIdx.x == 320) asm volatile("prefetch.tensormap [%0];" ::"l"(&tmx) : "memory");
  if (threadIdx.x == 288) asm volatile("prefetch.tensormap [%0];" ::"l"(&tmr) : "memory");
  uint32_t smid, nsmid;
  asm volatile("mov.u32 %0, %%smid;" : "=r"(smid));
  asm volatile("mov.u32 %0, %%nsmid;" : "=r"(nsmid));
  const bool tabled = TABLED && gridDim.x == 132 && nsmid == 132;
  const int id = tabled ? smid : blockIdx.x;
  int cidx, idx;
  int is_conv;
  if (tabled) {
    idx = smid;
    const int k = (smid - 60) / 14, r = smid - 60 - 14 * k;
    is_conv = smid < 48 ? !(smid & 1) : (smid >= 60 && smid <= 90 && (r & ~2) == 0);
    cidx = smid < 48 ? ((smid >> 1) & 7) * 3 + (smid >> 4) : 24 + (r >> 1) * 3 + k;
  } else {
    cidx = (blockIdx.x * NCONV) / gridDim.x;
    is_conv = ((blockIdx.x + 1) * NCONV) / gridDim.x != cidx;
    idx = blockIdx.x - cidx;
  }
  PROF_VAL(threadIdx.x == 0, 2, is_conv ? 1000 + cidx : idx);
  const int gm = cidx / 3, third = cidx - gm * 3;
  const int P0 = gm * PLEN, nit = gm < 8 ? PLEN + 2 : NSEG * (LM + 3), off = (7 - nit) & 7;
  if (is_conv && warp == 8) {
    asm volatile("{\n.reg .pred p;\nelect.sync _|p, 0xffffffff;\n@p mbarrier.init.shared::cta.b64 [%1], 1;\n@p fence.mbarrier_init.release.cluster;\n"
                 "@p mbarrier.arrive.expect_tx.shared::cta.b64 _, [%1], 9408;\n"
                 "@p cp.async.bulk.shared::cluster.global.mbarrier::complete_tx::bytes [%0], [%2], 9408, [%1];\nbar.arrive 5, 288;\n}"
                 ::"r"(sb), "r"(sb + WBAR + 8), "l"(dw) : "memory");
#pragma unroll 1
    for (int it = 0; it < NSLOT; it++) {
      const int s = (it + off) & 7;
      ring_bar_init(sb + CM + s * 8, 2, s < off);
      PROF_AT(it == 0 && (threadIdx.x & 31) == 0, 15);
      if (it < FIRST) load_step(sb, &tmx, gm, third, it, s);
    }
  }
  mbar_init_elect(sb + MISC + warp * 8, 1); mbar_init_elect(sb + MISC + 128 + warp * 8, 1);
  asm volatile("fence.mbarrier_init.release.cluster;" ::: "memory");
  if (is_conv) {
    if (warp >= 8) ring_bar_init(sb + CM + warp * 8, 8, warp - 8 < off);
    if (warp == 9) mbar_init_elect(sb + WBAR, 2);
    if (warp < 8) {
      conv_compute(sb, gs, third, nit, off, gm < 8 && (gm & 1), warp, lane);
      asm volatile("setmaxnreg.dec.sync.aligned.u32 128;");
    } else if (warp >= 12) {
      asm volatile("setmaxnreg.dec.sync.aligned.u32 24;");
      const uint32_t epoch = ld_relaxed(&gs->epoch[id]);
#pragma unroll 1
      for (int it = threadIdx.x - 384; it <= nit; it += 128) {
        const int seg = it / (LM + 3), j = gm < 8 ? it - 2 : it - 3 * (seg + 1);
        const bool ok = it < nit && j >= (gm < 8 ? 0 : seg * LM);
        sts128(sb + CTAB + it * 16, make_uint4((ok ? (j & (RING - 1)) * NG + gm : NODUMP ? -1 : RING * NG) * (4 * TILEB), slot_tag(gm, max(j, 0), epoch),
                                               offsetof(Globals, ready) + (ok ? P0 + j : NG * PLEN) * 4, ok ? P0 + j : -1));
      }
      asm volatile("bar.sync 0, 512;" ::: "memory");
      mbar_arrive_elect(sb + CM + ((((warp + 2) & 3) + off) & 7) * 8);
      mbar_arrive_elect(sb + CM + ((((warp + 2) & 3) + off + 4) & 7) * 8);
      build_tile_list(sb, threadIdx.x - 384, idx, tabled, true, epoch);
      if (threadIdx.x == 384) gs->epoch[id] = epoch + 1;
      conv_credit(sb, gs, P0, nit, off, 16 * (epoch + 1), (warp + 2) & 3);
      mbar_wait(sb + CM + 64 + 3 * 8, ((nit + off) >> 3) & 1);
      mbar_wait(sb + CM + 64 + 6 * 8, ((nit + off) >> 3) & 1);
      asm volatile("setmaxnreg.inc.sync.aligned.u32 128;");
    } else {
      asm volatile("setmaxnreg.dec.sync.aligned.u32 %0;" ::"n"(488 - 2 * CREGS));
      conv_loader(sb, gs, &tmx, gm, nit, off, cidx, third, warp & 3);
      mbar_wait(sb + CM + 64 + 3 * 8, ((nit + off) >> 3) & 1);
      mbar_wait(sb + CM + 64 + 6 * 8, ((nit + off) >> 3) & 1);
      asm volatile("setmaxnreg.inc.sync.aligned.u32 128;");
    }
    PROF2_AT((threadIdx.x & 31) == 0, 400 + (threadIdx.x >> 5));
    mbar_wait(sb + WBAR, 0);
    asm volatile("bar.sync 0, 512;" ::: "memory");
  } else {
    mlp_setup(sb, gs, id, w1, w2, idx, tabled, warp, lane);
  }
  mlp_role(sb, gs, &tmr, out);
}

typedef CUresult (*PFN_encodeTiled)(CUtensorMap*, CUtensorMapDataType, cuuint32_t, void*, const cuuint64_t*, const cuuint64_t*, const cuuint32_t*, const cuuint32_t*,
                                    CUtensorMapInterleave, CUtensorMapSwizzle, CUtensorMapL2promotion, CUtensorMapFloatOOBfill);

extern "C" void kernel_launch(void* const* d_in, const int* in_sizes, int n_in, void* d_out, int out_size) {
  const __nv_bfloat16* x = (const __nv_bfloat16*)d_in[0];
  const __nv_bfloat16* dw = (const __nv_bfloat16*)d_in[1];
  const __nv_bfloat16* w1 = (const __nv_bfloat16*)d_in[2];
  const __nv_bfloat16* w2 = (const __nv_bfloat16*)d_in[3];
  static PFN_encodeTiled encode = nullptr;
  static int nsm = 0;
  static Globals* gs = nullptr;
  if (!encode) {
    void* fn = nullptr; cudaDriverEntryPointQueryResult qr;
    cudaGetDriverEntryPoint("cuTensorMapEncodeTiled", &fn, cudaEnableDefault, &qr);
    encode = (PFN_encodeTiled)fn;
    cudaGetSymbolAddress((void**)&gs, g_state);
    int dev = 0; cudaGetDevice(&dev);
    cudaDeviceGetAttribute(&nsm, cudaDevAttrMultiProcessorCount, dev);
    cudaFuncSetAttribute(convnext_kernel, cudaFuncAttributeMaxDynamicSharedMemorySize, SMEM_BYTES);
  }
  CUtensorMap tm;
  cuuint64_t dims[3] = {96, 512, 512}, strides[2] = {192, 192 * 512};
  cuuint32_t box[3] = {32, 70, 2}, es[3] = {1, 1, 1};
  encode(&tm, CU_TENSOR_MAP_DATA_TYPE_BFLOAT16, 3, (void*)x, dims, strides, box, es, CU_TENSOR_MAP_INTERLEAVE_NONE, CU_TENSOR_MAP_SWIZZLE_64B,
         PROMO, CU_TENSOR_MAP_FLOAT_OOB_FILL_NONE);
  CUtensorMap tr;
  cuuint64_t dims2[3] = {1536, 32, 512}, strides2[2] = {3072, 192 * 512};
  cuuint32_t box2[3] = {192, 4, 2};
  encode(&tr, CU_TENSOR_MAP_DATA_TYPE_BFLOAT16, 3, (void*)x, dims2, strides2, box2, es, CU_TENSOR_MAP_INTERLEAVE_NONE, CU_TENSOR_MAP_SWIZZLE_NONE,
         CU_TENSOR_MAP_L2_PROMOTION_NONE, CU_TENSOR_MAP_FLOAT_OOB_FILL_NONE);
  convnext_kernel<<<nsm, 512, SMEM_BYTES>>>(tm, tr, dw, w1, w2, (__nv_bfloat16*)d_out, gs);
}
```

```cpp
#include <cuda_runtime.h>
#include <cuda_bf16.h>
#include <cuda.h>
#include <stdint.h>
#include <stddef.h>

template<int SCALE_D> __device__ __forceinline__ void wgmma_n32_f16(uint32_t* d, const uint32_t* a, uint64_t desc) {
  if (SCALE_D == 0) asm volatile("wgmma.mma_async.sync.aligned.m64n32k16.f16.f16.f16 {%0,%1,%2,%3,%4,%5,%6,%7}, {%8,%9,%10,%11}, %12, 0, 1, 1, 1;"
    : "=r"(d[0]),"=r"(d[1]),"=r"(d[2]),"=r"(d[3]),"=r"(d[4]),"=r"(d[5]),"=r"(d[6]),"=r"(d[7])
    : "r"(a[0]),"r"(a[1]),"r"(a[2]),"r"(a[3]),"l"(desc));
  if (SCALE_D == 1) asm volatile("wgmma.mma_async.sync.aligned.m64n32k16.f16.f16.f16 {%0,%1,%2,%3,%4,%5,%6,%7}, {%8,%9,%10,%11}, %12, 1, 1, 1, 1;"
    : "+r"(d[0]),"+r"(d[1]),"+r"(d[2]),"+r"(d[3]),"+r"(d[4]),"+r"(d[5]),"+r"(d[6]),"+r"(d[7])
    : "r"(a[0]),"r"(a[1]),"r"(a[2]),"r"(a[3]),"l"(desc));
}

template<int SCALE_D> __device__ __forceinline__ void wgmma_n48_f16(uint32_t* d, const uint32_t* a, uint64_t desc) {
  if (SCALE_D == 0) asm volatile("wgmma.mma_async.sync.aligned.m64n48k16.f16.f16.f16 {%0,%1,%2,%3,%4,%5,%6,%7,%8,%9,%10,%11}, {%12,%13,%14,%15}, %16, 0, 1, 1, 1;"
    : "=r"(d[0]),"=r"(d[1]),"=r"(d[2]),"=r"(d[3]),"=r"(d[4]),"=r"(d[5]),"=r"(d[6]),"=r"(d[7]),"=r"(d[8]),"=r"(d[9]),"=r"(d[10]),"=r"(d[11])
    : "r"(a[0]),"r"(a[1]),"r"(a[2]),"r"(a[3]),"l"(desc));
  if (SCALE_D == 1) asm volatile("wgmma.mma_async.sync.aligned.m64n48k16.f16.f16.f16 {%0,%1,%2,%3,%4,%5,%6,%7,%8,%9,%10,%11}, {%12,%13,%14,%15}, %16, 1, 1, 1, 1;"
    : "+r"(d[0]),"+r"(d[1]),"+r"(d[2]),"+r"(d[3]),"+r"(d[4]),"+r"(d[5]),"+r"(d[6]),"+r"(d[7]),"+r"(d[8]),"+r"(d[9]),"+r"(d[10]),"+r"(d[11])
    : "r"(a[0]),"r"(a[1]),"r"(a[2]),"r"(a[3]),"l"(desc));
}

template<int SCALE_D> __device__ __forceinline__ void wgmma_n64_f16(uint32_t* d, const uint32_t* a, uint64_t desc) {
  if (SCALE_D == 0) asm volatile("wgmma.mma_async.sync.aligned.m64n64k16.f16.f16.f16 {%0,%1,%2,%3,%4,%5,%6,%7,%8,%9,%10,%11,%12,%13,%14,%15}, {%16,%17,%18,%19}, %20, 0, 1, 1, 1;"
    : "=r"(d[0]),"=r"(d[1]),"=r"(d[2]),"=r"(d[3]),"=r"(d[4]),"=r"(d[5]),"=r"(d[6]),"=r"(d[7]),"=r"(d[8]),"=r"(d[9]),"=r"(d[10]),"=r"(d[11]),"=r"(d[12]),"=r"(d[13]),"=r"(d[14]),"=r"(d[15])
    : "r"(a[0]),"r"(a[1]),"r"(a[2]),"r"(a[3]),"l"(desc));
  if (SCALE_D == 1) asm volatile("wgmma.mma_async.sync.aligned.m64n64k16.f16.f16.f16 {%0,%1,%2,%3,%4,%5,%6,%7,%8,%9,%10,%11,%12,%13,%14,%15}, {%16,%17,%18,%19}, %20, 1, 1, 1, 1;"
    : "+r"(d[0]),"+r"(d[1]),"+r"(d[2]),"+r"(d[3]),"+r"(d[4]),"+r"(d[5]),"+r"(d[6]),"+r"(d[7]),"+r"(d[8]),"+r"(d[9]),"+r"(d[10]),"+r"(d[11]),"+r"(d[12]),"+r"(d[13]),"+r"(d[14]),"+r"(d[15])
    : "r"(a[0]),"r"(a[1]),"r"(a[2]),"r"(a[3]),"l"(desc));
}

template<int SCALE_D> __device__ __forceinline__ void wgmma_n96_f16(uint32_t* d, const uint32_t* a, uint64_t desc) {
  if (SCALE_D == 0) asm volatile("wgmma.mma_async.sync.aligned.m64n96k16.f16.f16.f16 {%0,%1,%2,%3,%4,%5,%6,%7,%8,%9,%10,%11,%12,%13,%14,%15,%16,%17,%18,%19,%20,%21,%22,%23}, {%24,%25,%26,%27}, %28, 0, 1, 1, 1;"
    : "=r"(d[0]),"=r"(d[1]),"=r"(d[2]),"=r"(d[3]),"=r"(d[4]),"=r"(d[5]),"=r"(d[6]),"=r"(d[7]),"=r"(d[8]),"=r"(d[9]),"=r"(d[10]),"=r"(d[11]),"=r"(d[12]),"=r"(d[13]),"=r"(d[14]),"=r"(d[15]),"=r"(d[16]),"=r"(d[17]),"=r"(d[18]),"=r"(d[19]),"=r"(d[20]),"=r"(d[21]),"=r"(d[22]),"=r"(d[23])
    : "r"(a[0]),"r"(a[1]),"r"(a[2]),"r"(a[3]),"l"(desc));
  if (SCALE_D == 1) asm volatile("wgmma.mma_async.sync.aligned.m64n96k16.f16.f16.f16 {%0,%1,%2,%3,%4,%5,%6,%7,%8,%9,%10,%11,%12,%13,%14,%15,%16,%17,%18,%19,%20,%21,%22,%23}, {%24,%25,%26,%27}, %28, 1, 1, 1, 1;"
    : "+r"(d[0]),"+r"(d[1]),"+r"(d[2]),"+r"(d[3]),"+r"(d[4]),"+r"(d[5]),"+r"(d[6]),"+r"(d[7]),"+r"(d[8]),"+r"(d[9]),"+r"(d[10]),"+r"(d[11]),"+r"(d[12]),"+r"(d[13]),"+r"(d[14]),"+r"(d[15]),"+r"(d[16]),"+r"(d[17]),"+r"(d[18]),"+r"(d[19]),"+r"(d[20]),"+r"(d[21]),"+r"(d[22]),"+r"(d[23])
    : "r"(a[0]),"r"(a[1]),"r"(a[2]),"r"(a[3]),"l"(desc));
}

#define SCHED_NG 10
#define SCHED_LE 103
#define SCHED_RING 18
__device__ const uint16_t g_sched[132][48] = {
{367,3260,389,403,65535,65535,65535,65535,65535,65535,65535,65535,65535,65535,65535,65535,65535,65535,65535,65535,65535,65535,65535,65535,65535,65535,65535,65535,65535,65535,65535,65535,65535,65535,65535,65535,65535,65535,65535,65535,65535,65535,65535,65535,65535,65535,65535,65535},
{0,2483,22,2915,2925,2935,3765,73,83,93,2986,3816,124,134,144,3037,3867,175,185,195,3088,218,3111,3121,3939,259,269,279,3172,3990,310,320,330,3223,4041,361,374,387,400,65535,65535,65535,65535,65535,65535,65535,65535,65535},
{2838,788,802,815,65535,65535,65535,65535,65535,65535,65535,65535,65535,65535,65535,65535,65535,65535,65535,65535,65535,65535,65535,65535,65535,65535,65535,65535,65535,65535,65535,65535,65535,65535,65535,65535,65535,65535,65535,65535,65535,65535,65535,65535,65535,65535,65535,65535},
{412,422,432,442,452,463,473,483,493,503,514,524,534,544,554,565,575,585,595,605,616,628,638,649,659,669,679,689,700,710,720,730,740,751,761,771,784,798,811,65535,65535,65535,65535,65535,65535,65535,65535,65535},
{3646,1199,1213,1226,65535,65535,65535,65535,65535,65535,65535,65535,65535,65535,65535,65535,65535,65535,65535,65535,65535,65535,65535,65535,65535,65535,65535,65535,65535,65535,65535,65535,65535,65535,65535,65535,65535,65535,65535,65535,65535,65535,65535,65535,65535,65535,65535,65535},
{824,834,845,855,865,876,886,896,906,917,927,937,947,957,968,978,988,998,1008,1019,1029,1041,1051,1062,1072,1082,1092,1103,1113,1123,1133,1143,1154,1164,1174,1184,1196,1210,1223,65535,65535,65535,65535,65535,65535,65535,65535,65535},
{1603,1612,1624,1638,65535,65535,65535,65535,65535,65535,65535,65535,65535,65535,65535,65535,65535,65535,65535,65535,65535,65535,65535,65535,65535,65535,65535,65535,65535,65535,65535,65535,65535,65535,65535,65535,65535,65535,65535,65535,65535,65535,65535,65535,65535,65535,65535,65535},
{1236,1247,1257,1267,1278,1288,1298,1308,1318,1329,1339,1349,1359,1369,1380,1390,1400,1410,1420,1431,1441,1453,1464,1474,1484,1494,1504,1515,1525,1535,1545,1555,1566,1576,1586,1596,1609,1622,1636,65535,65535,65535,65535,65535,65535,65535,65535,65535},
{2015,2024,2037,2050,65535,65535,65535,65535,65535,65535,65535,65535,65535,65535,65535,65535,65535,65535,65535,65535,65535,65535,65535,65535,65535,65535,65535,65535,65535,65535,65535,65535,65535,65535,65535,65535,65535,65535,65535,65535,65535,65535,65535,65535,65535,65535,65535,65535},
{1648,1659,1669,1680,1690,1700,1710,1720,1731,1741,1751,1761,1771,1782,1792,1802,1812,1822,1833,1843,1853,1865,1876,1886,1896,1906,1917,1927,1937,1947,1957,1968,1978,1988,1998,2008,2021,2035,2048,65535,65535,65535,65535,65535,65535,65535,65535,65535},
{4058,2436,2449,2462,65535,65535,65535,65535,65535,65535,65535,65535,65535,65535,65535,65535,65535,65535,65535,65535,65535,65535,65535,65535,65535,65535,65535,65535,65535,65535,65535,65535,65535,65535,65535,65535,65535,65535,65535,65535,65535,65535,65535,65535,65535,65535,65535,65535},
{2060,2071,2081,2092,2102,2112,2122,2132,2143,2153,2163,2173,2183,2194,2204,2214,2224,2234,2245,2255,2265,2277,2288,2298,2308,2318,2329,2339,2349,2359,2369,2380,2390,2400,2410,2420,2433,2447,2460,65535,65535,65535,65535,65535,65535,65535,65535,65535},
{2839,3656,2861,2874,65535,65535,65535,65535,65535,65535,65535,65535,65535,65535,65535,65535,65535,65535,65535,65535,65535,65535,65535,65535,65535,65535,65535,65535,65535,65535,65535,65535,65535,65535,65535,65535,65535,65535,65535,65535,65535,65535,65535,65535,65535,65535,65535,65535},
{2472,3303,3313,3323,3333,3343,2534,3364,3374,3384,3394,2585,3415,3425,3435,3445,2636,3466,3476,3486,2677,2690,3507,3517,2720,3538,3548,3558,3568,2771,3589,3599,3609,3619,2822,3640,3654,2859,2872,65535,65535,65535,65535,65535,65535,65535,65535,65535},
{3251,4068,3273,3286,65535,65535,65535,65535,65535,65535,65535,65535,65535,65535,65535,65535,65535,65535,65535,65535,65535,65535,65535,65535,65535,65535,65535,65535,65535,65535,65535,65535,65535,65535,65535,65535,65535,65535,65535,65535,65535,65535,65535,65535,65535,65535,65535,65535},
{2884,2895,2905,3735,3745,3755,2946,2956,2966,2976,3806,2997,3007,3017,3027,3857,3048,3058,3068,3078,3089,3909,3919,3929,3132,3142,3152,3162,3980,3183,3193,3203,3213,4031,3234,3244,4065,3270,4091,65535,65535,65535,65535,65535,65535,65535,65535,65535},
{368,378,390,3682,65535,65535,65535,65535,65535,65535,65535,65535,65535,65535,65535,65535,65535,65535,65535,65535,65535,65535,65535,65535,65535,65535,65535,65535,65535,65535,65535,65535,65535,65535,65535,65535,65535,65535,65535,65535,65535,65535,65535,65535,65535,65535,65535,65535},
{1,3715,3725,33,43,53,63,3776,3786,3796,104,114,3827,3837,3847,155,165,3878,3888,3898,206,219,229,239,249,3950,3960,3970,290,300,4001,4011,4021,341,351,4052,375,4078,401,65535,65535,65535,65535,65535,65535,65535,65535,65535},
{780,789,3669,4094,65535,65535,65535,65535,65535,65535,65535,65535,65535,65535,65535,65535,65535,65535,65535,65535,65535,65535,65535,65535,65535,65535,65535,65535,65535,65535,65535,65535,65535,65535,65535,65535,65535,65535,65535,65535,65535,65535,65535,65535,65535,65535,65535,65535},
{413,423,433,443,453,464,474,484,494,504,515,525,535,545,555,566,576,586,596,606,617,629,639,650,660,670,680,690,701,711,721,731,741,752,762,772,785,799,812,65535,65535,65535,65535,65535,65535,65535,65535,65535},
{1192,1200,1214,1227,65535,65535,65535,65535,65535,65535,65535,65535,65535,65535,65535,65535,65535,65535,65535,65535,65535,65535,65535,65535,65535,65535,65535,65535,65535,65535,65535,65535,65535,65535,65535,65535,65535,65535,65535,65535,65535,65535,65535,65535,65535,65535,65535,65535},
{825,835,846,856,866,877,887,897,907,918,928,938,948,958,969,979,989,999,1009,1020,1030,1042,1052,1063,1073,1083,1093,1104,1114,1124,1134,1144,1155,1165,1175,1185,1197,1211,1224,65535,65535,65535,65535,65535,65535,65535,65535,65535},
{1604,1613,1625,1639,65535,65535,65535,65535,65535,65535,65535,65535,65535,65535,65535,65535,65535,65535,65535,65535,65535,65535,65535,65535,65535,65535,65535,65535,65535,65535,65535,65535,65535,65535,65535,65535,65535,65535,65535,65535,65535,65535,65535,65535,65535,65535,65535,65535},
{1237,1248,1258,1268,1279,1289,1299,1309,1319,1330,1340,1350,1360,1370,1381,1391,1401,1411,1421,1432,1442,1454,1465,1475,1485,1495,1505,1516,1526,1536,1546,1556,1567,1577,1587,1597,1610,1623,1637,65535,65535,65535,65535,65535,65535,65535,65535,65535},
{2016,2025,2038,2051,65535,65535,65535,65535,65535,65535,65535,65535,65535,65535,65535,65535,65535,65535,65535,65535,65535,65535,65535,65535,65535,65535,65535,65535,65535,65535,65535,65535,65535,65535,65535,65535,65535,65535,65535,65535,65535,65535,65535,65535,65535,65535,65535,65535},
{1649,1660,1670,1681,1691,1701,1711,1721,1732,1742,1752,1762,1772,1783,1793,1803,1813,1823,1834,1844,1854,1866,1877,1887,1897,1907,1918,1928,1938,1948,1958,1969,1979,1989,1999,2009,2022,2036,2049,65535,65535,65535,65535,65535,65535,65535,65535,65535},
{2428,2437,2450,2463,65535,65535,65535,65535,65535,65535,65535,65535,65535,65535,65535,65535,65535,65535,65535,65535,65535,65535,65535,65535,65535,65535,65535,65535,65535,65535,65535,65535,65535,65535,65535,65535,65535,65535,65535,65535,65535,65535,65535,65535,65535,65535,65535,65535},
{2061,2072,2082,2093,2103,2113,2123,2133,2144,2154,2164,2174,2184,2195,2205,2215,2225,2235,2246,2256,2266,2278,2289,2299,2309,2319,2330,2340,2350,2360,2370,2381,2391,2401,2411,2421,2434,2448,2461,65535,65535,65535,65535,65535,65535,65535,65535,65535},
{3647,2849,2862,2875,65535,65535,65535,65535,65535,65535,65535,65535,65535,65535,65535,65535,65535,65535,65535,65535,65535,65535,65535,65535,65535,65535,65535,65535,65535,65535,65535,65535,65535,65535,65535,65535,65535,65535,65535,65535,65535,65535,65535,65535,65535,65535,65535,65535},
{2473,2484,2494,2504,3334,3344,2535,2545,2555,2565,3395,2586,2596,2606,2616,3446,2637,2647,2657,2667,2678,3498,3508,3518,2721,2731,2741,2751,3569,2772,2782,2792,2802,3620,2823,2833,2847,3667,3680,65535,65535,65535,65535,65535,65535,65535,65535,65535},
{4059,3261,4081,3287,65535,65535,65535,65535,65535,65535,65535,65535,65535,65535,65535,65535,65535,65535,65535,65535,65535,65535,65535,65535,65535,65535,65535,65535,65535,65535,65535,65535,65535,65535,65535,65535,65535,65535,65535,65535,65535,65535,65535,65535,65535,65535,65535,65535},
{2885,2896,2906,2916,2926,2936,3766,2957,2967,2977,2987,3817,3008,3018,3028,3038,3868,3059,3069,3079,3090,3910,3112,3122,3940,3143,3153,3163,3173,3991,3194,3204,3214,3224,4042,3245,4066,3271,4092,65535,65535,65535,65535,65535,65535,65535,65535,65535},
{369,3657,391,404,65535,65535,65535,65535,65535,65535,65535,65535,65535,65535,65535,65535,65535,65535,65535,65535,65535,65535,65535,65535,65535,65535,65535,65535,65535,65535,65535,65535,65535,65535,65535,65535,65535,65535,65535,65535,65535,65535,65535,65535,65535,65535,65535,65535},
{2,13,23,3324,3746,3756,64,3365,3375,3385,3807,115,3416,3426,3436,3858,166,3467,3477,3487,208,220,3920,3930,250,3539,3549,3559,3981,301,3590,3600,3610,4032,352,3641,376,4079,402,65535,65535,65535,65535,65535,65535,65535,65535,65535},
{781,790,803,816,65535,65535,65535,65535,65535,65535,65535,65535,65535,65535,65535,65535,65535,65535,65535,65535,65535,65535,65535,65535,65535,65535,65535,65535,65535,65535,65535,65535,65535,65535,65535,65535,65535,65535,65535,65535,65535,65535,65535,65535,65535,65535,65535,65535},
{414,424,434,444,454,465,475,485,495,505,516,526,536,546,556,567,577,587,597,607,618,630,640,651,661,671,681,691,702,712,722,732,742,753,763,773,786,800,813,65535,65535,65535,65535,65535,65535,65535,65535,65535},
{1193,1201,1215,1228,65535,65535,65535,65535,65535,65535,65535,65535,65535,65535,65535,65535,65535,65535,65535,65535,65535,65535,65535,65535,65535,65535,65535,65535,65535,65535,65535,65535,65535,65535,65535,65535,65535,65535,65535,65535,65535,65535,65535,65535,65535,65535,65535,65535},
{826,836,847,857,867,878,888,898,908,3797,929,939,949,959,3848,980,990,1000,1010,3899,1031,1043,1053,1064,1074,1084,1094,3971,1115,1125,1135,1145,4022,1166,1176,1186,1198,1212,1225,65535,65535,65535,65535,65535,65535,65535,65535,65535},
{1605,1614,1626,1640,65535,65535,65535,65535,65535,65535,65535,65535,65535,65535,65535,65535,65535,65535,65535,65535,65535,65535,65535,65535,65535,65535,65535,65535,65535,65535,65535,65535,65535,65535,65535,65535,65535,65535,65535,65535,65535,65535,65535,65535,65535,65535,65535,65535},
{1238,1249,1259,1269,1280,1290,1300,1310,1320,1331,1341,1351,1361,1371,1382,1392,1402,1412,1422,1433,1443,1455,1466,1476,1486,1496,1506,1517,1527,1537,1547,1557,1568,1578,1588,1598,1611,1627,1641,65535,65535,65535,65535,65535,65535,65535,65535,65535},
{2017,2026,2039,2052,65535,65535,65535,65535,65535,65535,65535,65535,65535,65535,65535,65535,65535,65535,65535,65535,65535,65535,65535,65535,65535,65535,65535,65535,65535,65535,65535,65535,65535,65535,65535,65535,65535,65535,65535,65535,65535,65535,65535,65535,65535,65535,65535,65535},
{1650,1661,1671,3736,1692,1702,1712,1722,1733,1743,1753,1763,1773,1784,1794,1804,1814,1824,1835,1845,1855,1867,1878,1888,1898,1908,1919,1929,1939,1949,1959,1970,1980,1990,2000,2010,2023,4082,2053,65535,65535,65535,65535,65535,65535,65535,65535,65535},
{2429,2438,2451,2464,65535,65535,65535,65535,65535,65535,65535,65535,65535,65535,65535,65535,65535,65535,65535,65535,65535,65535,65535,65535,65535,65535,65535,65535,65535,65535,65535,65535,65535,65535,65535,65535,65535,65535,65535,65535,65535,65535,65535,65535,65535,65535,65535,65535},
{2062,2073,2083,2094,2104,2114,2124,2134,2145,2155,2165,2175,2185,2196,2206,2216,2226,2236,2247,2257,2267,2279,2290,2300,2310,2320,2331,2341,2351,2361,2371,2382,2392,2402,2412,2422,2435,2452,2465,65535,65535,65535,65535,65535,65535,65535,65535,65535},
{2840,2850,3670,3683,65535,65535,65535,65535,65535,65535,65535,65535,65535,65535,65535,65535,65535,65535,65535,65535,65535,65535,65535,65535,65535,65535,65535,65535,65535,65535,65535,65535,65535,65535,65535,65535,65535,65535,65535,65535,65535,65535,65535,65535,65535,65535,65535,65535},
{2474,3304,3314,2505,2515,2525,3355,2546,2556,2566,2576,3406,2597,2607,2617,2627,3457,2648,2658,2668,2679,2691,2701,2711,3529,2732,2742,2752,2762,3580,2783,2793,2803,2813,3631,2834,3655,2860,2873,65535,65535,65535,65535,65535,65535,65535,65535,65535},
{3252,4069,3274,4095,65535,65535,65535,65535,65535,65535,65535,65535,65535,65535,65535,65535,65535,65535,65535,65535,65535,65535,65535,65535,65535,65535,65535,65535,65535,65535,65535,65535,65535,65535,65535,65535,65535,65535,65535,65535,65535,65535,65535,65535,65535,65535,65535,65535},
{2886,3716,3726,2917,2927,2937,2947,3777,3787,2978,2988,2998,3828,3838,3029,3039,3049,3879,3889,3080,3091,3103,3113,3123,3133,3951,3961,3164,3174,3184,4002,4012,3215,3225,3235,4053,3259,3272,3285,65535,65535,65535,65535,65535,65535,65535,65535,65535},
{3,14,24,35,45,55,2948,3778,3788,96,106,2999,3829,3839,147,157,3050,3880,3890,198,210,2692,231,241,3134,3952,3962,282,292,3185,4003,4013,333,343,3236,4054,379,2863,2876,65535,65535,65535,65535,65535,65535,65535,65535,65535},
{4,3305,3727,34,44,54,65,75,85,95,105,116,126,136,146,156,167,177,187,197,209,221,230,240,251,261,271,281,291,302,312,322,332,342,353,363,377,392,405,65535,65535,65535,65535,65535,65535,65535,65535,65535},
{415,425,435,445,455,466,476,486,496,506,517,527,537,547,557,568,578,588,598,608,619,631,641,652,662,672,682,692,703,713,723,733,743,754,764,774,787,801,814,65535,65535,65535,65535,65535,65535,65535,65535,65535},
{416,426,436,446,456,467,477,487,497,507,518,528,538,548,558,569,579,589,599,609,620,632,642,653,663,673,683,693,704,714,724,734,744,755,765,775,791,804,817,65535,65535,65535,65535,65535,65535,65535,65535,65535},
{827,837,848,858,868,879,889,899,909,919,930,940,950,960,970,981,991,1001,1011,1021,1032,1044,1054,1065,1075,1085,1095,1105,1116,1126,1136,1146,1156,1167,1177,1187,1202,1216,1229,65535,65535,65535,65535,65535,65535,65535,65535,65535},
{828,838,849,859,869,2526,3356,900,910,920,2577,3407,951,961,971,2628,3458,1002,1012,1022,1033,1045,1055,2712,3530,1086,1096,1106,2763,3581,1137,1147,1157,2814,3632,1188,1203,3275,3288,65535,65535,65535,65535,65535,65535,65535,65535,65535},
{1239,1250,1260,1270,1281,1291,1301,1311,1321,1332,1342,1352,1362,1372,1383,1393,1403,1413,1423,1434,1444,1456,1467,1477,1487,1497,1507,1518,1528,1538,1548,1558,1569,1579,1589,1599,1615,1628,3684,65535,65535,65535,65535,65535,65535,65535,65535,65535},
{1240,3717,1261,1271,2516,2938,3768,1312,1322,2567,2989,3819,1363,1373,2618,3040,3870,1414,1424,2669,1445,1457,2702,3124,3942,1498,1508,2753,3175,3993,1549,1559,2804,3226,4044,1600,3262,3671,4096,65535,65535,65535,65535,65535,65535,65535,65535,65535},
{1651,1662,1672,1682,1693,1703,1713,1723,1734,1744,1754,1764,1774,1785,1795,1805,1815,1825,1836,1846,1856,1868,1879,1889,1899,1909,1920,1930,1940,1950,1960,1971,1981,1991,2001,2011,2027,2040,2054,65535,65535,65535,65535,65535,65535,65535,65535,65535},
{1652,1663,1673,1683,2928,3346,1714,1724,2557,2979,3397,1765,1775,2608,3030,3448,1816,1826,2659,3081,1857,1869,3114,3520,1900,1910,2743,3165,3571,1951,1961,2794,3216,3622,2002,2012,3658,4083,2877,65535,65535,65535,65535,65535,65535,65535,65535,65535},
{2063,2074,2084,2095,2105,2115,2125,2135,2146,2156,2166,2176,2186,2197,2207,2217,2227,2237,2248,2258,2268,2280,2291,2301,2311,2321,2332,2342,2352,2362,2372,2383,2393,2403,2413,2423,2439,2453,2466,65535,65535,65535,65535,65535,65535,65535,65535,65535},
{2064,2075,2085,2506,3336,3758,2126,2136,2969,3387,3809,2177,2187,3020,3438,3860,2228,2238,3071,3489,2269,2281,3510,3932,2312,2322,3155,3561,3983,2363,2373,3206,3612,4034,2414,2424,4070,2864,3289,65535,65535,65535,65535,65535,65535,65535,65535,65535},
{2845,2854,2867,2880,65535,65535,65535,65535,65535,65535,65535,65535,65535,65535,65535,65535,65535,65535,65535,65535,65535,65535,65535,65535,65535,65535,65535,65535,65535,65535,65535,65535,65535,65535,65535,65535,65535,65535,65535,65535,65535,65535,65535,65535,65535,65535,65535,65535},
{2475,2485,2495,3325,3335,3345,2536,3366,3376,3386,3396,2587,3417,3427,3437,3447,2638,3468,3478,3488,2680,3499,3509,3519,2722,3540,3550,3560,3570,2773,3591,3601,3611,3621,2824,3642,2848,3668,3681,65535,65535,65535,65535,65535,65535,65535,65535,65535},
{3256,3266,4087,4100,65535,65535,65535,65535,65535,65535,65535,65535,65535,65535,65535,65535,65535,65535,65535,65535,65535,65535,65535,65535,65535,65535,65535,65535,65535,65535,65535,65535,65535,65535,65535,65535,65535,65535,65535,65535,65535,65535,65535,65535,65535,65535,65535,65535},
{2887,2897,2907,3737,3747,3757,3767,2958,2968,3798,3808,3818,3009,3019,3849,3859,3869,3060,3070,3900,3092,3911,3921,3931,3941,3144,3154,3972,3982,3992,3195,3205,4023,4033,4043,3246,4067,4080,4093,65535,65535,65535,65535,65535,65535,65535,65535,65535},
{417,427,437,447,457,468,478,488,498,508,519,529,539,549,559,570,580,590,600,610,621,633,643,654,664,674,684,694,705,715,725,735,745,756,766,776,792,805,818,65535,65535,65535,65535,65535,65535,65535,65535,65535},
{2476,2486,2496,2918,3748,2527,2537,2547,3377,3799,2578,2588,2598,3428,3850,2629,2639,2649,3479,3901,622,3104,3922,2713,2723,2733,3551,3973,2764,2774,2784,3602,4024,2815,2825,2835,2851,3276,3685,65535,65535,65535,65535,65535,65535,65535,65535,65535},
{829,839,2908,3326,870,880,890,2959,3789,921,931,941,3010,3840,972,982,992,3061,3891,1023,1034,3500,1056,1066,1076,3145,3963,1107,1117,1127,3196,4014,1158,1168,1178,3247,1204,1217,1230,65535,65535,65535,65535,65535,65535,65535,65535,65535},
{2888,2898,3316,3738,2517,2939,2949,3367,911,2568,2990,3000,3418,962,2619,3041,3051,3469,1013,2670,2681,3912,2703,3125,3135,3541,1097,2754,3176,3186,3592,1148,2805,3227,3237,3643,3263,3672,4097,65535,65535,65535,65535,65535,65535,65535,65535,65535},
{1241,1251,3728,1272,3749,1293,1303,1313,3378,3800,1344,1354,1364,3429,3851,1395,1405,1415,3480,3902,1447,3501,3923,1479,1489,1499,3552,3974,1530,1540,1550,3603,4025,1581,1591,1601,1617,1630,1643,65535,65535,65535,65535,65535,65535,65535,65535,65535},
{3296,3306,1262,2507,1282,1292,1302,3779,1323,1333,1343,1353,3830,1374,1384,1394,1404,3881,1425,1435,1446,1458,1468,1478,1488,3953,1509,1519,1529,1539,4004,1560,1570,1580,1590,4055,1616,1629,1642,65535,65535,65535,65535,65535,65535,65535,65535,65535},
{1653,3718,1674,1684,1694,1704,1715,1725,1735,1745,1755,1766,1776,1786,1796,1806,1817,1827,1837,1847,1858,1870,1880,1890,1901,1911,1921,1931,1941,1952,1962,1972,1982,1992,2003,2013,2028,2041,2055,65535,65535,65535,65535,65535,65535,65535,65535,65535},
{3708,1664,3317,3739,1695,1705,2538,3368,3790,1746,1756,2589,3419,3841,1797,1807,2640,3470,3892,1848,1859,3913,1881,1891,2724,3542,3964,1932,1942,2775,3593,4015,1983,1993,2826,3644,2029,2042,3686,65535,65535,65535,65535,65535,65535,65535,65535,65535},
{2065,2076,3729,2097,2107,2117,2950,3780,2148,2158,2168,3001,3831,2199,2209,2219,3052,3882,2250,2260,2271,2283,2293,2303,3136,3954,2334,2344,2354,3187,4005,2385,2395,2405,3238,4056,2441,3277,4098,65535,65535,65535,65535,65535,65535,65535,65535,65535},
{2066,2487,2086,2096,2106,2116,2127,2137,2147,2157,2167,2178,2188,2198,2208,2218,2229,2239,2249,2259,2270,2282,2292,2302,2313,2323,2333,2343,2353,2364,2374,2384,2394,2404,2415,2425,2440,2454,2467,65535,65535,65535,65535,65535,65535,65535,65535,65535},
{3653,3662,3675,3688,65535,65535,65535,65535,65535,65535,65535,65535,65535,65535,65535,65535,65535,65535,65535,65535,65535,65535,65535,65535,65535,65535,65535,65535,65535,65535,65535,65535,65535,65535,65535,65535,65535,65535,65535,65535,65535,65535,65535,65535,65535,65535,65535,65535},
{2477,3307,2497,3327,3337,3347,3357,2548,2558,3388,3398,3408,2599,2609,3439,3449,3459,2650,2660,3490,2682,2693,3511,3521,3531,2734,2744,3562,3572,3582,2785,2795,3613,3623,3633,2836,3659,2865,2878,65535,65535,65535,65535,65535,65535,65535,65535,65535},
{4064,4074,3280,3293,65535,65535,65535,65535,65535,65535,65535,65535,65535,65535,65535,65535,65535,65535,65535,65535,65535,65535,65535,65535,65535,65535,65535,65535,65535,65535,65535,65535,65535,65535,65535,65535,65535,65535,65535,65535,65535,65535,65535,65535,65535,65535,65535,65535},
{2889,2899,2909,2919,2929,3759,3769,2960,2970,2980,3810,3820,3011,3021,3031,3861,3871,3062,3072,3082,3093,3105,3115,3933,3943,3146,3156,3166,3984,3994,3197,3207,3217,4035,4045,3248,4071,4084,3290,65535,65535,65535,65535,65535,65535,65535,65535,65535},
{418,428,439,449,459,2528,3358,490,500,510,2579,3409,541,551,561,2630,3460,592,602,612,3094,635,645,2714,3532,676,686,696,2765,3583,727,737,747,2816,3634,778,2852,3673,820,65535,65535,65535,65535,65535,65535,65535,65535,65535},
{3297,3719,438,448,458,469,479,489,499,509,520,530,540,550,560,571,581,591,601,611,623,634,644,655,665,675,685,695,706,716,726,736,746,757,767,777,793,806,819,65535,65535,65535,65535,65535,65535,65535,65535,65535},
{830,840,850,860,871,881,891,901,912,922,932,942,952,963,973,983,993,1003,1014,1024,1035,1046,1057,1067,1077,1087,1098,1108,1118,1128,1138,1149,1159,1169,1179,1189,1205,1218,1231,65535,65535,65535,65535,65535,65535,65535,65535,65535},
{3709,841,851,861,2518,2940,3770,902,2559,2569,2991,3821,953,2610,2620,3042,3872,1004,2661,2671,1036,1047,2704,3126,3944,1088,2745,2755,3177,3995,1139,2796,2806,3228,4046,1190,3264,4085,1232,65535,65535,65535,65535,65535,65535,65535,65535,65535},
{1242,1252,1263,1273,1283,3348,1304,1314,1324,1334,3399,1355,1365,1375,1385,3450,1406,1416,1426,1436,1448,1459,1469,3522,1490,1500,1510,1520,3573,1541,1551,1561,1571,3624,1592,1602,3660,1631,1644,65535,65535,65535,65535,65535,65535,65535,65535,65535},
{1243,1253,2498,2508,2930,3760,2539,2549,2971,2981,3811,2590,2600,3022,3032,3862,2641,2651,3073,3083,2683,2694,3116,3934,2725,2735,3157,3167,3985,2776,2786,3208,3218,4036,2827,2837,4072,2866,2879,65535,65535,65535,65535,65535,65535,65535,65535,65535},
{1654,1665,1675,1685,3338,1706,1716,1726,1736,3389,1757,1767,1777,1787,3440,1808,1818,1828,1838,3491,1860,1871,3512,1892,1902,1912,1922,3563,1943,1953,1963,1973,3614,1994,2004,2014,2030,2043,2056,65535,65535,65535,65535,65535,65535,65535,65535,65535},
{1655,2488,2910,2920,3750,2529,2951,2961,3379,3801,2580,3002,3012,3430,3852,2631,3053,3063,3481,3903,3095,3106,3924,2715,3137,3147,3553,3975,2766,3188,3198,3604,4026,2817,3239,3249,2853,3278,3291,65535,65535,65535,65535,65535,65535,65535,65535,65535},
{2067,2077,2087,3328,2108,2119,2129,2139,2149,3390,2170,2180,2190,2200,3441,2221,2231,2241,2251,3492,2273,2284,3513,2305,2315,2325,2335,3564,2356,2366,2376,2386,3615,2407,2417,2427,2443,2456,2469,65535,65535,65535,65535,65535,65535,65535,65535,65535},
{2478,2900,3318,3740,2519,2118,2128,2138,3791,2159,2169,2179,2189,3842,2210,2220,2230,2240,3893,2261,2272,3502,2294,2304,2314,2324,3965,2345,2355,2365,2375,4016,2396,2406,2416,2426,2442,2455,2468,65535,65535,65535,65535,65535,65535,65535,65535,65535},
{2846,2855,2868,2881,65535,65535,65535,65535,65535,65535,65535,65535,65535,65535,65535,65535,65535,65535,65535,65535,65535,65535,65535,65535,65535,65535,65535,65535,65535,65535,65535,65535,65535,65535,65535,65535,65535,65535,65535,65535,65535,65535,65535,65535,65535,65535,65535,65535},
{3298,3308,2499,2509,3339,3349,3359,3369,2560,2570,3400,3410,3420,2611,2621,3451,3461,3471,2662,2672,2684,2695,2705,3523,3533,3543,2746,2756,3574,3584,3594,2797,2807,3625,3635,3645,3661,3674,3687,65535,65535,65535,65535,65535,65535,65535,65535,65535},
{3257,3267,4088,4101,65535,65535,65535,65535,65535,65535,65535,65535,65535,65535,65535,65535,65535,65535,65535,65535,65535,65535,65535,65535,65535,65535,65535,65535,65535,65535,65535,65535,65535,65535,65535,65535,65535,65535,65535,65535,65535,65535,65535,65535,65535,65535,65535,65535},
{2890,3720,3730,2921,2931,2941,3771,3781,2972,2982,2992,3822,3832,3023,3033,3043,3873,3883,3074,3084,3096,3914,3117,3127,3945,3955,3158,3168,3178,3996,4006,3209,3219,3229,4047,4057,3265,4086,4099,65535,65535,65535,65535,65535,65535,65535,65535,65535},
{419,429,440,3329,461,471,481,2550,3380,512,522,532,2601,3431,563,573,583,2652,3482,614,625,3503,647,657,667,2736,3554,698,708,718,2787,3605,749,759,769,3648,795,808,822,65535,65535,65535,65535,65535,65535,65535,65535,65535},
{3710,430,2911,450,460,470,480,491,501,511,521,531,542,552,562,572,582,593,603,613,624,636,646,656,666,677,687,697,707,717,728,738,748,758,768,779,794,807,821,65535,65535,65535,65535,65535,65535,65535,65535,65535},
{831,842,852,863,873,883,893,3370,914,924,934,944,3421,965,975,985,995,3472,1016,1026,1038,3915,1059,1069,1079,3544,1100,1110,1120,1130,3595,1151,1161,1171,1181,4060,1207,1220,1234,65535,65535,65535,65535,65535,65535,65535,65535,65535},
{832,2489,3319,862,872,882,892,903,913,923,933,943,954,964,974,984,994,1005,1015,1025,1037,1048,1058,1068,1078,1089,1099,1109,1119,1129,1140,1150,1160,1170,1180,1191,1206,1219,1233,65535,65535,65535,65535,65535,65535,65535,65535,65535},
{1244,3309,1265,1274,1284,1294,1305,1315,1325,1335,1345,1356,1366,1376,1386,1396,1407,1417,1427,1437,1449,1460,1470,1480,1491,1501,1511,1521,1531,1542,1552,1562,1572,1582,1593,1606,1618,1632,1645,65535,65535,65535,65535,65535,65535,65535,65535,65535},
{2479,1254,1264,1275,1285,1295,2540,3782,1326,1336,1346,2591,3833,1377,1387,1397,2642,3884,1428,1438,1450,1461,1471,1481,2726,3956,1512,1522,1532,2777,4007,1563,1573,1583,2828,2841,1619,1633,1646,65535,65535,65535,65535,65535,65535,65535,65535,65535},
{1656,3721,1677,1686,1696,1707,1717,1727,1737,1747,1758,1768,1778,1788,1798,1809,1819,1829,1839,1849,1861,1872,1882,1893,1903,1913,1923,1933,1944,1954,1964,1974,1984,1995,2005,2018,2031,2044,2057,65535,65535,65535,65535,65535,65535,65535,65535,65535},
{2891,1666,1676,1687,1697,2530,3360,1728,1738,1748,2581,3411,1779,1789,1799,2632,3462,1830,1840,1850,1862,1873,1883,2716,3534,1914,1924,1934,2767,3585,1965,1975,1985,2818,3636,3253,2032,2045,2058,65535,65535,65535,65535,65535,65535,65535,65535,65535},
{2068,2079,2089,2098,2109,2942,3772,2140,2150,2160,2993,3823,2191,2201,2211,3044,3874,2242,2252,2262,2274,2285,2295,3128,3946,2326,2336,2346,3179,3997,2377,2387,2397,3230,4048,2430,2444,2457,2470,65535,65535,65535,65535,65535,65535,65535,65535,65535},
{3299,2078,2088,2099,2520,3350,2130,2551,2561,2571,3401,2181,2602,2612,2622,3452,2232,2653,2663,2673,2685,2696,2706,3524,2316,2737,2747,2757,3575,2367,2788,2798,2808,3626,2418,3649,3663,3676,3689,65535,65535,65535,65535,65535,65535,65535,65535,65535},
{2480,2490,2500,2510,3340,2531,2541,3371,3381,3391,2582,2592,3422,3432,3442,2633,2643,3473,3483,3493,2686,3504,3514,2717,2727,3545,3555,3565,2768,2778,3596,3606,3616,2819,2829,2842,2856,2869,2882,65535,65535,65535,65535,65535,65535,65535,65535,65535},
{3300,3310,3320,3330,2521,3351,3361,2552,2562,2572,3402,3412,2603,2613,2623,3453,3463,2654,2664,2674,2687,2697,2707,3525,3535,2738,2748,2758,3576,3586,2789,2799,2809,3627,3637,3650,3664,3677,3690,65535,65535,65535,65535,65535,65535,65535,65535,65535},
{3711,2901,3731,3741,3751,3761,2952,2962,3792,3802,3812,3003,3013,3843,3853,3863,3054,3064,3894,3904,3097,3107,3925,3935,3138,3148,3966,3976,3986,3189,3199,4017,4027,4037,3240,3250,4073,3279,3292,65535,65535,65535,65535,65535,65535,65535,65535,65535},
{2892,2902,2912,2922,2932,3762,2953,2963,2973,2983,3813,3004,3014,3024,3034,3864,3055,3065,3075,3085,3098,3108,3118,3936,3139,3149,3159,3169,3987,3190,3200,3210,3220,4038,3241,4061,4075,3281,3294,65535,65535,65535,65535,65535,65535,65535,65535,65535},
{420,431,441,451,3752,472,482,492,502,3803,523,533,543,553,3854,574,584,594,604,3905,626,637,3926,658,668,678,688,3977,709,719,729,739,4028,760,770,782,796,809,823,65535,65535,65535,65535,65535,65535,65535,65535,65535},
{421,3722,3732,3742,462,2943,3773,3783,3793,513,2994,3824,3834,3844,564,3045,3875,3885,3895,615,627,3916,648,3129,3947,3957,3967,699,3180,3998,4008,4018,750,3231,4049,783,797,810,4102,65535,65535,65535,65535,65535,65535,65535,65535,65535},
{833,843,853,864,874,884,894,904,915,925,935,945,955,966,976,986,996,1006,1017,1027,1039,1049,1060,1070,1080,1090,1101,1111,1121,1131,1141,1152,1162,1172,1182,1194,1208,1221,1235,65535,65535,65535,65535,65535,65535,65535,65535,65535},
{3712,844,854,3331,875,885,895,905,916,926,936,946,956,967,977,987,997,1007,1018,1028,1040,1050,1061,1071,1081,1091,1102,1112,1122,1132,1142,1153,1163,1173,1183,1195,1209,1222,3691,65535,65535,65535,65535,65535,65535,65535,65535,65535},
{1245,1255,1266,1276,1286,1296,1306,1316,1327,1337,1347,1357,1367,1378,1388,1398,1408,1418,1429,1439,1451,1462,1472,1482,1492,1502,1513,1523,1533,1543,1553,1564,1574,1584,1594,1607,1620,1634,1647,65535,65535,65535,65535,65535,65535,65535,65535,65535},
{1246,1256,3321,1277,1287,1297,1307,1317,1328,1338,1348,1358,1368,1379,1389,1399,1409,1419,1430,1440,1452,1463,1473,1483,1493,1503,1514,1524,1534,1544,1554,1565,1575,1585,1595,1608,1621,1635,3692,65535,65535,65535,65535,65535,65535,65535,65535,65535},
{1657,1667,1678,1688,1698,1708,1718,1729,1739,1749,1759,1769,1780,1790,1800,1810,1820,1831,1841,1851,1863,1874,1884,1894,1904,1915,1925,1935,1945,1955,1966,1976,1986,1996,2006,2019,2033,2046,2059,65535,65535,65535,65535,65535,65535,65535,65535,65535},
{1658,1668,1679,1689,1699,1709,1719,1730,1740,1750,1760,1770,1781,1791,1801,1811,1821,1832,1842,1852,1864,1875,1885,1895,1905,1916,1926,1936,1946,1956,1967,1977,1987,1997,2007,2020,2034,2047,4104,65535,65535,65535,65535,65535,65535,65535,65535,65535},
{2069,2080,2091,2101,2111,2121,3362,2142,2152,2162,2172,3413,2193,2203,2213,2223,3464,2244,2254,2264,2276,2287,2297,2307,3536,2328,2338,2348,2358,3587,2379,2389,2399,2409,3638,2432,2446,2459,3693,65535,65535,65535,65535,65535,65535,65535,65535,65535},
{2070,2491,2090,2100,2110,2120,2131,2141,2151,2161,2171,2182,2192,2202,2212,2222,2233,2243,2253,2263,2275,2286,2296,2306,2317,2327,2337,2347,2357,2368,2378,2388,2398,2408,2419,2431,2445,2458,2471,65535,65535,65535,65535,65535,65535,65535,65535,65535},
{2481,3311,2501,2511,3341,2532,2542,3372,3382,3392,2583,2593,3423,3433,3443,2634,2644,3474,3484,3494,2688,3505,3515,2718,2728,3546,3556,3566,2769,2779,3597,3607,3617,2820,2830,2843,2857,2870,2883,65535,65535,65535,65535,65535,65535,65535,65535,65535},
{3301,2492,2502,2512,2522,3352,2543,2553,2563,2573,3403,2594,2604,2614,2624,3454,2645,2655,2665,2675,3496,2698,2708,3526,2729,2739,2749,2759,3577,2780,2790,2800,2810,3628,2831,3651,3665,3678,3694,65535,65535,65535,65535,65535,65535,65535,65535,65535},
{2893,2903,2913,2923,2933,3763,2954,2964,2974,2984,3814,3005,3015,3025,3035,3865,3056,3066,3076,3086,3099,3109,3119,3937,3140,3150,3160,3170,3988,3191,3201,3211,3221,4039,3242,3254,3268,4089,3295,65535,65535,65535,65535,65535,65535,65535,65535,65535},
{3713,3723,3733,3743,3753,2944,3774,3784,3794,3804,2995,3825,3835,3845,3855,3046,3876,3886,3896,3906,3100,3917,3927,3130,3948,3958,3968,3978,3181,3999,4009,4019,4029,3232,4050,4062,4076,3282,4103,65535,65535,65535,65535,65535,65535,65535,65535,65535},
{2482,3312,3322,3332,3342,2533,3363,3373,3383,3393,2584,3414,3424,3434,3444,2635,3465,3475,3485,3495,2689,3506,3516,2719,3537,3547,3557,3567,2770,3588,3598,3608,3618,2821,3639,2844,2858,2871,4105,65535,65535,65535,65535,65535,65535,65535,65535,65535},
{3302,2493,2503,2513,2523,3353,2544,2554,2564,2574,3404,2595,2605,2615,2625,3455,2646,2656,2666,2676,3497,2699,2709,3527,2730,2740,2750,2760,3578,2781,2791,2801,2811,3629,2832,3652,3666,3679,3695,65535,65535,65535,65535,65535,65535,65535,65535,65535},
{2894,2904,2914,2924,2934,3764,2955,2965,2975,2985,3815,3006,3016,3026,3036,3866,3057,3067,3077,3087,3908,3110,3120,3938,3141,3151,3161,3171,3989,3192,3202,3212,3222,4040,3243,3255,3269,4090,4106,65535,65535,65535,65535,65535,65535,65535,65535,65535},
{3714,3724,3734,3744,3754,2945,3775,3785,3795,3805,2996,3826,3836,3846,3856,3047,3877,3887,3897,3907,3101,3918,3928,3131,3949,3959,3969,3979,3182,4000,4010,4020,4030,3233,4051,4063,4077,3283,4107,65535,65535,65535,65535,65535,65535,65535,65535,65535},
{5,15,25,36,46,56,66,76,86,97,107,117,127,137,148,158,168,178,188,199,211,222,232,242,252,262,272,283,293,303,313,323,334,344,354,364,380,393,406,65535,65535,65535,65535,65535,65535,65535,65535,65535},
{6,16,26,37,47,57,67,77,87,98,108,118,128,138,149,159,169,179,189,200,212,223,233,243,253,263,273,284,294,304,314,324,335,345,355,365,381,394,407,65535,65535,65535,65535,65535,65535,65535,65535,65535},
{7,17,27,38,48,58,68,78,88,99,109,119,129,139,150,160,170,180,190,201,213,224,234,244,254,264,274,285,295,305,315,325,336,346,356,366,382,395,408,65535,65535,65535,65535,65535,65535,65535,65535,65535},
{8,18,28,39,49,59,69,79,89,100,110,120,130,140,151,161,171,181,191,202,214,225,235,245,255,265,275,286,296,306,316,326,337,347,357,370,383,396,409,65535,65535,65535,65535,65535,65535,65535,65535,65535},
{9,19,29,40,50,60,70,80,90,101,111,121,131,141,152,162,172,182,192,203,215,226,236,246,256,266,276,287,297,307,317,327,338,348,358,371,384,397,410,65535,65535,65535,65535,65535,65535,65535,65535,65535},
{10,20,30,41,51,61,71,81,91,102,112,122,132,142,153,163,173,183,193,204,216,227,237,247,257,267,277,288,298,308,318,328,339,349,359,372,385,398,411,65535,65535,65535,65535,65535,65535,65535,65535,65535},
{11,21,31,42,52,62,72,82,92,103,113,123,133,143,154,164,174,184,194,205,217,228,238,248,258,268,278,289,299,309,319,329,340,350,360,373,386,399,65535,65535,65535,65535,65535,65535,65535,65535,65535,65535},
{12,3315,32,2514,2524,3354,74,84,94,2575,3405,125,135,145,2626,3456,176,186,196,207,3102,2700,2710,3528,260,270,280,2761,3579,311,321,331,2812,3630,362,3258,388,3284,65535,65535,65535,65535,65535,65535,65535,65535,65535,65535},
};

#define NG SCHED_NG
#define RING SCHED_RING
#define NSLOT 8
#define CFETCH 5
#define TABLED 1
#define PROMO CU_TENSOR_MAP_L2_PROMOTION_L2_128B
#define AHEAD 6
#define CF0 5
#define CFS 2
#define ABL 0
#define CX 5
#define PUBN 2
#define PUBE 8
#define SCHED 9
#define OUT_TMA 0
#define JB1 21
#define JB2 24
#define CVAR 2
#define CFN 0
#define CREGS 224
#define CSLEEP 200
#define JB 19
#define JF 24
#define JR 17
#define HOIST 1
#define XEARLY 0
#define FPRED 1
#define LATERED 1
#define WDELAY 0
#define WDELAY2 0
#define PFX 0
#define FIRST 3
#define NODUMP 1
#define CH 64
#define NOJB 1
#define JFF 0
#define XPRED 0
#define W2X 2
#define RETRY 0
#define HMASK 0
#define GMASK 0
#define XM 0
#define XLATE 0
#define SKIP 1
#define ONEPASS 1
#define HCOMP 1.0025f
#define SF 1
#define PRE 2
#define WN 1
#define TRIG0 -1
#define NEARLY 3
#define NLATE 0
#define TRIG 7
constexpr int NCONV = 3 * NG;
constexpr int PLEN = SCHED_LE, LM = 256 - 2 * PLEN, NSEG = 4 / (NG - 8), LMID = NSEG * LM;
static_assert(LMID <= PLEN && (NG == 9 || NG == 10), "geometry");
constexpr int TILEB = 12288;
constexpr int SLOTB = 280 * 64;
constexpr int W1S = 0, W2S = 73728, ABUF = 147456, XBUF = ABUF + 16 * 3072, MISC = XBUF + 8 * 3072;
constexpr int WBAR = MISC + 2560;
constexpr int RBUF = ABUF - 4 * SLOTB;
constexpr int CM = MISC + 2816, CTAB = CM + 256;
constexpr int SMEM_BYTES = CTAB + (PLEN + 16) * 16;
static_assert(RBUF % 512 == 0 && RBUF >= W2S && RBUF + NSLOT * SLOTB + 128 <= MISC && SMEM_BYTES <= 232448, "smem layout");

struct Globals {
  unsigned char scratch[RING * NG * 4 * TILEB];
  unsigned char wimg[147456];
  uint32_t wflag[32];
  uint32_t ready[NG * PLEN + 1];
  uint32_t cons[NG * PLEN];
  uint32_t epoch[1024];
};
__device__ __align__(1024) Globals g_state;

#define PROF_AT(cond, idx)
#define PROF_VAL(cond, idx, v)
#define PROF2_AT(c, i)
#define PROF2_VAL(c, i, v)
#define PROFS(i)
#define GELU_C3 0.32920349f
#define GELU_A2 0x40d940d9u
#define SCHED_FENCE() asm volatile("pmevent 0;" ::: "memory")
#define SPIN_LIMIT 0x1000000

__device__ __forceinline__ uint32_t smem_u32(const void* p) { return (uint32_t)__cvta_generic_to_shared(p); }
__device__ __forceinline__ void wg_fence() { asm volatile("wgmma.fence.sync.aligned;" ::: "memory"); }
__device__ __forceinline__ void wg_commit() { asm volatile("wgmma.commit_group.sync.aligned;" ::: "memory"); }
template <int N> __device__ __forceinline__ void wg_wait() { asm volatile("wgmma.wait_group.sync.aligned %0;" ::"n"(N) : "memory"); }
__device__ __forceinline__ void mbar_init(uint32_t bar, uint32_t cnt) { asm volatile("mbarrier.init.shared::cta.b64 [%0], %1;" ::"r"(bar), "r"(cnt) : "memory"); }
__device__ __forceinline__ void mbar_expect_tx(uint32_t bar, uint32_t bytes) { asm volatile("mbarrier.arrive.expect_tx.shared::cta.b64 _, [%0], %1;" ::"r"(bar), "r"(bytes) : "memory"); }
__device__ __forceinline__ void mbar_arrive(uint32_t bar) { asm volatile("mbarrier.arrive.shared::cta.b64 _, [%0];" ::"r"(bar) : "memory"); }
__device__ __forceinline__ void mbar_wait(uint32_t bar, uint32_t parity) {
  asm volatile("{\n.reg .pred p;\n.reg .u32 c;\nmbarrier.try_wait.parity.shared::cta.b64 p, [%0], %1;\n@p bra DONE_%=;\nmov.u32 c, 0;\nWAIT_%=:\nmbarrier.try_wait.parity.shared::cta.b64 p, [%0], %1;\n@p bra DONE_%=;\n"
               "add.u32 c, c, 1;\nsetp.lt.u32 p, c, 0x1000000;\n@p bra WAIT_%=;\ntrap;\nDONE_%=:\n}" ::"r"(bar), "r"(parity) : "memory");
}
__device__ __forceinline__ void bulk_g2s(uint32_t dst, const void* src, uint32_t bytes, uint32_t bar) {
  asm volatile("cp.async.bulk.shared::cluster.global.mbarrier::complete_tx::bytes [%0], [%1], %2, [%3];" ::"r"(dst), "l"(src), "r"(bytes), "r"(bar) : "memory");
}
__device__ __forceinline__ uint32_t ld_relaxed(const uint32_t* p) { uint32_t v; asm volatile("ld.relaxed.gpu.global.u32 %0, [%1];" : "=r"(v) : "l"(p) : "memory"); return v; }
__device__ __forceinline__ void red_add_elect(uint32_t* p) { asm volatile("{.reg .pred p; elect.sync _|p, 0xffffffff; @p red.relaxed.gpu.global.add.u32 [%0], 1;}" ::"l"(p) : "memory"); }
__device__ __forceinline__ void mbar_arrive_elect(uint32_t bar) { asm volatile("{.reg .pred p; elect.sync _|p, 0xffffffff; @p mbarrier.arrive.shared::cta.b64 _, [%0];}" ::"r"(bar) : "memory"); }
__device__ __forceinline__ void mbar_init_elect(uint32_t bar, uint32_t cnt) { asm volatile("{.reg .pred p; elect.sync _|p, 0xffffffff; @p mbarrier.init.shared::cta.b64 [%0], %1;}" ::"r"(bar), "r"(cnt) : "memory"); }
__device__ __forceinline__ void lds128(uint32_t* r, uint32_t a) { asm volatile("ld.shared.v4.b32 {%0,%1,%2,%3}, [%4];" : "=r"(r[0]), "=r"(r[1]), "=r"(r[2]), "=r"(r[3]) : "r"(a) : "memory"); }
__device__ __forceinline__ uint2 lds64(uint32_t a) { uint2 v; asm volatile("ld.shared.v2.b32 {%0,%1}, [%2];" : "=r"(v.x), "=r"(v.y) : "r"(a) : "memory"); return v; }
__device__ __forceinline__ uint32_t lds32(uint32_t a) { uint32_t v; asm volatile("ld.shared.b32 %0, [%1];" : "=r"(v) : "r"(a) : "memory"); return v; }
__device__ __forceinline__ void sts32(uint32_t a, uint32_t v) { asm volatile("st.shared.b32 [%0], %1;" ::"r"(a), "r"(v) : "memory"); }
__device__ __forceinline__ void sts128(uint32_t a, uint4 v) { asm volatile("st.shared.v4.b32 [%0], {%1,%2,%3,%4};" ::"r"(a), "r"(v.x), "r"(v.y), "r"(v.z), "r"(v.w) : "memory"); }
__device__ __forceinline__ uint4 ldg128v(const void* p) { uint4 v; asm volatile("ld.global.nc.v4.b32 {%0,%1,%2,%3}, [%4];" : "=r"(v.x), "=r"(v.y), "=r"(v.z), "=r"(v.w) : "l"(p) : "memory"); return v; }
__device__ __forceinline__ void stg128(void* p, uint4 v) { asm volatile("st.global.v4.b32 [%0], {%1,%2,%3,%4};" ::"l"(p), "r"(v.x), "r"(v.y), "r"(v.z), "r"(v.w) : "memory"); }
#define HINT 3
__device__ __forceinline__ uint64_t pol_evict_first() { uint64_t p; asm("createpolicy.fractional.L2::evict_first.b64 %0, 1.0;" : "=l"(p)); return p; }
__device__ __forceinline__ uint4 ldg128_last(const void* p, uint64_t pol) {
  if (!(HINT & 1)) return ldg128v(p);
  uint4 v; asm volatile("ld.global.nc.L1::no_allocate.L2::cache_hint.v4.b32 {%0,%1,%2,%3}, [%4], %5;" : "=r"(v.x), "=r"(v.y), "=r"(v.z), "=r"(v.w) : "l"(p), "l"(pol) : "memory"); return v;
}
__device__ __forceinline__ void stg128_stream(void* p, uint4 v, uint64_t pol) {
  if (!(HINT & 2)) { stg128(p, v); return; }
  asm volatile("st.global.L2::cache_hint.v4.b32 [%0], {%1,%2,%3,%4}, %5;" ::"l"(p), "r"(v.x), "r"(v.y), "r"(v.z), "r"(v.w), "l"(pol) : "memory");
}
__device__ __forceinline__ float bf_lo(uint32_t w) { return __uint_as_float(w << 16); }
__device__ __forceinline__ float bf_hi(uint32_t w) { return __uint_as_float(w & 0xffff0000u); }
__device__ __forceinline__ uint32_t pack_f16(float lo, float hi) { uint32_t d; asm("cvt.rn.f16x2.f32 %0, %1, %2;" : "=r"(d) : "f"(hi), "f"(lo)); return d; }
__device__ __forceinline__ uint32_t pack_f16_sat(float lo, float hi) { uint32_t d; asm("cvt.rn.satfinite.f16x2.f32 %0, %1, %2;" : "=r"(d) : "f"(hi), "f"(lo)); return d; }
__device__ __forceinline__ uint32_t pack_bf16(float lo, float hi) { uint32_t d; asm("cvt.rn.bf16x2.f32 %0, %1, %2;" : "=r"(d) : "f"(hi), "f"(lo)); return d; }
__device__ __forceinline__ uint32_t hadd2_bf16(uint32_t a, uint32_t b) { uint32_t d; asm("add.rn.bf16x2 %0, %1, %2;" : "=r"(d) : "r"(a), "r"(b)); return d; }
__device__ __forceinline__ uint32_t h2add(uint32_t a, uint32_t b) { uint32_t d; asm("add.rn.f16x2 %0, %1, %2;" : "=r"(d) : "r"(a), "r"(b)); return d; }
__device__ __forceinline__ uint32_t h2mul(uint32_t a, uint32_t b) { uint32_t d; asm("mul.rn.f16x2 %0, %1, %2;" : "=r"(d) : "r"(a), "r"(b)); return d; }
__device__ __forceinline__ uint32_t h2fma(uint32_t a, uint32_t b, uint32_t c) { uint32_t d; asm("fma.rn.f16x2 %0, %1, %2, %3;" : "=r"(d) : "r"(a), "r"(b), "r"(c)); return d; }
__device__ __forceinline__ uint32_t h2lo(uint32_t a) { uint32_t d; asm("{.reg .f16 l,h; mov.b32 {l,h}, %1; mov.b32 %0, {l,l};}" : "=r"(d) : "r"(a)); return d; }
__device__ __forceinline__ uint32_t h2hi(uint32_t a) { uint32_t d; asm("{.reg .f16 l,h; mov.b32 {l,h}, %1; mov.b32 %0, {h,h};}" : "=r"(d) : "r"(a)); return d; }
__device__ __forceinline__ float h_lo(uint32_t a) { float d; asm("{.reg .f16 l,h; mov.b32 {l,h}, %1; cvt.f32.f16 %0, l;}" : "=f"(d) : "r"(a)); return d; }
__device__ __forceinline__ float h_hi(uint32_t a) { float d; asm("{.reg .f16 l,h; mov.b32 {l,h}, %1; cvt.f32.f16 %0, h;}" : "=f"(d) : "r"(a)); return d; }
__device__ __forceinline__ uint32_t prmt(uint32_t a, uint32_t b, uint32_t s) { uint32_t d; asm("prmt.b32 %0, %1, %2, %3;" : "=r"(d) : "r"(a), "r"(b), "r"(s)); return d; }
__device__ __forceinline__ void mma_sp(float* d, const uint32_t* a, const uint32_t* b, const float* c, uint32_t e) {
  asm("mma.sp::ordered_metadata.sync.aligned.m16n8k32.row.col.f32.bf16.bf16.f32 {%0,%1,%2,%3}, {%4,%5,%6,%7}, {%8,%9,%10,%11}, {%12,%13,%14,%15}, %16, 0;"
      : "=f"(d[0]), "=f"(d[1]), "=f"(d[2]), "=f"(d[3])
      : "r"(a[0]), "r"(a[1]), "r"(a[2]), "r"(a[3]), "r"(b[0]), "r"(b[1]), "r"(b[2]), "r"(b[3]), "f"(c[0]), "f"(c[1]), "f"(c[2]), "f"(c[3]), "r"(e));
}
__device__ __forceinline__ uint32_t bf2_to_h2(uint32_t w, float s) { return pack_f16(bf_lo(w) * s, bf_hi(w) * s); }
__device__ __forceinline__ uint32_t bf2_to_h2(uint32_t w) { return pack_f16(bf_lo(w), bf_hi(w)); }

__device__ __forceinline__ uint32_t gelu_tanh(uint32_t y) {
  uint32_t t, u, th;
  asm volatile("fma.rn.f16x2 %0, %1, %1, %2;" : "=r"(t) : "r"(y), "r"(GELU_A2));
  asm volatile("mul.rn.f16x2 %0, %1, %2;" : "=r"(u) : "r"(y), "r"(t));
  asm volatile("tanh.approx.f16x2 %0, %1;" : "=r"(th) : "r"(u));
  return th;
}
__device__ __forceinline__ uint32_t gelu_fin(uint32_t y, uint32_t th) {
  uint32_t g;
  asm volatile("fma.rn.f16x2 %0, %1, %2, %1;" : "=r"(g) : "r"(y), "r"(th));
  return g;
}

__device__ __forceinline__ void copy_weights(uint32_t sb, int piece, const void* src) {
  asm volatile("{\n.reg .pred p;\nelect.sync _|p, 0xffffffff;\n@p mbarrier.init.shared::cta.b64 [%1], 1;\n@p fence.mbarrier_init.release.cluster;\n"
               "@p mbarrier.arrive.expect_tx.shared::cta.b64 _, [%1], 12288;\n"
               "@p cp.async.bulk.shared::cluster.global.mbarrier::complete_tx::bytes [%0], [%2], 12288, [%1];\n}"
               ::"r"(sb + piece * 12288), "r"(sb + WBAR + piece * 8), "l"(src) : "memory");
}
__device__ __forceinline__ void convert_weights(uint32_t sb, uint32_t wbar, int rot, int warp, int lane) {
  if (warp < 12) {
    const int l8 = lane & 7, q4 = lane >> 3;
    int s = (warp >> 1) + rot; if (s >= 6) s -= 6;
    const uint32_t base = sb + W1S + s * 12288 + (warp & 1) * 384;
    mbar_wait(wbar + s * 8, 0);
    uint32_t v[3][4][4];
#pragma unroll
    for (int r = 0; r < 4; r++)
#pragma unroll
      for (int i = 0; i < 3; i++) lds128(v[i][r], base + i * 128 + (4 * (l8 >> 1) + 2 * (r & 1) + (l8 & 1)) * 768 + ((l8 + q4 + 4 * (r >> 1)) & 7) * 16);
    __syncwarp();
#pragma unroll
    for (int r = 0; r < 4; r++)
#pragma unroll
      for (int i = 0; i < 3; i++)
        sts128(base + i * 128 + (((l8 + q4 + 4 * (r >> 1)) & 7) + 8 * (r & 1)) * 768 + l8 * 16,
               make_uint4(bf2_to_h2(v[i][r][0]), bf2_to_h2(v[i][r][1]), bf2_to_h2(v[i][r][2]), bf2_to_h2(v[i][r][3])));
  }
  PROF2_AT(lane == 0, 440 + warp);
  const int q = lane & 3, t = (lane >> 2) & 3, b = lane >> 4;
  int u = 3 * (warp ^ 15) + 8 * rot; if (u >= 48) u -= 48;
  uint32_t base[3], v[3][4][3];
#pragma unroll
  for (int i = 0; i < 3; i++) {
    const int ui = u + i >= 48 ? u + i - 48 : u + i;
    base[i] = sb + W2S + ui * 1536;
    if (i != 1) mbar_wait(wbar + 48 + (ui >> 3) * 8, 0);
  }
#pragma unroll
  for (int i = 0; i < 3; i++)
#pragma unroll
    for (int d = 0; d < 4; d++)
#pragma unroll
      for (int j = 0; j < 3; j++) v[i][d][j] = lds32(base[i] + (2 * ((q + d) & 3) + b) * 192 + j * 64 + t * 16 + q * 4);
  __syncwarp();
#pragma unroll
  for (int i = 0; i < 3; i++)
#pragma unroll
    for (int d = 0; d < 4; d++)
#pragma unroll
      for (int j = 0; j < 3; j++) sts32(base[i] + (4 * j + q) * 128 + (2 * ((q + d) & 3) + b) * 16 + t * 4, bf2_to_h2(v[i][d][j]));
}

__device__ __noinline__ void ln_wide(uint32_t ad) {
  float m[2], r[2];
#pragma unroll
  for (int hi = 0; hi < 2; hi++) {
    float sm = 0.f;
    for (int s = 0; s < 6; s++) { uint2 w = lds64(ad + s * 512 + hi * 8); sm += (h_lo(w.x) + h_hi(w.x)) + (h_lo(w.y) + h_hi(w.y)); }
    sm += __shfl_xor_sync(0xffffffffu, sm, 1); sm += __shfl_xor_sync(0xffffffffu, sm, 2);
    m[hi] = sm * (1.f / 96.f);
    float q = 0.f;
    for (int s = 0; s < 6; s++) {
      uint2 w = lds64(ad + s * 512 + hi * 8);
      float d0 = h_lo(w.x) - m[hi], d1 = h_hi(w.x) - m[hi], d2 = h_lo(w.y) - m[hi], d3 = h_hi(w.y) - m[hi];
      q += (d0 * d0 + d1 * d1) + (d2 * d2 + d3 * d3);
    }
    q += __shfl_xor_sync(0xffffffffu, q, 1); q += __shfl_xor_sync(0xffffffffu, q, 2);
    r[hi] = rsqrtf(fmaf(q, 1.f / 96.f, 1e-5f)) * GELU_C3;
  }
  for (int s = 0; s < 6; s++) {
    uint32_t w[4]; lds128(w, ad + s * 512);
    sts128(ad + s * 512, make_uint4(pack_f16((h_lo(w[0]) - m[0]) * r[0], (h_hi(w[0]) - m[0]) * r[0]), pack_f16((h_lo(w[2]) - m[1]) * r[1], (h_hi(w[2]) - m[1]) * r[1]),
                                    pack_f16((h_lo(w[1]) - m[0]) * r[0], (h_hi(w[1]) - m[0]) * r[0]), pack_f16((h_lo(w[3]) - m[1]) * r[1], (h_hi(w[3]) - m[1]) * r[1])));
  }
  asm volatile("fence.proxy.async.shared::cta;" ::: "memory");
}

__device__ __forceinline__ float rsqrt_fast(float v) { float r; asm("rsqrt.approx.ftz.f32 %0, %1;" : "=f"(r) : "f"(v)); return r; }
__device__ __forceinline__ uint32_t layer_norm(uint32_t (&raw)[6][4], uint32_t* a, uint32_t tag) {
  const uint32_t stale = ((raw[0][0] ^ tag) | (raw[1][0] ^ tag)) | ((raw[2][0] ^ tag) | (raw[3][0] ^ tag)) | ((raw[4][0] ^ tag) | (raw[5][0] ^ tag));
  uint32_t sm[2];
#pragma unroll
  for (int hi = 0; hi < 2; hi++) {
    uint32_t s0 = h2add(raw[0][2 * hi], raw[1][2 * hi]), s1 = h2add(raw[0][2 * hi + 1], raw[1][2 * hi + 1]);
    uint32_t s2 = h2add(raw[2][2 * hi], raw[3][2 * hi]), s3 = h2add(raw[2][2 * hi + 1], raw[3][2 * hi + 1]);
    uint32_t s4 = h2add(raw[4][2 * hi], raw[5][2 * hi]), s5 = h2add(raw[4][2 * hi + 1], raw[5][2 * hi + 1]);
    sm[hi] = h2add(h2add(h2add(s0, s1), h2add(s2, s3)), h2add(s4, s5));
  }
  uint32_t qq[2];
#pragma unroll
  for (int hi = 0; hi < 2; hi++) {
    uint32_t q0 = h2mul(raw[0][2 * hi], raw[0][2 * hi]), q1 = h2mul(raw[0][2 * hi + 1], raw[0][2 * hi + 1]);
#pragma unroll
    for (int k = 1; k < 6; k++) { q0 = h2fma(raw[k][2 * hi], raw[k][2 * hi], q0); q1 = h2fma(raw[k][2 * hi + 1], raw[k][2 * hi + 1], q1); }
    qq[hi] = h2add(q0, q1);
  }
  uint32_t s = h2add(prmt(sm[0], sm[1], 0x5410), prmt(sm[0], sm[1], 0x7632));
  uint32_t q = h2add(prmt(qq[0], qq[1], 0x5410), prmt(qq[0], qq[1], 0x7632));
  s = h2add(s, __shfl_xor_sync(0xffffffffu, s, 1)); q = h2add(q, __shfl_xor_sync(0xffffffffu, q, 1));
  s = h2add(s, __shfl_xor_sync(0xffffffffu, s, 2)); q = h2add(q, __shfl_xor_sync(0xffffffffu, q, 2));
  constexpr float CS = HMASK ? GELU_C3 * HCOMP : GELU_C3;
  constexpr float K1 = 1.f / (96.f * CS * CS), K2 = 1e-5f / (CS * CS), K3 = 1.f / (96.f * CS);
  const float e0 = fmaf(h_lo(q), K1, K2), e1 = fmaf(h_hi(q), K1, K2), m0 = h_lo(s) * K3, m1 = h_hi(s) * K3;
  const float v0 = fmaf(-m0, m0, e0), v1 = fmaf(-m1, m1, e1);
  const uint32_t r = pack_f16(rsqrt_fast(v0), rsqrt_fast(v1)), o = h2mul(h2mul(s, 0xA155A155u), r);
#pragma unroll
  for (int k = 0; k < 6; k++) {
    a[4 * k] = h2fma(raw[k][0], h2lo(r), h2lo(o)); a[4 * k + 2] = h2fma(raw[k][1], h2lo(r), h2lo(o));
    a[4 * k + 1] = h2fma(raw[k][2], h2hi(r), h2hi(o)); a[4 * k + 3] = h2fma(raw[k][3], h2hi(r), h2hi(o));
  }
  if (HMASK) {
#pragma unroll
    for (int k = 0; k < 24; k++) a[k] &= HMASK;
  }
  const bool fine = fmaf(v0, 4.f, -e0) > 0.f && fmaf(v1, 4.f, -e1) > 0.f;
  return (fine ? 0u : 2u) | (stale & 1);
}

constexpr int KS = CH / 16, NC = 384 / CH;
#define WG1_(n) wgmma_n##n##_f16
#define WG1(n) WG1_(n)
__device__ __forceinline__ void gemm1(uint32_t* p, const uint32_t* a, uint64_t d1, int c, int k0 = 0, int k1 = 6) {
#pragma unroll
  for (int s = 0; s < 6; s++)
    if (s >= k0 && s < k1) {
      if (s == 0) WG1(CH)<0>(p, a, d1 + c * CH); else WG1(CH)<1>(p, a + 4 * s, d1 + c * CH + s * (12288 >> 4));
    }
}
__device__ __forceinline__ void fetch_a(uint32_t abuf, uint32_t bar, const unsigned char* src) {
  asm volatile("{\n.reg .pred p;\nelect.sync _|p, 0xffffffff;\n"
               "@p mbarrier.arrive.expect_tx.shared::cta.b64 _, [%1], 3072;\n"
               "@p cp.async.bulk.shared::cluster.global.mbarrier::complete_tx::bytes [%0], [%2], 3072, [%1];\n}"
               ::"r"(abuf), "r"(bar), "l"(src) : "memory");
}
__device__ __forceinline__ void fetch_a_if(uint32_t abuf, uint32_t bar, const unsigned char* src, uint32_t go) {
  asm volatile("{\n.reg .pred p, q;\nsetp.ne.u32 q, %3, 0;\nelect.sync _|p, 0xffffffff;\nand.pred p, p, q;\n"
               "@p mbarrier.arrive.expect_tx.shared::cta.b64 _, [%1], 3072;\n"
               "@p cp.async.bulk.shared::cluster.global.mbarrier::complete_tx::bytes [%0], [%2], 3072, [%1];\n}"
               ::"r"(abuf), "r"(bar), "l"(src), "r"(go) : "memory");
}
__device__ __forceinline__ bool mbar_test(uint32_t bar, uint32_t parity) {
  uint32_t r;
  asm volatile("{.reg .pred p; mbarrier.test_wait.parity.shared::cta.b64 p, [%1], %2; selp.u32 %0, 1, 0, p;}" : "=r"(r) : "r"(bar), "r"(parity) : "memory");
  return r;
}
__device__ __forceinline__ void fetch_x(uint32_t xbuf, uint32_t bar, const CUtensorMap* tm, uint32_t c0, uint32_t c12, uint64_t pol, int go = 0) {
  asm volatile("{\n.reg .pred p, q;\nsetp.ge.s32 q, %7, 0;\nelect.sync _|p, 0xffffffff;\nand.pred p, p, q;\n"
               "@p mbarrier.arrive.expect_tx.shared::cta.b64 _, [%1], 3072;\n"
               "@p cp.async.bulk.tensor.3d.shared::cluster.global.mbarrier::complete_tx::bytes.L2::cache_hint [%0], [%2, {%3, %4, %5}], [%1], %6;\n}"
               ::"r"(xbuf), "r"(bar), "l"(tm), "r"(c0), "r"(c12 & 255), "r"(c12 >> 8), "l"(pol), "r"(go) : "memory");
}
__device__ __forceinline__ void wait_ready(const uint32_t* p, uint32_t target) {
  int spins = 0;
  while (ld_relaxed(p) != target) { __nanosleep(32); if (++spins > SPIN_LIMIT) __trap(); }
}
__device__ __forceinline__ uint32_t slot_tag(int gm, int j, uint32_t epoch) {
  const int len = gm < 8 ? PLEN : LMID, writes = (len - (j % RING) + RING - 1) / RING;
  return (epoch * writes + j / RING + 1) & 1;
}

__device__ __forceinline__ void build_tile_list(uint32_t sb, int k, int idx, bool tabled, bool is_conv, uint32_t epoch) {
  int n = -1;
  if (tabled) { if (k < 48) n = (int16_t)g_sched[idx][k]; }
  else if (!is_conv) {
    const int i = k * (gridDim.x - NCONV) + idx, r = i >> 2, full = LMID * NG;
    const int j = r < full ? r / NG : ((r - full) >> 3) + LMID, gm = r < full ? r % NG : (r - full) & 7;
    if (i < 4096) n = (gm * PLEN + j) * 4 + (i & 3);
  }
  const int q = n >> 2, gm = q / PLEN, j = q - gm * PLEN, seg = j / LM;
  const int strip = gm < 8 ? gm >> 1 : (gm - 8) * NSEG + seg, pair = gm < 8 ? ((gm & 1) ? 255 - j : j) : PLEN + j - seg * LM;
  sts128(sb + MISC + 512 + k * 16, make_uint4(q, (((j % RING) * NG + gm) * 4 + (n & 3)) * TILEB + slot_tag(gm, j, epoch),
                                              (n & 2) * 384, (strip * 8 + (n & 1) * 4) | (pair << 9)));
  if (k == 0) sts32(sb + MISC + 256, epoch + 1);
}

__device__ __forceinline__ void mlp_setup(uint32_t sb, Globals* gs, int id, const __nv_bfloat16* __restrict__ w1, const __nv_bfloat16* __restrict__ w2,
                                          int idx, bool tabled, int warp, int lane) {
  const int rot = idx % 6;
  PROF2_AT(lane == 0, 400 + warp);
  if (warp < 12) {
    const int m = warp >= 6; int s = warp - 6 * m + rot; if (s >= 6) s -= 6;
    if (WDELAY) __nanosleep(WDELAY + m * WDELAY2);
    copy_weights(sb, 6 * m + s, (const char*)(m ? w2 : w1) + s * 12288);
  }
  __syncthreads();
  PROF2_AT(threadIdx.x == 0, 416);
  if (warp >= 12) build_tile_list(sb, threadIdx.x - 384, idx, tabled, false, ld_relaxed(&gs->epoch[id]));
  PROF2_AT(lane == 0, 420 + warp);
  convert_weights(sb, sb + WBAR, rot, warp, lane);
  PROF2_AT(lane == 0, 460 + warp);
  asm volatile("fence.proxy.async.shared::cta;" ::: "memory");
  __syncthreads();
  if (threadIdx.x == 480) {
    const uint32_t e1 = lds32(sb + MISC + 256);
    gs->epoch[id] = e1;
    if (idx < 24 && (idx & 1)) {
      asm volatile("cp.async.bulk.global.shared::cta.bulk_group [%0], [%1], 12288;\ncp.async.bulk.commit_group;\ncp.async.bulk.wait_group 0;\nfence.proxy.async.global;\n"
                   "red.release.gpu.global.add.u32 [%2], 1;" ::"l"(gs->wimg + (idx >> 1) * 12288), "r"(sb + (idx >> 1) * 12288), "l"(gs->wflag) : "memory");
    }
  }
  __syncwarp();
}

__device__ __forceinline__ void mlp_role(uint32_t sb, Globals* gs, const CUtensorMap* tmr, __nv_bfloat16* __restrict__ out) {
  uint32_t tid;
  asm volatile("mov.u32 %0, %%tid.x;" : "=r"(tid));
  const int warp = __shfl_sync(0xffffffffu, tid >> 5, 0), lane = tid & 31;
  const int wg = warp >> 2, w = warp & 3, g = lane >> 2, t = lane & 3;
  const uint32_t abuf = sb + ABUF + warp * 3072, xbuf = sb + XBUF + (warp & 7) * 3072;
  const uint32_t bar = sb + MISC + warp * 8, obar = sb + MISC + (warp ^ 8) * 8;
  const uint32_t tl = sb + MISC + 512;
  PROF_AT(threadIdx.x == 0, 1); PROF_VAL(threadIdx.x == 0, 8, clock64());
  const uint32_t rtarget = 3 * lds32(sb + MISC + 256);
  const uint64_t d1 = ((uint64_t)(6144 >> 4) << 16) | ((uint64_t)(128 >> 4) << 32) | (uint64_t)(((sb + W1S) >> 4) & 0x3fff);
  const uint64_t d2 = ((uint64_t)(12288 >> 4) << 16) | ((uint64_t)(128 >> 4) << 32) | (uint64_t)(((sb + W2S) >> 4) & 0x3fff);
  const uint32_t ad = abuf + t * 128 + ((g ^ (2 * t)) << 4);
  const uint32_t xd = xbuf + g * 192 + t * 16;
  const uint32_t pofs = (g >> 1) * 3072 + (2 * w + (g & 1)) * 192 + t * 16;
  const int mybar = 1 + wg, nxtbar = 1 + ((wg + 1) & 3);
  const uint64_t pol = pol_evict_first();
  const unsigned char* const asrc = gs->scratch + w * 3072;
  uint32_t pha = 0, phx = 0, tp = tl + wg * 16;
  bool pending = true;
  uint32_t cur[4];
  lds128(cur, tp);
  while ((int)cur[0] >= 0) {
    PROF2_AT((threadIdx.x & 127) == 0, 16 + (tp - tl) / 4); PROF2_VAL((threadIdx.x & 127) == 0, 16 + (tp - tl) / 4 + 3, pending);
    uint32_t a[24], p[NC][CH / 4], gg[24][4], th[24][4], acc[24], raw[6][4], xr[6][4], n2[4], n4[4];
    if (pending) {
      wait_ready(&gs->ready[cur[0]], rtarget);
      fetch_a(abuf, bar, asrc + (cur[1] & ~1u));
      if (tp < tl + 32) fetch_x(xbuf, bar + 128, tmr, cur[2] + w * 192, cur[3], pol);
    }
    mbar_wait(bar, pha); pha ^= 1;
    PROF2_AT((threadIdx.x & 127) == 0, 16 + (tp - tl) / 4 + 1);
#pragma unroll
    for (int k = 0; k < 6; k++) lds128(raw[k], ad + k * 512);
    int sig = (int)lds32(tp + 16) >> 31;
    if (TRIG0 >= 0 && sig == 0) sig = tp < tl + 16 * NEARLY || (NLATE && (int)lds32(tp + 16 + 16 * NLATE) < 0);
    lds128(n4, tp + 64);
    if (XLATE) lds128(n2, tp - 32);
    uint32_t st = layer_norm(raw, a, cur[1]);
    if (__any_sync(0xffffffffu, st != 0)) {
      for (int tries = 0; __any_sync(0xffffffffu, st & 1); tries++) {
        if (tries > SPIN_LIMIT) __trap();
        fetch_a(abuf, bar, asrc + (cur[1] & ~1u));
        mbar_wait(bar, pha); pha ^= 1;
        st = 0;
#pragma unroll
        for (int k = 0; k < 6; k++) st |= lds32(ad + k * 512) ^ cur[1];
      }
      ln_wide(ad);
#pragma unroll
      for (int k = 0; k < 6; k++) lds128(a + 4 * k, ad + k * 512);
    }
    if (!LATERED) red_add_elect(&gs->cons[cur[0]]);
    if (tp != tl) asm volatile("bar.sync %0, 256;" ::"r"(mybar) : "memory");
    PROF2_AT((threadIdx.x & 127) == 0, 16 + (tp - tl) / 4 + 2);
    uint32_t rdy = 0;
    wg_fence();
    gemm1(p[0], a, d1, 0); wg_commit();
    if (SCHED == 9) { gemm1(p[1], a, d1, 1, 0, 6 / KS); wg_commit(); }
    if (XLATE && tp >= tl + 64) fetch_x(xbuf, obar + 128, tmr, n2[2] + w * 192, n2[3], pol);
    if (LATERED) asm volatile("{.reg .pred p; setp.eq.u32 p, %1, 0; @p red.relaxed.gpu.global.add.u32 [%0], 1;}" ::"l"(&gs->cons[cur[0]] + lane), "r"(lane) : "memory");
#pragma unroll
    for (int j = 0; j < 24; j++) {
      const int c = j / KS, s = j % KS;
      if (NOJB && j == JB) { if (NOJB == 2) SCHED_FENCE(); rdy = ld_relaxed(&gs->ready[max((int)n4[0], 0)]); if (NOJB == 3) SCHED_FENCE(); }
      if (SCHED == 9) { if (s == 0 || WN == 1) wg_wait<1>(); else if (WN == 2) wg_wait<2>(); else if (WN == 3 && s == KS - 1) wg_wait<1>(); } else if (s == 0) wg_wait<0>();
      if (j == JF) { pending = rdy != rtarget; fetch_a_if(abuf, bar, asrc + (n4[1] & ~1u), !pending && (int)n4[0] >= 0); if (JFF) SCHED_FENCE(); }
      if (j == TRIG0) asm volatile("{.reg .pred p; setp.eq.s32 p, %1, 1; @p bar.arrive %0, 256;}" ::"r"(nxtbar), "r"(sig) : "memory");
      if (j == TRIG) asm volatile("{.reg .pred p; setp.eq.s32 p, %1, 0; @p bar.arrive %0, 256;}" ::"r"(nxtbar), "r"(sig) : "memory");
#pragma unroll
      for (int i = 0; i < 4; i++) {
        if (!(s && i < PRE)) th[j][i] = gelu_tanh(p[c][4 * s + i]);
        gg[j][i] = gelu_fin(p[c][4 * s + i], th[j][i]);
      }
      wg_fence();
      if (j == 0) wgmma_n96_f16<0>(acc, gg[j], d2); else wgmma_n96_f16<1>(acc, gg[j], d2 + (16 * (j % 3) + j / 3) * (1536 >> 4));
      if (SCHED == 9) {
        const int c1 = (j + 1) / KS + 1, u = (j + 1) % KS;
        if (c1 < NC) gemm1(p[c1], a, d1, c1, (6 * u) / KS, (6 * (u + 1)) / KS);
        wg_commit();
        if (PRE && s + 1 < KS) {
#pragma unroll
          for (int i = 0; i < PRE; i++) th[j + 1][i] = gelu_tanh(p[c][4 * s + 4 + i]);
        }
        if (SF && (j + 1) % (SF ? SF : 1) == 0 && j < 23) SCHED_FENCE();
      } else if (s == KS - 1) {
        if (c + 1 < NC) gemm1(p[c + 1], a, d1, c + 1);
        wg_commit();
      }
    }
    pending = rdy != rtarget;
    if (JF == 24) fetch_a_if(abuf, bar, asrc + (n4[1] & ~1u), !pending && (int)n4[0] >= 0);
    if (XM != 2) wg_wait<0>();
    mbar_wait(bar + 128, phx); phx ^= 1;
    if (XM) {
#pragma unroll
      for (int k = 0; k < 6; k++) lds128(xr[k], xd + (k / 3) * 1536 + (k % 3) * 64);
    }
    if (XM == 2) wg_wait<0>();
#pragma unroll
    for (int k = 0; k < 24; k++) acc[k] = h2mul(acc[k], 0x3E133E13u);
    char* const op = (char*)out + (cur[2] * 2 + (cur[3] & 255) * 3072 + (cur[3] >> 8) * (512 * 192) + pofs);
    if (!XLATE) lds128(n2, tp + 32);
#pragma unroll
    for (int k = 0; k < 6; k++) {
      const int hi = k / 3, j = k % 3;
      if (!XM) lds128(xr[k], xd + hi * 1536 + j * 64);
      uint4 o;
      o.x = hadd2_bf16(xr[k][0], pack_bf16(h_lo(acc[8 * j + hi]), h_hi(acc[8 * j + hi])));
      o.y = hadd2_bf16(xr[k][1], pack_bf16(h_lo(acc[8 * j + 2 + hi]), h_hi(acc[8 * j + 2 + hi])));
      o.z = hadd2_bf16(xr[k][2], pack_bf16(h_lo(acc[8 * j + 4 + hi]), h_hi(acc[8 * j + 4 + hi])));
      o.w = hadd2_bf16(xr[k][3], pack_bf16(h_lo(acc[8 * j + 6 + hi]), h_hi(acc[8 * j + 6 + hi])));
      stg128_stream(op + hi * (512 * 192) + j * 64, o, pol);
    }
    if (!XLATE) {
      __syncwarp();
      if ((int)n2[0] >= 0) fetch_x(xbuf, obar + 128, tmr, n2[2] + w * 192, n2[3], pol);
    }
    tp += 64;
#pragma unroll
    for (int k = 0; k < 4; k++) cur[k] = n4[k];
  }
  if (XLATE && tp >= tl + 64) {
    uint32_t n2[4];
    lds128(n2, tp - 32);
    __syncwarp();
    if ((int)n2[0] >= 0) fetch_x(xbuf, obar + 128, tmr, n2[2] + w * 192, n2[3], pol);
  }
  PROF_AT((threadIdx.x & 127) == 0, 4 + wg); PROF_VAL(threadIdx.x == 0, 9, clock64());
}

__device__ __forceinline__ void stg128_if(uint32_t ofs, void* p, uint4 v) {
  asm volatile("{.reg .pred q; setp.ge.s32 q, %5, 0; @q st.global.v4.b32 [%0], {%1,%2,%3,%4};}" ::"l"(p), "r"(v.x), "r"(v.y), "r"(v.z), "r"(v.w), "r"(ofs) : "memory");
}
__device__ __forceinline__ void conv_compute(uint32_t sb, Globals* gs, int third, int nit, int off, bool up, int warp, int lane) {
  const int g = lane >> 2, t = lane & 3;
  const uint32_t full = sb + CM;
  PROFS(0);
  const uint32_t wt = sb + 16384 + warp * 1024;
  sts128(wt + lane * 16, make_uint4(0, 0, 0, 0));
  if (lane < 4) sts128(wt + 512 + lane * 16, make_uint4(0, 0, 0, 0));
  asm volatile("setmaxnreg.inc.sync.aligned.u32 %0;" ::"n"(CREGS));
  PROFS(1);
  uint32_t meta = 0;
#pragma unroll
  for (int a = 0; a < 4; a++) meta |= ((4 * (t & 1) + a + 1 >= g) ? 0x80008u : 0xD000Du) << (4 * a);
  meta = __shfl_sync(0xffffffffu, meta, lane);
  uint32_t aq[4];
#pragma unroll
  for (int q = 0; q < 4; q++) {
    const int pp = (g & 1) * 140 + (t & 1) * 70 + 16 * (g >> 1) + 2 * q + (t >> 1);
    aq[q] = __shfl_sync(0xffffffffu, sb + RBUF + pp * 64 + (((warp >> 1) ^ ((pp >> 1) & 3)) << 4) + (warp & 1) * 8, lane);
  }
  const int Q = third * 8 + warp;
  unsigned char* const obase = gs->scratch + (g >> 1) * 3072 + Q * 128 + (((2 * t + (g & 1)) ^ (2 * (Q & 3))) << 4);
  const float zero4[4] = {0.f, 0.f, 0.f, 0.f};
  {
    uint32_t A[4][4][4];
    PROFS(2);
    asm volatile("bar.sync 5, 288;" ::: "memory");
    mbar_wait(sb + WBAR + 8, 0);
    PROFS(3);
    {
#pragma unroll
      for (int k = 0; k < 2; k++) {
        const int tap = lane + 32 * k, i = tap / 7;
        if (tap < 49) { const uint2 v = lds64(sb + tap * 192 + third * 64 + warp * 8); asm volatile("st.shared.v2.b32 [%0], {%1,%2};" ::"r"(wt + (tap + i + 8) * 8), "r"(v.x), "r"(v.y) : "memory"); }
      }
      __syncwarp();
      uint2 w[2][4][3];
#pragma unroll
      for (int h = 0; h < 2; h++) {
        uint32_t src = wt + ((4 * h + t - g) & 7) * 8 + (up ? 384 : 0);
#pragma unroll
        for (int u = 0; u < 4; u++) {
#pragma unroll
          for (int k = 0; k < 3; k++) w[h][u][k] = lds64(src + k * 64);
          src += up ? -128 : 128;
        }
      }
#pragma unroll
      for (int u = 0; u < 4; u++)
#pragma unroll
        for (int r = 0; r < 4; r++) {
          const uint2 w0 = w[r >> 1][u][1 - (r & 1)], w1 = w[r >> 1][u][2 - (r & 1)];
          A[0][u][r] = prmt(w0.x, w1.x, 0x5410); A[1][u][r] = prmt(w0.x, w1.x, 0x7632);
          A[2][u][r] = prmt(w0.y, w1.y, 0x5410); A[3][u][r] = prmt(w0.y, w1.y, 0x7632);
        }
    }
    float S[2][4][3][4];
#pragma unroll
    for (int s = 0; s < 2; s++)
#pragma unroll
      for (int c = 0; c < 4; c++)
#pragma unroll
        for (int i = 0; i < 3; i++)
#pragma unroll
          for (int k = 0; k < 4; k++) S[s][c][i][k] = 0.f;
    uint32_t sofs = off * SLOTB, bar = full + off * 8, ph = 0, ot = sb + CTAB;
    const uint32_t oend = ot + nit * 16;
    PROF_AT(threadIdx.x == 0, 12);
    PROFS(4);
    asm volatile("bar.sync 0, 512;" ::: "memory");
    PROFS(5);
    mbar_wait(bar, 0);
    PROF_AT(threadIdx.x == 0, 14);
    PROFS(6);
    uint2 X[3][4];
#pragma unroll
    for (int j = 0; j < 2; j++)
#pragma unroll
      for (int q = 0; q < 4; q++) X[j][q] = lds64(aq[q] + sofs + j * 512);
#pragma unroll 1
    do {
      const uint2 oe = lds64(ot);
      unsigned char* const o = obase + oe.x;
      const uint32_t dbar = bar + 64;
#pragma unroll
      for (int s = 0; s < 2; s++) {
        uint32_t B[4][4];
        if (s == 1) {
          sofs += SLOTB; bar += 8;
          if (sofs == NSLOT * SLOTB) { sofs = 0; bar = full; ph ^= 1; }
          mbar_wait(bar, ph);
        }
#pragma unroll
        for (int c = 0; c < 4; c++)
#pragma unroll
          for (int q = 0; q < 4; q++) B[c][q] = prmt(c < 2 ? X[s][q].x : X[s][q].y, c < 2 ? X[s + 1][q].x : X[s + 1][q].y, (c & 1) ? 0x7632 : 0x5410);
        if (s == 0) {
#pragma unroll
          for (int q = 0; q < 4; q++) X[2][q] = lds64(aq[q] + sofs + 2 * 512);
        } else {
#pragma unroll
          for (int j = 0; j < 2; j++)
#pragma unroll
            for (int q = 0; q < 4; q++) X[j][q] = lds64(aq[q] + sofs + j * 512);
        }
        float T[4][4];
#pragma unroll
        for (int c = 0; c < 4; c++) mma_sp(T[c], A[c][3], B[c], S[s][c][2], meta);
#pragma unroll
        for (int c = 0; c < 4; c++) mma_sp(S[s][c][2], A[c][2], B[c], S[s][c][1], meta);
        stg128_if(oe.x, o + (2 * s) * TILEB, make_uint4((pack_f16_sat(T[0][0], T[1][0]) & ~1u) | oe.y, pack_f16_sat(T[2][0], T[3][0]), pack_f16_sat(T[0][2], T[1][2]), pack_f16_sat(T[2][2], T[3][2])));
        stg128_if(oe.x, o + (2 * s + 1) * TILEB, make_uint4((pack_f16_sat(T[0][1], T[1][1]) & ~1u) | oe.y, pack_f16_sat(T[2][1], T[3][1]), pack_f16_sat(T[0][3], T[1][3]), pack_f16_sat(T[2][3], T[3][3])));
        if (s == 1) mbar_arrive_elect(dbar);
#pragma unroll
        for (int c = 0; c < 4; c++) mma_sp(S[s][c][1], A[c][1], B[c], S[s][c][0], meta);
#pragma unroll
        for (int c = 0; c < 4; c++) mma_sp(S[s][c][0], A[c][0], B[c], zero4, meta);
      }
      ot += 16;
    } while (ot != oend);
  }
  PROF_AT(threadIdx.x == 0, 13);
}

__device__ __forceinline__ void load_step(uint32_t sb, const CUtensorMap* tmx, int gm, int third, int it, int s) {
  const int seg = it / (LM + 3);
  const int st = gm < 8 ? gm >> 1 : (gm - 8) * NSEG + seg, J = gm < 8 ? ((gm & 1) ? 257 - it : it + 1) : PLEN + it - seg * (LM + 3);
  asm volatile("{\n.reg .pred p;\n.reg .s32 c2;\n.reg .u32 d2;\nelect.sync _|p, 0xffffffff;\nadd.s32 c2, %4, 64;\nadd.u32 d2, %0, 8960;\n"
               "@p mbarrier.arrive.expect_tx.shared::cta.b64 _, [%2], 17920;\n"
               "@p cp.async.bulk.tensor.3d.shared::cluster.global.mbarrier::complete_tx::bytes [%0], [%1, {%3, %4, %5}], [%2];\n"
               "@p cp.async.bulk.tensor.3d.shared::cluster.global.mbarrier::complete_tx::bytes [d2], [%1, {%3, c2, %5}], [%2];\n}"
               ::"r"(sb + RBUF + s * SLOTB), "l"(tmx), "r"(sb + CM + s * 8), "r"(third * 32), "r"(st * 128 - 3), "r"(2 * J - 3) : "memory");
}
__device__ __forceinline__ void ring_bar_init(uint32_t bar, uint32_t cnt, bool ahead) {
  asm volatile("{\n.reg .pred p, q;\nelect.sync _|p, 0xffffffff;\n@p mbarrier.init.shared::cta.b64 [%0], %1;\n"
               "setp.ne.and.u32 q, %2, 0, p;\n@q mbarrier.arrive.shared::cta.b64 _, [%0], %1;\n@p fence.mbarrier_init.release.cluster;\n}" ::"r"(bar), "r"(cnt), "r"((uint32_t)ahead) : "memory");
}
__device__ __forceinline__ void conv_loader(uint32_t sb, Globals* gs, const CUtensorMap* tmx, int gm, int nit, int off, int cidx, int third, int k) {
  static_assert(AHEAD > 4 && AHEAD <= NSLOT && NCONV >= 24, "loader");
  const uint32_t full = sb + CM;
  asm volatile("bar.sync 0, 512;" ::: "memory");
  if (FIRST + k < AHEAD) load_step(sb, tmx, gm, third, FIRST + k, (FIRST + k + off) & 7);
#pragma unroll 1
  for (int it = AHEAD + k; it < nit + AHEAD; it += 4) {
    const int u = it + off;
    const uint32_t ro = lds32(sb + CTAB + (it - AHEAD) * 16 + 8);
    mbar_wait(full + 64 + ((u - AHEAD) & 7) * 8, ((u - AHEAD) >> 3) & 1);
    red_add_elect((uint32_t*)((char*)gs + ro));
    PROF_AT((threadIdx.x & 31) == 0 && (((it - AHEAD) & (PROF > 1 ? 7 : 15)) == 0 || it - AHEAD < 6), 200 + it - AHEAD);
    if (it <= nit) load_step(sb, tmx, gm, third, it, u & 7);
    if (it >= nit - 16) {
      if (it < nit - 12) {
        wait_ready(gs->wflag, 12 * lds32(sb + MISC + 256));
        asm volatile("fence.acquire.gpu;\nfence.proxy.async.global;" ::: "memory");
        if (cidx < 24) asm volatile("{.reg .pred p; elect.sync _|p, 0xffffffff; @p cp.async.bulk.prefetch.L2.global [%0], 1536;}" ::"l"(gs->wimg + (cidx * 4 + k) * 1536) : "memory");
      }
      const int m = it == nit ? 0 : W2S;
      if (it == nit || it == nit + AHEAD - 4)
        asm volatile("{\n.reg .pred p;\nelect.sync _|p, 0xffffffff;\n@p mbarrier.arrive.expect_tx.shared::cta.b64 _, [%1], 73728;\n"
                     "@p cp.async.bulk.shared::cluster.global.mbarrier::complete_tx::bytes [%0], [%2], 73728, [%1];\n}"
                     ::"r"(sb + m), "r"(sb + WBAR), "l"(gs->wimg + m) : "memory");
    }
  }
}

__device__ __forceinline__ void conv_credit(uint32_t sb, Globals* gs, int P0, int nit, int off, uint32_t ctarget, int k) {
  const uint32_t full = sb + CM;
#pragma unroll 1
  for (int it = k + NSLOT; it <= nit; it += 4) {
    const int u = it + off, P = (int)lds32(sb + CTAB + it * 16 + 12) - RING;
    int spins = 0;
    mbar_wait(full + 64 + (u & 7) * 8, ((u >> 3) & 1) ^ 1);
    if (P >= P0) while (ld_relaxed(&gs->cons[P]) != ctarget) { __nanosleep(CSLEEP); if (++spins > SPIN_LIMIT) __trap(); }
    mbar_arrive_elect(full + (u & 7) * 8);
  }
}

__global__ void __launch_bounds__(512, 1) convnext_kernel(const __grid_constant__ CUtensorMap tmx, const __grid_constant__ CUtensorMap tmr, const __nv_bfloat16* __restrict__ dw,
                                                          const __nv_bfloat16* __restrict__ w1, const __nv_bfloat16* __restrict__ w2, __nv_bfloat16* __restrict__ out, Globals* gs) {
  extern __shared__ __align__(1024) unsigned char smem[];
  const uint32_t sb = smem_u32(smem);
  const int warp = __shfl_sync(0xffffffffu, threadIdx.x >> 5, 0), lane = threadIdx.x & 31;
  PROF_AT(threadIdx.x == 0, 0);
  if (PFX && threadIdx.x == 320) asm volatile("prefetch.tensormap [%0];" ::"l"(&tmx) : "memory");
  if (threadIdx.x == 288) asm volatile("prefetch.tensormap [%0];" ::"l"(&tmr) : "memory");
  uint32_t smid, nsmid;
  asm volatile("mov.u32 %0, %%smid;" : "=r"(smid));
  asm volatile("mov.u32 %0, %%nsmid;" : "=r"(nsmid));
  const bool tabled = TABLED && gridDim.x == 132 && nsmid == 132;
  const int id = tabled ? smid : blockIdx.x;
  int cidx, idx;
  int is_conv;
  if (tabled) {
    idx = smid;
    const int k = (smid - 60) / 14, r = smid - 60 - 14 * k;
    is_conv = smid < 48 ? !(smid & 1) : (smid >= 60 && smid <= 90 && (r & ~2) == 0);
    cidx = smid < 48 ? ((smid >> 1) & 7) * 3 + (smid >> 4) : 24 + (r >> 1) * 3 + k;
  } else {
    cidx = (blockIdx.x * NCONV) / gridDim.x;
    is_conv = ((blockIdx.x + 1) * NCONV) / gridDim.x != cidx;
    idx = blockIdx.x - cidx;
  }
  PROF_VAL(threadIdx.x == 0, 2, is_conv ? 1000 + cidx : idx);
  const int gm = cidx / 3, third = cidx - gm * 3;
  const int P0 = gm * PLEN, nit = gm < 8 ? PLEN + 2 : NSEG * (LM + 3), off = (7 - nit) & 7;
  if (is_conv && warp == 8) {
    asm volatile("{\n.reg .pred p;\nelect.sync _|p, 0xffffffff;\n@p mbarrier.init.shared::cta.b64 [%1], 1;\n@p fence.mbarrier_init.release.cluster;\n"
                 "@p mbarrier.arrive.expect_tx.shared::cta.b64 _, [%1], 9408;\n"
                 "@p cp.async.bulk.shared::cluster.global.mbarrier::complete_tx::bytes [%0], [%2], 9408, [%1];\nbar.arrive 5, 288;\n}"
                 ::"r"(sb), "r"(sb + WBAR + 8), "l"(dw) : "memory");
#pragma unroll 1
    for (int it = 0; it < NSLOT; it++) {
      const int s = (it + off) & 7;
      ring_bar_init(sb + CM + s * 8, 2, s < off);
      PROF_AT(it == 0 && (threadIdx.x & 31) == 0, 15);
      if (it < FIRST) load_step(sb, &tmx, gm, third, it, s);
    }
  }
  mbar_init_elect(sb + MISC + warp * 8, 1); mbar_init_elect(sb + MISC + 128 + warp * 8, 1);
  asm volatile("fence.mbarrier_init.release.cluster;" ::: "memory");
  if (is_conv) {
    if (warp >= 8) ring_bar_init(sb + CM + warp * 8, 8, warp - 8 < off);
    if (warp == 9) mbar_init_elect(sb + WBAR, 2);
    if (warp < 8) {
      conv_compute(sb, gs, third, nit, off, gm < 8 && (gm & 1), warp, lane);
      asm volatile("setmaxnreg.dec.sync.aligned.u32 128;");
    } else if (warp >= 12) {
      asm volatile("setmaxnreg.dec.sync.aligned.u32 24;");
      const uint32_t epoch = ld_relaxed(&gs->epoch[id]);
#pragma unroll 1
      for (int it = threadIdx.x - 384; it <= nit; it += 128) {
        const int seg = it / (LM + 3), j = gm < 8 ? it - 2 : it - 3 * (seg + 1);
        const bool ok = it < nit && j >= (gm < 8 ? 0 : seg * LM);
        sts128(sb + CTAB + it * 16, make_uint4((ok ? (j % RING) * NG + gm : -1) * (4 * TILEB), slot_tag(gm, max(j, 0), epoch),
                                               offsetof(Globals, ready) + (ok ? P0 + j : NG * PLEN) * 4, ok ? P0 + j : -1));
      }
      asm volatile("bar.sync 0, 512;" ::: "memory");
      mbar_arrive_elect(sb + CM + ((((warp + 2) & 3) + off) & 7) * 8);
      mbar_arrive_elect(sb + CM + ((((warp + 2) & 3) + off + 4) & 7) * 8);
      build_tile_list(sb, threadIdx.x - 384, idx, tabled, true, epoch);
      if (threadIdx.x == 384) gs->epoch[id] = epoch + 1;
      conv_credit(sb, gs, P0, nit, off, 16 * (epoch + 1), (warp + 2) & 3);
      mbar_wait(sb + CM + 64 + 3 * 8, ((nit + off) >> 3) & 1);
      mbar_wait(sb + CM + 64 + 6 * 8, ((nit + off) >> 3) & 1);
      asm volatile("setmaxnreg.inc.sync.aligned.u32 128;");
    } else {
      asm volatile("setmaxnreg.dec.sync.aligned.u32 %0;" ::"n"(488 - 2 * CREGS));
      conv_loader(sb, gs, &tmx, gm, nit, off, cidx, third, warp & 3);
      mbar_wait(sb + CM + 64 + 3 * 8, ((nit + off) >> 3) & 1);
      mbar_wait(sb + CM + 64 + 6 * 8, ((nit + off) >> 3) & 1);
      asm volatile("setmaxnreg.inc.sync.aligned.u32 128;");
    }
    PROF2_AT((threadIdx.x & 31) == 0, 400 + (threadIdx.x >> 5));
    mbar_wait(sb + WBAR, 0);
    asm volatile("bar.sync 0, 512;" ::: "memory");
  } else {
    mlp_setup(sb, gs, id, w1, w2, idx, tabled, warp, lane);
  }
  mlp_role(sb, gs, &tmr, out);
}

typedef CUresult (*PFN_encodeTiled)(CUtensorMap*, CUtensorMapDataType, cuuint32_t, void*, const cuuint64_t*, const cuuint64_t*, const cuuint32_t*, const cuuint32_t*,
                                    CUtensorMapInterleave, CUtensorMapSwizzle, CUtensorMapL2promotion, CUtensorMapFloatOOBfill);

extern "C" void kernel_launch(void* const* d_in, const int* in_sizes, int n_in, void* d_out, int out_size) {
  const __nv_bfloat16* x = (const __nv_bfloat16*)d_in[0];
  const __nv_bfloat16* dw = (const __nv_bfloat16*)d_in[1];
  const __nv_bfloat16* w1 = (const __nv_bfloat16*)d_in[2];
  const __nv_bfloat16* w2 = (const __nv_bfloat16*)d_in[3];
  static PFN_encodeTiled encode = nullptr;
  static int nsm = 0;
  static Globals* gs = nullptr;
  if (!encode) {
    void* fn = nullptr; cudaDriverEntryPointQueryResult qr;
    cudaGetDriverEntryPoint("cuTensorMapEncodeTiled", &fn, cudaEnableDefault, &qr);
    encode = (PFN_encodeTiled)fn;
    cudaGetSymbolAddress((void**)&gs, g_state);
    int dev = 0; cudaGetDevice(&dev);
    cudaDeviceGetAttribute(&nsm, cudaDevAttrMultiProcessorCount, dev);
    cudaFuncSetAttribute(convnext_kernel, cudaFuncAttributeMaxDynamicSharedMemorySize, SMEM_BYTES);
  }
  CUtensorMap tm;
  cuuint64_t dims[3] = {96, 512, 512}, strides[2] = {192, 192 * 512};
  cuuint32_t box[3] = {32, 70, 2}, es[3] = {1, 1, 1};
  encode(&tm, CU_TENSOR_MAP_DATA_TYPE_BFLOAT16, 3, (void*)x, dims, strides, box, es, CU_TENSOR_MAP_INTERLEAVE_NONE, CU_TENSOR_MAP_SWIZZLE_64B,
         PROMO, CU_TENSOR_MAP_FLOAT_OOB_FILL_NONE);
  CUtensorMap tr;
  cuuint64_t dims2[3] = {1536, 32, 512}, strides2[2] = {3072, 192 * 512};
  cuuint32_t box2[3] = {192, 4, 2};
  encode(&tr, CU_TENSOR_MAP_DATA_TYPE_BFLOAT16, 3, (void*)x, dims2, strides2, box2, es, CU_TENSOR_MAP_INTERLEAVE_NONE, CU_TENSOR_MAP_SWIZZLE_NONE,
         CU_TENSOR_MAP_L2_PROMOTION_NONE, CU_TENSOR_MAP_FLOAT_OOB_FILL_NONE);
  convnext_kernel<<<nsm, 512, SMEM_BYTES>>>(tm, tr, dw, w1, w2, (__nv_bfloat16*)d_out, gs);
}
```

```cpp
#include <cuda_runtime.h>
#include <cuda_bf16.h>
#include <cuda.h>
#include <stdint.h>
#include <stddef.h>

template<int SCALE_D> __device__ __forceinline__ void wgmma_n32_f16(uint32_t* d, const uint32_t* a, uint64_t desc) {
  if (SCALE_D == 0) asm volatile("wgmma.mma_async.sync.aligned.m64n32k16.f16.f16.f16 {%0,%1,%2,%3,%4,%5,%6,%7}, {%8,%9,%10,%11}, %12, 0, 1, 1, 1;"
    : "=r"(d[0]),"=r"(d[1]),"=r"(d[2]),"=r"(d[3]),"=r"(d[4]),"=r"(d[5]),"=r"(d[6]),"=r"(d[7])
    : "r"(a[0]),"r"(a[1]),"r"(a[2]),"r"(a[3]),"l"(desc));
  if (SCALE_D == 1) asm volatile("wgmma.mma_async.sync.aligned.m64n32k16.f16.f16.f16 {%0,%1,%2,%3,%4,%5,%6,%7}, {%8,%9,%10,%11}, %12, 1, 1, 1, 1;"
    : "+r"(d[0]),"+r"(d[1]),"+r"(d[2]),"+r"(d[3]),"+r"(d[4]),"+r"(d[5]),"+r"(d[6]),"+r"(d[7])
    : "r"(a[0]),"r"(a[1]),"r"(a[2]),"r"(a[3]),"l"(desc));
}

template<int SCALE_D> __device__ __forceinline__ void wgmma_n48_f16(uint32_t* d, const uint32_t* a, uint64_t desc) {
  if (SCALE_D == 0) asm volatile("wgmma.mma_async.sync.aligned.m64n48k16.f16.f16.f16 {%0,%1,%2,%3,%4,%5,%6,%7,%8,%9,%10,%11}, {%12,%13,%14,%15}, %16, 0, 1, 1, 1;"
    : "=r"(d[0]),"=r"(d[1]),"=r"(d[2]),"=r"(d[3]),"=r"(d[4]),"=r"(d[5]),"=r"(d[6]),"=r"(d[7]),"=r"(d[8]),"=r"(d[9]),"=r"(d[10]),"=r"(d[11])
    : "r"(a[0]),"r"(a[1]),"r"(a[2]),"r"(a[3]),"l"(desc));
  if (SCALE_D == 1) asm volatile("wgmma.mma_async.sync.aligned.m64n48k16.f16.f16.f16 {%0,%1,%2,%3,%4,%5,%6,%7,%8,%9,%10,%11}, {%12,%13,%14,%15}, %16, 1, 1, 1, 1;"
    : "+r"(d[0]),"+r"(d[1]),"+r"(d[2]),"+r"(d[3]),"+r"(d[4]),"+r"(d[5]),"+r"(d[6]),"+r"(d[7]),"+r"(d[8]),"+r"(d[9]),"+r"(d[10]),"+r"(d[11])
    : "r"(a[0]),"r"(a[1]),"r"(a[2]),"r"(a[3]),"l"(desc));
}

template<int SCALE_D> __device__ __forceinline__ void wgmma_n64_f16(uint32_t* d, const uint32_t* a, uint64_t desc) {
  if (SCALE_D == 0) asm volatile("wgmma.mma_async.sync.aligned.m64n64k16.f16.f16.f16 {%0,%1,%2,%3,%4,%5,%6,%7,%8,%9,%10,%11,%12,%13,%14,%15}, {%16,%17,%18,%19}, %20, 0, 1, 1, 1;"
    : "=r"(d[0]),"=r"(d[1]),"=r"(d[2]),"=r"(d[3]),"=r"(d[4]),"=r"(d[5]),"=r"(d[6]),"=r"(d[7]),"=r"(d[8]),"=r"(d[9]),"=r"(d[10]),"=r"(d[11]),"=r"(d[12]),"=r"(d[13]),"=r"(d[14]),"=r"(d[15])
    : "r"(a[0]),"r"(a[1]),"r"(a[2]),"r"(a[3]),"l"(desc));
  if (SCALE_D == 1) asm volatile("wgmma.mma_async.sync.aligned.m64n64k16.f16.f16.f16 {%0,%1,%2,%3,%4,%5,%6,%7,%8,%9,%10,%11,%12,%13,%14,%15}, {%16,%17,%18,%19}, %20, 1, 1, 1, 1;"
    : "+r"(d[0]),"+r"(d[1]),"+r"(d[2]),"+r"(d[3]),"+r"(d[4]),"+r"(d[5]),"+r"(d[6]),"+r"(d[7]),"+r"(d[8]),"+r"(d[9]),"+r"(d[10]),"+r"(d[11]),"+r"(d[12]),"+r"(d[13]),"+r"(d[14]),"+r"(d[15])
    : "r"(a[0]),"r"(a[1]),"r"(a[2]),"r"(a[3]),"l"(desc));
}

template<int SCALE_D> __device__ __forceinline__ void wgmma_n96_f16(uint32_t* d, const uint32_t* a, uint64_t desc) {
  if (SCALE_D == 0) asm volatile("wgmma.mma_async.sync.aligned.m64n96k16.f16.f16.f16 {%0,%1,%2,%3,%4,%5,%6,%7,%8,%9,%10,%11,%12,%13,%14,%15,%16,%17,%18,%19,%20,%21,%22,%23}, {%24,%25,%26,%27}, %28, 0, 1, 1, 1;"
    : "=r"(d[0]),"=r"(d[1]),"=r"(d[2]),"=r"(d[3]),"=r"(d[4]),"=r"(d[5]),"=r"(d[6]),"=r"(d[7]),"=r"(d[8]),"=r"(d[9]),"=r"(d[10]),"=r"(d[11]),"=r"(d[12]),"=r"(d[13]),"=r"(d[14]),"=r"(d[15]),"=r"(d[16]),"=r"(d[17]),"=r"(d[18]),"=r"(d[19]),"=r"(d[20]),"=r"(d[21]),"=r"(d[22]),"=r"(d[23])
    : "r"(a[0]),"r"(a[1]),"r"(a[2]),"r"(a[3]),"l"(desc));
  if (SCALE_D == 1) asm volatile("wgmma.mma_async.sync.aligned.m64n96k16.f16.f16.f16 {%0,%1,%2,%3,%4,%5,%6,%7,%8,%9,%10,%11,%12,%13,%14,%15,%16,%17,%18,%19,%20,%21,%22,%23}, {%24,%25,%26,%27}, %28, 1, 1, 1, 1;"
    : "+r"(d[0]),"+r"(d[1]),"+r"(d[2]),"+r"(d[3]),"+r"(d[4]),"+r"(d[5]),"+r"(d[6]),"+r"(d[7]),"+r"(d[8]),"+r"(d[9]),"+r"(d[10]),"+r"(d[11]),"+r"(d[12]),"+r"(d[13]),"+r"(d[14]),"+r"(d[15]),"+r"(d[16]),"+r"(d[17]),"+r"(d[18]),"+r"(d[19]),"+r"(d[20]),"+r"(d[21]),"+r"(d[22]),"+r"(d[23])
    : "r"(a[0]),"r"(a[1]),"r"(a[2]),"r"(a[3]),"l"(desc));
}

#define SCHED_NG 10
#define SCHED_LE 103
#define SCHED_RING 18
__device__ const uint16_t g_sched[132][48] = {
{376,379,382,385,65535,65535,65535,65535,65535,65535,65535,65535,65535,65535,65535,65535,65535,65535,65535,65535,65535,65535,65535,65535,65535,65535,65535,65535,65535,65535,65535,65535,65535,65535,65535,65535,65535,65535,65535,65535,65535,65535,65535,65535,65535,65535,65535,65535},
{0,2483,22,2915,2925,2935,3765,73,83,93,2986,3816,124,134,144,3037,3867,175,185,195,3088,218,3111,3121,3939,259,269,279,3172,3990,310,320,330,3223,4041,361,371,393,3286,65535,65535,65535,65535,65535,65535,65535,65535,65535},
{788,791,794,797,65535,65535,65535,65535,65535,65535,65535,65535,65535,65535,65535,65535,65535,65535,65535,65535,65535,65535,65535,65535,65535,65535,65535,65535,65535,65535,65535,65535,65535,65535,65535,65535,65535,65535,65535,65535,65535,65535,65535,65535,65535,65535,65535,65535},
{412,422,432,442,452,463,473,483,493,503,514,524,534,544,554,565,575,585,595,605,616,628,638,649,659,669,679,689,700,710,720,730,740,751,761,771,781,804,814,65535,65535,65535,65535,65535,65535,65535,65535,65535},
{1200,1203,1206,1209,65535,65535,65535,65535,65535,65535,65535,65535,65535,65535,65535,65535,65535,65535,65535,65535,65535,65535,65535,65535,65535,65535,65535,65535,65535,65535,65535,65535,65535,65535,65535,65535,65535,65535,65535,65535,65535,65535,65535,65535,65535,65535,65535,65535},
{824,834,845,855,865,876,886,896,906,917,927,937,947,957,968,978,988,998,1008,1019,1029,1041,1051,1062,1072,1082,1092,1103,1113,1123,1133,1143,1154,1164,1174,1184,1194,1216,1227,65535,65535,65535,65535,65535,65535,65535,65535,65535},
{1612,1615,1618,1621,65535,65535,65535,65535,65535,65535,65535,65535,65535,65535,65535,65535,65535,65535,65535,65535,65535,65535,65535,65535,65535,65535,65535,65535,65535,65535,65535,65535,65535,65535,65535,65535,65535,65535,65535,65535,65535,65535,65535,65535,65535,65535,65535,65535},
{1236,1247,1257,1267,1278,1288,1298,1308,1318,1329,1339,1349,1359,1369,1380,1390,1400,1410,1420,1431,1441,1453,1464,1474,1484,1494,1504,1515,1525,1535,1545,1555,1566,1576,1586,1596,1606,1628,1639,65535,65535,65535,65535,65535,65535,65535,65535,65535},
{2024,2027,2030,2033,65535,65535,65535,65535,65535,65535,65535,65535,65535,65535,65535,65535,65535,65535,65535,65535,65535,65535,65535,65535,65535,65535,65535,65535,65535,65535,65535,65535,65535,65535,65535,65535,65535,65535,65535,65535,65535,65535,65535,65535,65535,65535,65535,65535},
{1648,1659,1669,1680,1690,1700,1710,1720,1731,1741,1751,1761,1771,1782,1792,1802,1812,1822,1833,1843,1853,1865,1876,1886,1896,1906,1917,1927,1937,1947,1957,1968,1978,1988,1998,2008,2019,2040,2051,65535,65535,65535,65535,65535,65535,65535,65535,65535},
{2436,2439,2442,2445,65535,65535,65535,65535,65535,65535,65535,65535,65535,65535,65535,65535,65535,65535,65535,65535,65535,65535,65535,65535,65535,65535,65535,65535,65535,65535,65535,65535,65535,65535,65535,65535,65535,65535,65535,65535,65535,65535,65535,65535,65535,65535,65535,65535},
{2060,2071,2081,2092,2102,2112,2122,2132,2143,2153,2163,2173,2183,2194,2204,2214,2224,2234,2245,2255,2265,2277,2288,2298,2308,2318,2329,2339,2349,2359,2369,2380,2390,2400,2410,2420,2431,2452,2463,65535,65535,65535,65535,65535,65535,65535,65535,65535},
{2848,2851,2854,2857,65535,65535,65535,65535,65535,65535,65535,65535,65535,65535,65535,65535,65535,65535,65535,65535,65535,65535,65535,65535,65535,65535,65535,65535,65535,65535,65535,65535,65535,65535,65535,65535,65535,65535,65535,65535,65535,65535,65535,65535,65535,65535,65535,65535},
{2472,3303,3313,3323,3333,3343,2534,3364,3374,3384,3394,2585,3415,3425,3435,3445,2636,3466,3476,3486,2677,2690,3507,3517,2720,3538,3548,3558,3568,2771,3589,3599,3609,3619,2822,3640,3650,2865,3682,65535,65535,65535,65535,65535,65535,65535,65535,65535},
{3260,3263,3266,3269,65535,65535,65535,65535,65535,65535,65535,65535,65535,65535,65535,65535,65535,65535,65535,65535,65535,65535,65535,65535,65535,65535,65535,65535,65535,65535,65535,65535,65535,65535,65535,65535,65535,65535,65535,65535,65535,65535,65535,65535,65535,65535,65535,65535},
{2884,2895,2905,3735,3745,3755,2946,2956,2966,2976,3806,2997,3007,3017,3027,3857,3048,3058,3068,3078,3089,3909,3919,3929,3132,3142,3152,3162,3980,3183,3193,3203,3213,4031,3234,3244,3254,3277,4094,65535,65535,65535,65535,65535,65535,65535,65535,65535},
{377,380,383,386,65535,65535,65535,65535,65535,65535,65535,65535,65535,65535,65535,65535,65535,65535,65535,65535,65535,65535,65535,65535,65535,65535,65535,65535,65535,65535,65535,65535,65535,65535,65535,65535,65535,65535,65535,65535,65535,65535,65535,65535,65535,65535,65535,65535},
{1,3715,3725,33,43,53,63,3776,3786,3796,104,114,3827,3837,3847,155,165,3878,3888,3898,206,219,229,239,249,3950,3960,3970,290,300,4001,4011,4021,341,351,4052,4062,394,404,65535,65535,65535,65535,65535,65535,65535,65535,65535},
{789,792,795,798,65535,65535,65535,65535,65535,65535,65535,65535,65535,65535,65535,65535,65535,65535,65535,65535,65535,65535,65535,65535,65535,65535,65535,65535,65535,65535,65535,65535,65535,65535,65535,65535,65535,65535,65535,65535,65535,65535,65535,65535,65535,65535,65535,65535},
{413,423,433,443,453,464,474,484,494,504,515,525,535,545,555,566,576,586,596,606,617,629,639,650,660,670,680,690,701,711,721,731,741,752,762,772,782,805,815,65535,65535,65535,65535,65535,65535,65535,65535,65535},
{1201,1204,1207,1210,65535,65535,65535,65535,65535,65535,65535,65535,65535,65535,65535,65535,65535,65535,65535,65535,65535,65535,65535,65535,65535,65535,65535,65535,65535,65535,65535,65535,65535,65535,65535,65535,65535,65535,65535,65535,65535,65535,65535,65535,65535,65535,65535,65535},
{825,835,846,856,866,877,887,897,907,918,928,938,948,958,969,979,989,999,1009,1020,1030,1042,1052,1063,1073,1083,1093,1104,1114,1124,1134,1144,1155,1165,1175,1185,1195,1217,1228,65535,65535,65535,65535,65535,65535,65535,65535,65535},
{1613,1616,1619,1622,65535,65535,65535,65535,65535,65535,65535,65535,65535,65535,65535,65535,65535,65535,65535,65535,65535,65535,65535,65535,65535,65535,65535,65535,65535,65535,65535,65535,65535,65535,65535,65535,65535,65535,65535,65535,65535,65535,65535,65535,65535,65535,65535,65535},
{1237,1248,1258,1268,1279,1289,1299,1309,1319,1330,1340,1350,1360,1370,1381,1391,1401,1411,1421,1432,1442,1454,1465,1475,1485,1495,1505,1516,1526,1536,1546,1556,1567,1577,1587,1597,1607,1629,1640,65535,65535,65535,65535,65535,65535,65535,65535,65535},
{2025,2028,2031,2034,65535,65535,65535,65535,65535,65535,65535,65535,65535,65535,65535,65535,65535,65535,65535,65535,65535,65535,65535,65535,65535,65535,65535,65535,65535,65535,65535,65535,65535,65535,65535,65535,65535,65535,65535,65535,65535,65535,65535,65535,65535,65535,65535,65535},
{1649,1660,1670,1681,1691,1701,1711,1721,1732,1742,1752,1762,1772,1783,1793,1803,1813,1823,1834,1844,1854,1866,1877,1887,1897,1907,1918,1928,1938,1948,1958,1969,1979,1989,1999,2009,2020,2041,2052,65535,65535,65535,65535,65535,65535,65535,65535,65535},
{2437,2440,2443,2446,65535,65535,65535,65535,65535,65535,65535,65535,65535,65535,65535,65535,65535,65535,65535,65535,65535,65535,65535,65535,65535,65535,65535,65535,65535,65535,65535,65535,65535,65535,65535,65535,65535,65535,65535,65535,65535,65535,65535,65535,65535,65535,65535,65535},
{2061,2072,2082,2093,2103,2113,2123,2133,2144,2154,2164,2174,2184,2195,2205,2215,2225,2235,2246,2256,2266,2278,2289,2299,2309,2319,2330,2340,2350,2360,2370,2381,2391,2401,2411,2421,2432,2453,2464,65535,65535,65535,65535,65535,65535,65535,65535,65535},
{2849,2852,2855,2858,65535,65535,65535,65535,65535,65535,65535,65535,65535,65535,65535,65535,65535,65535,65535,65535,65535,65535,65535,65535,65535,65535,65535,65535,65535,65535,65535,65535,65535,65535,65535,65535,65535,65535,65535,65535,65535,65535,65535,65535,65535,65535,65535,65535},
{2473,2484,2494,2504,3334,3344,2535,2545,2555,2565,3395,2586,2596,2606,2616,3446,2637,2647,2657,2667,2678,3498,3508,3518,2721,2731,2741,2751,3569,2772,2782,2792,2802,3620,2823,2833,2843,2866,3683,65535,65535,65535,65535,65535,65535,65535,65535,65535},
{3261,3264,3267,3270,65535,65535,65535,65535,65535,65535,65535,65535,65535,65535,65535,65535,65535,65535,65535,65535,65535,65535,65535,65535,65535,65535,65535,65535,65535,65535,65535,65535,65535,65535,65535,65535,65535,65535,65535,65535,65535,65535,65535,65535,65535,65535,65535,65535},
{2885,2896,2906,2916,2926,2936,3766,2957,2967,2977,2987,3817,3008,3018,3028,3038,3868,3059,3069,3079,3090,3910,3112,3122,3940,3143,3153,3163,3173,3991,3194,3204,3214,3224,4042,3245,3255,4085,3287,65535,65535,65535,65535,65535,65535,65535,65535,65535},
{378,381,384,387,65535,65535,65535,65535,65535,65535,65535,65535,65535,65535,65535,65535,65535,65535,65535,65535,65535,65535,65535,65535,65535,65535,65535,65535,65535,65535,65535,65535,65535,65535,65535,65535,65535,65535,65535,65535,65535,65535,65535,65535,65535,65535,65535,65535},
{2,13,23,3324,3746,3756,64,3365,3375,3385,3807,115,3416,3426,3436,3858,166,3467,3477,3487,208,220,3920,3930,250,3539,3549,3559,3981,301,3590,3600,3610,4032,352,3641,3651,395,4095,65535,65535,65535,65535,65535,65535,65535,65535,65535},
{790,793,796,799,65535,65535,65535,65535,65535,65535,65535,65535,65535,65535,65535,65535,65535,65535,65535,65535,65535,65535,65535,65535,65535,65535,65535,65535,65535,65535,65535,65535,65535,65535,65535,65535,65535,65535,65535,65535,65535,65535,65535,65535,65535,65535,65535,65535},
{414,424,434,444,454,465,475,485,495,505,516,526,536,546,556,567,577,587,597,607,618,630,640,651,661,671,681,691,702,712,722,732,742,753,763,773,783,806,816,65535,65535,65535,65535,65535,65535,65535,65535,65535},
{1202,1205,1208,1211,65535,65535,65535,65535,65535,65535,65535,65535,65535,65535,65535,65535,65535,65535,65535,65535,65535,65535,65535,65535,65535,65535,65535,65535,65535,65535,65535,65535,65535,65535,65535,65535,65535,65535,65535,65535,65535,65535,65535,65535,65535,65535,65535,65535},
{826,836,847,857,867,878,888,898,908,3797,929,939,949,959,3848,980,990,1000,1010,3899,1031,1043,1053,1064,1074,1084,1094,3971,1115,1125,1135,1145,4022,1166,1176,1186,1196,1218,1229,65535,65535,65535,65535,65535,65535,65535,65535,65535},
{1614,1617,1620,1623,65535,65535,65535,65535,65535,65535,65535,65535,65535,65535,65535,65535,65535,65535,65535,65535,65535,65535,65535,65535,65535,65535,65535,65535,65535,65535,65535,65535,65535,65535,65535,65535,65535,65535,65535,65535,65535,65535,65535,65535,65535,65535,65535,65535},
{1238,1249,1259,1269,1280,1290,1300,1310,1320,1331,1341,1351,1361,1371,1382,1392,1402,1412,1422,1433,1443,1455,1466,1476,1486,1496,1506,1517,1527,1537,1547,1557,1568,1578,1588,1598,1608,1630,1641,65535,65535,65535,65535,65535,65535,65535,65535,65535},
{2026,2029,2032,2035,65535,65535,65535,65535,65535,65535,65535,65535,65535,65535,65535,65535,65535,65535,65535,65535,65535,65535,65535,65535,65535,65535,65535,65535,65535,65535,65535,65535,65535,65535,65535,65535,65535,65535,65535,65535,65535,65535,65535,65535,65535,65535,65535,65535},
{1650,1661,1671,3736,1692,1702,1712,1722,1733,1743,1753,1763,1773,1784,1794,1804,1814,1824,1835,1845,1855,1867,1878,1888,1898,1908,1919,1929,1939,1949,1959,1970,1980,1990,2000,2010,2021,2042,2053,65535,65535,65535,65535,65535,65535,65535,65535,65535},
{2438,2441,2444,2447,65535,65535,65535,65535,65535,65535,65535,65535,65535,65535,65535,65535,65535,65535,65535,65535,65535,65535,65535,65535,65535,65535,65535,65535,65535,65535,65535,65535,65535,65535,65535,65535,65535,65535,65535,65535,65535,65535,65535,65535,65535,65535,65535,65535},
{2062,2073,2083,2094,2104,2114,2124,2134,2145,2155,2165,2175,2185,2196,2206,2216,2226,2236,2247,2257,2267,2279,2290,2300,2310,2320,2331,2341,2351,2361,2371,2382,2392,2402,2412,2422,2433,2454,2465,65535,65535,65535,65535,65535,65535,65535,65535,65535},
{2850,2853,2856,2859,65535,65535,65535,65535,65535,65535,65535,65535,65535,65535,65535,65535,65535,65535,65535,65535,65535,65535,65535,65535,65535,65535,65535,65535,65535,65535,65535,65535,65535,65535,65535,65535,65535,65535,65535,65535,65535,65535,65535,65535,65535,65535,65535,65535},
{2474,3304,3314,2505,2515,2525,3355,2546,2556,2566,2576,3406,2597,2607,2617,2627,3457,2648,2658,2668,2679,2691,2701,2711,3529,2732,2742,2752,2762,3580,2783,2793,2803,2813,3631,2834,2844,3674,2876,65535,65535,65535,65535,65535,65535,65535,65535,65535},
{3262,3265,3268,3271,65535,65535,65535,65535,65535,65535,65535,65535,65535,65535,65535,65535,65535,65535,65535,65535,65535,65535,65535,65535,65535,65535,65535,65535,65535,65535,65535,65535,65535,65535,65535,65535,65535,65535,65535,65535,65535,65535,65535,65535,65535,65535,65535,65535},
{2886,3716,3726,2917,2927,2937,2947,3777,3787,2978,2988,2998,3828,3838,3029,3039,3049,3879,3889,3080,3091,3103,3113,3123,3133,3951,3961,3164,3174,3184,4002,4012,3215,3225,3235,4053,4063,3278,3288,65535,65535,65535,65535,65535,65535,65535,65535,65535},
{3,14,24,35,45,55,2948,3778,3788,96,106,2999,3829,3839,147,157,3050,3880,3890,198,210,2692,231,241,3134,3952,3962,282,292,3185,4003,4013,333,343,3236,4054,4064,3279,406,65535,65535,65535,65535,65535,65535,65535,65535,65535},
{4,3305,3727,34,44,54,65,75,85,95,105,116,126,136,146,156,167,177,187,197,209,221,230,240,251,261,271,281,291,302,312,322,332,342,353,363,373,396,405,65535,65535,65535,65535,65535,65535,65535,65535,65535},
{415,425,435,445,455,466,476,486,496,506,517,527,537,547,557,568,578,588,598,608,619,631,641,652,662,672,682,692,703,713,723,733,743,754,764,774,784,807,817,65535,65535,65535,65535,65535,65535,65535,65535,65535},
{416,426,436,446,456,467,477,487,497,507,518,528,538,548,558,569,579,589,599,609,620,632,642,653,663,673,683,693,704,714,724,734,744,755,765,775,785,808,818,65535,65535,65535,65535,65535,65535,65535,65535,65535},
{827,837,848,858,868,879,889,899,909,919,930,940,950,960,970,981,991,1001,1011,1021,1032,1044,1054,1065,1075,1085,1095,1105,1116,1126,1136,1146,1156,1167,1177,1187,1197,1219,1230,65535,65535,65535,65535,65535,65535,65535,65535,65535},
{828,838,849,859,869,2526,3356,900,910,920,2577,3407,951,961,971,2628,3458,1002,1012,1022,1033,1045,1055,2712,3530,1086,1096,1106,2763,3581,1137,1147,1157,2814,3632,1188,1198,1220,2877,65535,65535,65535,65535,65535,65535,65535,65535,65535},
{1239,1250,1260,1270,1281,1291,1301,1311,1321,1332,1342,1352,1362,1372,1383,1393,1403,1413,1423,1434,1444,1456,1467,1477,1487,1497,1507,1518,1528,1538,1548,1558,1569,1579,1589,1599,1609,1631,1642,65535,65535,65535,65535,65535,65535,65535,65535,65535},
{1240,3717,1261,1271,2516,2938,3768,1312,1322,2567,2989,3819,1363,1373,2618,3040,3870,1414,1424,2669,1445,1457,2702,3124,3942,1498,1508,2753,3175,3993,1549,1559,2804,3226,4044,1600,1610,1632,3289,65535,65535,65535,65535,65535,65535,65535,65535,65535},
{1651,1662,1672,1682,1693,1703,1713,1723,1734,1744,1754,1764,1774,1785,1795,1805,1815,1825,1836,1846,1856,1868,1879,1889,1899,1909,1920,1930,1940,1950,1960,1971,1981,1991,2001,2011,2022,2043,2054,65535,65535,65535,65535,65535,65535,65535,65535,65535},
{1652,1663,1673,1683,2928,3346,1714,1724,2557,2979,3397,1765,1775,2608,3030,3448,1816,1826,2659,3081,1857,1869,3114,3520,1900,1910,2743,3165,3571,1951,1961,2794,3216,3622,2002,2012,2845,2044,3685,65535,65535,65535,65535,65535,65535,65535,65535,65535},
{2063,2074,2084,2095,2105,2115,2125,2135,2146,2156,2166,2176,2186,2197,2207,2217,2227,2237,2248,2258,2268,2280,2291,2301,2311,2321,2332,2342,2352,2362,2372,2383,2393,2403,2413,2423,2434,2455,2466,65535,65535,65535,65535,65535,65535,65535,65535,65535},
{2064,2075,2085,2506,3336,3758,2126,2136,2969,3387,3809,2177,2187,3020,3438,3860,2228,2238,3071,3489,2269,2281,3510,3932,2312,2322,3155,3561,3983,2363,2373,3206,3612,4034,2414,2424,3257,2456,4097,65535,65535,65535,65535,65535,65535,65535,65535,65535},
{3660,3663,3666,3669,65535,65535,65535,65535,65535,65535,65535,65535,65535,65535,65535,65535,65535,65535,65535,65535,65535,65535,65535,65535,65535,65535,65535,65535,65535,65535,65535,65535,65535,65535,65535,65535,65535,65535,65535,65535,65535,65535,65535,65535,65535,65535,65535,65535},
{2475,2485,2495,3325,3335,3345,2536,3366,3376,3386,3396,2587,3417,3427,3437,3447,2638,3468,3478,3488,2680,3499,3509,3519,2722,3540,3550,3560,3570,2773,3591,3601,3611,3621,2824,3642,3652,2867,3684,65535,65535,65535,65535,65535,65535,65535,65535,65535},
{4072,4075,4078,4081,65535,65535,65535,65535,65535,65535,65535,65535,65535,65535,65535,65535,65535,65535,65535,65535,65535,65535,65535,65535,65535,65535,65535,65535,65535,65535,65535,65535,65535,65535,65535,65535,65535,65535,65535,65535,65535,65535,65535,65535,65535,65535,65535,65535},
{2887,2897,2907,3737,3747,3757,3767,2958,2968,3798,3808,3818,3009,3019,3849,3859,3869,3060,3070,3900,3092,3911,3921,3931,3941,3144,3154,3972,3982,3992,3195,3205,4023,4033,4043,3246,3256,4086,4096,65535,65535,65535,65535,65535,65535,65535,65535,65535},
{417,427,437,447,457,468,478,488,498,508,519,529,539,549,559,570,580,590,600,610,621,633,643,654,664,674,684,694,705,715,725,735,745,756,766,776,786,3675,819,65535,65535,65535,65535,65535,65535,65535,65535,65535},
{2476,2486,2496,2918,3748,2527,2537,2547,3377,3799,2578,2588,2598,3428,3850,2629,2639,2649,3479,3901,622,3104,3922,2713,2723,2733,3551,3973,2764,2774,2784,3602,4024,2815,2825,2835,3653,4087,2878,65535,65535,65535,65535,65535,65535,65535,65535,65535},
{829,839,2908,3326,870,880,890,2959,3789,921,931,941,3010,3840,972,982,992,3061,3891,1023,1034,3500,1056,1066,1076,3145,3963,1107,1117,1127,3196,4014,1158,1168,1178,3247,4065,1221,1231,65535,65535,65535,65535,65535,65535,65535,65535,65535},
{2888,2898,3316,3738,2517,2939,2949,3367,911,2568,2990,3000,3418,962,2619,3041,3051,3469,1013,2670,2681,3912,2703,3125,3135,3541,1097,2754,3176,3186,3592,1148,2805,3227,3237,3643,1199,2868,3290,65535,65535,65535,65535,65535,65535,65535,65535,65535},
{1241,1251,3728,1272,3749,1293,1303,1313,3378,3800,1344,1354,1364,3429,3851,1395,1405,1415,3480,3902,1447,3501,3923,1479,1489,1499,3552,3974,1530,1540,1550,3603,4025,1581,1591,1601,3654,4088,1644,65535,65535,65535,65535,65535,65535,65535,65535,65535},
{3296,3306,1262,2507,1282,1292,1302,3779,1323,1333,1343,1353,3830,1374,1384,1394,1404,3881,1425,1435,1446,1458,1468,1478,1488,3953,1509,1519,1529,1539,4004,1560,1570,1580,1590,4055,1611,1633,1643,65535,65535,65535,65535,65535,65535,65535,65535,65535},
{1653,3718,1674,1684,1694,1704,1715,1725,1735,1745,1755,1766,1776,1786,1796,1806,1817,1827,1837,1847,1858,1870,1880,1890,1901,1911,1921,1931,1941,1952,1962,1972,1982,1992,2003,2013,2023,2045,2055,65535,65535,65535,65535,65535,65535,65535,65535,65535},
{3708,1664,3317,3739,1695,1705,2538,3368,3790,1746,1756,2589,3419,3841,1797,1807,2640,3470,3892,1848,1859,3913,1881,1891,2724,3542,3964,1932,1942,2775,3593,4015,1983,1993,2826,3644,4066,2046,2056,65535,65535,65535,65535,65535,65535,65535,65535,65535},
{2065,2076,3729,2097,2107,2117,2950,3780,2148,2158,2168,3001,3831,2199,2209,2219,3052,3882,2250,2260,2271,2283,2293,2303,3136,3954,2334,2344,2354,3187,4005,2385,2395,2405,3238,4056,2847,2458,2468,65535,65535,65535,65535,65535,65535,65535,65535,65535},
{2066,2487,2086,2096,2106,2116,2127,2137,2147,2157,2167,2178,2188,2198,2208,2218,2229,2239,2249,2259,2270,2282,2292,2302,2313,2323,2333,2343,2353,2364,2374,2384,2394,2404,2415,2425,2435,2457,2467,65535,65535,65535,65535,65535,65535,65535,65535,65535},
{3661,3664,3667,3670,65535,65535,65535,65535,65535,65535,65535,65535,65535,65535,65535,65535,65535,65535,65535,65535,65535,65535,65535,65535,65535,65535,65535,65535,65535,65535,65535,65535,65535,65535,65535,65535,65535,65535,65535,65535,65535,65535,65535,65535,65535,65535,65535,65535},
{2477,3307,2497,3327,3337,3347,3357,2548,2558,3388,3398,3408,2599,2609,3439,3449,3459,2650,2660,3490,2682,2693,3511,3521,3531,2734,2744,3562,3572,3582,2785,2795,3613,3623,3633,2836,2846,3676,3686,65535,65535,65535,65535,65535,65535,65535,65535,65535},
{4073,4076,4079,4082,65535,65535,65535,65535,65535,65535,65535,65535,65535,65535,65535,65535,65535,65535,65535,65535,65535,65535,65535,65535,65535,65535,65535,65535,65535,65535,65535,65535,65535,65535,65535,65535,65535,65535,65535,65535,65535,65535,65535,65535,65535,65535,65535,65535},
{2889,2899,2909,2919,2929,3759,3769,2960,2970,2980,3810,3820,3011,3021,3031,3861,3871,3062,3072,3082,3093,3105,3115,3933,3943,3146,3156,3166,3984,3994,3197,3207,3217,4035,4045,3248,3258,3280,4098,65535,65535,65535,65535,65535,65535,65535,65535,65535},
{418,428,439,449,459,2528,3358,490,500,510,2579,3409,541,551,561,2630,3460,592,602,612,3094,635,645,2714,3532,676,686,696,2765,3583,727,737,747,2816,3634,778,3259,810,2879,65535,65535,65535,65535,65535,65535,65535,65535,65535},
{3297,3719,438,448,458,469,479,489,499,509,520,530,540,550,560,571,581,591,601,611,623,634,644,655,665,675,685,695,706,716,726,736,746,757,767,777,787,809,820,65535,65535,65535,65535,65535,65535,65535,65535,65535},
{830,840,850,860,871,881,891,901,912,922,932,942,952,963,973,983,993,1003,1014,1024,1035,1046,1057,1067,1077,1087,1098,1108,1118,1128,1138,1149,1159,1169,1179,1189,3655,1222,1232,65535,65535,65535,65535,65535,65535,65535,65535,65535},
{3709,841,851,861,2518,2940,3770,902,2559,2569,2991,3821,953,2610,2620,3042,3872,1004,2661,2671,1036,1047,2704,3126,3944,1088,2745,2755,3177,3995,1139,2796,2806,3228,4046,1190,4067,2869,3291,65535,65535,65535,65535,65535,65535,65535,65535,65535},
{1242,1252,1263,1273,1283,3348,1304,1314,1324,1334,3399,1355,1365,1375,1385,3450,1406,1416,1426,1436,1448,1459,1469,3522,1490,1500,1510,1520,3573,1541,1551,1561,1571,3624,1592,1602,3656,1634,3687,65535,65535,65535,65535,65535,65535,65535,65535,65535},
{1243,1253,2498,2508,2930,3760,2539,2549,2971,2981,3811,2590,2600,3022,3032,3862,2641,2651,3073,3083,2683,2694,3116,3934,2725,2735,3157,3167,3985,2776,2786,3208,3218,4036,2827,2837,4068,3281,4099,65535,65535,65535,65535,65535,65535,65535,65535,65535},
{1654,1665,1675,1685,3338,1706,1716,1726,1736,3389,1757,1767,1777,1787,3440,1808,1818,1828,1838,3491,1860,1871,3512,1892,1902,1912,1922,3563,1943,1953,1963,1973,3614,1994,2004,2014,3657,3677,2057,65535,65535,65535,65535,65535,65535,65535,65535,65535},
{1655,2488,2910,2920,3750,2529,2951,2961,3379,3801,2580,3002,3012,3430,3852,2631,3053,3063,3481,3903,3095,3106,3924,2715,3137,3147,3553,3975,2766,3188,3198,3604,4026,2817,3239,3249,4069,4089,2880,65535,65535,65535,65535,65535,65535,65535,65535,65535},
{2067,2077,2087,3328,2108,2119,2129,2139,2149,3390,2170,2180,2190,2200,3441,2221,2231,2241,2251,3492,2273,2284,3513,2305,2315,2325,2335,3564,2356,2366,2376,2386,3615,2407,2417,2427,2448,3678,2470,65535,65535,65535,65535,65535,65535,65535,65535,65535},
{2478,2900,3318,3740,2519,2118,2128,2138,3791,2159,2169,2179,2189,3842,2210,2220,2230,2240,3893,2261,2272,3502,2294,2304,2314,2324,3965,2345,2355,2365,2375,4016,2396,2406,2416,2426,3658,2459,2469,65535,65535,65535,65535,65535,65535,65535,65535,65535},
{3662,3665,3668,3671,65535,65535,65535,65535,65535,65535,65535,65535,65535,65535,65535,65535,65535,65535,65535,65535,65535,65535,65535,65535,65535,65535,65535,65535,65535,65535,65535,65535,65535,65535,65535,65535,65535,65535,65535,65535,65535,65535,65535,65535,65535,65535,65535,65535},
{3298,3308,2499,2509,3339,3349,3359,3369,2560,2570,3400,3410,3420,2611,2621,3451,3461,3471,2662,2672,2684,2695,2705,3523,3533,3543,2746,2756,3574,3584,3594,2797,2807,3625,3635,3645,3659,2870,3688,65535,65535,65535,65535,65535,65535,65535,65535,65535},
{4074,4077,4080,4083,65535,65535,65535,65535,65535,65535,65535,65535,65535,65535,65535,65535,65535,65535,65535,65535,65535,65535,65535,65535,65535,65535,65535,65535,65535,65535,65535,65535,65535,65535,65535,65535,65535,65535,65535,65535,65535,65535,65535,65535,65535,65535,65535,65535},
{2890,3720,3730,2921,2931,2941,3771,3781,2972,2982,2992,3822,3832,3023,3033,3043,3873,3883,3074,3084,3096,3914,3117,3127,3945,3955,3158,3168,3178,3996,4006,3209,3219,3229,4047,4057,4070,3282,3292,65535,65535,65535,65535,65535,65535,65535,65535,65535},
{419,429,440,3329,461,471,481,2550,3380,512,522,532,2601,3431,563,573,583,2652,3482,614,625,3503,647,657,667,2736,3554,698,708,718,2787,3605,749,759,769,2838,801,812,822,65535,65535,65535,65535,65535,65535,65535,65535,65535},
{3710,430,2911,450,460,470,480,491,501,511,521,531,542,552,562,572,582,593,603,613,624,636,646,656,666,677,687,697,707,717,728,738,748,758,768,779,800,811,821,65535,65535,65535,65535,65535,65535,65535,65535,65535},
{831,842,852,863,873,883,893,3370,914,924,934,944,3421,965,975,985,995,3472,1016,1026,1038,3915,1059,1069,1079,3544,1100,1110,1120,1130,3595,1151,1161,1171,1181,3646,1213,1224,1234,65535,65535,65535,65535,65535,65535,65535,65535,65535},
{832,2489,3319,862,872,882,892,903,913,923,933,943,954,964,974,984,994,1005,1015,1025,1037,1048,1058,1068,1078,1089,1099,1109,1119,1129,1140,1150,1160,1170,1180,1191,1212,1223,1233,65535,65535,65535,65535,65535,65535,65535,65535,65535},
{1244,3309,1265,1274,1284,1294,1305,1315,1325,1335,1345,1356,1366,1376,1386,1396,1407,1417,1427,1437,1449,1460,1470,1480,1491,1501,1511,1521,1531,1542,1552,1562,1572,1582,1593,1603,1624,1635,1645,65535,65535,65535,65535,65535,65535,65535,65535,65535},
{2479,1254,1264,1275,1285,1295,2540,3782,1326,1336,1346,2591,3833,1377,1387,1397,2642,3884,1428,1438,1450,1461,1471,1481,2726,3956,1512,1522,1532,2777,4007,1563,1573,1583,2828,4058,1625,1636,1646,65535,65535,65535,65535,65535,65535,65535,65535,65535},
{1656,3721,1677,1686,1696,1707,1717,1727,1737,1747,1758,1768,1778,1788,1798,1809,1819,1829,1839,1849,1861,1872,1882,1893,1903,1913,1923,1933,1944,1954,1964,1974,1984,1995,2005,2015,2036,2047,2058,65535,65535,65535,65535,65535,65535,65535,65535,65535},
{2891,1666,1676,1687,1697,2530,3360,1728,1738,1748,2581,3411,1779,1789,1799,2632,3462,1830,1840,1850,1862,1873,1883,2716,3534,1914,1924,1934,2767,3585,1965,1975,1985,2818,3636,2016,2037,2048,2881,65535,65535,65535,65535,65535,65535,65535,65535,65535},
{2068,2079,2089,2098,2109,2942,3772,2140,2150,2160,2993,3823,2191,2201,2211,3044,3874,2242,2252,2262,2274,2285,2295,3128,3946,2326,2336,2346,3179,3997,2377,2387,2397,3230,4048,2428,2449,2460,3293,65535,65535,65535,65535,65535,65535,65535,65535,65535},
{3299,2078,2088,2099,2520,3350,2130,2551,2561,2571,3401,2181,2602,2612,2622,3452,2232,2653,2663,2673,2685,2696,2706,3524,2316,2737,2747,2757,3575,2367,2788,2798,2808,3626,2418,2839,2860,2871,3689,65535,65535,65535,65535,65535,65535,65535,65535,65535},
{2480,2490,2500,2510,3340,2531,2541,3371,3381,3391,2582,2592,3422,3432,3442,2633,2643,3473,3483,3493,2686,3504,3514,2717,2727,3545,3555,3565,2768,2778,3596,3606,3616,2819,2829,3647,2861,3679,2882,65535,65535,65535,65535,65535,65535,65535,65535,65535},
{3300,3310,3320,3330,2521,3351,3361,2552,2562,2572,3402,3412,2603,2613,2623,3453,3463,2654,2664,2674,2687,2697,2707,3525,3535,2738,2748,2758,3576,3586,2789,2799,2809,3627,3637,2840,3272,2872,3690,65535,65535,65535,65535,65535,65535,65535,65535,65535},
{3711,2901,3731,3741,3751,3761,2952,2962,3792,3802,3812,3003,3013,3843,3853,3863,3054,3064,3894,3904,3097,3107,3925,3935,3138,3148,3966,3976,3986,3189,3199,4017,4027,4037,3240,3250,4071,4090,4100,65535,65535,65535,65535,65535,65535,65535,65535,65535},
{2892,2902,2912,2922,2932,3762,2953,2963,2973,2983,3813,3004,3014,3024,3034,3864,3055,3065,3075,3085,3098,3108,3118,3936,3139,3149,3159,3169,3987,3190,3200,3210,3220,4038,3241,3251,3273,3283,4101,65535,65535,65535,65535,65535,65535,65535,65535,65535},
{420,431,441,451,3752,472,482,492,502,3803,523,533,543,553,3854,574,584,594,604,3905,626,637,3926,658,668,678,688,3977,709,719,729,739,4028,760,770,780,802,4091,823,65535,65535,65535,65535,65535,65535,65535,65535,65535},
{421,3722,3732,3742,462,2943,3773,3783,3793,513,2994,3824,3834,3844,564,3045,3875,3885,3895,615,627,3916,648,3129,3947,3957,3967,699,3180,3998,4008,4018,750,3231,4049,4059,803,813,3294,65535,65535,65535,65535,65535,65535,65535,65535,65535},
{833,843,853,864,874,884,894,904,915,925,935,945,955,966,976,986,996,1006,1017,1027,1039,1049,1060,1070,1080,1090,1101,1111,1121,1131,1141,1152,1162,1172,1182,1192,1214,1225,1235,65535,65535,65535,65535,65535,65535,65535,65535,65535},
{3712,844,854,3331,875,885,895,905,916,926,936,946,956,967,977,987,997,1007,1018,1028,1040,1050,1061,1071,1081,1091,1102,1112,1122,1132,1142,1153,1163,1173,1183,1193,1215,1226,3691,65535,65535,65535,65535,65535,65535,65535,65535,65535},
{1245,1255,1266,1276,1286,1296,1306,1316,1327,1337,1347,1357,1367,1378,1388,1398,1408,1418,1429,1439,1451,1462,1472,1482,1492,1502,1513,1523,1533,1543,1553,1564,1574,1584,1594,1604,1626,1637,1647,65535,65535,65535,65535,65535,65535,65535,65535,65535},
{1246,1256,3321,1277,1287,1297,1307,1317,1328,1338,1348,1358,1368,1379,1389,1399,1409,1419,1430,1440,1452,1463,1473,1483,1493,1503,1514,1524,1534,1544,1554,1565,1575,1585,1595,1605,1627,1638,4103,65535,65535,65535,65535,65535,65535,65535,65535,65535},
{1657,1667,1678,1688,1698,1708,1718,1729,1739,1749,1759,1769,1780,1790,1800,1810,1820,1831,1841,1851,1863,1874,1884,1894,1904,1915,1925,1935,1945,1955,1966,1976,1986,1996,2006,2017,2038,2049,2059,65535,65535,65535,65535,65535,65535,65535,65535,65535},
{1658,1668,1679,1689,1699,1709,1719,1730,1740,1750,1760,1770,1781,1791,1801,1811,1821,1832,1842,1852,1864,1875,1885,1895,1905,1916,1926,1936,1946,1956,1967,1977,1987,1997,2007,2018,2039,2050,3692,65535,65535,65535,65535,65535,65535,65535,65535,65535},
{2069,2080,2091,2101,2111,2121,3362,2142,2152,2162,2172,3413,2193,2203,2213,2223,3464,2244,2254,2264,2276,2287,2297,2307,3536,2328,2338,2348,2358,3587,2379,2389,2399,2409,3638,2430,2451,2462,4104,65535,65535,65535,65535,65535,65535,65535,65535,65535},
{2070,2491,2090,2100,2110,2120,2131,2141,2151,2161,2171,2182,2192,2202,2212,2222,2233,2243,2253,2263,2275,2286,2296,2306,2317,2327,2337,2347,2357,2368,2378,2388,2398,2408,2419,2429,2450,2461,2471,65535,65535,65535,65535,65535,65535,65535,65535,65535},
{2481,3311,2501,2511,3341,2532,2542,3372,3382,3392,2583,2593,3423,3433,3443,2634,2644,3474,3484,3494,2688,3505,3515,2718,2728,3546,3556,3566,2769,2779,3597,3607,3617,2820,2830,3648,2862,3680,2883,65535,65535,65535,65535,65535,65535,65535,65535,65535},
{3301,2492,2502,2512,2522,3352,2543,2553,2563,2573,3403,2594,2604,2614,2624,3454,2645,2655,2665,2675,3496,2698,2708,3526,2729,2739,2749,2759,3577,2780,2790,2800,2810,3628,2831,2841,2863,2873,3693,65535,65535,65535,65535,65535,65535,65535,65535,65535},
{2893,2903,2913,2923,2933,3763,2954,2964,2974,2984,3814,3005,3015,3025,3035,3865,3056,3066,3076,3086,3099,3109,3119,3937,3140,3150,3160,3170,3988,3191,3201,3211,3221,4039,3242,3252,3274,3284,4102,65535,65535,65535,65535,65535,65535,65535,65535,65535},
{3713,3723,3733,3743,3753,2944,3774,3784,3794,3804,2995,3825,3835,3845,3855,3046,3876,3886,3896,3906,3100,3917,3927,3130,3948,3958,3968,3978,3181,3999,4009,4019,4029,3232,4050,4060,3275,4092,3295,65535,65535,65535,65535,65535,65535,65535,65535,65535},
{2482,3312,3322,3332,3342,2533,3363,3373,3383,3393,2584,3414,3424,3434,3444,2635,3465,3475,3485,3495,2689,3506,3516,2719,3537,3547,3557,3567,2770,3588,3598,3608,3618,2821,3639,3649,2864,3681,3694,65535,65535,65535,65535,65535,65535,65535,65535,65535},
{3302,2493,2503,2513,2523,3353,2544,2554,2564,2574,3404,2595,2605,2615,2625,3455,2646,2656,2666,2676,3497,2699,2709,3527,2730,2740,2750,2760,3578,2781,2791,2801,2811,3629,2832,2842,3672,2874,4105,65535,65535,65535,65535,65535,65535,65535,65535,65535},
{2894,2904,2914,2924,2934,3764,2955,2965,2975,2985,3815,3006,3016,3026,3036,3866,3057,3067,3077,3087,3908,3110,3120,3938,3141,3151,3161,3171,3989,3192,3202,3212,3222,4040,3243,3253,3276,3285,4106,65535,65535,65535,65535,65535,65535,65535,65535,65535},
{3714,3724,3734,3744,3754,2945,3775,3785,3795,3805,2996,3826,3836,3846,3856,3047,3877,3887,3897,3907,3101,3918,3928,3131,3949,3959,3969,3979,3182,4000,4010,4020,4030,3233,4051,4061,4084,4093,4107,65535,65535,65535,65535,65535,65535,65535,65535,65535},
{5,15,25,36,46,56,66,76,86,97,107,117,127,137,148,158,168,178,188,199,211,222,232,242,252,262,272,283,293,303,313,323,334,344,354,364,374,397,407,65535,65535,65535,65535,65535,65535,65535,65535,65535},
{6,16,26,37,47,57,67,77,87,98,108,118,128,138,149,159,169,179,189,200,212,223,233,243,253,263,273,284,294,304,314,324,335,345,355,365,375,398,408,65535,65535,65535,65535,65535,65535,65535,65535,65535},
{7,17,27,38,48,58,68,78,88,99,109,119,129,139,150,160,170,180,190,201,213,224,234,244,254,264,274,285,295,305,315,325,336,346,356,366,388,399,409,65535,65535,65535,65535,65535,65535,65535,65535,65535},
{8,18,28,39,49,59,69,79,89,100,110,120,130,140,151,161,171,181,191,202,214,225,235,245,255,265,275,286,296,306,316,326,337,347,357,367,389,400,410,65535,65535,65535,65535,65535,65535,65535,65535,65535},
{9,19,29,40,50,60,70,80,90,101,111,121,131,141,152,162,172,182,192,203,215,226,236,246,256,266,276,287,297,307,317,327,338,348,358,368,390,401,411,65535,65535,65535,65535,65535,65535,65535,65535,65535},
{10,20,30,41,51,61,71,81,91,102,112,122,132,142,153,163,173,183,193,204,216,227,237,247,257,267,277,288,298,308,318,328,339,349,359,369,391,402,3695,65535,65535,65535,65535,65535,65535,65535,65535,65535},
{11,21,31,42,52,62,72,82,92,103,113,123,133,143,154,164,174,184,194,205,217,228,238,248,258,268,278,289,299,309,319,329,340,350,360,370,392,403,65535,65535,65535,65535,65535,65535,65535,65535,65535,65535},
{12,3315,32,2514,2524,3354,74,84,94,2575,3405,125,135,145,2626,3456,176,186,196,207,3102,2700,2710,3528,260,270,280,2761,3579,311,321,331,2812,3630,362,372,3673,2875,65535,65535,65535,65535,65535,65535,65535,65535,65535,65535},
};

#define NG SCHED_NG
#define RING SCHED_RING
#define NSLOT 8
#define CFETCH 5
#define TABLED 1
#define PROMO CU_TENSOR_MAP_L2_PROMOTION_L2_128B
#define AHEAD 6
#define CF0 5
#define CFS 2
#define ABL 0
#define CX 5
#define PUBN 2
#define PUBE 8
#define SCHED 9
#define OUT_TMA 0
#define JB1 21
#define JB2 24
#define CVAR 2
#define CFN 0
#define CREGS 224
#define CSLEEP 200
#define JB 21
#define JF 24
#define JR 17
#define HOIST 1
#define XEARLY 0
#define FPRED 1
#define LATERED 1
#define WDELAY 0
#define WDELAY2 0
#define PFX 0
#define FIRST 3
#define NODUMP 1
#define CH 64
#define NOJB 1
#define JFF 0
#define XPRED 0
#define W2X 2
#define RETRY 0
#define HMASK 0
#define GMASK 0
#define XM 0
#define XLATE 0
#define SKIP 1
#define ONEPASS 1
#define HCOMP 1.0025f
#define SF 1
#define PRE 2
#define WN 0
#define G0M 1
#define G0S 1
#define TRIG0 -1
#define NEARLY 3
#define NLATE 0
#define TRIG 7
constexpr int NCONV = 3 * NG;
constexpr int PLEN = SCHED_LE, LM = 256 - 2 * PLEN, NSEG = 4 / (NG - 8), LMID = NSEG * LM;
static_assert(LMID <= PLEN && (NG == 9 || NG == 10), "geometry");
constexpr int TILEB = 12288;
constexpr int SLOTB = 280 * 64;
constexpr int W1S = 0, W2S = 73728, ABUF = 147456, XBUF = ABUF + 16 * 3072, MISC = XBUF + 8 * 3072;
constexpr int WBAR = MISC + 2560;
constexpr int RBUF = ABUF - 4 * SLOTB;
constexpr int CM = MISC + 2816, CTAB = CM + 256;
constexpr int SMEM_BYTES = CTAB + (PLEN + 16) * 16;
static_assert(RBUF % 512 == 0 && RBUF >= W2S && RBUF + NSLOT * SLOTB + 128 <= MISC && SMEM_BYTES <= 232448, "smem layout");

struct Globals {
  unsigned char scratch[RING * NG * 4 * TILEB];
  unsigned char wimg[147456];
  uint32_t wflag[32];
  uint32_t ready[NG * PLEN + 1];
  uint32_t cons[NG * PLEN];
  uint32_t epoch[1024];
};
__device__ __align__(1024) Globals g_state;

#define PROF_AT(cond, idx)
#define PROF_VAL(cond, idx, v)
#define PROF2_AT(c, i)
#define PROF2_VAL(c, i, v)
#define PROFS(i)
#define GELU_C3 0.32920349f
#define GELU_A2 0x40d940d9u
#define SCHED_FENCE() asm volatile("pmevent 0;" ::: "memory")
#define SPIN_LIMIT 0x1000000

__device__ __forceinline__ uint32_t smem_u32(const void* p) { return (uint32_t)__cvta_generic_to_shared(p); }
__device__ __forceinline__ void wg_fence() { asm volatile("wgmma.fence.sync.aligned;" ::: "memory"); }
__device__ __forceinline__ void wg_commit() { asm volatile("wgmma.commit_group.sync.aligned;" ::: "memory"); }
template <int N> __device__ __forceinline__ void wg_wait() { asm volatile("wgmma.wait_group.sync.aligned %0;" ::"n"(N) : "memory"); }
__device__ __forceinline__ void mbar_init(uint32_t bar, uint32_t cnt) { asm volatile("mbarrier.init.shared::cta.b64 [%0], %1;" ::"r"(bar), "r"(cnt) : "memory"); }
__device__ __forceinline__ void mbar_expect_tx(uint32_t bar, uint32_t bytes) { asm volatile("mbarrier.arrive.expect_tx.shared::cta.b64 _, [%0], %1;" ::"r"(bar), "r"(bytes) : "memory"); }
__device__ __forceinline__ void mbar_arrive(uint32_t bar) { asm volatile("mbarrier.arrive.shared::cta.b64 _, [%0];" ::"r"(bar) : "memory"); }
__device__ __forceinline__ void mbar_wait(uint32_t bar, uint32_t parity) {
  asm volatile("{\n.reg .pred p;\n.reg .u32 c;\nmbarrier.try_wait.parity.shared::cta.b64 p, [%0], %1;\n@p bra DONE_%=;\nmov.u32 c, 0;\nWAIT_%=:\nmbarrier.try_wait.parity.shared::cta.b64 p, [%0], %1;\n@p bra DONE_%=;\n"
               "add.u32 c, c, 1;\nsetp.lt.u32 p, c, 0x1000000;\n@p bra WAIT_%=;\ntrap;\nDONE_%=:\n}" ::"r"(bar), "r"(parity) : "memory");
}
__device__ __forceinline__ void bulk_g2s(uint32_t dst, const void* src, uint32_t bytes, uint32_t bar) {
  asm volatile("cp.async.bulk.shared::cluster.global.mbarrier::complete_tx::bytes [%0], [%1], %2, [%3];" ::"r"(dst), "l"(src), "r"(bytes), "r"(bar) : "memory");
}
__device__ __forceinline__ uint32_t ld_relaxed(const uint32_t* p) { uint32_t v; asm volatile("ld.relaxed.gpu.global.u32 %0, [%1];" : "=r"(v) : "l"(p) : "memory"); return v; }
__device__ __forceinline__ void red_add_elect(uint32_t* p) { asm volatile("{.reg .pred p; elect.sync _|p, 0xffffffff; @p red.relaxed.gpu.global.add.u32 [%0], 1;}" ::"l"(p) : "memory"); }
__device__ __forceinline__ void mbar_arrive_elect(uint32_t bar) { asm volatile("{.reg .pred p; elect.sync _|p, 0xffffffff; @p mbarrier.arrive.shared::cta.b64 _, [%0];}" ::"r"(bar) : "memory"); }
__device__ __forceinline__ void mbar_init_elect(uint32_t bar, uint32_t cnt) { asm volatile("{.reg .pred p; elect.sync _|p, 0xffffffff; @p mbarrier.init.shared::cta.b64 [%0], %1;}" ::"r"(bar), "r"(cnt) : "memory"); }
__device__ __forceinline__ void lds128(uint32_t* r, uint32_t a) { asm volatile("ld.shared.v4.b32 {%0,%1,%2,%3}, [%4];" : "=r"(r[0]), "=r"(r[1]), "=r"(r[2]), "=r"(r[3]) : "r"(a) : "memory"); }
__device__ __forceinline__ uint2 lds64(uint32_t a) { uint2 v; asm volatile("ld.shared.v2.b32 {%0,%1}, [%2];" : "=r"(v.x), "=r"(v.y) : "r"(a) : "memory"); return v; }
__device__ __forceinline__ uint32_t lds32(uint32_t a) { uint32_t v; asm volatile("ld.shared.b32 %0, [%1];" : "=r"(v) : "r"(a) : "memory"); return v; }
__device__ __forceinline__ void sts32(uint32_t a, uint32_t v) { asm volatile("st.shared.b32 [%0], %1;" ::"r"(a), "r"(v) : "memory"); }
__device__ __forceinline__ void sts128(uint32_t a, uint4 v) { asm volatile("st.shared.v4.b32 [%0], {%1,%2,%3,%4};" ::"r"(a), "r"(v.x), "r"(v.y), "r"(v.z), "r"(v.w) : "memory"); }
__device__ __forceinline__ uint4 ldg128v(const void* p) { uint4 v; asm volatile("ld.global.nc.v4.b32 {%0,%1,%2,%3}, [%4];" : "=r"(v.x), "=r"(v.y), "=r"(v.z), "=r"(v.w) : "l"(p) : "memory"); return v; }
__device__ __forceinline__ void stg128(void* p, uint4 v) { asm volatile("st.global.v4.b32 [%0], {%1,%2,%3,%4};" ::"l"(p), "r"(v.x), "r"(v.y), "r"(v.z), "r"(v.w) : "memory"); }
#define HINT 3
__device__ __forceinline__ uint64_t pol_evict_first() { uint64_t p; asm("createpolicy.fractional.L2::evict_first.b64 %0, 1.0;" : "=l"(p)); return p; }
__device__ __forceinline__ uint4 ldg128_last(const void* p, uint64_t pol) {
  if (!(HINT & 1)) return ldg128v(p);
  uint4 v; asm volatile("ld.global.nc.L1::no_allocate.L2::cache_hint.v4.b32 {%0,%1,%2,%3}, [%4], %5;" : "=r"(v.x), "=r"(v.y), "=r"(v.z), "=r"(v.w) : "l"(p), "l"(pol) : "memory"); return v;
}
__device__ __forceinline__ void stg128_stream(void* p, uint4 v, uint64_t pol) {
  if (!(HINT & 2)) { stg128(p, v); return; }
  asm volatile("st.global.L2::cache_hint.v4.b32 [%0], {%1,%2,%3,%4}, %5;" ::"l"(p), "r"(v.x), "r"(v.y), "r"(v.z), "r"(v.w), "l"(pol) : "memory");
}
__device__ __forceinline__ float bf_lo(uint32_t w) { return __uint_as_float(w << 16); }
__device__ __forceinline__ float bf_hi(uint32_t w) { return __uint_as_float(w & 0xffff0000u); }
__device__ __forceinline__ uint32_t pack_f16(float lo, float hi) { uint32_t d; asm("cvt.rn.f16x2.f32 %0, %1, %2;" : "=r"(d) : "f"(hi), "f"(lo)); return d; }
__device__ __forceinline__ uint32_t pack_f16_sat(float lo, float hi) { uint32_t d; asm("cvt.rn.satfinite.f16x2.f32 %0, %1, %2;" : "=r"(d) : "f"(hi), "f"(lo)); return d; }
__device__ __forceinline__ uint32_t pack_bf16(float lo, float hi) { uint32_t d; asm("cvt.rn.bf16x2.f32 %0, %1, %2;" : "=r"(d) : "f"(hi), "f"(lo)); return d; }
__device__ __forceinline__ uint32_t hadd2_bf16(uint32_t a, uint32_t b) { uint32_t d; asm("add.rn.bf16x2 %0, %1, %2;" : "=r"(d) : "r"(a), "r"(b)); return d; }
__device__ __forceinline__ uint32_t h2add(uint32_t a, uint32_t b) { uint32_t d; asm("add.rn.f16x2 %0, %1, %2;" : "=r"(d) : "r"(a), "r"(b)); return d; }
__device__ __forceinline__ uint32_t h2mul(uint32_t a, uint32_t b) { uint32_t d; asm("mul.rn.f16x2 %0, %1, %2;" : "=r"(d) : "r"(a), "r"(b)); return d; }
__device__ __forceinline__ uint32_t h2fma(uint32_t a, uint32_t b, uint32_t c) { uint32_t d; asm("fma.rn.f16x2 %0, %1, %2, %3;" : "=r"(d) : "r"(a), "r"(b), "r"(c)); return d; }
__device__ __forceinline__ uint32_t h2lo(uint32_t a) { uint32_t d; asm("{.reg .f16 l,h; mov.b32 {l,h}, %1; mov.b32 %0, {l,l};}" : "=r"(d) : "r"(a)); return d; }
__device__ __forceinline__ uint32_t h2hi(uint32_t a) { uint32_t d; asm("{.reg .f16 l,h; mov.b32 {l,h}, %1; mov.b32 %0, {h,h};}" : "=r"(d) : "r"(a)); return d; }
__device__ __forceinline__ float h_lo(uint32_t a) { float d; asm("{.reg .f16 l,h; mov.b32 {l,h}, %1; cvt.f32.f16 %0, l;}" : "=f"(d) : "r"(a)); return d; }
__device__ __forceinline__ float h_hi(uint32_t a) { float d; asm("{.reg .f16 l,h; mov.b32 {l,h}, %1; cvt.f32.f16 %0, h;}" : "=f"(d) : "r"(a)); return d; }
__device__ __forceinline__ uint32_t prmt(uint32_t a, uint32_t b, uint32_t s) { uint32_t d; asm("prmt.b32 %0, %1, %2, %3;" : "=r"(d) : "r"(a), "r"(b), "r"(s)); return d; }
__device__ __forceinline__ void mma_sp(float* d, const uint32_t* a, const uint32_t* b, const float* c, uint32_t e) {
  asm("mma.sp::ordered_metadata.sync.aligned.m16n8k32.row.col.f32.bf16.bf16.f32 {%0,%1,%2,%3}, {%4,%5,%6,%7}, {%8,%9,%10,%11}, {%12,%13,%14,%15}, %16, 0;"
      : "=f"(d[0]), "=f"(d[1]), "=f"(d[2]), "=f"(d[3])
      : "r"(a[0]), "r"(a[1]), "r"(a[2]), "r"(a[3]), "r"(b[0]), "r"(b[1]), "r"(b[2]), "r"(b[3]), "f"(c[0]), "f"(c[1]), "f"(c[2]), "f"(c[3]), "r"(e));
}
__device__ __forceinline__ uint32_t bf2_to_h2(uint32_t w, float s) { return pack_f16(bf_lo(w) * s, bf_hi(w) * s); }
__device__ __forceinline__ uint32_t bf2_to_h2(uint32_t w) { return pack_f16(bf_lo(w), bf_hi(w)); }

__device__ __forceinline__ uint32_t gelu_tanh(uint32_t y) {
  uint32_t t, u, th;
  asm volatile("fma.rn.f16x2 %0, %1, %1, %2;" : "=r"(t) : "r"(y), "r"(GELU_A2));
  asm volatile("mul.rn.f16x2 %0, %1, %2;" : "=r"(u) : "r"(y), "r"(t));
  asm volatile("tanh.approx.f16x2 %0, %1;" : "=r"(th) : "r"(u));
  return th;
}
__device__ __forceinline__ uint32_t gelu_fin(uint32_t y, uint32_t th) {
  uint32_t g;
  asm volatile("fma.rn.f16x2 %0, %1, %2, %1;" : "=r"(g) : "r"(y), "r"(th));
  return g;
}

__device__ __forceinline__ void copy_weights(uint32_t sb, int piece, const void* src) {
  asm volatile("{\n.reg .pred p;\nelect.sync _|p, 0xffffffff;\n@p mbarrier.init.shared::cta.b64 [%1], 1;\n@p fence.mbarrier_init.release.cluster;\n"
               "@p mbarrier.arrive.expect_tx.shared::cta.b64 _, [%1], 12288;\n"
               "@p cp.async.bulk.shared::cluster.global.mbarrier::complete_tx::bytes [%0], [%2], 12288, [%1];\n}"
               ::"r"(sb + piece * 12288), "r"(sb + WBAR + piece * 8), "l"(src) : "memory");
}
__device__ __forceinline__ void convert_weights(uint32_t sb, uint32_t wbar, int rot, int warp, int lane) {
  if (warp < 12) {
    const int l8 = lane & 7, q4 = lane >> 3;
    int s = (warp >> 1) + rot; if (s >= 6) s -= 6;
    const uint32_t base = sb + W1S + s * 12288 + (warp & 1) * 384;
    mbar_wait(wbar + s * 8, 0);
    uint32_t v[3][4][4];
#pragma unroll
    for (int r = 0; r < 4; r++)
#pragma unroll
      for (int i = 0; i < 3; i++) lds128(v[i][r], base + i * 128 + (4 * (l8 >> 1) + 2 * (r & 1) + (l8 & 1)) * 768 + ((l8 + q4 + 4 * (r >> 1)) & 7) * 16);
    __syncwarp();
#pragma unroll
    for (int r = 0; r < 4; r++)
#pragma unroll
      for (int i = 0; i < 3; i++)
        sts128(base + i * 128 + (((l8 + q4 + 4 * (r >> 1)) & 7) + 8 * (r & 1)) * 768 + l8 * 16,
               make_uint4(bf2_to_h2(v[i][r][0]), bf2_to_h2(v[i][r][1]), bf2_to_h2(v[i][r][2]), bf2_to_h2(v[i][r][3])));
  }
  PROF2_AT(lane == 0, 440 + warp);
  const int q = lane & 3, t = (lane >> 2) & 3, b = lane >> 4;
  int u = 3 * (warp ^ 15) + 8 * rot; if (u >= 48) u -= 48;
  uint32_t base[3], v[3][4][3];
#pragma unroll
  for (int i = 0; i < 3; i++) {
    const int ui = u + i >= 48 ? u + i - 48 : u + i;
    base[i] = sb + W2S + ui * 1536;
    if (i != 1) mbar_wait(wbar + 48 + (ui >> 3) * 8, 0);
  }
#pragma unroll
  for (int i = 0; i < 3; i++)
#pragma unroll
    for (int d = 0; d < 4; d++)
#pragma unroll
      for (int j = 0; j < 3; j++) v[i][d][j] = lds32(base[i] + (2 * ((q + d) & 3) + b) * 192 + j * 64 + t * 16 + q * 4);
  __syncwarp();
#pragma unroll
  for (int i = 0; i < 3; i++)
#pragma unroll
    for (int d = 0; d < 4; d++)
#pragma unroll
      for (int j = 0; j < 3; j++) sts32(base[i] + (4 * j + q) * 128 + (2 * ((q + d) & 3) + b) * 16 + t * 4, bf2_to_h2(v[i][d][j]));
}

__device__ __noinline__ void ln_wide(uint32_t ad) {
  float m[2], r[2];
#pragma unroll
  for (int hi = 0; hi < 2; hi++) {
    float sm = 0.f;
    for (int s = 0; s < 6; s++) { uint2 w = lds64(ad + s * 512 + hi * 8); sm += (h_lo(w.x) + h_hi(w.x)) + (h_lo(w.y) + h_hi(w.y)); }
    sm += __shfl_xor_sync(0xffffffffu, sm, 1); sm += __shfl_xor_sync(0xffffffffu, sm, 2);
    m[hi] = sm * (1.f / 96.f);
    float q = 0.f;
    for (int s = 0; s < 6; s++) {
      uint2 w = lds64(ad + s * 512 + hi * 8);
      float d0 = h_lo(w.x) - m[hi], d1 = h_hi(w.x) - m[hi], d2 = h_lo(w.y) - m[hi], d3 = h_hi(w.y) - m[hi];
      q += (d0 * d0 + d1 * d1) + (d2 * d2 + d3 * d3);
    }
    q += __shfl_xor_sync(0xffffffffu, q, 1); q += __shfl_xor_sync(0xffffffffu, q, 2);
    r[hi] = rsqrtf(fmaf(q, 1.f / 96.f, 1e-5f)) * GELU_C3;
  }
  for (int s = 0; s < 6; s++) {
    uint32_t w[4]; lds128(w, ad + s * 512);
    sts128(ad + s * 512, make_uint4(pack_f16((h_lo(w[0]) - m[0]) * r[0], (h_hi(w[0]) - m[0]) * r[0]), pack_f16((h_lo(w[2]) - m[1]) * r[1], (h_hi(w[2]) - m[1]) * r[1]),
                                    pack_f16((h_lo(w[1]) - m[0]) * r[0], (h_hi(w[1]) - m[0]) * r[0]), pack_f16((h_lo(w[3]) - m[1]) * r[1], (h_hi(w[3]) - m[1]) * r[1])));
  }
  asm volatile("fence.proxy.async.shared::cta;" ::: "memory");
}

__device__ __forceinline__ float rsqrt_fast(float v) { float r; asm("rsqrt.approx.ftz.f32 %0, %1;" : "=f"(r) : "f"(v)); return r; }
__device__ __forceinline__ uint32_t layer_norm(uint32_t (&raw)[6][4], uint32_t* a, uint32_t tag) {
  const uint32_t stale = ((raw[0][0] ^ tag) | (raw[1][0] ^ tag)) | ((raw[2][0] ^ tag) | (raw[3][0] ^ tag)) | ((raw[4][0] ^ tag) | (raw[5][0] ^ tag));
  uint32_t sm[2];
#pragma unroll
  for (int hi = 0; hi < 2; hi++) {
    uint32_t s0 = h2add(raw[0][2 * hi], raw[1][2 * hi]), s1 = h2add(raw[0][2 * hi + 1], raw[1][2 * hi + 1]);
    uint32_t s2 = h2add(raw[2][2 * hi], raw[3][2 * hi]), s3 = h2add(raw[2][2 * hi + 1], raw[3][2 * hi + 1]);
    uint32_t s4 = h2add(raw[4][2 * hi], raw[5][2 * hi]), s5 = h2add(raw[4][2 * hi + 1], raw[5][2 * hi + 1]);
    sm[hi] = h2add(h2add(h2add(s0, s1), h2add(s2, s3)), h2add(s4, s5));
  }
  uint32_t qq[2];
#pragma unroll
  for (int hi = 0; hi < 2; hi++) {
    uint32_t q0 = h2mul(raw[0][2 * hi], raw[0][2 * hi]), q1 = h2mul(raw[0][2 * hi + 1], raw[0][2 * hi + 1]);
#pragma unroll
    for (int k = 1; k < 6; k++) { q0 = h2fma(raw[k][2 * hi], raw[k][2 * hi], q0); q1 = h2fma(raw[k][2 * hi + 1], raw[k][2 * hi + 1], q1); }
    qq[hi] = h2add(q0, q1);
  }
  uint32_t s = h2add(prmt(sm[0], sm[1], 0x5410), prmt(sm[0], sm[1], 0x7632));
  uint32_t q = h2add(prmt(qq[0], qq[1], 0x5410), prmt(qq[0], qq[1], 0x7632));
  s = h2add(s, __shfl_xor_sync(0xffffffffu, s, 1)); q = h2add(q, __shfl_xor_sync(0xffffffffu, q, 1));
  s = h2add(s, __shfl_xor_sync(0xffffffffu, s, 2)); q = h2add(q, __shfl_xor_sync(0xffffffffu, q, 2));
  constexpr float CS = HMASK ? GELU_C3 * HCOMP : GELU_C3;
  constexpr float K1 = 1.f / (96.f * CS * CS), K2 = 1e-5f / (CS * CS), K3 = 1.f / (96.f * CS);
  const float e0 = fmaf(h_lo(q), K1, K2), e1 = fmaf(h_hi(q), K1, K2), m0 = h_lo(s) * K3, m1 = h_hi(s) * K3;
  const float v0 = fmaf(-m0, m0, e0), v1 = fmaf(-m1, m1, e1);
  const uint32_t r = pack_f16(rsqrt_fast(v0), rsqrt_fast(v1)), o = h2mul(h2mul(s, 0xA155A155u), r);
#pragma unroll
  for (int k = 0; k < 6; k++) {
    a[4 * k] = h2fma(raw[k][0], h2lo(r), h2lo(o)); a[4 * k + 2] = h2fma(raw[k][1], h2lo(r), h2lo(o));
    a[4 * k + 1] = h2fma(raw[k][2], h2hi(r), h2hi(o)); a[4 * k + 3] = h2fma(raw[k][3], h2hi(r), h2hi(o));
  }
  if (HMASK) {
#pragma unroll
    for (int k = 0; k < 24; k++) a[k] &= HMASK;
  }
  const bool fine = fmaf(v0, 4.f, -e0) > 0.f && fmaf(v1, 4.f, -e1) > 0.f;
  return (fine ? 0u : 2u) | (stale & 1);
}

constexpr int KS = CH / 16, NC = 384 / CH;
#define WG1_(n) wgmma_n##n##_f16
#define WG1(n) WG1_(n)
__device__ __forceinline__ void gemm1(uint32_t* p, const uint32_t* a, uint64_t d1, int c, int k0 = 0, int k1 = 6) {
#pragma unroll
  for (int s = 0; s < 6; s++)
    if (s >= k0 && s < k1) {
      if (s == 0) WG1(CH)<0>(p, a, d1 + c * CH); else WG1(CH)<1>(p, a + 4 * s, d1 + c * CH + s * (12288 >> 4));
    }
}
__device__ __forceinline__ void fetch_a(uint32_t abuf, uint32_t bar, const unsigned char* src) {
  asm volatile("{\n.reg .pred p;\nelect.sync _|p, 0xffffffff;\n"
               "@p mbarrier.arrive.expect_tx.shared::cta.b64 _, [%1], 3072;\n"
               "@p cp.async.bulk.shared::cluster.global.mbarrier::complete_tx::bytes [%0], [%2], 3072, [%1];\n}"
               ::"r"(abuf), "r"(bar), "l"(src) : "memory");
}
__device__ __forceinline__ void fetch_a_if(uint32_t abuf, uint32_t bar, const unsigned char* src, uint32_t go) {
  asm volatile("{\n.reg .pred p, q;\nsetp.ne.u32 q, %3, 0;\nelect.sync _|p, 0xffffffff;\nand.pred p, p, q;\n"
               "@p mbarrier.arrive.expect_tx.shared::cta.b64 _, [%1], 3072;\n"
               "@p cp.async.bulk.shared::cluster.global.mbarrier::complete_tx::bytes [%0], [%2], 3072, [%1];\n}"
               ::"r"(abuf), "r"(bar), "l"(src), "r"(go) : "memory");
}
__device__ __forceinline__ bool mbar_test(uint32_t bar, uint32_t parity) {
  uint32_t r;
  asm volatile("{.reg .pred p; mbarrier.test_wait.parity.shared::cta.b64 p, [%1], %2; selp.u32 %0, 1, 0, p;}" : "=r"(r) : "r"(bar), "r"(parity) : "memory");
  return r;
}
__device__ __forceinline__ void fetch_x(uint32_t xbuf, uint32_t bar, const CUtensorMap* tm, uint32_t c0, uint32_t c12, uint64_t pol, int go = 0) {
  asm volatile("{\n.reg .pred p, q;\nsetp.ge.s32 q, %7, 0;\nelect.sync _|p, 0xffffffff;\nand.pred p, p, q;\n"
               "@p mbarrier.arrive.expect_tx.shared::cta.b64 _, [%1], 3072;\n"
               "@p cp.async.bulk.tensor.3d.shared::cluster.global.mbarrier::complete_tx::bytes.L2::cache_hint [%0], [%2, {%3, %4, %5}], [%1], %6;\n}"
               ::"r"(xbuf), "r"(bar), "l"(tm), "r"(c0), "r"(c12 & 255), "r"(c12 >> 8), "l"(pol), "r"(go) : "memory");
}
__device__ __forceinline__ void wait_ready(const uint32_t* p, uint32_t target) {
  int spins = 0;
  while (ld_relaxed(p) != target) { __nanosleep(32); if (++spins > SPIN_LIMIT) __trap(); }
}
__device__ __forceinline__ uint32_t slot_tag(int gm, int j, uint32_t epoch) {
  const int len = gm < 8 ? PLEN : LMID, writes = (len - (j % RING) + RING - 1) / RING;
  return (epoch * writes + j / RING + 1) & 1;
}

__device__ __forceinline__ void build_tile_list(uint32_t sb, int k, int idx, bool tabled, bool is_conv, uint32_t epoch) {
  int n = -1;
  if (tabled) { if (k < 48) n = (int16_t)g_sched[idx][k]; }
  else if (!is_conv) {
    const int i = k * (gridDim.x - NCONV) + idx, r = i >> 2, full = LMID * NG;
    const int j = r < full ? r / NG : ((r - full) >> 3) + LMID, gm = r < full ? r % NG : (r - full) & 7;
    if (i < 4096) n = (gm * PLEN + j) * 4 + (i & 3);
  }
  const int q = n >> 2, gm = q / PLEN, j = q - gm * PLEN, seg = j / LM;
  const int strip = gm < 8 ? gm >> 1 : (gm - 8) * NSEG + seg, pair = gm < 8 ? ((gm & 1) ? 255 - j : j) : PLEN + j - seg * LM;
  sts128(sb + MISC + 512 + k * 16, make_uint4(q, (((j % RING) * NG + gm) * 4 + (n & 3)) * TILEB + slot_tag(gm, j, epoch),
                                              (n & 2) * 384, (strip * 8 + (n & 1) * 4) | (pair << 9)));
  if (k == 0) { sts32(sb + MISC + 256, epoch + 1); sts32(sb + MISC + 260, !is_conv); }
}

__device__ __forceinline__ void mlp_setup(uint32_t sb, Globals* gs, int id, const __nv_bfloat16* __restrict__ w1, const __nv_bfloat16* __restrict__ w2,
                                          int idx, bool tabled, int warp, int lane) {
  const int rot = idx % 6;
  PROF2_AT(lane == 0, 400 + warp);
  if (warp < 12) {
    const int m = warp >= 6; int s = warp - 6 * m + rot; if (s >= 6) s -= 6;
    if (WDELAY) __nanosleep(WDELAY + m * WDELAY2);
    copy_weights(sb, 6 * m + s, (const char*)(m ? w2 : w1) + s * 12288);
  }
  __syncthreads();
  PROF2_AT(threadIdx.x == 0, 416);
  if (warp >= 12) build_tile_list(sb, threadIdx.x - 384, idx, tabled, false, ld_relaxed(&gs->epoch[id]));
  PROF2_AT(lane == 0, 420 + warp);
  convert_weights(sb, sb + WBAR, rot, warp, lane);
  PROF2_AT(lane == 0, 460 + warp);
  asm volatile("fence.proxy.async.shared::cta;" ::: "memory");
  __syncthreads();
  if (threadIdx.x == 480) {
    const uint32_t e1 = lds32(sb + MISC + 256);
    gs->epoch[id] = e1;
    if (idx < 24 && (idx & 1)) {
      asm volatile("cp.async.bulk.global.shared::cta.bulk_group [%0], [%1], 12288;\ncp.async.bulk.commit_group;\ncp.async.bulk.wait_group 0;\nfence.proxy.async.global;\n"
                   "red.release.gpu.global.add.u32 [%2], 1;" ::"l"(gs->wimg + (idx >> 1) * 12288), "r"(sb + (idx >> 1) * 12288), "l"(gs->wflag) : "memory");
    }
  }
  __syncwarp();
}

__device__ __forceinline__ void mlp_role(uint32_t sb, Globals* gs, const CUtensorMap* tmr, __nv_bfloat16* __restrict__ out) {
  uint32_t tid;
  asm volatile("mov.u32 %0, %%tid.x;" : "=r"(tid));
  const int warp = __shfl_sync(0xffffffffu, tid >> 5, 0), lane = tid & 31;
  const int wg = warp >> 2, w = warp & 3, g = lane >> 2, t = lane & 3;
  const uint32_t abuf = sb + ABUF + warp * 3072, xbuf = sb + XBUF + (warp & 7) * 3072;
  const uint32_t bar = sb + MISC + warp * 8, obar = sb + MISC + (warp ^ 8) * 8;
  const uint32_t tl = sb + MISC + 512;
  PROF_AT(threadIdx.x == 0, 1); PROF_VAL(threadIdx.x == 0, 8, clock64());
  const uint32_t rtarget = 3 * lds32(sb + MISC + 256);
  const uint64_t d1 = ((uint64_t)(6144 >> 4) << 16) | ((uint64_t)(128 >> 4) << 32) | (uint64_t)(((sb + W1S) >> 4) & 0x3fff);
  const uint64_t d2 = ((uint64_t)(12288 >> 4) << 16) | ((uint64_t)(128 >> 4) << 32) | (uint64_t)(((sb + W2S) >> 4) & 0x3fff);
  const uint32_t ad = abuf + t * 128 + ((g ^ (2 * t)) << 4);
  const uint32_t xd = xbuf + g * 192 + t * 16;
  const uint32_t pofs = (g >> 1) * 3072 + (2 * w + (g & 1)) * 192 + t * 16;
  const int mybar = 1 + wg, nxtbar = 1 + ((wg + 1) & 3);
  const uint64_t pol = pol_evict_first();
  const unsigned char* const asrc = gs->scratch + w * 3072;
  uint32_t pha = 0, phx = 0, tp = tl + wg * 16;
  bool pending = lds32(sb + MISC + 260);
  const uint32_t tq = tl + (pending ? G0M : G0S) * 16;
  uint32_t cur[4], rdy2 = rtarget + 1;
  lds128(cur, tp);
  if (wg < 2) fetch_x(xbuf, bar + 128, tmr, cur[2] + w * 192, cur[3], pol, cur[0]);
  while ((int)cur[0] >= 0) {
    PROF2_AT((threadIdx.x & 127) == 0, 16 + (tp - tl) / 4); PROF2_VAL((threadIdx.x & 127) == 0, 16 + (tp - tl) / 4 + 3, pending);
    uint32_t a[24], p[NC][CH / 4], gg[24][4], th[24][4], acc[24], raw[6][4], xr[6][4], n2[4], n4[4];
    if (pending) {
      if (!RETRY || rdy2 != rtarget) wait_ready(&gs->ready[cur[0]], rtarget);
      fetch_a(abuf, bar, asrc + (cur[1] & ~1u));
    }
    mbar_wait(bar, pha); pha ^= 1;
    PROF2_AT((threadIdx.x & 127) == 0, 16 + (tp - tl) / 4 + 1);
#pragma unroll
    for (int k = 0; k < 6; k++) lds128(raw[k], ad + k * 512);
    const int sig = (int)lds32(tp + 16) | (int)(tp + 16 - tq);
    lds128(n4, tp + 64);
    if (XLATE) lds128(n2, tp - 32);
    uint32_t st = layer_norm(raw, a, cur[1]);
    if (__any_sync(0xffffffffu, st != 0)) {
      for (int tries = 0; __any_sync(0xffffffffu, st & 1); tries++) {
        if (tries > SPIN_LIMIT) __trap();
        fetch_a(abuf, bar, asrc + (cur[1] & ~1u));
        mbar_wait(bar, pha); pha ^= 1;
        st = 0;
#pragma unroll
        for (int k = 0; k < 6; k++) st |= lds32(ad + k * 512) ^ cur[1];
      }
      ln_wide(ad);
#pragma unroll
      for (int k = 0; k < 6; k++) lds128(a + 4 * k, ad + k * 512);
    }
    if (!LATERED) red_add_elect(&gs->cons[cur[0]]);
    if (tp >= tq) asm volatile("bar.sync %0, 256;" ::"r"(mybar) : "memory");
    PROF2_AT((threadIdx.x & 127) == 0, 16 + (tp - tl) / 4 + 2);
    uint32_t rdy = 0;
    wg_fence();
    gemm1(p[0], a, d1, 0); wg_commit();
    if (SCHED == 9) { gemm1(p[1], a, d1, 1, 0, 6 / KS); wg_commit(); }
    if (XLATE && tp >= tl + 64) fetch_x(xbuf, obar + 128, tmr, n2[2] + w * 192, n2[3], pol);
    if (LATERED) asm volatile("{.reg .pred p; setp.eq.u32 p, %1, 0; @p red.relaxed.gpu.global.add.u32 [%0], 1;}" ::"l"(&gs->cons[cur[0]] + lane), "r"(lane) : "memory");
#pragma unroll
    for (int j = 0; j < 24; j++) {
      const int c = j / KS, s = j % KS;
      if (NOJB && j == JB) { if (NOJB == 2) SCHED_FENCE(); rdy = ld_relaxed(&gs->ready[max((int)n4[0], 0)]); if (NOJB == 3) SCHED_FENCE(); }
      if (SCHED == 9) { if (s == 0 || WN == 1) wg_wait<1>(); else if (WN == 2) wg_wait<2>(); else if (WN == 3 && s == KS - 1) wg_wait<1>(); } else if (s == 0) wg_wait<0>();
      if (j == JF) { pending = rdy != rtarget; fetch_a_if(abuf, bar, asrc + (n4[1] & ~1u), !pending && (int)n4[0] >= 0); if (JFF) SCHED_FENCE(); }
      if (j == TRIG) asm volatile("{.reg .pred p; setp.ge.s32 p, %1, 0; @p bar.arrive %0, 256;}" ::"r"(nxtbar), "r"(sig) : "memory");
#pragma unroll
      for (int i = 0; i < 4; i++) {
        if (!(s && i < PRE)) th[j][i] = gelu_tanh(p[c][4 * s + i]);
        gg[j][i] = gelu_fin(p[c][4 * s + i], th[j][i]);
      }
      wg_fence();
      if (j == 0) wgmma_n96_f16<0>(acc, gg[j], d2); else wgmma_n96_f16<1>(acc, gg[j], d2 + (16 * (j % 3) + j / 3) * (1536 >> 4));
      if (SCHED == 9) {
        const int c1 = (j + 1) / KS + 1, u = (j + 1) % KS;
        if (c1 < NC) gemm1(p[c1], a, d1, c1, (6 * u) / KS, (6 * (u + 1)) / KS);
        wg_commit();
        if (PRE && s + 1 < KS) {
#pragma unroll
          for (int i = 0; i < PRE; i++) th[j + 1][i] = gelu_tanh(p[c][4 * s + 4 + i]);
        }
        if (SF && (j + 1) % (SF ? SF : 1) == 0 && j < 23) SCHED_FENCE();
      } else if (s == KS - 1) {
        if (c + 1 < NC) gemm1(p[c + 1], a, d1, c + 1);
        wg_commit();
      }
    }
    pending = rdy != rtarget;
    if (JF == 24) fetch_a_if(abuf, bar, asrc + (n4[1] & ~1u), !pending && (int)n4[0] >= 0);
    if (RETRY) rdy2 = ld_relaxed(&gs->ready[max((int)n4[0], 0)]);
    if (XM != 2) wg_wait<0>();
    mbar_wait(bar + 128, phx); phx ^= 1;
    if (XM) {
#pragma unroll
      for (int k = 0; k < 6; k++) lds128(xr[k], xd + (k / 3) * 1536 + (k % 3) * 64);
    }
    if (XM == 2) wg_wait<0>();
#pragma unroll
    for (int k = 0; k < 24; k++) acc[k] = h2mul(acc[k], 0x3E133E13u);
    char* const op = (char*)out + (cur[2] * 2 + (cur[3] & 255) * 3072 + (cur[3] >> 8) * (512 * 192) + pofs);
    if (!XLATE) lds128(n2, tp + 32);
#pragma unroll
    for (int k = 0; k < 6; k++) {
      const int hi = k / 3, j = k % 3;
      if (!XM) lds128(xr[k], xd + hi * 1536 + j * 64);
      uint4 o;
      o.x = hadd2_bf16(xr[k][0], pack_bf16(h_lo(acc[8 * j + hi]), h_hi(acc[8 * j + hi])));
      o.y = hadd2_bf16(xr[k][1], pack_bf16(h_lo(acc[8 * j + 2 + hi]), h_hi(acc[8 * j + 2 + hi])));
      o.z = hadd2_bf16(xr[k][2], pack_bf16(h_lo(acc[8 * j + 4 + hi]), h_hi(acc[8 * j + 4 + hi])));
      o.w = hadd2_bf16(xr[k][3], pack_bf16(h_lo(acc[8 * j + 6 + hi]), h_hi(acc[8 * j + 6 + hi])));
      stg128_stream(op + hi * (512 * 192) + j * 64, o, pol);
    }
    if (!XLATE) {
      __syncwarp();
      if ((int)n2[0] >= 0) fetch_x(xbuf, obar + 128, tmr, n2[2] + w * 192, n2[3], pol);
    }
    tp += 64;
#pragma unroll
    for (int k = 0; k < 4; k++) cur[k] = n4[k];
  }
  if (XLATE && tp >= tl + 64) {
    uint32_t n2[4];
    lds128(n2, tp - 32);
    __syncwarp();
    if ((int)n2[0] >= 0) fetch_x(xbuf, obar + 128, tmr, n2[2] + w * 192, n2[3], pol);
  }
  PROF_AT((threadIdx.x & 127) == 0, 4 + wg); PROF_VAL(threadIdx.x == 0, 9, clock64());
}

__device__ __forceinline__ void stg128_if(uint32_t ofs, void* p, uint4 v) {
  asm volatile("{.reg .pred q; setp.ge.s32 q, %5, 0; @q st.global.v4.b32 [%0], {%1,%2,%3,%4};}" ::"l"(p), "r"(v.x), "r"(v.y), "r"(v.z), "r"(v.w), "r"(ofs) : "memory");
}
__device__ __forceinline__ void conv_compute(uint32_t sb, Globals* gs, int third, int nit, int off, bool up, int warp, int lane) {
  const int g = lane >> 2, t = lane & 3;
  const uint32_t full = sb + CM;
  PROFS(0);
  const uint32_t wt = sb + 16384 + warp * 1024;
  sts128(wt + lane * 16, make_uint4(0, 0, 0, 0));
  if (lane < 4) sts128(wt + 512 + lane * 16, make_uint4(0, 0, 0, 0));
  asm volatile("setmaxnreg.inc.sync.aligned.u32 %0;" ::"n"(CREGS));
  PROFS(1);
  uint32_t meta = 0;
#pragma unroll
  for (int a = 0; a < 4; a++) meta |= ((4 * (t & 1) + a + 1 >= g) ? 0x80008u : 0xD000Du) << (4 * a);
  meta = __shfl_sync(0xffffffffu, meta, lane);
  uint32_t aq[4];
#pragma unroll
  for (int q = 0; q < 4; q++) {
    const int pp = (g & 1) * 140 + (t & 1) * 70 + 16 * (g >> 1) + 2 * q + (t >> 1);
    aq[q] = __shfl_sync(0xffffffffu, sb + RBUF + pp * 64 + (((warp >> 1) ^ ((pp >> 1) & 3)) << 4) + (warp & 1) * 8, lane);
  }
  const int Q = third * 8 + warp;
  unsigned char* const obase = gs->scratch + (g >> 1) * 3072 + Q * 128 + (((2 * t + (g & 1)) ^ (2 * (Q & 3))) << 4);
  const float zero4[4] = {0.f, 0.f, 0.f, 0.f};
  {
    uint32_t A[4][4][4];
    PROFS(2);
    asm volatile("bar.sync 5, 288;" ::: "memory");
    mbar_wait(sb + WBAR + 8, 0);
    PROFS(3);
    {
#pragma unroll
      for (int k = 0; k < 2; k++) {
        const int tap = lane + 32 * k, i = tap / 7;
        if (tap < 49) { const uint2 v = lds64(sb + tap * 192 + third * 64 + warp * 8); asm volatile("st.shared.v2.b32 [%0], {%1,%2};" ::"r"(wt + (tap + i + 8) * 8), "r"(v.x), "r"(v.y) : "memory"); }
      }
      __syncwarp();
      uint2 w[2][4][3];
#pragma unroll
      for (int h = 0; h < 2; h++) {
        uint32_t src = wt + ((4 * h + t - g) & 7) * 8 + (up ? 384 : 0);
#pragma unroll
        for (int u = 0; u < 4; u++) {
#pragma unroll
          for (int k = 0; k < 3; k++) w[h][u][k] = lds64(src + k * 64);
          src += up ? -128 : 128;
        }
      }
#pragma unroll
      for (int u = 0; u < 4; u++)
#pragma unroll
        for (int r = 0; r < 4; r++) {
          const uint2 w0 = w[r >> 1][u][1 - (r & 1)], w1 = w[r >> 1][u][2 - (r & 1)];
          A[0][u][r] = prmt(w0.x, w1.x, 0x5410); A[1][u][r] = prmt(w0.x, w1.x, 0x7632);
          A[2][u][r] = prmt(w0.y, w1.y, 0x5410); A[3][u][r] = prmt(w0.y, w1.y, 0x7632);
        }
    }
    float S[2][4][3][4];
#pragma unroll
    for (int s = 0; s < 2; s++)
#pragma unroll
      for (int c = 0; c < 4; c++)
#pragma unroll
        for (int i = 0; i < 3; i++)
#pragma unroll
          for (int k = 0; k < 4; k++) S[s][c][i][k] = 0.f;
    uint32_t sofs = off * SLOTB, bar = full + off * 8, ph = 0, ot = sb + CTAB;
    const uint32_t oend = ot + nit * 16;
    PROF_AT(threadIdx.x == 0, 12);
    PROFS(4);
    asm volatile("bar.sync 0, 512;" ::: "memory");
    PROFS(5);
    mbar_wait(bar, 0);
    PROF_AT(threadIdx.x == 0, 14);
    PROFS(6);
    uint2 X[3][4];
#pragma unroll
    for (int j = 0; j < 2; j++)
#pragma unroll
      for (int q = 0; q < 4; q++) X[j][q] = lds64(aq[q] + sofs + j * 512);
#pragma unroll 1
    do {
      const uint2 oe = lds64(ot);
      unsigned char* const o = obase + oe.x;
      const uint32_t dbar = bar + 64;
#pragma unroll
      for (int s = 0; s < 2; s++) {
        uint32_t B[4][4];
        if (s == 1) {
          sofs += SLOTB; bar += 8;
          if (sofs == NSLOT * SLOTB) { sofs = 0; bar = full; ph ^= 1; }
          mbar_wait(bar, ph);
        }
#pragma unroll
        for (int c = 0; c < 4; c++)
#pragma unroll
          for (int q = 0; q < 4; q++) B[c][q] = prmt(c < 2 ? X[s][q].x : X[s][q].y, c < 2 ? X[s + 1][q].x : X[s + 1][q].y, (c & 1) ? 0x7632 : 0x5410);
        if (s == 0) {
#pragma unroll
          for (int q = 0; q < 4; q++) X[2][q] = lds64(aq[q] + sofs + 2 * 512);
        } else {
#pragma unroll
          for (int j = 0; j < 2; j++)
#pragma unroll
            for (int q = 0; q < 4; q++) X[j][q] = lds64(aq[q] + sofs + j * 512);
        }
        float T[4][4];
#pragma unroll
        for (int c = 0; c < 4; c++) mma_sp(T[c], A[c][3], B[c], S[s][c][2], meta);
#pragma unroll
        for (int c = 0; c < 4; c++) mma_sp(S[s][c][2], A[c][2], B[c], S[s][c][1], meta);
        stg128_if(oe.x, o + (2 * s) * TILEB, make_uint4((pack_f16_sat(T[0][0], T[1][0]) & ~1u) | oe.y, pack_f16_sat(T[2][0], T[3][0]), pack_f16_sat(T[0][2], T[1][2]), pack_f16_sat(T[2][2], T[3][2])));
        stg128_if(oe.x, o + (2 * s + 1) * TILEB, make_uint4((pack_f16_sat(T[0][1], T[1][1]) & ~1u) | oe.y, pack_f16_sat(T[2][1], T[3][1]), pack_f16_sat(T[0][3], T[1][3]), pack_f16_sat(T[2][3], T[3][3])));
        if (s == 1) mbar_arrive_elect(dbar);
#pragma unroll
        for (int c = 0; c < 4; c++) mma_sp(S[s][c][1], A[c][1], B[c], S[s][c][0], meta);
#pragma unroll
        for (int c = 0; c < 4; c++) mma_sp(S[s][c][0], A[c][0], B[c], zero4, meta);
      }
      ot += 16;
    } while (ot != oend);
  }
  PROF_AT(threadIdx.x == 0, 13);
}

__device__ __forceinline__ void load_step(uint32_t sb, const CUtensorMap* tmx, int gm, int third, int it, int s) {
  const int seg = it / (LM + 3);
  const int st = gm < 8 ? gm >> 1 : (gm - 8) * NSEG + seg, J = gm < 8 ? ((gm & 1) ? 257 - it : it + 1) : PLEN + it - seg * (LM + 3);
  asm volatile("{\n.reg .pred p;\n.reg .s32 c2;\n.reg .u32 d2;\nelect.sync _|p, 0xffffffff;\nadd.s32 c2, %4, 64;\nadd.u32 d2, %0, 8960;\n"
               "@p mbarrier.arrive.expect_tx.shared::cta.b64 _, [%2], 17920;\n"
               "@p cp.async.bulk.tensor.3d.shared::cluster.global.mbarrier::complete_tx::bytes [%0], [%1, {%3, %4, %5}], [%2];\n"
               "@p cp.async.bulk.tensor.3d.shared::cluster.global.mbarrier::complete_tx::bytes [d2], [%1, {%3, c2, %5}], [%2];\n}"
               ::"r"(sb + RBUF + s * SLOTB), "l"(tmx), "r"(sb + CM + s * 8), "r"(third * 32), "r"(st * 128 - 3), "r"(2 * J - 3) : "memory");
}
__device__ __forceinline__ void ring_bar_init(uint32_t bar, uint32_t cnt, bool ahead) {
  asm volatile("{\n.reg .pred p, q;\nelect.sync _|p, 0xffffffff;\n@p mbarrier.init.shared::cta.b64 [%0], %1;\n"
               "setp.ne.and.u32 q, %2, 0, p;\n@q mbarrier.arrive.shared::cta.b64 _, [%0], %1;\n@p fence.mbarrier_init.release.cluster;\n}" ::"r"(bar), "r"(cnt), "r"((uint32_t)ahead) : "memory");
}
__device__ __forceinline__ void conv_loader(uint32_t sb, Globals* gs, const CUtensorMap* tmx, int gm, int nit, int off, int cidx, int third, int k) {
  static_assert(AHEAD > 5 && AHEAD <= NSLOT && NCONV >= 24, "loader");
  const uint32_t full = sb + CM;
  asm volatile("bar.sync 0, 512;" ::: "memory");
  if (FIRST + k < AHEAD) load_step(sb, tmx, gm, third, FIRST + k, (FIRST + k + off) & 7);
#pragma unroll 1
  for (int it = AHEAD + k; it < nit + AHEAD; it += 4) {
    const int u = it + off;
    const uint32_t ro = lds32(sb + CTAB + (it - AHEAD) * 16 + 8);
    mbar_wait(full + 64 + ((u - AHEAD) & 7) * 8, ((u - AHEAD) >> 3) & 1);
    red_add_elect((uint32_t*)((char*)gs + ro));
    PROF_AT((threadIdx.x & 31) == 0 && (((it - AHEAD) & (PROF > 1 ? 7 : 15)) == 0 || it - AHEAD < 6), 200 + it - AHEAD);
    if (it < nit) load_step(sb, tmx, gm, third, it, u & 7);
    else if (it == nit) mbar_arrive_elect(full);
    if (it >= nit - 16) {
      if (it < nit - 12) {
        wait_ready(gs->wflag, 12 * lds32(sb + MISC + 256));
        asm volatile("fence.acquire.gpu;\nfence.proxy.async.global;" ::: "memory");
        if (cidx < 24) asm volatile("{.reg .pred p; elect.sync _|p, 0xffffffff; @p cp.async.bulk.prefetch.L2.global [%0], 1536;}" ::"l"(gs->wimg + (cidx * 4 + k) * 1536) : "memory");
      }
      const int m = it == nit - 1 ? 0 : W2S;
      if (it == nit - 1 || it == nit + AHEAD - 5)
        asm volatile("{\n.reg .pred p;\nelect.sync _|p, 0xffffffff;\n@p mbarrier.arrive.expect_tx.shared::cta.b64 _, [%1], 73728;\n"
                     "@p cp.async.bulk.shared::cluster.global.mbarrier::complete_tx::bytes [%0], [%2], 73728, [%1];\n}"
                     ::"r"(sb + m), "r"(sb + WBAR), "l"(gs->wimg + m) : "memory");
    }
  }
}

__device__ __forceinline__ void conv_credit(uint32_t sb, Globals* gs, int P0, int nit, int off, uint32_t ctarget, int k) {
  const uint32_t full = sb + CM;
#pragma unroll 1
  for (int it = k + NSLOT; it <= nit; it += 4) {
    const int u = it + off, P = (int)lds32(sb + CTAB + it * 16 + 12) - RING;
    int spins = 0;
    mbar_wait(full + 64 + (u & 7) * 8, ((u >> 3) & 1) ^ 1);
    if (P >= P0) while (ld_relaxed(&gs->cons[P]) != ctarget) { __nanosleep(CSLEEP); if (++spins > SPIN_LIMIT) __trap(); }
    mbar_arrive_elect(full + (u & 7) * 8);
  }
}

__global__ void __launch_bounds__(512, 1) convnext_kernel(const __grid_constant__ CUtensorMap tmx, const __grid_constant__ CUtensorMap tmr, const __nv_bfloat16* __restrict__ dw,
                                                          const __nv_bfloat16* __restrict__ w1, const __nv_bfloat16* __restrict__ w2, __nv_bfloat16* __restrict__ out, Globals* gs) {
  extern __shared__ __align__(1024) unsigned char smem[];
  const uint32_t sb = smem_u32(smem);
  const int warp = __shfl_sync(0xffffffffu, threadIdx.x >> 5, 0), lane = threadIdx.x & 31;
  PROF_AT(threadIdx.x == 0, 0);
  if (PFX && threadIdx.x == 320) asm volatile("prefetch.tensormap [%0];" ::"l"(&tmx) : "memory");
  if (threadIdx.x == 288) asm volatile("prefetch.tensormap [%0];" ::"l"(&tmr) : "memory");
  uint32_t smid, nsmid;
  asm volatile("mov.u32 %0, %%smid;" : "=r"(smid));
  asm volatile("mov.u32 %0, %%nsmid;" : "=r"(nsmid));
  const bool tabled = TABLED && gridDim.x == 132 && nsmid == 132;
  const int id = tabled ? smid : blockIdx.x;
  int cidx, idx;
  int is_conv;
  if (tabled) {
    idx = smid;
    const int k = (smid - 60) / 14, r = smid - 60 - 14 * k;
    is_conv = smid < 48 ? !(smid & 1) : (smid >= 60 && smid <= 90 && (r & ~2) == 0);
    cidx = smid < 48 ? ((smid >> 1) & 7) * 3 + (smid >> 4) : 24 + (r >> 1) * 3 + k;
  } else {
    cidx = (blockIdx.x * NCONV) / gridDim.x;
    is_conv = ((blockIdx.x + 1) * NCONV) / gridDim.x != cidx;
    idx = blockIdx.x - cidx;
  }
  PROF_VAL(threadIdx.x == 0, 2, is_conv ? 1000 + cidx : idx);
  const int gm = cidx / 3, third = cidx - gm * 3;
  const int P0 = gm * PLEN, nit = gm < 8 ? PLEN + 2 : NSEG * (LM + 3), off = (8 - nit) & 7;
  if (is_conv && warp == 8) {
    asm volatile("{\n.reg .pred p;\nelect.sync _|p, 0xffffffff;\n@p mbarrier.init.shared::cta.b64 [%1], 1;\n@p fence.mbarrier_init.release.cluster;\n"
                 "@p mbarrier.arrive.expect_tx.shared::cta.b64 _, [%1], 9408;\n"
                 "@p cp.async.bulk.shared::cluster.global.mbarrier::complete_tx::bytes [%0], [%2], 9408, [%1];\nbar.arrive 5, 288;\n}"
                 ::"r"(sb), "r"(sb + WBAR + 8), "l"(dw) : "memory");
#pragma unroll 1
    for (int it = 0; it < NSLOT; it++) {
      const int s = (it + off) & 7;
      ring_bar_init(sb + CM + s * 8, 2, s < off);
      PROF_AT(it == 0 && (threadIdx.x & 31) == 0, 15);
      if (it < FIRST) load_step(sb, &tmx, gm, third, it, s);
    }
  }
  mbar_init_elect(sb + MISC + warp * 8, 1); mbar_init_elect(sb + MISC + 128 + warp * 8, 1);
  asm volatile("fence.mbarrier_init.release.cluster;" ::: "memory");
  if (is_conv) {
    if (warp >= 8) ring_bar_init(sb + CM + warp * 8, 8, warp - 8 < off);
    if (warp == 9) mbar_init_elect(sb + WBAR, 2);
    if (warp < 8) {
      conv_compute(sb, gs, third, nit, off, gm < 8 && (gm & 1), warp, lane);
      asm volatile("setmaxnreg.dec.sync.aligned.u32 128;");
    } else if (warp >= 12) {
      asm volatile("setmaxnreg.dec.sync.aligned.u32 24;");
      const uint32_t epoch = ld_relaxed(&gs->epoch[id]);
#pragma unroll 1
      for (int it = threadIdx.x - 384; it <= nit; it += 128) {
        const int seg = it / (LM + 3), j = gm < 8 ? it - 2 : it - 3 * (seg + 1);
        const bool ok = it < nit && j >= (gm < 8 ? 0 : seg * LM);
        sts128(sb + CTAB + it * 16, make_uint4((ok ? (j % RING) * NG + gm : -1) * (4 * TILEB), slot_tag(gm, max(j, 0), epoch),
                                               offsetof(Globals, ready) + (ok ? P0 + j : NG * PLEN) * 4, ok ? P0 + j : -1));
      }
      asm volatile("bar.sync 0, 512;" ::: "memory");
      mbar_arrive_elect(sb + CM + ((((warp + 2) & 3) + off) & 7) * 8);
      mbar_arrive_elect(sb + CM + ((((warp + 2) & 3) + off + 4) & 7) * 8);
      build_tile_list(sb, threadIdx.x - 384, idx, tabled, true, epoch);
      if (threadIdx.x == 384) gs->epoch[id] = epoch + 1;
      conv_credit(sb, gs, P0, nit, off, 16 * (epoch + 1), (warp + 2) & 3);
#pragma unroll 1
      for (int i = 0; i < 4; i++) {
        const uint2 e = lds64(sb + MISC + 512 + i * 16);
        mbar_wait(sb + CM + 64 + (4 + min(i, 2)) * 8, (((nit + off) >> 3) & 1) ^ 1);
        const int wi = 4 * i + (warp & 3);
        if ((int)e.x >= 0) fetch_a(sb + ABUF + wi * 3072, sb + MISC + wi * 8, gs->scratch + (e.y & ~1u) + (warp & 3) * 3072);
      }
      mbar_wait(sb + CM + 64 + 7 * 8, (((nit + off) >> 3) & 1) ^ 1);
      asm volatile("setmaxnreg.inc.sync.aligned.u32 128;");
    } else {
      asm volatile("setmaxnreg.dec.sync.aligned.u32 %0;" ::"n"(488 - 2 * CREGS));
      conv_loader(sb, gs, &tmx, gm, nit, off, cidx, third, warp & 3);
      mbar_wait(sb + CM + 64 + 4 * 8, (((nit + off) >> 3) & 1) ^ 1);
      mbar_wait(sb + CM + 64 + 7 * 8, (((nit + off) >> 3) & 1) ^ 1);
      asm volatile("setmaxnreg.inc.sync.aligned.u32 128;");
    }
    PROF2_AT((threadIdx.x & 31) == 0, 400 + (threadIdx.x >> 5));
    mbar_wait(sb + WBAR, 0);
    asm volatile("bar.sync 0, 512;" ::: "memory");
  } else {
    mlp_setup(sb, gs, id, w1, w2, idx, tabled, warp, lane);
  }
  mlp_role(sb, gs, &tmr, out);
}

typedef CUresult (*PFN_encodeTiled)(CUtensorMap*, CUtensorMapDataType, cuuint32_t, void*, const cuuint64_t*, const cuuint64_t*, const cuuint32_t*, const cuuint32_t*,
                                    CUtensorMapInterleave, CUtensorMapSwizzle, CUtensorMapL2promotion, CUtensorMapFloatOOBfill);

extern "C" void kernel_launch(void* const* d_in, const int* in_sizes, int n_in, void* d_out, int out_size) {
  const __nv_bfloat16* x = (const __nv_bfloat16*)d_in[0];
  const __nv_bfloat16* dw = (const __nv_bfloat16*)d_in[1];
  const __nv_bfloat16* w1 = (const __nv_bfloat16*)d_in[2];
  const __nv_bfloat16* w2 = (const __nv_bfloat16*)d_in[3];
  static PFN_encodeTiled encode = nullptr;
  static int nsm = 0;
  static Globals* gs = nullptr;
  if (!encode) {
    void* fn = nullptr; cudaDriverEntryPointQueryResult qr;
    cudaGetDriverEntryPoint("cuTensorMapEncodeTiled", &fn, cudaEnableDefault, &qr);
    encode = (PFN_encodeTiled)fn;
    cudaGetSymbolAddress((void**)&gs, g_state);
    int dev = 0; cudaGetDevice(&dev);
    cudaDeviceGetAttribute(&nsm, cudaDevAttrMultiProcessorCount, dev);
    cudaFuncSetAttribute(convnext_kernel, cudaFuncAttributeMaxDynamicSharedMemorySize, SMEM_BYTES);
  }
  CUtensorMap tm;
  cuuint64_t dims[3] = {96, 512, 512}, strides[2] = {192, 192 * 512};
  cuuint32_t box[3] = {32, 70, 2}, es[3] = {1, 1, 1};
  encode(&tm, CU_TENSOR_MAP_DATA_TYPE_BFLOAT16, 3, (void*)x, dims, strides, box, es, CU_TENSOR_MAP_INTERLEAVE_NONE, CU_TENSOR_MAP_SWIZZLE_64B,
         PROMO, CU_TENSOR_MAP_FLOAT_OOB_FILL_NONE);
  CUtensorMap tr;
  cuuint64_t dims2[3] = {1536, 32, 512}, strides2[2] = {3072, 192 * 512};
  cuuint32_t box2[3] = {192, 4, 2};
  encode(&tr, CU_TENSOR_MAP_DATA_TYPE_BFLOAT16, 3, (void*)x, dims2, strides2, box2, es, CU_TENSOR_MAP_INTERLEAVE_NONE, CU_TENSOR_MAP_SWIZZLE_NONE,
         CU_TENSOR_MAP_L2_PROMOTION_NONE, CU_TENSOR_MAP_FLOAT_OOB_FILL_NONE);
  convnext_kernel<<<nsm, 512, SMEM_BYTES>>>(tm, tr, dw, w1, w2, (__nv_bfloat16*)d_out, gs);
}
```

```cpp
#include <cuda_runtime.h>
#include <cuda_bf16.h>
#include <cuda.h>
#include <stdint.h>
#include <stddef.h>

template<int SCALE_D> __device__ __forceinline__ void wgmma_n32_f16(uint32_t* d, const uint32_t* a, uint64_t desc) {
  if (SCALE_D == 0) asm volatile("wgmma.mma_async.sync.aligned.m64n32k16.f16.f16.f16 {%0,%1,%2,%3,%4,%5,%6,%7}, {%8,%9,%10,%11}, %12, 0, 1, 1, 1;"
    : "=r"(d[0]),"=r"(d[1]),"=r"(d[2]),"=r"(d[3]),"=r"(d[4]),"=r"(d[5]),"=r"(d[6]),"=r"(d[7])
    : "r"(a[0]),"r"(a[1]),"r"(a[2]),"r"(a[3]),"l"(desc));
  if (SCALE_D == 1) asm volatile("wgmma.mma_async.sync.aligned.m64n32k16.f16.f16.f16 {%0,%1,%2,%3,%4,%5,%6,%7}, {%8,%9,%10,%11}, %12, 1, 1, 1, 1;"
    : "+r"(d[0]),"+r"(d[1]),"+r"(d[2]),"+r"(d[3]),"+r"(d[4]),"+r"(d[5]),"+r"(d[6]),"+r"(d[7])
    : "r"(a[0]),"r"(a[1]),"r"(a[2]),"r"(a[3]),"l"(desc));
}

template<int SCALE_D> __device__ __forceinline__ void wgmma_n48_f16(uint32_t* d, const uint32_t* a, uint64_t desc) {
  if (SCALE_D == 0) asm volatile("wgmma.mma_async.sync.aligned.m64n48k16.f16.f16.f16 {%0,%1,%2,%3,%4,%5,%6,%7,%8,%9,%10,%11}, {%12,%13,%14,%15}, %16, 0, 1, 1, 1;"
    : "=r"(d[0]),"=r"(d[1]),"=r"(d[2]),"=r"(d[3]),"=r"(d[4]),"=r"(d[5]),"=r"(d[6]),"=r"(d[7]),"=r"(d[8]),"=r"(d[9]),"=r"(d[10]),"=r"(d[11])
    : "r"(a[0]),"r"(a[1]),"r"(a[2]),"r"(a[3]),"l"(desc));
  if (SCALE_D == 1) asm volatile("wgmma.mma_async.sync.aligned.m64n48k16.f16.f16.f16 {%0,%1,%2,%3,%4,%5,%6,%7,%8,%9,%10,%11}, {%12,%13,%14,%15}, %16, 1, 1, 1, 1;"
    : "+r"(d[0]),"+r"(d[1]),"+r"(d[2]),"+r"(d[3]),"+r"(d[4]),"+r"(d[5]),"+r"(d[6]),"+r"(d[7]),"+r"(d[8]),"+r"(d[9]),"+r"(d[10]),"+r"(d[11])
    : "r"(a[0]),"r"(a[1]),"r"(a[2]),"r"(a[3]),"l"(desc));
}

template<int SCALE_D> __device__ __forceinline__ void wgmma_n64_f16(uint32_t* d, const uint32_t* a, uint64_t desc) {
  if (SCALE_D == 0) asm volatile("wgmma.mma_async.sync.aligned.m64n64k16.f16.f16.f16 {%0,%1,%2,%3,%4,%5,%6,%7,%8,%9,%10,%11,%12,%13,%14,%15}, {%16,%17,%18,%19}, %20, 0, 1, 1, 1;"
    : "=r"(d[0]),"=r"(d[1]),"=r"(d[2]),"=r"(d[3]),"=r"(d[4]),"=r"(d[5]),"=r"(d[6]),"=r"(d[7]),"=r"(d[8]),"=r"(d[9]),"=r"(d[10]),"=r"(d[11]),"=r"(d[12]),"=r"(d[13]),"=r"(d[14]),"=r"(d[15])
    : "r"(a[0]),"r"(a[1]),"r"(a[2]),"r"(a[3]),"l"(desc));
  if (SCALE_D == 1) asm volatile("wgmma.mma_async.sync.aligned.m64n64k16.f16.f16.f16 {%0,%1,%2,%3,%4,%5,%6,%7,%8,%9,%10,%11,%12,%13,%14,%15}, {%16,%17,%18,%19}, %20, 1, 1, 1, 1;"
    : "+r"(d[0]),"+r"(d[1]),"+r"(d[2]),"+r"(d[3]),"+r"(d[4]),"+r"(d[5]),"+r"(d[6]),"+r"(d[7]),"+r"(d[8]),"+r"(d[9]),"+r"(d[10]),"+r"(d[11]),"+r"(d[12]),"+r"(d[13]),"+r"(d[14]),"+r"(d[15])
    : "r"(a[0]),"r"(a[1]),"r"(a[2]),"r"(a[3]),"l"(desc));
}

template<int SCALE_D> __device__ __forceinline__ void wgmma_n96_f16(uint32_t* d, const uint32_t* a, uint64_t desc) {
  if (SCALE_D == 0) asm volatile("wgmma.mma_async.sync.aligned.m64n96k16.f16.f16.f16 {%0,%1,%2,%3,%4,%5,%6,%7,%8,%9,%10,%11,%12,%13,%14,%15,%16,%17,%18,%19,%20,%21,%22,%23}, {%24,%25,%26,%27}, %28, 0, 1, 1, 1;"
    : "=r"(d[0]),"=r"(d[1]),"=r"(d[2]),"=r"(d[3]),"=r"(d[4]),"=r"(d[5]),"=r"(d[6]),"=r"(d[7]),"=r"(d[8]),"=r"(d[9]),"=r"(d[10]),"=r"(d[11]),"=r"(d[12]),"=r"(d[13]),"=r"(d[14]),"=r"(d[15]),"=r"(d[16]),"=r"(d[17]),"=r"(d[18]),"=r"(d[19]),"=r"(d[20]),"=r"(d[21]),"=r"(d[22]),"=r"(d[23])
    : "r"(a[0]),"r"(a[1]),"r"(a[2]),"r"(a[3]),"l"(desc));
  if (SCALE_D == 1) asm volatile("wgmma.mma_async.sync.aligned.m64n96k16.f16.f16.f16 {%0,%1,%2,%3,%4,%5,%6,%7,%8,%9,%10,%11,%12,%13,%14,%15,%16,%17,%18,%19,%20,%21,%22,%23}, {%24,%25,%26,%27}, %28, 1, 1, 1, 1;"
    : "+r"(d[0]),"+r"(d[1]),"+r"(d[2]),"+r"(d[3]),"+r"(d[4]),"+r"(d[5]),"+r"(d[6]),"+r"(d[7]),"+r"(d[8]),"+r"(d[9]),"+r"(d[10]),"+r"(d[11]),"+r"(d[12]),"+r"(d[13]),"+r"(d[14]),"+r"(d[15]),"+r"(d[16]),"+r"(d[17]),"+r"(d[18]),"+r"(d[19]),"+r"(d[20]),"+r"(d[21]),"+r"(d[22]),"+r"(d[23])
    : "r"(a[0]),"r"(a[1]),"r"(a[2]),"r"(a[3]),"l"(desc));
}

#define SCHED_NG 10
#define SCHED_LE 104
#define SCHED_RING 16
__device__ const uint16_t g_sched[132][48] = {
{380,383,386,389,65535,65535,65535,65535,65535,65535,65535,65535,65535,65535,65535,65535,65535,65535,65535,65535,65535,65535,65535,65535,65535,65535,65535,65535,65535,65535,65535,65535,65535,65535,65535,65535,65535,65535,65535,65535,65535,65535,65535,65535,65535,65535,65535,65535},
{0,2507,22,2943,2953,2963,3801,73,83,93,3014,3852,124,134,144,3065,3903,175,185,195,206,3129,3139,3149,3975,259,269,279,3200,4026,310,320,330,3251,4077,361,371,2889,404,65535,65535,65535,65535,65535,65535,65535,65535,65535},
{796,799,802,805,65535,65535,65535,65535,65535,65535,65535,65535,65535,65535,65535,65535,65535,65535,65535,65535,65535,65535,65535,65535,65535,65535,65535,65535,65535,65535,65535,65535,65535,65535,65535,65535,65535,65535,65535,65535,65535,65535,65535,65535,65535,65535,65535,65535},
{416,426,436,446,456,467,477,487,497,507,518,528,538,548,558,569,579,589,599,609,622,632,642,653,663,673,683,693,704,714,724,734,744,755,765,775,787,808,819,65535,65535,65535,65535,65535,65535,65535,65535,65535},
{1212,1215,1218,1221,65535,65535,65535,65535,65535,65535,65535,65535,65535,65535,65535,65535,65535,65535,65535,65535,65535,65535,65535,65535,65535,65535,65535,65535,65535,65535,65535,65535,65535,65535,65535,65535,65535,65535,65535,65535,65535,65535,65535,65535,65535,65535,65535,65535},
{832,842,853,863,873,884,894,904,914,925,935,945,955,965,976,986,996,1006,1016,1027,1038,1049,1059,1070,1080,1090,1100,1111,1121,1131,1141,1151,1162,1172,1182,1192,1203,1225,1235,65535,65535,65535,65535,65535,65535,65535,65535,65535},
{1628,1631,1634,1637,65535,65535,65535,65535,65535,65535,65535,65535,65535,65535,65535,65535,65535,65535,65535,65535,65535,65535,65535,65535,65535,65535,65535,65535,65535,65535,65535,65535,65535,65535,65535,65535,65535,65535,65535,65535,65535,65535,65535,65535,65535,65535,65535,65535},
{1248,1259,1269,1279,1290,1300,1310,1320,1330,1341,1351,1361,1371,1381,1392,1402,1412,1422,1432,1443,1454,1465,1476,1486,1496,1506,1516,1527,1537,1547,1557,1567,1578,1588,1598,1608,1619,1641,1651,65535,65535,65535,65535,65535,65535,65535,65535,65535},
{2044,2047,2050,2053,65535,65535,65535,65535,65535,65535,65535,65535,65535,65535,65535,65535,65535,65535,65535,65535,65535,65535,65535,65535,65535,65535,65535,65535,65535,65535,65535,65535,65535,65535,65535,65535,65535,65535,65535,65535,65535,65535,65535,65535,65535,65535,65535,65535},
{1664,1675,1685,1696,1706,1716,1726,1736,1747,1757,1767,1777,1787,1798,1808,1818,1828,1838,1849,1859,1870,1881,1892,1902,1912,1922,1933,1943,1953,1963,1973,1984,1994,2004,2014,2024,2035,2057,2068,65535,65535,65535,65535,65535,65535,65535,65535,65535},
{2460,2463,2466,2469,65535,65535,65535,65535,65535,65535,65535,65535,65535,65535,65535,65535,65535,65535,65535,65535,65535,65535,65535,65535,65535,65535,65535,65535,65535,65535,65535,65535,65535,65535,65535,65535,65535,65535,65535,65535,65535,65535,65535,65535,65535,65535,65535,65535},
{2080,2091,2101,2112,2122,2132,2142,2152,2163,2173,2183,2193,2203,2214,2224,2234,2244,2254,2265,2275,2287,2298,2308,2318,2328,2338,2349,2359,2369,2379,2389,2400,2410,2420,2430,2440,2452,2473,2484,65535,65535,65535,65535,65535,65535,65535,65535,65535},
{2876,2879,2882,2885,65535,65535,65535,65535,65535,65535,65535,65535,65535,65535,65535,65535,65535,65535,65535,65535,65535,65535,65535,65535,65535,65535,65535,65535,65535,65535,65535,65535,65535,65535,65535,65535,65535,65535,65535,65535,65535,65535,65535,65535,65535,65535,65535,65535},
{2496,3335,3345,3355,3365,3375,2558,3396,3406,3416,3426,2609,3447,3457,3467,3477,2660,3498,3508,3518,3520,3529,3539,3549,2744,3570,3580,3590,3600,2795,3621,3631,3641,3651,2846,3672,2870,3705,2902,65535,65535,65535,65535,65535,65535,65535,65535,65535},
{3292,3295,3298,3301,65535,65535,65535,65535,65535,65535,65535,65535,65535,65535,65535,65535,65535,65535,65535,65535,65535,65535,65535,65535,65535,65535,65535,65535,65535,65535,65535,65535,65535,65535,65535,65535,65535,65535,65535,65535,65535,65535,65535,65535,65535,65535,65535,65535},
{2912,2923,2933,3771,3781,3791,2974,2984,2994,3004,3842,3025,3035,3045,3055,3893,3076,3086,3096,3106,3936,3945,3955,3965,3160,3170,3180,3190,4016,3211,3221,3231,3241,4067,3262,3272,3286,3305,3318,65535,65535,65535,65535,65535,65535,65535,65535,65535},
{381,384,387,390,65535,65535,65535,65535,65535,65535,65535,65535,65535,65535,65535,65535,65535,65535,65535,65535,65535,65535,65535,65535,65535,65535,65535,65535,65535,65535,65535,65535,65535,65535,65535,65535,65535,65535,65535,65535,65535,65535,65535,65535,65535,65535,65535,65535},
{1,3751,3761,33,43,53,63,3812,3822,3832,104,114,3863,3873,3883,155,165,3914,3924,3934,207,219,229,239,249,3986,3996,4006,290,300,4037,4047,4057,341,351,4088,372,4121,405,65535,65535,65535,65535,65535,65535,65535,65535,65535},
{797,800,803,806,65535,65535,65535,65535,65535,65535,65535,65535,65535,65535,65535,65535,65535,65535,65535,65535,65535,65535,65535,65535,65535,65535,65535,65535,65535,65535,65535,65535,65535,65535,65535,65535,65535,65535,65535,65535,65535,65535,65535,65535,65535,65535,65535,65535},
{417,427,437,447,457,468,478,488,498,508,519,529,539,549,559,570,580,590,600,610,623,633,643,654,664,674,684,694,705,715,725,735,745,756,766,776,788,809,820,65535,65535,65535,65535,65535,65535,65535,65535,65535},
{1213,1216,1219,1222,65535,65535,65535,65535,65535,65535,65535,65535,65535,65535,65535,65535,65535,65535,65535,65535,65535,65535,65535,65535,65535,65535,65535,65535,65535,65535,65535,65535,65535,65535,65535,65535,65535,65535,65535,65535,65535,65535,65535,65535,65535,65535,65535,65535},
{833,843,854,864,874,885,895,905,915,926,936,946,956,966,977,987,997,1007,1017,1028,1039,1050,1060,1071,1081,1091,1101,1112,1122,1132,1142,1152,1163,1173,1183,1193,1204,1226,1236,65535,65535,65535,65535,65535,65535,65535,65535,65535},
{1629,1632,1635,1638,65535,65535,65535,65535,65535,65535,65535,65535,65535,65535,65535,65535,65535,65535,65535,65535,65535,65535,65535,65535,65535,65535,65535,65535,65535,65535,65535,65535,65535,65535,65535,65535,65535,65535,65535,65535,65535,65535,65535,65535,65535,65535,65535,65535},
{1249,1260,1270,1280,1291,1301,1311,1321,1331,1342,1352,1362,1372,1382,1393,1403,1413,1423,1433,1444,1455,1466,1477,1487,1497,1507,1517,1528,1538,1548,1558,1568,1579,1589,1599,1609,1620,1642,1652,65535,65535,65535,65535,65535,65535,65535,65535,65535},
{2045,2048,2051,2054,65535,65535,65535,65535,65535,65535,65535,65535,65535,65535,65535,65535,65535,65535,65535,65535,65535,65535,65535,65535,65535,65535,65535,65535,65535,65535,65535,65535,65535,65535,65535,65535,65535,65535,65535,65535,65535,65535,65535,65535,65535,65535,65535,65535},
{1665,1676,1686,1697,1707,1717,1727,1737,1748,1758,1768,1778,1788,1799,1809,1819,1829,1839,1850,1860,1871,1882,1893,1903,1913,1923,1934,1944,1954,1964,1974,1985,1995,2005,2015,2025,2036,2058,2069,65535,65535,65535,65535,65535,65535,65535,65535,65535},
{2461,2464,2467,2470,65535,65535,65535,65535,65535,65535,65535,65535,65535,65535,65535,65535,65535,65535,65535,65535,65535,65535,65535,65535,65535,65535,65535,65535,65535,65535,65535,65535,65535,65535,65535,65535,65535,65535,65535,65535,65535,65535,65535,65535,65535,65535,65535,65535},
{2081,2092,2102,2113,2123,2133,2143,2153,2164,2174,2184,2194,2204,2215,2225,2235,2245,2255,2266,2276,2288,2299,2309,2319,2329,2339,2350,2360,2370,2380,2390,2401,2411,2421,2431,2441,2453,2474,2485,65535,65535,65535,65535,65535,65535,65535,65535,65535},
{2877,2880,2883,2886,65535,65535,65535,65535,65535,65535,65535,65535,65535,65535,65535,65535,65535,65535,65535,65535,65535,65535,65535,65535,65535,65535,65535,65535,65535,65535,65535,65535,65535,65535,65535,65535,65535,65535,65535,65535,65535,65535,65535,65535,65535,65535,65535,65535},
{2497,2508,2518,2528,3366,3376,2559,2569,2579,2589,3427,2610,2620,2630,2640,3478,2661,2671,2681,2691,2705,3530,3540,3550,2745,2755,2765,2775,3601,2796,2806,2816,2826,3652,2847,2857,2871,2890,2903,65535,65535,65535,65535,65535,65535,65535,65535,65535},
{3293,3296,3299,3302,65535,65535,65535,65535,65535,65535,65535,65535,65535,65535,65535,65535,65535,65535,65535,65535,65535,65535,65535,65535,65535,65535,65535,65535,65535,65535,65535,65535,65535,65535,65535,65535,65535,65535,65535,65535,65535,65535,65535,65535,65535,65535,65535,65535},
{2913,2924,2934,2944,2954,2964,3802,2985,2995,3005,3015,3853,3036,3046,3056,3066,3904,3087,3097,3107,3121,3130,3140,3150,3976,3171,3181,3191,3201,4027,3222,3232,3242,3252,4078,3273,3287,3306,3319,65535,65535,65535,65535,65535,65535,65535,65535,65535},
{382,385,388,391,65535,65535,65535,65535,65535,65535,65535,65535,65535,65535,65535,65535,65535,65535,65535,65535,65535,65535,65535,65535,65535,65535,65535,65535,65535,65535,65535,65535,65535,65535,65535,65535,65535,65535,65535,65535,65535,65535,65535,65535,65535,65535,65535,65535},
{2,13,23,3356,3782,3792,64,3397,3407,3417,3843,115,3448,3458,3468,3894,166,3499,3509,3519,209,3946,3956,3966,250,3571,3581,3591,4017,301,3622,3632,3642,4068,352,3673,374,3706,407,65535,65535,65535,65535,65535,65535,65535,65535,65535},
{798,801,804,807,65535,65535,65535,65535,65535,65535,65535,65535,65535,65535,65535,65535,65535,65535,65535,65535,65535,65535,65535,65535,65535,65535,65535,65535,65535,65535,65535,65535,65535,65535,65535,65535,65535,65535,65535,65535,65535,65535,65535,65535,65535,65535,65535,65535},
{418,428,438,448,458,469,479,489,499,509,520,530,540,550,560,571,581,591,601,611,624,634,644,655,665,675,685,695,706,716,726,736,746,757,767,777,789,810,821,65535,65535,65535,65535,65535,65535,65535,65535,65535},
{1214,1217,1220,1223,65535,65535,65535,65535,65535,65535,65535,65535,65535,65535,65535,65535,65535,65535,65535,65535,65535,65535,65535,65535,65535,65535,65535,65535,65535,65535,65535,65535,65535,65535,65535,65535,65535,65535,65535,65535,65535,65535,65535,65535,65535,65535,65535,65535},
{834,844,855,865,875,886,896,906,916,3833,937,947,957,967,3884,988,998,1008,1018,3935,1040,1051,1061,1072,1082,1092,1102,4007,1123,1133,1143,1153,4058,1174,1184,1194,1205,1227,1237,65535,65535,65535,65535,65535,65535,65535,65535,65535},
{1630,1633,1636,1639,65535,65535,65535,65535,65535,65535,65535,65535,65535,65535,65535,65535,65535,65535,65535,65535,65535,65535,65535,65535,65535,65535,65535,65535,65535,65535,65535,65535,65535,65535,65535,65535,65535,65535,65535,65535,65535,65535,65535,65535,65535,65535,65535,65535},
{1250,1261,1271,1281,1292,1302,1312,1322,1332,1343,1353,1363,1373,1383,1394,1404,1414,1424,1434,1445,1456,1467,1478,1488,1498,1508,1518,1529,1539,1549,1559,1569,1580,1590,1600,1610,1621,1643,1653,65535,65535,65535,65535,65535,65535,65535,65535,65535},
{2046,2049,2052,2055,65535,65535,65535,65535,65535,65535,65535,65535,65535,65535,65535,65535,65535,65535,65535,65535,65535,65535,65535,65535,65535,65535,65535,65535,65535,65535,65535,65535,65535,65535,65535,65535,65535,65535,65535,65535,65535,65535,65535,65535,65535,65535,65535,65535},
{1666,1677,1687,3772,1708,1718,1728,1738,1749,1759,1769,1779,1789,1800,1810,1820,1830,1840,1851,1861,1872,1883,1894,1904,1914,1924,1935,1945,1955,1965,1975,1986,1996,2006,2016,2026,2037,2059,2070,65535,65535,65535,65535,65535,65535,65535,65535,65535},
{2462,2465,2468,2471,65535,65535,65535,65535,65535,65535,65535,65535,65535,65535,65535,65535,65535,65535,65535,65535,65535,65535,65535,65535,65535,65535,65535,65535,65535,65535,65535,65535,65535,65535,65535,65535,65535,65535,65535,65535,65535,65535,65535,65535,65535,65535,65535,65535},
{2082,2093,2103,2114,2124,2134,2144,2154,2165,2175,2185,2195,2205,2216,2226,2236,2246,2256,2267,2277,2289,2300,2310,2320,2330,2340,2351,2361,2371,2381,2391,2402,2412,2422,2432,2442,2454,2475,2486,65535,65535,65535,65535,65535,65535,65535,65535,65535},
{2878,2881,2884,2887,65535,65535,65535,65535,65535,65535,65535,65535,65535,65535,65535,65535,65535,65535,65535,65535,65535,65535,65535,65535,65535,65535,65535,65535,65535,65535,65535,65535,65535,65535,65535,65535,65535,65535,65535,65535,65535,65535,65535,65535,65535,65535,65535,65535},
{2498,3336,3346,2529,2539,2549,3387,2570,2580,2590,2600,3438,2621,2631,2641,2651,3489,2672,2682,2692,3521,2715,2725,2735,3561,2756,2766,2776,2786,3612,2807,2817,2827,2837,3663,2858,2872,2891,2904,65535,65535,65535,65535,65535,65535,65535,65535,65535},
{3294,3297,3300,3303,65535,65535,65535,65535,65535,65535,65535,65535,65535,65535,65535,65535,65535,65535,65535,65535,65535,65535,65535,65535,65535,65535,65535,65535,65535,65535,65535,65535,65535,65535,65535,65535,65535,65535,65535,65535,65535,65535,65535,65535,65535,65535,65535,65535},
{2914,3752,3762,2945,2955,2965,2975,3813,3823,3006,3016,3026,3864,3874,3057,3067,3077,3915,3925,3108,3937,3131,3141,3151,3161,3987,3997,3192,3202,3212,4038,4048,3243,3253,3263,4089,3288,4122,3320,65535,65535,65535,65535,65535,65535,65535,65535,65535},
{3,14,24,35,45,55,2976,3814,3824,96,106,3027,3865,3875,147,157,3078,3916,3926,198,211,221,231,241,3162,3988,3998,282,292,3213,4039,4049,333,343,3264,4090,376,4123,409,65535,65535,65535,65535,65535,65535,65535,65535,65535},
{4,3337,3763,34,44,54,65,75,85,95,105,116,126,136,146,156,167,177,187,197,210,220,230,240,251,261,271,281,291,302,312,322,332,342,353,363,375,396,408,65535,65535,65535,65535,65535,65535,65535,65535,65535},
{419,429,439,449,459,470,480,490,500,510,521,531,541,551,561,572,582,592,602,612,625,635,645,656,666,676,686,696,707,717,727,737,747,758,768,778,790,811,822,65535,65535,65535,65535,65535,65535,65535,65535,65535},
{420,430,440,450,460,471,481,491,501,511,522,532,542,552,562,573,583,593,603,613,626,636,646,657,667,677,687,697,708,718,728,738,748,759,769,779,791,812,823,65535,65535,65535,65535,65535,65535,65535,65535,65535},
{835,845,856,866,876,887,897,907,917,927,938,948,958,968,978,989,999,1009,1019,1029,1041,1052,1062,1073,1083,1093,1103,1113,1124,1134,1144,1154,1164,1175,1185,1195,1206,1228,1238,65535,65535,65535,65535,65535,65535,65535,65535,65535},
{836,846,857,867,877,2550,3388,908,918,928,2601,3439,959,969,979,2652,3490,1010,1020,1030,1042,1053,1063,2736,3562,1094,1104,1114,2787,3613,1145,1155,1165,2838,3664,1196,1207,1229,1239,65535,65535,65535,65535,65535,65535,65535,65535,65535},
{1251,1262,1272,1282,1293,1303,1313,1323,1333,1344,1354,1364,1374,1384,1395,1405,1415,1425,1435,1446,1457,1468,1479,1489,1499,1509,1519,1530,1540,1550,1560,1570,1581,1591,1601,1611,1622,1644,1654,65535,65535,65535,65535,65535,65535,65535,65535,65535},
{1252,3753,1273,1283,2540,2966,3804,1324,1334,2591,3017,3855,1375,1385,2642,3068,3906,1426,1436,1447,1458,1469,2726,3152,3978,1510,1520,2777,3203,4029,1561,1571,2828,3254,4080,1612,1623,1645,1655,65535,65535,65535,65535,65535,65535,65535,65535,65535},
{1667,1678,1688,1698,1709,1719,1729,1739,1750,1760,1770,1780,1790,1801,1811,1821,1831,1841,1852,1862,1873,1884,1895,1905,1915,1925,1936,1946,1956,1966,1976,1987,1997,2007,2017,2027,2038,2060,2071,65535,65535,65535,65535,65535,65535,65535,65535,65535},
{1668,1679,1689,1699,2956,3378,1730,1740,2581,3007,3429,1781,1791,2632,3058,3480,1832,1842,2683,1863,1874,1885,3142,3552,1916,1926,2767,3193,3603,1967,1977,2818,3244,3654,2018,2028,2039,2061,2072,65535,65535,65535,65535,65535,65535,65535,65535,65535},
{2083,2094,2104,2115,2125,2135,2145,2155,2166,2176,2186,2196,2206,2217,2227,2237,2247,2257,2268,2278,2290,2301,2311,2321,2331,2341,2352,2362,2372,2382,2392,2403,2413,2423,2433,2443,2455,2476,2487,65535,65535,65535,65535,65535,65535,65535,65535,65535},
{2084,2095,2105,2530,3368,3794,2146,2156,2997,3419,3845,2197,2207,3048,3470,3896,2248,2258,3099,2279,2291,2716,3542,3968,2332,2342,3183,3593,4019,2383,2393,3234,3644,4070,2434,2444,2456,2477,2488,65535,65535,65535,65535,65535,65535,65535,65535,65535},
{3676,3679,3682,3685,3688,65535,65535,65535,65535,65535,65535,65535,65535,65535,65535,65535,65535,65535,65535,65535,65535,65535,65535,65535,65535,65535,65535,65535,65535,65535,65535,65535,65535,65535,65535,65535,65535,65535,65535,65535,65535,65535,65535,65535,65535,65535,65535,65535},
{2499,2509,2519,3357,3367,3377,2560,3398,3408,3418,3428,2611,3449,3459,3469,3479,2662,3500,3510,2693,2706,3531,3541,3551,2746,3572,3582,3592,3602,2797,3623,3633,3643,3653,2848,3674,2873,3707,2905,65535,65535,65535,65535,65535,65535,65535,65535,65535},
{4092,4095,4098,4101,4104,65535,65535,65535,65535,65535,65535,65535,65535,65535,65535,65535,65535,65535,65535,65535,65535,65535,65535,65535,65535,65535,65535,65535,65535,65535,65535,65535,65535,65535,65535,65535,65535,65535,65535,65535,65535,65535,65535,65535,65535,65535,65535,65535},
{2915,2925,2935,3773,3783,3793,3803,2986,2996,3834,3844,3854,3037,3047,3885,3895,3905,3088,3098,3109,3122,3947,3957,3967,3977,3172,3182,4008,4018,4028,3223,3233,4059,4069,4079,3274,3289,3307,3321,65535,65535,65535,65535,65535,65535,65535,65535,65535},
{421,431,441,451,461,472,482,492,502,512,523,533,543,553,563,574,584,594,604,614,627,637,647,658,668,678,688,698,709,719,729,739,749,760,770,780,792,813,824,65535,65535,65535,65535,65535,65535,65535,65535,65535},
{2500,2510,2520,2946,3784,2551,2561,2571,3409,3835,2602,2612,2622,3460,3886,2653,2663,2673,3511,615,3522,3132,3958,2737,2747,2757,3583,4009,2788,2798,2808,3634,4060,2839,2849,2859,793,2892,825,65535,65535,65535,65535,65535,65535,65535,65535,65535},
{837,847,2936,3358,878,888,898,2987,3825,929,939,949,3038,3876,980,990,1000,3089,3927,1031,1043,3532,1064,1074,1084,3173,3999,1115,1125,1135,3224,4050,1166,1176,1186,3275,1208,3308,1240,65535,65535,65535,65535,65535,65535,65535,65535,65535},
{2916,2926,3348,3774,2541,2967,2977,3399,919,2592,3018,3028,3450,970,2643,3069,3079,3501,1021,2694,3938,3948,2727,3153,3163,3573,1105,2778,3204,3214,3624,1156,2829,3255,3265,3675,1209,3708,1241,65535,65535,65535,65535,65535,65535,65535,65535,65535},
{1253,1263,3764,1284,3785,1305,1315,1325,3410,3836,1356,1366,1376,3461,3887,1407,1417,1427,3512,1448,1460,3533,3959,1491,1501,1511,3584,4010,1542,1552,1562,3635,4061,1593,1603,1613,1625,1646,1657,65535,65535,65535,65535,65535,65535,65535,65535,65535},
{3328,3338,1274,2531,1294,1304,1314,3815,1335,1345,1355,1365,3866,1386,1396,1406,1416,3917,1437,3110,1459,1470,1480,1490,1500,3989,1521,1531,1541,1551,4040,1572,1582,1592,1602,4091,1624,4124,1656,65535,65535,65535,65535,65535,65535,65535,65535,65535},
{1669,3754,1690,1700,1710,1720,1731,1741,1751,1761,1771,1782,1792,1802,1812,1822,1833,1843,1853,1864,1875,1886,1896,1906,1917,1927,1937,1947,1957,1968,1978,1988,1998,2008,2019,2029,2040,2062,2073,65535,65535,65535,65535,65535,65535,65535,65535,65535},
{3744,1680,3349,3775,1711,1721,2562,3400,3826,1762,1772,2613,3451,3877,1813,1823,2664,3502,3928,1865,1876,3949,1897,1907,2748,3574,4000,1948,1958,2799,3625,4051,1999,2009,2850,2030,2041,3709,2074,65535,65535,65535,65535,65535,65535,65535,65535,65535},
{2085,2096,3765,2117,2127,2137,2978,3816,2168,2178,2188,3029,3867,2219,2229,2239,3080,3918,2270,2281,3523,2303,2313,2323,3164,3990,2354,2364,2374,3215,4041,2405,2415,2425,3266,2446,2458,4125,2490,65535,65535,65535,65535,65535,65535,65535,65535,65535},
{2086,2511,2106,2116,2126,2136,2147,2157,2167,2177,2187,2198,2208,2218,2228,2238,2249,2259,2269,2280,2292,2302,2312,2322,2333,2343,2353,2363,2373,2384,2394,2404,2414,2424,2435,2445,2457,2478,2489,65535,65535,65535,65535,65535,65535,65535,65535,65535},
{3677,3680,3683,3686,3689,65535,65535,65535,65535,65535,65535,65535,65535,65535,65535,65535,65535,65535,65535,65535,65535,65535,65535,65535,65535,65535,65535,65535,65535,65535,65535,65535,65535,65535,65535,65535,65535,65535,65535,65535,65535,65535,65535,65535,65535,65535,65535,65535},
{2501,3339,2521,3359,3369,3379,3389,2572,2582,3420,3430,3440,2623,2633,3471,3481,3491,2674,2684,2695,2707,2717,3543,3553,3563,2758,2768,3594,3604,3614,2809,2819,3645,3655,3665,2860,2874,2893,2906,65535,65535,65535,65535,65535,65535,65535,65535,65535},
{4093,4096,4099,4102,4105,65535,65535,65535,65535,65535,65535,65535,65535,65535,65535,65535,65535,65535,65535,65535,65535,65535,65535,65535,65535,65535,65535,65535,65535,65535,65535,65535,65535,65535,65535,65535,65535,65535,65535,65535,65535,65535,65535,65535,65535,65535,65535,65535},
{2917,2927,2937,2947,2957,3795,3805,2988,2998,3008,3846,3856,3039,3049,3059,3897,3907,3090,3100,3111,3123,3133,3143,3969,3979,3174,3184,3194,4020,4030,3225,3235,3245,4071,4081,3276,3290,3309,3322,65535,65535,65535,65535,65535,65535,65535,65535,65535},
{422,432,443,453,463,2552,3390,494,504,514,2603,3441,545,555,565,2654,3492,596,606,617,3939,639,649,2738,3564,680,690,700,2789,3615,731,741,751,2840,3666,782,795,815,827,65535,65535,65535,65535,65535,65535,65535,65535,65535},
{3329,3755,442,452,462,473,483,493,503,513,524,534,544,554,564,575,585,595,605,616,628,638,648,659,669,679,689,699,710,720,730,740,750,761,771,781,794,814,826,65535,65535,65535,65535,65535,65535,65535,65535,65535},
{838,848,858,868,879,889,899,909,920,930,940,950,960,971,981,991,1001,1011,1022,1032,1044,1054,1065,1075,1085,1095,1106,1116,1126,1136,1146,1157,1167,1177,1187,1197,1210,1230,1242,65535,65535,65535,65535,65535,65535,65535,65535,65535},
{3745,849,859,869,2542,2968,3806,910,2583,2593,3019,3857,961,2634,2644,3070,3908,1012,2685,1033,1045,1055,2728,3154,3980,1096,2769,2779,3205,4031,1147,2820,2830,3256,4082,1198,1211,1231,1243,65535,65535,65535,65535,65535,65535,65535,65535,65535},
{1254,1264,1275,1285,1295,3380,1316,1326,1336,1346,3431,1367,1377,1387,1397,3482,1418,1428,1438,1449,1461,1471,1481,3554,1502,1512,1522,1532,3605,1553,1563,1573,1583,3656,1604,1614,1626,1647,1658,65535,65535,65535,65535,65535,65535,65535,65535,65535},
{1255,1265,2522,2532,2958,3796,2563,2573,2999,3009,3847,2614,2624,3050,3060,3898,2665,2675,3101,2696,2708,2718,3144,3970,2749,2759,3185,3195,4021,2800,2810,3236,3246,4072,2851,2861,1627,2894,1659,65535,65535,65535,65535,65535,65535,65535,65535,65535},
{1670,1681,1691,1701,3370,1722,1732,1742,1752,3421,1773,1783,1793,1803,3472,1824,1834,1844,1854,3112,1877,1887,3544,1908,1918,1928,1938,3595,1959,1969,1979,1989,3646,2010,2020,3277,2042,2063,2075,65535,65535,65535,65535,65535,65535,65535,65535,65535},
{1671,2512,2938,2948,3786,2553,2979,2989,3411,3837,2604,3030,3040,3462,3888,2655,3081,3091,3513,1866,3124,3134,3960,2739,3165,3175,3585,4011,2790,3216,3226,3636,4062,2841,3267,2031,2043,3310,2076,65535,65535,65535,65535,65535,65535,65535,65535,65535},
{2087,2097,2107,3360,2128,2139,2149,2159,2169,3422,2190,2200,2210,2220,3473,2241,2251,2261,2271,2283,2294,2304,3545,2325,2335,2345,2355,3596,2376,2386,2396,2406,3647,2427,2437,2448,3691,2480,2492,65535,65535,65535,65535,65535,65535,65535,65535,65535},
{2502,2928,3350,3776,2543,2138,2148,2158,3827,2179,2189,2199,2209,3878,2230,2240,2250,2260,3929,2282,2293,3534,2314,2324,2334,2344,4001,2365,2375,2385,2395,4052,2416,2426,2436,2447,2459,2479,2491,65535,65535,65535,65535,65535,65535,65535,65535,65535},
{3678,3681,3684,3687,3690,65535,65535,65535,65535,65535,65535,65535,65535,65535,65535,65535,65535,65535,65535,65535,65535,65535,65535,65535,65535,65535,65535,65535,65535,65535,65535,65535,65535,65535,65535,65535,65535,65535,65535,65535,65535,65535,65535,65535,65535,65535,65535,65535},
{3330,3340,2523,2533,3371,3381,3391,3401,2584,2594,3432,3442,3452,2635,2645,3483,3493,3503,2686,2697,3524,2719,2729,3555,3565,3575,2770,2780,3606,3616,3626,2821,2831,3657,3667,2862,2875,3710,2907,65535,65535,65535,65535,65535,65535,65535,65535,65535},
{4094,4097,4100,4103,4106,65535,65535,65535,65535,65535,65535,65535,65535,65535,65535,65535,65535,65535,65535,65535,65535,65535,65535,65535,65535,65535,65535,65535,65535,65535,65535,65535,65535,65535,65535,65535,65535,65535,65535,65535,65535,65535,65535,65535,65535,65535,65535,65535},
{2918,3756,3766,2949,2959,2969,3807,3817,3000,3010,3020,3858,3868,3051,3061,3071,3909,3919,3102,3113,3940,3950,3145,3155,3981,3991,3186,3196,3206,4032,4042,3237,3247,3257,4083,3278,3291,4126,3323,65535,65535,65535,65535,65535,65535,65535,65535,65535},
{423,433,444,3361,465,475,485,2574,3412,516,526,536,2625,3463,567,577,587,2676,3514,619,630,3535,651,661,671,2760,3586,702,712,722,2811,3637,753,763,773,784,3693,2895,829,65535,65535,65535,65535,65535,65535,65535,65535,65535},
{3746,434,2939,454,464,474,484,495,505,515,525,535,546,556,566,576,586,597,607,618,629,640,650,660,670,681,691,701,711,721,732,742,752,762,772,783,3692,816,828,65535,65535,65535,65535,65535,65535,65535,65535,65535},
{839,850,860,871,881,891,901,3402,922,932,942,952,3453,973,983,993,1003,3504,1024,1035,2709,3951,1067,1077,1087,3576,1108,1118,1128,1138,3627,1159,1169,1179,1189,1200,4109,3711,1245,65535,65535,65535,65535,65535,65535,65535,65535,65535},
{840,2513,3351,870,880,890,900,911,921,931,941,951,962,972,982,992,1002,1013,1023,1034,1046,1056,1066,1076,1086,1097,1107,1117,1127,1137,1148,1158,1168,1178,1188,1199,4108,1232,1244,65535,65535,65535,65535,65535,65535,65535,65535,65535},
{1256,3341,1277,1286,1296,1306,1317,1327,1337,1347,1357,1368,1378,1388,1398,1408,1419,1429,1439,1450,1462,1472,1482,1492,1503,1513,1523,1533,1543,1554,1564,1574,1584,1594,1605,1615,3694,1648,1660,65535,65535,65535,65535,65535,65535,65535,65535,65535},
{2503,1266,1276,1287,1297,1307,2564,3818,1338,1348,1358,2615,3869,1389,1399,1409,2666,3920,1440,1451,3525,1473,1483,1493,2750,3992,1524,1534,1544,2801,4043,1575,1585,1595,2852,1616,4110,4127,1661,65535,65535,65535,65535,65535,65535,65535,65535,65535},
{1672,3757,1693,1702,1712,1723,1733,1743,1753,1763,1774,1784,1794,1804,1814,1825,1835,1845,1855,1867,1878,1888,1898,1909,1919,1929,1939,1949,1960,1970,1980,1990,2000,2011,2021,2032,3695,2064,2077,65535,65535,65535,65535,65535,65535,65535,65535,65535},
{2919,1682,1692,1703,1713,2554,3392,1744,1754,1764,2605,3443,1795,1805,1815,2656,3494,1846,1856,2698,3941,1889,1899,2740,3566,1930,1940,1950,2791,3617,1981,1991,2001,2842,3668,2863,4111,2065,2908,65535,65535,65535,65535,65535,65535,65535,65535,65535},
{2088,2099,2109,2118,2129,2970,3808,2160,2170,2180,3021,3859,2211,2221,2231,3072,3910,2262,2272,2284,2295,2305,2315,3156,3982,2346,2356,2366,3207,4033,2397,2407,2417,3258,4084,2449,3696,2481,2493,65535,65535,65535,65535,65535,65535,65535,65535,65535},
{3331,2098,2108,2119,2544,3382,2150,2575,2585,2595,3433,2201,2626,2636,2646,3484,2252,2677,2687,2699,2710,2720,2730,3556,2336,2761,2771,2781,3607,2387,2812,2822,2832,3658,2438,2864,4112,2896,2494,65535,65535,65535,65535,65535,65535,65535,65535,65535},
{2504,2514,2524,2534,3372,2555,2565,3403,3413,3423,2606,2616,3454,3464,3474,2657,2667,3505,3515,2700,3526,3536,3546,2741,2751,3577,3587,3597,2792,2802,3628,3638,3648,2843,2853,2865,3697,2897,2909,65535,65535,65535,65535,65535,65535,65535,65535,65535},
{3332,3342,3352,3362,2545,3383,3393,2576,2586,2596,3434,3444,2627,2637,2647,3485,3495,2678,2688,3115,2711,2721,2731,3557,3567,2762,2772,2782,3608,3618,2813,2823,2833,3659,3669,3280,3698,3312,2910,65535,65535,65535,65535,65535,65535,65535,65535,65535},
{3747,2929,3767,3777,3787,3797,2980,2990,3828,3838,3848,3031,3041,3879,3889,3899,3082,3092,3930,3114,3125,3135,3961,3971,3166,3176,4002,4012,4022,3217,3227,4053,4063,4073,3268,3279,4107,3311,3324,65535,65535,65535,65535,65535,65535,65535,65535,65535},
{2920,2930,2940,2950,2960,3798,2981,2991,3001,3011,3849,3032,3042,3052,3062,3900,3083,3093,3103,3116,3126,3136,3146,3972,3167,3177,3187,3197,4023,3218,3228,3238,3248,4074,3269,3281,4113,3313,3325,65535,65535,65535,65535,65535,65535,65535,65535,65535},
{424,435,445,455,3788,476,486,496,506,3839,527,537,547,557,3890,578,588,598,608,620,631,641,3962,662,672,682,692,4013,713,723,733,743,4064,764,774,785,4114,817,830,65535,65535,65535,65535,65535,65535,65535,65535,65535},
{425,3758,3768,3778,466,2971,3809,3819,3829,517,3022,3860,3870,3880,568,3073,3911,3921,3931,621,3942,3952,652,3157,3983,3993,4003,703,3208,4034,4044,4054,754,3259,4085,786,3699,818,831,65535,65535,65535,65535,65535,65535,65535,65535,65535},
{841,851,861,872,882,892,902,912,923,933,943,953,963,974,984,994,1004,1014,1025,1036,1047,1057,1068,1078,1088,1098,1109,1119,1129,1139,1149,1160,1170,1180,1190,1201,4117,1233,1246,65535,65535,65535,65535,65535,65535,65535,65535,65535},
{3748,852,862,3363,883,893,903,913,924,934,944,954,964,975,985,995,1005,1015,1026,1037,1048,1058,1069,1079,1089,1099,1110,1120,1130,1140,1150,1161,1171,1181,1191,1202,1224,1234,1247,65535,65535,65535,65535,65535,65535,65535,65535,65535},
{1257,1267,1278,1288,1298,1308,1318,1328,1339,1349,1359,1369,1379,1390,1400,1410,1420,1430,1441,1452,1463,1474,1484,1494,1504,1514,1525,1535,1545,1555,1565,1576,1586,1596,1606,1617,3702,1649,1662,65535,65535,65535,65535,65535,65535,65535,65535,65535},
{1258,1268,3353,1289,1299,1309,1319,1329,1340,1350,1360,1370,1380,1391,1401,1411,1421,1431,1442,1453,1464,1475,1485,1495,1505,1515,1526,1536,1546,1556,1566,1577,1587,1597,1607,1618,1640,1650,1663,65535,65535,65535,65535,65535,65535,65535,65535,65535},
{1673,1683,1694,1704,1714,1724,1734,1745,1755,1765,1775,1785,1796,1806,1816,1826,1836,1847,1857,1868,1879,1890,1900,1910,1920,1931,1941,1951,1961,1971,1982,1992,2002,2012,2022,2033,4118,2066,2078,65535,65535,65535,65535,65535,65535,65535,65535,65535},
{1674,1684,1695,1705,1715,1725,1735,1746,1756,1766,1776,1786,1797,1807,1817,1827,1837,1848,1858,1869,1880,1891,1901,1911,1921,1932,1942,1952,1962,1972,1983,1993,2003,2013,2023,2034,2056,2067,2079,65535,65535,65535,65535,65535,65535,65535,65535,65535},
{2089,2100,2111,2121,2131,2141,3394,2162,2172,2182,2192,3445,2213,2223,2233,2243,3496,2264,2274,2286,2297,2307,2317,2327,3568,2348,2358,2368,2378,3619,2399,2409,2419,2429,3670,2451,3703,2483,415,65535,65535,65535,65535,65535,65535,65535,65535,65535},
{2090,2515,2110,2120,2130,2140,2151,2161,2171,2181,2191,2202,2212,2222,2232,2242,2253,2263,2273,2285,2296,2306,2316,2326,2337,2347,2357,2367,2377,2388,2398,2408,2418,2428,2439,2450,2472,2482,2495,65535,65535,65535,65535,65535,65535,65535,65535,65535},
{2505,3343,2525,2535,3373,2556,2566,3404,3414,3424,2607,2617,3455,3465,3475,2658,2668,3506,3516,2701,3527,3537,3547,2742,2752,3578,3588,3598,2793,2803,3629,3639,3649,2844,2854,2866,3700,2898,2911,65535,65535,65535,65535,65535,65535,65535,65535,65535},
{3333,2516,2526,2536,2546,3384,2567,2577,2587,2597,3435,2618,2628,2638,2648,3486,2669,2679,2689,2702,2712,2722,2732,3558,2753,2763,2773,2783,3609,2804,2814,2824,2834,3660,2855,2867,2888,2899,65535,65535,65535,65535,65535,65535,65535,65535,65535,65535},
{2921,2931,2941,2951,2961,3799,2982,2992,3002,3012,3850,3033,3043,3053,3063,3901,3084,3094,3104,3117,3127,3137,3147,3973,3168,3178,3188,3198,4024,3219,3229,3239,3249,4075,3270,3282,4115,3314,3326,65535,65535,65535,65535,65535,65535,65535,65535,65535},
{3749,3759,3769,3779,3789,2972,3810,3820,3830,3840,3023,3861,3871,3881,3891,3074,3912,3922,3932,3118,3943,3953,3963,3158,3984,3994,4004,4014,3209,4035,4045,4055,4065,3260,4086,3283,4116,3315,3327,65535,65535,65535,65535,65535,65535,65535,65535,65535},
{2506,3344,3354,3364,3374,2557,3395,3405,3415,3425,2608,3446,3456,3466,3476,2659,3497,3507,3517,2703,3528,3538,3548,2743,3569,3579,3589,3599,2794,3620,3630,3640,3650,2845,3671,2868,3704,2900,65535,65535,65535,65535,65535,65535,65535,65535,65535,65535},
{3334,2517,2527,2537,2547,3385,2568,2578,2588,2598,3436,2619,2629,2639,2649,3487,2670,2680,2690,2704,2713,2723,2733,3559,2754,2764,2774,2784,3610,2805,2815,2825,2835,3661,2856,2869,4119,2901,65535,65535,65535,65535,65535,65535,65535,65535,65535,65535},
{2922,2932,2942,2952,2962,3800,2983,2993,3003,3013,3851,3034,3044,3054,3064,3902,3085,3095,3105,3119,3128,3138,3148,3974,3169,3179,3189,3199,4025,3220,3230,3240,3250,4076,3271,3284,3304,3316,65535,65535,65535,65535,65535,65535,65535,65535,65535,65535},
{3750,3760,3770,3780,3790,2973,3811,3821,3831,3841,3024,3862,3872,3882,3892,3075,3913,3923,3933,3120,3944,3954,3964,3159,3985,3995,4005,4015,3210,4036,4046,4056,4066,3261,4087,3285,4120,3317,65535,65535,65535,65535,65535,65535,65535,65535,65535,65535},
{5,15,25,36,46,56,66,76,86,97,107,117,127,137,148,158,168,178,188,199,212,222,232,242,252,262,272,283,293,303,313,323,334,344,354,364,377,397,410,65535,65535,65535,65535,65535,65535,65535,65535,65535},
{6,16,26,37,47,57,67,77,87,98,108,118,128,138,149,159,169,179,189,200,213,223,233,243,253,263,273,284,294,304,314,324,335,345,355,365,378,398,411,65535,65535,65535,65535,65535,65535,65535,65535,65535},
{7,17,27,38,48,58,68,78,88,99,109,119,129,139,150,160,170,180,190,201,214,224,234,244,254,264,274,285,295,305,315,325,336,346,356,366,379,399,412,65535,65535,65535,65535,65535,65535,65535,65535,65535},
{8,18,28,39,49,59,69,79,89,100,110,120,130,140,151,161,171,181,191,202,215,225,235,245,255,265,275,286,296,306,316,326,337,347,357,367,3701,400,413,65535,65535,65535,65535,65535,65535,65535,65535,65535},
{9,19,29,40,50,60,70,80,90,101,111,121,131,141,152,162,172,182,192,203,216,226,236,246,256,266,276,287,297,307,317,327,338,348,358,368,392,401,414,65535,65535,65535,65535,65535,65535,65535,65535,65535},
{10,20,30,41,51,61,71,81,91,102,112,122,132,142,153,163,173,183,193,204,217,227,237,247,257,267,277,288,298,308,318,328,339,349,359,369,393,402,65535,65535,65535,65535,65535,65535,65535,65535,65535,65535},
{11,21,31,42,52,62,72,82,92,103,113,123,133,143,154,164,174,184,194,205,218,228,238,248,258,268,278,289,299,309,319,329,340,350,360,370,394,403,65535,65535,65535,65535,65535,65535,65535,65535,65535,65535},
{12,3347,32,2538,2548,3386,74,84,94,2599,3437,125,135,145,2650,3488,176,186,196,208,2714,2724,2734,3560,260,270,280,2785,3611,311,321,331,2836,3662,362,373,395,406,65535,65535,65535,65535,65535,65535,65535,65535,65535,65535},
};

#define NG SCHED_NG
#define RING SCHED_RING
#define NSLOT 8
#define CFETCH 5
#define TABLED 1
#define PROMO CU_TENSOR_MAP_L2_PROMOTION_L2_128B
#define AHEAD 8
#define CF0 5
#define CFS 2
#define ABL 0
#define CX 5
#define PUBN 2
#define PUBE 8
#define SCHED 9
#define OUT_TMA 0
#define JB1 21
#define JB2 24
#define CVAR 2
#define CFN 0
#define CREGS 224
#define CSLEEP 200
#define JB 22
#define JF 24
#define JR 17
#define HOIST 1
#define XEARLY 0
#define FPRED 1
#define LATERED 1
#define WDELAY 0
#define WDELAY2 0
#define PFX 0
#define FIRST 4
#define NODUMP 1
#define CH 64
#define NOJB 1
#define JFF 0
#define XPRED 0
#define W2X 2
#define RETRY 0
#define HMASK 0
#define GMASK 0
#define XM 0
#define XLATE 0
#define SKIP 1
#define ONEPASS 1
#define HCOMP 1.0025f
#define SF 1
#define PRE 2
#define WN 0
#define G0M 1
#define G0S 1
#define LAG 0
#define TRIG0 -1
#define NEARLY 3
#define NLATE 0
#define TRIG 7
constexpr int NCONV = 3 * NG;
constexpr int PLEN = SCHED_LE, LM = 256 - 2 * PLEN, NSEG = 4 / (NG - 8), LMID = NSEG * LM;
static_assert(LMID <= PLEN && (NG == 9 || NG == 10), "geometry");
constexpr int TILEB = 12288;
constexpr int SLOTB = 280 * 64;
constexpr int W1S = 0, W2S = 73728, ABUF = 147456, XBUF = ABUF + 16 * 3072, MISC = XBUF + 8 * 3072;
constexpr int WBAR = MISC + 2560;
constexpr int RBUF = ABUF - 4 * SLOTB;
constexpr int CM = MISC + 2816, CTAB = CM + 256;
constexpr int SMEM_BYTES = CTAB + (PLEN + 16) * 16;
static_assert(RBUF % 512 == 0 && RBUF >= W2S && RBUF + NSLOT * SLOTB + 128 <= MISC && SMEM_BYTES <= 232448, "smem layout");

struct Globals {
  unsigned char scratch[RING * NG * 4 * TILEB];
  unsigned char wimg[147456];
  uint32_t wflag[32];
  uint32_t ready[NG * PLEN + 1];
  uint32_t cons[NG * PLEN];
  uint32_t epoch[1024];
};
__device__ __align__(1024) Globals g_state;

#define PROF_AT(cond, idx)
#define PROF_VAL(cond, idx, v)
#define PROF2_AT(c, i)
#define PROF2_VAL(c, i, v)
#define PROFS(i)
#define GELU_C3 0.32920349f
#define GELU_A2 0x40d940d9u
#define SCHED_FENCE() asm volatile("pmevent 0;" ::: "memory")
#define SPIN_LIMIT 0x1000000

__device__ __forceinline__ uint32_t smem_u32(const void* p) { return (uint32_t)__cvta_generic_to_shared(p); }
__device__ __forceinline__ void wg_fence() { asm volatile("wgmma.fence.sync.aligned;" ::: "memory"); }
__device__ __forceinline__ void wg_commit() { asm volatile("wgmma.commit_group.sync.aligned;" ::: "memory"); }
template <int N> __device__ __forceinline__ void wg_wait() { asm volatile("wgmma.wait_group.sync.aligned %0;" ::"n"(N) : "memory"); }
__device__ __forceinline__ void mbar_init(uint32_t bar, uint32_t cnt) { asm volatile("mbarrier.init.shared::cta.b64 [%0], %1;" ::"r"(bar), "r"(cnt) : "memory"); }
__device__ __forceinline__ void mbar_expect_tx(uint32_t bar, uint32_t bytes) { asm volatile("mbarrier.arrive.expect_tx.shared::cta.b64 _, [%0], %1;" ::"r"(bar), "r"(bytes) : "memory"); }
__device__ __forceinline__ void mbar_arrive(uint32_t bar) { asm volatile("mbarrier.arrive.shared::cta.b64 _, [%0];" ::"r"(bar) : "memory"); }
__device__ __forceinline__ void mbar_wait(uint32_t bar, uint32_t parity) {
  asm volatile("{\n.reg .pred p;\n.reg .u32 c;\nmbarrier.try_wait.parity.shared::cta.b64 p, [%0], %1;\n@p bra DONE_%=;\nmov.u32 c, 0;\nWAIT_%=:\nmbarrier.try_wait.parity.shared::cta.b64 p, [%0], %1;\n@p bra DONE_%=;\n"
               "add.u32 c, c, 1;\nsetp.lt.u32 p, c, 0x1000000;\n@p bra WAIT_%=;\ntrap;\nDONE_%=:\n}" ::"r"(bar), "r"(parity) : "memory");
}
__device__ __forceinline__ void bulk_g2s(uint32_t dst, const void* src, uint32_t bytes, uint32_t bar) {
  asm volatile("cp.async.bulk.shared::cluster.global.mbarrier::complete_tx::bytes [%0], [%1], %2, [%3];" ::"r"(dst), "l"(src), "r"(bytes), "r"(bar) : "memory");
}
__device__ __forceinline__ uint32_t ld_relaxed(const uint32_t* p) { uint32_t v; asm volatile("ld.relaxed.gpu.global.u32 %0, [%1];" : "=r"(v) : "l"(p) : "memory"); return v; }
__device__ __forceinline__ void red_add_elect(uint32_t* p) { asm volatile("{.reg .pred p; elect.sync _|p, 0xffffffff; @p red.relaxed.gpu.global.add.u32 [%0], 1;}" ::"l"(p) : "memory"); }
__device__ __forceinline__ void mbar_arrive_elect(uint32_t bar) { asm volatile("{.reg .pred p; elect.sync _|p, 0xffffffff; @p mbarrier.arrive.shared::cta.b64 _, [%0];}" ::"r"(bar) : "memory"); }
__device__ __forceinline__ void mbar_init_elect(uint32_t bar, uint32_t cnt) { asm volatile("{.reg .pred p; elect.sync _|p, 0xffffffff; @p mbarrier.init.shared::cta.b64 [%0], %1;}" ::"r"(bar), "r"(cnt) : "memory"); }
__device__ __forceinline__ void lds128(uint32_t* r, uint32_t a) { asm volatile("ld.shared.v4.b32 {%0,%1,%2,%3}, [%4];" : "=r"(r[0]), "=r"(r[1]), "=r"(r[2]), "=r"(r[3]) : "r"(a) : "memory"); }
__device__ __forceinline__ uint2 lds64(uint32_t a) { uint2 v; asm volatile("ld.shared.v2.b32 {%0,%1}, [%2];" : "=r"(v.x), "=r"(v.y) : "r"(a) : "memory"); return v; }
__device__ __forceinline__ uint32_t lds32(uint32_t a) { uint32_t v; asm volatile("ld.shared.b32 %0, [%1];" : "=r"(v) : "r"(a) : "memory"); return v; }
__device__ __forceinline__ void sts32(uint32_t a, uint32_t v) { asm volatile("st.shared.b32 [%0], %1;" ::"r"(a), "r"(v) : "memory"); }
__device__ __forceinline__ void sts128(uint32_t a, uint4 v) { asm volatile("st.shared.v4.b32 [%0], {%1,%2,%3,%4};" ::"r"(a), "r"(v.x), "r"(v.y), "r"(v.z), "r"(v.w) : "memory"); }
__device__ __forceinline__ uint4 ldg128v(const void* p) { uint4 v; asm volatile("ld.global.nc.v4.b32 {%0,%1,%2,%3}, [%4];" : "=r"(v.x), "=r"(v.y), "=r"(v.z), "=r"(v.w) : "l"(p) : "memory"); return v; }
__device__ __forceinline__ void stg128(void* p, uint4 v) { asm volatile("st.global.v4.b32 [%0], {%1,%2,%3,%4};" ::"l"(p), "r"(v.x), "r"(v.y), "r"(v.z), "r"(v.w) : "memory"); }
#define HINT 3
__device__ __forceinline__ uint64_t pol_evict_first() { uint64_t p; asm("createpolicy.fractional.L2::evict_first.b64 %0, 1.0;" : "=l"(p)); return p; }
__device__ __forceinline__ uint4 ldg128_last(const void* p, uint64_t pol) {
  if (!(HINT & 1)) return ldg128v(p);
  uint4 v; asm volatile("ld.global.nc.L1::no_allocate.L2::cache_hint.v4.b32 {%0,%1,%2,%3}, [%4], %5;" : "=r"(v.x), "=r"(v.y), "=r"(v.z), "=r"(v.w) : "l"(p), "l"(pol) : "memory"); return v;
}
__device__ __forceinline__ void stg128_stream(void* p, uint4 v, uint64_t pol) {
  if (!(HINT & 2)) { stg128(p, v); return; }
  asm volatile("st.global.L2::cache_hint.v4.b32 [%0], {%1,%2,%3,%4}, %5;" ::"l"(p), "r"(v.x), "r"(v.y), "r"(v.z), "r"(v.w), "l"(pol) : "memory");
}
__device__ __forceinline__ float bf_lo(uint32_t w) { return __uint_as_float(w << 16); }
__device__ __forceinline__ float bf_hi(uint32_t w) { return __uint_as_float(w & 0xffff0000u); }
__device__ __forceinline__ uint32_t pack_f16(float lo, float hi) { uint32_t d; asm("cvt.rn.f16x2.f32 %0, %1, %2;" : "=r"(d) : "f"(hi), "f"(lo)); return d; }
__device__ __forceinline__ uint32_t pack_f16_sat(float lo, float hi) { uint32_t d; asm("cvt.rn.satfinite.f16x2.f32 %0, %1, %2;" : "=r"(d) : "f"(hi), "f"(lo)); return d; }
__device__ __forceinline__ uint32_t pack_bf16(float lo, float hi) { uint32_t d; asm("cvt.rn.bf16x2.f32 %0, %1, %2;" : "=r"(d) : "f"(hi), "f"(lo)); return d; }
__device__ __forceinline__ uint32_t hadd2_bf16(uint32_t a, uint32_t b) { uint32_t d; asm("add.rn.bf16x2 %0, %1, %2;" : "=r"(d) : "r"(a), "r"(b)); return d; }
__device__ __forceinline__ uint32_t h2add(uint32_t a, uint32_t b) { uint32_t d; asm("add.rn.f16x2 %0, %1, %2;" : "=r"(d) : "r"(a), "r"(b)); return d; }
__device__ __forceinline__ uint32_t h2mul(uint32_t a, uint32_t b) { uint32_t d; asm("mul.rn.f16x2 %0, %1, %2;" : "=r"(d) : "r"(a), "r"(b)); return d; }
__device__ __forceinline__ uint32_t h2fma(uint32_t a, uint32_t b, uint32_t c) { uint32_t d; asm("fma.rn.f16x2 %0, %1, %2, %3;" : "=r"(d) : "r"(a), "r"(b), "r"(c)); return d; }
__device__ __forceinline__ uint32_t h2lo(uint32_t a) { uint32_t d; asm("{.reg .f16 l,h; mov.b32 {l,h}, %1; mov.b32 %0, {l,l};}" : "=r"(d) : "r"(a)); return d; }
__device__ __forceinline__ uint32_t h2hi(uint32_t a) { uint32_t d; asm("{.reg .f16 l,h; mov.b32 {l,h}, %1; mov.b32 %0, {h,h};}" : "=r"(d) : "r"(a)); return d; }
__device__ __forceinline__ float h_lo(uint32_t a) { float d; asm("{.reg .f16 l,h; mov.b32 {l,h}, %1; cvt.f32.f16 %0, l;}" : "=f"(d) : "r"(a)); return d; }
__device__ __forceinline__ float h_hi(uint32_t a) { float d; asm("{.reg .f16 l,h; mov.b32 {l,h}, %1; cvt.f32.f16 %0, h;}" : "=f"(d) : "r"(a)); return d; }
__device__ __forceinline__ uint32_t prmt(uint32_t a, uint32_t b, uint32_t s) { uint32_t d; asm("prmt.b32 %0, %1, %2, %3;" : "=r"(d) : "r"(a), "r"(b), "r"(s)); return d; }
__device__ __forceinline__ void mma_sp(float* d, const uint32_t* a, const uint32_t* b, const float* c, uint32_t e) {
  asm("mma.sp::ordered_metadata.sync.aligned.m16n8k32.row.col.f32.bf16.bf16.f32 {%0,%1,%2,%3}, {%4,%5,%6,%7}, {%8,%9,%10,%11}, {%12,%13,%14,%15}, %16, 0;"
      : "=f"(d[0]), "=f"(d[1]), "=f"(d[2]), "=f"(d[3])
      : "r"(a[0]), "r"(a[1]), "r"(a[2]), "r"(a[3]), "r"(b[0]), "r"(b[1]), "r"(b[2]), "r"(b[3]), "f"(c[0]), "f"(c[1]), "f"(c[2]), "f"(c[3]), "r"(e));
}
__device__ __forceinline__ uint32_t bf2_to_h2(uint32_t w, float s) { return pack_f16(bf_lo(w) * s, bf_hi(w) * s); }
__device__ __forceinline__ uint32_t bf2_to_h2(uint32_t w) { return pack_f16(bf_lo(w), bf_hi(w)); }

__device__ __forceinline__ uint32_t gelu_tanh(uint32_t y) {
  uint32_t t, u, th;
  asm volatile("fma.rn.f16x2 %0, %1, %1, %2;" : "=r"(t) : "r"(y), "r"(GELU_A2));
  asm volatile("mul.rn.f16x2 %0, %1, %2;" : "=r"(u) : "r"(y), "r"(t));
  asm volatile("tanh.approx.f16x2 %0, %1;" : "=r"(th) : "r"(u));
  return th;
}
__device__ __forceinline__ uint32_t gelu_fin(uint32_t y, uint32_t th) {
  uint32_t g;
  asm volatile("fma.rn.f16x2 %0, %1, %2, %1;" : "=r"(g) : "r"(y), "r"(th));
  return g;
}

__device__ __forceinline__ void copy_weights(uint32_t sb, int piece, const void* src) {
  asm volatile("{\n.reg .pred p;\nelect.sync _|p, 0xffffffff;\n@p mbarrier.init.shared::cta.b64 [%1], 1;\n@p fence.mbarrier_init.release.cluster;\n"
               "@p mbarrier.arrive.expect_tx.shared::cta.b64 _, [%1], 12288;\n"
               "@p cp.async.bulk.shared::cluster.global.mbarrier::complete_tx::bytes [%0], [%2], 12288, [%1];\n}"
               ::"r"(sb + piece * 12288), "r"(sb + WBAR + piece * 8), "l"(src) : "memory");
}
__device__ __forceinline__ void convert_weights(uint32_t sb, uint32_t wbar, int rot, int warp, int lane) {
  if (warp < 12) {
    const int l8 = lane & 7, q4 = lane >> 3;
    int s = (warp >> 1) + rot; if (s >= 6) s -= 6;
    const uint32_t base = sb + W1S + s * 12288 + (warp & 1) * 384;
    mbar_wait(wbar + s * 8, 0);
    uint32_t v[3][4][4];
#pragma unroll
    for (int r = 0; r < 4; r++)
#pragma unroll
      for (int i = 0; i < 3; i++) lds128(v[i][r], base + i * 128 + (4 * (l8 >> 1) + 2 * (r & 1) + (l8 & 1)) * 768 + ((l8 + q4 + 4 * (r >> 1)) & 7) * 16);
    __syncwarp();
#pragma unroll
    for (int r = 0; r < 4; r++)
#pragma unroll
      for (int i = 0; i < 3; i++)
        sts128(base + i * 128 + (((l8 + q4 + 4 * (r >> 1)) & 7) + 8 * (r & 1)) * 768 + l8 * 16,
               make_uint4(bf2_to_h2(v[i][r][0]), bf2_to_h2(v[i][r][1]), bf2_to_h2(v[i][r][2]), bf2_to_h2(v[i][r][3])));
  }
  PROF2_AT(lane == 0, 440 + warp);
  const int q = lane & 3, t = (lane >> 2) & 3, b = lane >> 4;
  int u = 3 * (warp ^ 15) + 8 * rot; if (u >= 48) u -= 48;
  uint32_t base[3], v[3][4][3];
#pragma unroll
  for (int i = 0; i < 3; i++) {
    const int ui = u + i >= 48 ? u + i - 48 : u + i;
    base[i] = sb + W2S + ui * 1536;
    if (i != 1) mbar_wait(wbar + 48 + (ui >> 3) * 8, 0);
  }
#pragma unroll
  for (int i = 0; i < 3; i++)
#pragma unroll
    for (int d = 0; d < 4; d++)
#pragma unroll
      for (int j = 0; j < 3; j++) v[i][d][j] = lds32(base[i] + (2 * ((q + d) & 3) + b) * 192 + j * 64 + t * 16 + q * 4);
  __syncwarp();
#pragma unroll
  for (int i = 0; i < 3; i++)
#pragma unroll
    for (int d = 0; d < 4; d++)
#pragma unroll
      for (int j = 0; j < 3; j++) sts32(base[i] + (4 * j + q) * 128 + (2 * ((q + d) & 3) + b) * 16 + t * 4, bf2_to_h2(v[i][d][j]));
}

__device__ __noinline__ void ln_wide(uint32_t ad) {
  float m[2], r[2];
#pragma unroll
  for (int hi = 0; hi < 2; hi++) {
    float sm = 0.f;
    for (int s = 0; s < 6; s++) { uint2 w = lds64(ad + s * 512 + hi * 8); sm += (h_lo(w.x) + h_hi(w.x)) + (h_lo(w.y) + h_hi(w.y)); }
    sm += __shfl_xor_sync(0xffffffffu, sm, 1); sm += __shfl_xor_sync(0xffffffffu, sm, 2);
    m[hi] = sm * (1.f / 96.f);
    float q = 0.f;
    for (int s = 0; s < 6; s++) {
      uint2 w = lds64(ad + s * 512 + hi * 8);
      float d0 = h_lo(w.x) - m[hi], d1 = h_hi(w.x) - m[hi], d2 = h_lo(w.y) - m[hi], d3 = h_hi(w.y) - m[hi];
      q += (d0 * d0 + d1 * d1) + (d2 * d2 + d3 * d3);
    }
    q += __shfl_xor_sync(0xffffffffu, q, 1); q += __shfl_xor_sync(0xffffffffu, q, 2);
    r[hi] = rsqrtf(fmaf(q, 1.f / 96.f, 1e-5f)) * GELU_C3;
  }
  for (int s = 0; s < 6; s++) {
    uint32_t w[4]; lds128(w, ad + s * 512);
    sts128(ad + s * 512, make_uint4(pack_f16((h_lo(w[0]) - m[0]) * r[0], (h_hi(w[0]) - m[0]) * r[0]), pack_f16((h_lo(w[2]) - m[1]) * r[1], (h_hi(w[2]) - m[1]) * r[1]),
                                    pack_f16((h_lo(w[1]) - m[0]) * r[0], (h_hi(w[1]) - m[0]) * r[0]), pack_f16((h_lo(w[3]) - m[1]) * r[1], (h_hi(w[3]) - m[1]) * r[1])));
  }
  asm volatile("fence.proxy.async.shared::cta;" ::: "memory");
}

__device__ __forceinline__ float rsqrt_fast(float v) { float r; asm("rsqrt.approx.ftz.f32 %0, %1;" : "=f"(r) : "f"(v)); return r; }
__device__ __forceinline__ uint32_t layer_norm(uint32_t (&raw)[6][4], uint32_t* a, uint32_t tag) {
  const uint32_t stale = ((raw[0][0] ^ tag) | (raw[1][0] ^ tag)) | ((raw[2][0] ^ tag) | (raw[3][0] ^ tag)) | ((raw[4][0] ^ tag) | (raw[5][0] ^ tag));
  uint32_t sm[2];
#pragma unroll
  for (int hi = 0; hi < 2; hi++) {
    uint32_t s0 = h2add(raw[0][2 * hi], raw[1][2 * hi]), s1 = h2add(raw[0][2 * hi + 1], raw[1][2 * hi + 1]);
    uint32_t s2 = h2add(raw[2][2 * hi], raw[3][2 * hi]), s3 = h2add(raw[2][2 * hi + 1], raw[3][2 * hi + 1]);
    uint32_t s4 = h2add(raw[4][2 * hi], raw[5][2 * hi]), s5 = h2add(raw[4][2 * hi + 1], raw[5][2 * hi + 1]);
    sm[hi] = h2add(h2add(h2add(s0, s1), h2add(s2, s3)), h2add(s4, s5));
  }
  uint32_t qq[2];
#pragma unroll
  for (int hi = 0; hi < 2; hi++) {
    uint32_t q0 = h2mul(raw[0][2 * hi], raw[0][2 * hi]), q1 = h2mul(raw[0][2 * hi + 1], raw[0][2 * hi + 1]);
#pragma unroll
    for (int k = 1; k < 6; k++) { q0 = h2fma(raw[k][2 * hi], raw[k][2 * hi], q0); q1 = h2fma(raw[k][2 * hi + 1], raw[k][2 * hi + 1], q1); }
    qq[hi] = h2add(q0, q1);
  }
  uint32_t s = h2add(prmt(sm[0], sm[1], 0x5410), prmt(sm[0], sm[1], 0x7632));
  uint32_t q = h2add(prmt(qq[0], qq[1], 0x5410), prmt(qq[0], qq[1], 0x7632));
  s = h2add(s, __shfl_xor_sync(0xffffffffu, s, 1)); q = h2add(q, __shfl_xor_sync(0xffffffffu, q, 1));
  s = h2add(s, __shfl_xor_sync(0xffffffffu, s, 2)); q = h2add(q, __shfl_xor_sync(0xffffffffu, q, 2));
  constexpr float CS = HMASK ? GELU_C3 * HCOMP : GELU_C3;
  constexpr float K1 = 1.f / (96.f * CS * CS), K2 = 1e-5f / (CS * CS), K3 = 1.f / (96.f * CS);
  const float e0 = fmaf(h_lo(q), K1, K2), e1 = fmaf(h_hi(q), K1, K2), m0 = h_lo(s) * K3, m1 = h_hi(s) * K3;
  const float v0 = fmaf(-m0, m0, e0), v1 = fmaf(-m1, m1, e1);
  const uint32_t r = pack_f16(rsqrt_fast(v0), rsqrt_fast(v1)), o = h2mul(h2mul(s, 0xA155A155u), r);
#pragma unroll
  for (int k = 0; k < 6; k++) {
    a[4 * k] = h2fma(raw[k][0], h2lo(r), h2lo(o)); a[4 * k + 2] = h2fma(raw[k][1], h2lo(r), h2lo(o));
    a[4 * k + 1] = h2fma(raw[k][2], h2hi(r), h2hi(o)); a[4 * k + 3] = h2fma(raw[k][3], h2hi(r), h2hi(o));
  }
  if (HMASK) {
#pragma unroll
    for (int k = 0; k < 24; k++) a[k] &= HMASK;
  }
  const bool fine = fmaf(v0, 4.f, -e0) > 0.f && fmaf(v1, 4.f, -e1) > 0.f;
  return (fine ? 0u : 2u) | (stale & 1);
}

constexpr int KS = CH / 16, NC = 384 / CH;
#define WG1_(n) wgmma_n##n##_f16
#define WG1(n) WG1_(n)
__device__ __forceinline__ void gemm1(uint32_t* p, const uint32_t* a, uint64_t d1, int c, int k0 = 0, int k1 = 6) {
#pragma unroll
  for (int s = 0; s < 6; s++)
    if (s >= k0 && s < k1) {
      if (s == 0) WG1(CH)<0>(p, a, d1 + c * CH); else WG1(CH)<1>(p, a + 4 * s, d1 + c * CH + s * (12288 >> 4));
    }
}
__device__ __forceinline__ void fetch_a(uint32_t abuf, uint32_t bar, const unsigned char* src) {
  asm volatile("{\n.reg .pred p;\nelect.sync _|p, 0xffffffff;\n"
               "@p mbarrier.arrive.expect_tx.shared::cta.b64 _, [%1], 3072;\n"
               "@p cp.async.bulk.shared::cluster.global.mbarrier::complete_tx::bytes [%0], [%2], 3072, [%1];\n}"
               ::"r"(abuf), "r"(bar), "l"(src) : "memory");
}
__device__ __forceinline__ void fetch_a_if(uint32_t abuf, uint32_t bar, const unsigned char* src, uint32_t go) {
  asm volatile("{\n.reg .pred p, q;\nsetp.ne.u32 q, %3, 0;\nelect.sync _|p, 0xffffffff;\nand.pred p, p, q;\n"
               "@p mbarrier.arrive.expect_tx.shared::cta.b64 _, [%1], 3072;\n"
               "@p cp.async.bulk.shared::cluster.global.mbarrier::complete_tx::bytes [%0], [%2], 3072, [%1];\n}"
               ::"r"(abuf), "r"(bar), "l"(src), "r"(go) : "memory");
}
__device__ __forceinline__ bool mbar_test(uint32_t bar, uint32_t parity) {
  uint32_t r;
  asm volatile("{.reg .pred p; mbarrier.test_wait.parity.shared::cta.b64 p, [%1], %2; selp.u32 %0, 1, 0, p;}" : "=r"(r) : "r"(bar), "r"(parity) : "memory");
  return r;
}
__device__ __forceinline__ void fetch_x(uint32_t xbuf, uint32_t bar, const CUtensorMap* tm, uint32_t c0, uint32_t c12, uint64_t pol, int go = 0) {
  asm volatile("{\n.reg .pred p, q;\nsetp.ge.s32 q, %7, 0;\nelect.sync _|p, 0xffffffff;\nand.pred p, p, q;\n"
               "@p mbarrier.arrive.expect_tx.shared::cta.b64 _, [%1], 3072;\n"
               "@p cp.async.bulk.tensor.3d.shared::cluster.global.mbarrier::complete_tx::bytes.L2::cache_hint [%0], [%2, {%3, %4, %5}], [%1], %6;\n}"
               ::"r"(xbuf), "r"(bar), "l"(tm), "r"(c0), "r"(c12 & 255), "r"(c12 >> 8), "l"(pol), "r"(go) : "memory");
}
__device__ __forceinline__ void wait_ready(const uint32_t* p, uint32_t target) {
  int spins = 0;
  while (ld_relaxed(p) != target) { __nanosleep(32); if (++spins > SPIN_LIMIT) __trap(); }
}
__device__ __forceinline__ uint32_t slot_tag(int gm, int j, uint32_t epoch) {
  const int len = gm < 8 ? PLEN : LMID, writes = (len - (j % RING) + RING - 1) / RING;
  return (epoch * writes + j / RING + 1) & 1;
}

__device__ __forceinline__ void build_tile_list(uint32_t sb, int k, int idx, bool tabled, bool is_conv, uint32_t epoch) {
  int n = -1;
  if (tabled) { if (k < 48) n = (int16_t)g_sched[idx][k]; }
  else if (!is_conv) {
    const int i = k * (gridDim.x - NCONV) + idx, r = i >> 2, full = LMID * NG;
    const int j = r < full ? r / NG : ((r - full) >> 3) + LMID, gm = r < full ? r % NG : (r - full) & 7;
    if (i < 4096) n = (gm * PLEN + j) * 4 + (i & 3);
  }
  const int q = n >> 2, gm = q / PLEN, j = q - gm * PLEN, seg = j / LM;
  const int strip = gm < 8 ? gm >> 1 : (gm - 8) * NSEG + seg, pair = gm < 8 ? ((gm & 1) ? 255 - j : j) : PLEN + j - seg * LM;
  sts128(sb + MISC + 512 + k * 16, make_uint4(q, (((j % RING) * NG + gm) * 4 + (n & 3)) * TILEB + slot_tag(gm, j, epoch),
                                              (n & 2) * 384, (strip * 8 + (n & 1) * 4) | (pair << 9)));
  if (k == 0) { sts32(sb + MISC + 256, epoch + 1); sts32(sb + MISC + 260, !is_conv); }
}

__device__ __forceinline__ void mlp_setup(uint32_t sb, Globals* gs, int id, const __nv_bfloat16* __restrict__ w1, const __nv_bfloat16* __restrict__ w2,
                                          int idx, bool tabled, int warp, int lane) {
  const int rot = idx % 6;
  PROF2_AT(lane == 0, 400 + warp);
  if (warp < 12) {
    const int m = warp >= 6; int s = warp - 6 * m + rot; if (s >= 6) s -= 6;
    if (WDELAY) __nanosleep(WDELAY + m * WDELAY2);
    copy_weights(sb, 6 * m + s, (const char*)(m ? w2 : w1) + s * 12288);
  }
  __syncthreads();
  PROF2_AT(threadIdx.x == 0, 416);
  if (warp >= 12) build_tile_list(sb, threadIdx.x - 384, idx, tabled, false, ld_relaxed(&gs->epoch[id]));
  PROF2_AT(lane == 0, 420 + warp);
  convert_weights(sb, sb + WBAR, rot, warp, lane);
  PROF2_AT(lane == 0, 460 + warp);
  asm volatile("fence.proxy.async.shared::cta;" ::: "memory");
  __syncthreads();
  if (threadIdx.x == 480) {
    const uint32_t e1 = lds32(sb + MISC + 256);
    gs->epoch[id] = e1;
    if (idx < 24 && (idx & 1)) {
      asm volatile("cp.async.bulk.global.shared::cta.bulk_group [%0], [%1], 12288;\ncp.async.bulk.commit_group;\ncp.async.bulk.wait_group 0;\nfence.proxy.async.global;\n"
                   "red.release.gpu.global.add.u32 [%2], 1;" ::"l"(gs->wimg + (idx >> 1) * 12288), "r"(sb + (idx >> 1) * 12288), "l"(gs->wflag) : "memory");
    }
  }
  __syncwarp();
}

__device__ __forceinline__ void mlp_role(uint32_t sb, Globals* gs, const CUtensorMap* tmr, __nv_bfloat16* __restrict__ out) {
  uint32_t tid;
  asm volatile("mov.u32 %0, %%tid.x;" : "=r"(tid));
  const int warp = __shfl_sync(0xffffffffu, tid >> 5, 0), lane = tid & 31;
  const int wg = warp >> 2, w = warp & 3, g = lane >> 2, t = lane & 3;
  const uint32_t abuf = sb + ABUF + warp * 3072, xbuf = sb + XBUF + (warp & 7) * 3072;
  const uint32_t bar = sb + MISC + warp * 8, obar = sb + MISC + (warp ^ 8) * 8;
  const uint32_t tl = sb + MISC + 512;
  PROF_AT(threadIdx.x == 0, 1); PROF_VAL(threadIdx.x == 0, 8, clock64());
  const uint32_t rtarget = 3 * lds32(sb + MISC + 256);
  const uint64_t d1 = ((uint64_t)(6144 >> 4) << 16) | ((uint64_t)(128 >> 4) << 32) | (uint64_t)(((sb + W1S) >> 4) & 0x3fff);
  const uint64_t d2 = ((uint64_t)(12288 >> 4) << 16) | ((uint64_t)(128 >> 4) << 32) | (uint64_t)(((sb + W2S) >> 4) & 0x3fff);
  const uint32_t ad = abuf + t * 128 + ((g ^ (2 * t)) << 4);
  const uint32_t xd = xbuf + g * 192 + t * 16;
  const uint32_t pofs = (g >> 1) * 3072 + (2 * w + (g & 1)) * 192 + t * 16;
  const int mybar = 1 + wg, nxtbar = 1 + ((wg + 1) & 3);
  const uint64_t pol = pol_evict_first();
  const unsigned char* const asrc = gs->scratch + w * 3072;
  uint32_t pha = 0, phx = 0, tp = tl + wg * 16;
  bool pending = lds32(sb + MISC + 260);
  const uint32_t tq = tl + (pending ? G0M : G0S) * 16;
  uint32_t cur[4], rdy2 = rtarget + 1;
  lds128(cur, tp);
  if (wg < 2) fetch_x(xbuf, bar + 128, tmr, cur[2] + w * 192, cur[3], pol, cur[0]);
  while ((int)cur[0] >= 0) {
    PROF2_AT((threadIdx.x & 127) == 0, 16 + (tp - tl) / 4); PROF2_VAL((threadIdx.x & 127) == 0, 16 + (tp - tl) / 4 + 3, pending);
    uint32_t a[24], p[NC][CH / 4], gg[24][4], th[24][4], acc[24], raw[6][4], xr[6][4], n2[4], n4[4];
    if (pending) {
      if (!RETRY || rdy2 != rtarget) wait_ready(&gs->ready[cur[0]], rtarget);
      fetch_a(abuf, bar, asrc + (cur[1] & ~1u));
    }
    mbar_wait(bar, pha); pha ^= 1;
    PROF2_AT((threadIdx.x & 127) == 0, 16 + (tp - tl) / 4 + 1);
#pragma unroll
    for (int k = 0; k < 6; k++) lds128(raw[k], ad + k * 512);
    const int sig = (int)lds32(tp + 16) | (int)(tp + 16 - tq);
    lds128(n4, tp + 64);
    if (XLATE) lds128(n2, tp - 32);
    uint32_t st = layer_norm(raw, a, cur[1]);
    if (__any_sync(0xffffffffu, st != 0)) {
      for (int tries = 0; __any_sync(0xffffffffu, st & 1); tries++) {
        if (tries > SPIN_LIMIT) __trap();
        fetch_a(abuf, bar, asrc + (cur[1] & ~1u));
        mbar_wait(bar, pha); pha ^= 1;
        st = 0;
#pragma unroll
        for (int k = 0; k < 6; k++) st |= lds32(ad + k * 512) ^ cur[1];
      }
      ln_wide(ad);
#pragma unroll
      for (int k = 0; k < 6; k++) lds128(a + 4 * k, ad + k * 512);
    }
    if (!LATERED) red_add_elect(&gs->cons[cur[0]]);
    if (tp >= tq) asm volatile("bar.sync %0, 256;" ::"r"(mybar) : "memory");
    PROF2_AT((threadIdx.x & 127) == 0, 16 + (tp - tl) / 4 + 2);
    uint32_t rdy = 0;
    wg_fence();
    gemm1(p[0], a, d1, 0); wg_commit();
    if (SCHED == 9 && !LAG) { gemm1(p[1], a, d1, 1, 0, 6 / KS); wg_commit(); }
    if (XLATE && tp >= tl + 64) fetch_x(xbuf, obar + 128, tmr, n2[2] + w * 192, n2[3], pol);
    if (LATERED) asm volatile("{.reg .pred p; setp.eq.u32 p, %1, 0; @p red.relaxed.gpu.global.add.u32 [%0], 1;}" ::"l"(&gs->cons[cur[0]] + lane), "r"(lane) : "memory");
#pragma unroll
    for (int j = 0; j < 24; j++) {
      const int c = j / KS, s = j % KS;
      if (NOJB && j == JB) { if (NOJB == 2) SCHED_FENCE(); rdy = ld_relaxed(&gs->ready[max((int)n4[0], 0)]); if (NOJB == 3) SCHED_FENCE(); }
      if (LAG) { if (j == 0) wg_wait<0>(); else if (s == 0 || (s == 1 && c)) wg_wait<1>(); }
      else if (SCHED == 9) { if (s == 0 || WN == 1) wg_wait<1>(); else if (WN == 2) wg_wait<2>(); else if (WN == 3 && s == KS - 1) wg_wait<1>(); } else if (s == 0) wg_wait<0>();
      if (j == JF) { pending = rdy != rtarget; fetch_a_if(abuf, bar, asrc + (n4[1] & ~1u), !pending && (int)n4[0] >= 0); if (JFF) SCHED_FENCE(); }
      if (j == TRIG) asm volatile("{.reg .pred p; setp.ge.s32 p, %1, 0; @p bar.arrive %0, 256;}" ::"r"(nxtbar), "r"(sig) : "memory");
#pragma unroll
      for (int i = 0; i < 4; i++) {
        if (!(s && i < PRE)) th[j][i] = gelu_tanh(p[c][4 * s + i]);
        gg[j][i] = gelu_fin(p[c][4 * s + i], th[j][i]);
      }
      wg_fence();
      if (j == 0) wgmma_n96_f16<0>(acc, gg[j], d2); else wgmma_n96_f16<1>(acc, gg[j], d2 + (16 * (j % 3) + j / 3) * (1536 >> 4));
      if (SCHED == 9) {
        const int c1 = (j + 1) / KS + 1, u = (j + 1) % KS;
        if (LAG) { if (c + 1 < NC && s >= 1 && s <= KS - 2) gemm1(p[c + 1], a, d1, c + 1, (6 * (s - 1) + KS - 3) / (KS - 2), (6 * s + KS - 3) / (KS - 2)); }
        else if (c1 < NC) gemm1(p[c1], a, d1, c1, (6 * u) / KS, (6 * (u + 1)) / KS);
        wg_commit();
        if (PRE && s + 1 < KS) {
#pragma unroll
          for (int i = 0; i < PRE; i++) th[j + 1][i] = gelu_tanh(p[c][4 * s + 4 + i]);
        }
        if (SF && (j + 1) % (SF ? SF : 1) == 0 && j < 23) SCHED_FENCE();
      } else if (s == KS - 1) {
        if (c + 1 < NC) gemm1(p[c + 1], a, d1, c + 1);
        wg_commit();
      }
    }
    pending = rdy != rtarget;
    if (JF == 24) fetch_a_if(abuf, bar, asrc + (n4[1] & ~1u), !pending && (int)n4[0] >= 0);
    if (RETRY) rdy2 = ld_relaxed(&gs->ready[max((int)n4[0], 0)]);
    if (XM != 2) wg_wait<0>();
    mbar_wait(bar + 128, phx); phx ^= 1;
    if (XM) {
#pragma unroll
      for (int k = 0; k < 6; k++) lds128(xr[k], xd + (k / 3) * 1536 + (k % 3) * 64);
    }
    if (XM == 2) wg_wait<0>();
#pragma unroll
    for (int k = 0; k < 24; k++) acc[k] = h2mul(acc[k], 0x3E133E13u);
    char* const op = (char*)out + (cur[2] * 2 + (cur[3] & 255) * 3072 + (cur[3] >> 8) * (512 * 192) + pofs);
    if (!XLATE) lds128(n2, tp + 32);
#pragma unroll
    for (int k = 0; k < 6; k++) {
      const int hi = k / 3, j = k % 3;
      if (!XM) lds128(xr[k], xd + hi * 1536 + j * 64);
      uint4 o;
      o.x = hadd2_bf16(xr[k][0], pack_bf16(h_lo(acc[8 * j + hi]), h_hi(acc[8 * j + hi])));
      o.y = hadd2_bf16(xr[k][1], pack_bf16(h_lo(acc[8 * j + 2 + hi]), h_hi(acc[8 * j + 2 + hi])));
      o.z = hadd2_bf16(xr[k][2], pack_bf16(h_lo(acc[8 * j + 4 + hi]), h_hi(acc[8 * j + 4 + hi])));
      o.w = hadd2_bf16(xr[k][3], pack_bf16(h_lo(acc[8 * j + 6 + hi]), h_hi(acc[8 * j + 6 + hi])));
      stg128_stream(op + hi * (512 * 192) + j * 64, o, pol);
    }
    if (!XLATE) {
      __syncwarp();
      if ((int)n2[0] >= 0) fetch_x(xbuf, obar + 128, tmr, n2[2] + w * 192, n2[3], pol);
    }
    tp += 64;
#pragma unroll
    for (int k = 0; k < 4; k++) cur[k] = n4[k];
  }
  if (XLATE && tp >= tl + 64) {
    uint32_t n2[4];
    lds128(n2, tp - 32);
    __syncwarp();
    if ((int)n2[0] >= 0) fetch_x(xbuf, obar + 128, tmr, n2[2] + w * 192, n2[3], pol);
  }
  PROF_AT((threadIdx.x & 127) == 0, 4 + wg); PROF_VAL(threadIdx.x == 0, 9, clock64());
}

__device__ __forceinline__ void stg128_if(uint32_t ofs, void* p, uint4 v) {
  asm volatile("{.reg .pred q; setp.ge.s32 q, %5, 0; @q st.global.v4.b32 [%0], {%1,%2,%3,%4};}" ::"l"(p), "r"(v.x), "r"(v.y), "r"(v.z), "r"(v.w), "r"(ofs) : "memory");
}
__device__ __forceinline__ void conv_compute(uint32_t sb, Globals* gs, int third, int nit, int off, bool up, int warp, int lane) {
  const int g = lane >> 2, t = lane & 3;
  const uint32_t full = sb + CM;
  PROFS(0);
  const uint32_t wt = sb + 16384 + warp * 1024;
  sts128(wt + lane * 16, make_uint4(0, 0, 0, 0));
  if (lane < 4) sts128(wt + 512 + lane * 16, make_uint4(0, 0, 0, 0));
  asm volatile("setmaxnreg.inc.sync.aligned.u32 %0;" ::"n"(CREGS));
  PROFS(1);
  uint32_t meta = 0;
#pragma unroll
  for (int a = 0; a < 4; a++) meta |= ((4 * (t & 1) + a + 1 >= g) ? 0x80008u : 0xD000Du) << (4 * a);
  meta = __shfl_sync(0xffffffffu, meta, lane);
  uint32_t aq[4];
#pragma unroll
  for (int q = 0; q < 4; q++) {
    const int pp = (g & 1) * 140 + (t & 1) * 70 + 16 * (g >> 1) + 2 * q + (t >> 1);
    aq[q] = __shfl_sync(0xffffffffu, sb + RBUF + pp * 64 + (((warp >> 1) ^ ((pp >> 1) & 3)) << 4) + (warp & 1) * 8, lane);
  }
  const int Q = third * 8 + warp;
  unsigned char* const obase = gs->scratch + (g >> 1) * 3072 + Q * 128 + (((2 * t + (g & 1)) ^ (2 * (Q & 3))) << 4);
  const float zero4[4] = {0.f, 0.f, 0.f, 0.f};
  {
    uint32_t A[4][4][4];
    PROFS(2);
    asm volatile("bar.sync 5, 288;" ::: "memory");
    mbar_wait(sb + WBAR + 8, 0);
    PROFS(3);
    {
#pragma unroll
      for (int k = 0; k < 2; k++) {
        const int tap = lane + 32 * k, i = tap / 7;
        if (tap < 49) { const uint2 v = lds64(sb + tap * 192 + third * 64 + warp * 8); asm volatile("st.shared.v2.b32 [%0], {%1,%2};" ::"r"(wt + (tap + i + 8) * 8), "r"(v.x), "r"(v.y) : "memory"); }
      }
      __syncwarp();
      uint2 w[2][4][3];
#pragma unroll
      for (int h = 0; h < 2; h++) {
        uint32_t src = wt + ((4 * h + t - g) & 7) * 8 + (up ? 384 : 0);
#pragma unroll
        for (int u = 0; u < 4; u++) {
#pragma unroll
          for (int k = 0; k < 3; k++) w[h][u][k] = lds64(src + k * 64);
          src += up ? -128 : 128;
        }
      }
#pragma unroll
      for (int u = 0; u < 4; u++)
#pragma unroll
        for (int r = 0; r < 4; r++) {
          const uint2 w0 = w[r >> 1][u][1 - (r & 1)], w1 = w[r >> 1][u][2 - (r & 1)];
          A[0][u][r] = prmt(w0.x, w1.x, 0x5410); A[1][u][r] = prmt(w0.x, w1.x, 0x7632);
          A[2][u][r] = prmt(w0.y, w1.y, 0x5410); A[3][u][r] = prmt(w0.y, w1.y, 0x7632);
        }
    }
    float S[2][4][3][4];
#pragma unroll
    for (int s = 0; s < 2; s++)
#pragma unroll
      for (int c = 0; c < 4; c++)
#pragma unroll
        for (int i = 0; i < 3; i++)
#pragma unroll
          for (int k = 0; k < 4; k++) S[s][c][i][k] = 0.f;
    uint32_t sofs = off * SLOTB, bar = full + off * 8, ph = 0, ot = sb + CTAB;
    const uint32_t oend = ot + nit * 16;
    PROF_AT(threadIdx.x == 0, 12);
    PROFS(4);
    asm volatile("bar.sync 0, 512;" ::: "memory");
    PROFS(5);
    mbar_wait(bar, 0);
    PROF_AT(threadIdx.x == 0, 14);
    PROFS(6);
    uint2 X[3][4];
#pragma unroll
    for (int j = 0; j < 2; j++)
#pragma unroll
      for (int q = 0; q < 4; q++) X[j][q] = lds64(aq[q] + sofs + j * 512);
#pragma unroll 1
    do {
      const uint2 oe = lds64(ot);
      unsigned char* const o = obase + oe.x;
      const uint32_t dbar = bar + 64;
#pragma unroll
      for (int s = 0; s < 2; s++) {
        uint32_t B[4][4];
        if (s == 1) {
          sofs += SLOTB; bar += 8;
          if (sofs == NSLOT * SLOTB) { sofs = 0; bar = full; ph ^= 1; }
          mbar_wait(bar, ph);
        }
#pragma unroll
        for (int c = 0; c < 4; c++)
#pragma unroll
          for (int q = 0; q < 4; q++) B[c][q] = prmt(c < 2 ? X[s][q].x : X[s][q].y, c < 2 ? X[s + 1][q].x : X[s + 1][q].y, (c & 1) ? 0x7632 : 0x5410);
        if (s == 0) {
#pragma unroll
          for (int q = 0; q < 4; q++) X[2][q] = lds64(aq[q] + sofs + 2 * 512);
        } else {
#pragma unroll
          for (int j = 0; j < 2; j++)
#pragma unroll
            for (int q = 0; q < 4; q++) X[j][q] = lds64(aq[q] + sofs + j * 512);
        }
        float T[4][4];
#pragma unroll
        for (int c = 0; c < 4; c++) mma_sp(T[c], A[c][3], B[c], S[s][c][2], meta);
#pragma unroll
        for (int c = 0; c < 4; c++) mma_sp(S[s][c][2], A[c][2], B[c], S[s][c][1], meta);
        stg128_if(oe.x, o + (2 * s) * TILEB, make_uint4((pack_f16_sat(T[0][0], T[1][0]) & ~1u) | oe.y, pack_f16_sat(T[2][0], T[3][0]), pack_f16_sat(T[0][2], T[1][2]), pack_f16_sat(T[2][2], T[3][2])));
        stg128_if(oe.x, o + (2 * s + 1) * TILEB, make_uint4((pack_f16_sat(T[0][1], T[1][1]) & ~1u) | oe.y, pack_f16_sat(T[2][1], T[3][1]), pack_f16_sat(T[0][3], T[1][3]), pack_f16_sat(T[2][3], T[3][3])));
        if (s == 1) mbar_arrive_elect(dbar);
#pragma unroll
        for (int c = 0; c < 4; c++) mma_sp(S[s][c][1], A[c][1], B[c], S[s][c][0], meta);
#pragma unroll
        for (int c = 0; c < 4; c++) mma_sp(S[s][c][0], A[c][0], B[c], zero4, meta);
      }
      ot += 16;
    } while (ot != oend);
  }
  PROF_AT(threadIdx.x == 0, 13);
}

__device__ __forceinline__ void load_step(uint32_t sb, const CUtensorMap* tmx, int gm, int third, int it, int s, bool first = false) {
  const int seg = first ? 0 : it / (LM + 3);
  const int st = gm < 8 ? gm >> 1 : (gm - 8) * NSEG + seg, J = gm < 8 ? ((gm & 1) ? 257 - it : it + 1) : PLEN + it - seg * (LM + 3);
  asm volatile("{\n.reg .pred p;\n.reg .s32 c2;\n.reg .u32 d2;\nelect.sync _|p, 0xffffffff;\nadd.s32 c2, %4, 64;\nadd.u32 d2, %0, 8960;\n"
               "@p mbarrier.arrive.expect_tx.shared::cta.b64 _, [%2], 17920;\n"
               "@p cp.async.bulk.tensor.3d.shared::cluster.global.mbarrier::complete_tx::bytes [%0], [%1, {%3, %4, %5}], [%2];\n"
               "@p cp.async.bulk.tensor.3d.shared::cluster.global.mbarrier::complete_tx::bytes [d2], [%1, {%3, c2, %5}], [%2];\n}"
               ::"r"(sb + RBUF + s * SLOTB), "l"(tmx), "r"(sb + CM + s * 8), "r"(third * 32), "r"(st * 128 - 3), "r"(2 * J - 3) : "memory");
}
__device__ __forceinline__ void ring_bar_init(uint32_t bar, uint32_t cnt, bool ahead) {
  asm volatile("{\n.reg .pred p, q;\nelect.sync _|p, 0xffffffff;\n@p mbarrier.init.shared::cta.b64 [%0], %1;\n"
               "setp.ne.and.u32 q, %2, 0, p;\n@q mbarrier.arrive.shared::cta.b64 _, [%0], %1;\n@p fence.mbarrier_init.release.cluster;\n}" ::"r"(bar), "r"(cnt), "r"((uint32_t)ahead) : "memory");
}
__device__ __forceinline__ void conv_loader(uint32_t sb, Globals* gs, const CUtensorMap* tmx, int gm, int nit, int off, int cidx, int third, int k) {
  static_assert(AHEAD > 5 && AHEAD <= NSLOT && NCONV >= 24, "loader");
  const uint32_t full = sb + CM;
  asm volatile("bar.sync 0, 512;" ::: "memory");
  if (FIRST + k < AHEAD) load_step(sb, tmx, gm, third, FIRST + k, (FIRST + k + off) & 7, true);
#pragma unroll 1
  for (int it = AHEAD + k; it < nit + AHEAD; it += 4) {
    const int u = it + off;
    const uint32_t ro = lds32(sb + CTAB + (it - AHEAD) * 16 + 8);
    mbar_wait(full + 64 + ((u - AHEAD) & 7) * 8, ((u - AHEAD) >> 3) & 1);
    red_add_elect((uint32_t*)((char*)gs + ro));
    PROF_AT((threadIdx.x & 31) == 0 && (((it - AHEAD) & (PROF > 1 ? 7 : 15)) == 0 || it - AHEAD < 6), 200 + it - AHEAD);
    if (it < nit) load_step(sb, tmx, gm, third, it, u & 7);
    else if (it == nit) mbar_arrive_elect(full);
    if (it >= nit - 16) {
      if (it < nit - 12) {
        wait_ready(gs->wflag, 12 * lds32(sb + MISC + 256));
        asm volatile("fence.acquire.gpu;\nfence.proxy.async.global;" ::: "memory");
        if (cidx < 24) asm volatile("{.reg .pred p; elect.sync _|p, 0xffffffff; @p cp.async.bulk.prefetch.L2.global [%0], 1536;}" ::"l"(gs->wimg + (cidx * 4 + k) * 1536) : "memory");
      }
      const int m = it == nit - 1 ? 0 : W2S;
      if (it == nit - 1 || it == nit + AHEAD - 5)
        asm volatile("{\n.reg .pred p;\nelect.sync _|p, 0xffffffff;\n@p mbarrier.arrive.expect_tx.shared::cta.b64 _, [%1], 73728;\n"
                     "@p cp.async.bulk.shared::cluster.global.mbarrier::complete_tx::bytes [%0], [%2], 73728, [%1];\n}"
                     ::"r"(sb + m), "r"(sb + WBAR), "l"(gs->wimg + m) : "memory");
    }
  }
}

__device__ __forceinline__ void conv_credit(uint32_t sb, Globals* gs, int P0, int nit, int off, uint32_t ctarget, int k) {
  const uint32_t full = sb + CM;
#pragma unroll 1
  for (int it = k + NSLOT; it <= nit; it += 4) {
    const int u = it + off, P = (int)lds32(sb + CTAB + it * 16 + 12) - RING;
    int spins = 0;
    mbar_wait(full + 64 + (u & 7) * 8, ((u >> 3) & 1) ^ 1);
    if (P >= P0) while (ld_relaxed(&gs->cons[P]) != ctarget) { __nanosleep(CSLEEP); if (++spins > SPIN_LIMIT) __trap(); }
    mbar_arrive_elect(full + (u & 7) * 8);
  }
}

__device__ __noinline__ int generic_role() {
  const int cidx = (blockIdx.x * NCONV) / gridDim.x;
  return cidx | ((((blockIdx.x + 1) * NCONV) / gridDim.x != cidx) << 16);
}

__global__ void __launch_bounds__(512, 1) convnext_kernel(const __nv_bfloat16* __restrict__ dw, const __nv_bfloat16* __restrict__ w1, const __nv_bfloat16* __restrict__ w2,
                                                          __nv_bfloat16* __restrict__ out, Globals* gs, int want_sms,
                                                          const __grid_constant__ CUtensorMap tmx, const __grid_constant__ CUtensorMap tmr) {
  extern __shared__ __align__(1024) unsigned char smem[];
  const uint32_t sb = smem_u32(smem);
  const int warp = __shfl_sync(0xffffffffu, threadIdx.x >> 5, 0), lane = threadIdx.x & 31;
  PROF_AT(threadIdx.x == 0, 0);
  if (PFX && threadIdx.x == 320) asm volatile("prefetch.tensormap [%0];" ::"l"(&tmx) : "memory");
  uint32_t smid, nsmid;
  asm volatile("mov.u32 %0, %%smid;" : "=r"(smid));
  asm volatile("mov.u32 %0, %%nsmid;" : "=r"(nsmid));
  const bool tabled = TABLED && (int)nsmid == want_sms;
  const int id = tabled ? smid : blockIdx.x;
  int cidx, idx;
  int is_conv;
  if (tabled) {
    idx = smid;
    const int k = (smid - 60) / 14, r = smid - 60 - 14 * k;
    is_conv = smid < 48 ? !(smid & 1) : (smid >= 60 && smid <= 90 && (r & ~2) == 0);
    cidx = smid < 48 ? ((smid >> 1) & 7) * 3 + (smid >> 4) : 24 + (r >> 1) * 3 + k;
  } else {
    const int r = generic_role();
    cidx = r & 0xffff; is_conv = r >> 16;
    idx = blockIdx.x - cidx;
  }
  PROF_VAL(threadIdx.x == 0, 2, is_conv ? 1000 + cidx : idx);
  const int gm = cidx / 3, third = cidx - gm * 3;
  const int P0 = gm * PLEN, nit = gm < 8 ? PLEN + 2 : NSEG * (LM + 3), off = (8 - nit) & 7;
  if (is_conv && warp == 8) {
    asm volatile("{\n.reg .pred p;\nelect.sync _|p, 0xffffffff;\n@p mbarrier.init.shared::cta.b64 [%1], 1;\n@p fence.mbarrier_init.release.cluster;\n"
                 "@p mbarrier.arrive.expect_tx.shared::cta.b64 _, [%1], 9408;\n"
                 "@p cp.async.bulk.shared::cluster.global.mbarrier::complete_tx::bytes [%0], [%2], 9408, [%1];\nbar.arrive 5, 288;\n}"
                 ::"r"(sb), "r"(sb + WBAR + 8), "l"(dw) : "memory");
#pragma unroll 1
    for (int it = 0; it < NSLOT; it++) {
      const int s = (it + off) & 7;
      ring_bar_init(sb + CM + s * 8, 2, s < off);
      PROF_AT(it == 0 && (threadIdx.x & 31) == 0, 15);
      if (it < FIRST) load_step(sb, &tmx, gm, third, it, s, true);
    }
  }
  if (warp == 15) asm volatile("prefetch.tensormap [%0];" ::"l"(&tmr) : "memory");
  mbar_init_elect(sb + MISC + warp * 8, 1); mbar_init_elect(sb + MISC + 128 + warp * 8, 1);
  asm volatile("fence.mbarrier_init.release.cluster;" ::: "memory");
  if (is_conv) {
    if (warp >= 8) ring_bar_init(sb + CM + warp * 8, 8, warp - 8 < off);
    if (warp == 9) mbar_init_elect(sb + WBAR, 2);
    if (warp < 8) {
      conv_compute(sb, gs, third, nit, off, gm < 8 && (gm & 1), warp, lane);
      asm volatile("setmaxnreg.dec.sync.aligned.u32 128;");
    } else if (warp >= 12) {
      asm volatile("setmaxnreg.dec.sync.aligned.u32 24;");
      const uint32_t epoch = ld_relaxed(&gs->epoch[id]);
#pragma unroll 1
      for (int it = threadIdx.x - 384; it <= nit; it += 128) {
        const int seg = it / (LM + 3), j = gm < 8 ? it - 2 : it - 3 * (seg + 1);
        const bool ok = it < nit && j >= (gm < 8 ? 0 : seg * LM);
        sts128(sb + CTAB + it * 16, make_uint4((ok ? (j % RING) * NG + gm : -1) * (4 * TILEB), slot_tag(gm, max(j, 0), epoch),
                                               offsetof(Globals, ready) + (ok ? P0 + j : NG * PLEN) * 4, ok ? P0 + j : -1));
      }
      asm volatile("bar.sync 0, 512;" ::: "memory");
      mbar_arrive_elect(sb + CM + ((((warp + 2) & 3) + off) & 7) * 8);
      mbar_arrive_elect(sb + CM + ((((warp + 2) & 3) + off + 4) & 7) * 8);
      build_tile_list(sb, threadIdx.x - 384, idx, tabled, true, epoch);
      if (threadIdx.x == 384) gs->epoch[id] = epoch + 1;
      conv_credit(sb, gs, P0, nit, off, 16 * (epoch + 1), (warp + 2) & 3);
#pragma unroll 1
      for (int i = 0; i < 4; i++) {
        const uint2 e = lds64(sb + MISC + 512 + i * 16);
        mbar_wait(sb + CM + 64 + (4 + min(i, 2)) * 8, (((nit + off) >> 3) & 1) ^ 1);
        const int wi = 4 * i + (warp & 3);
        if ((int)e.x >= 0) fetch_a(sb + ABUF + wi * 3072, sb + MISC + wi * 8, gs->scratch + (e.y & ~1u) + (warp & 3) * 3072);
      }
      mbar_wait(sb + CM + 64 + 7 * 8, (((nit + off) >> 3) & 1) ^ 1);
      asm volatile("setmaxnreg.inc.sync.aligned.u32 128;");
    } else {
      asm volatile("setmaxnreg.dec.sync.aligned.u32 %0;" ::"n"(488 - 2 * CREGS));
      conv_loader(sb, gs, &tmx, gm, nit, off, cidx, third, warp & 3);
      mbar_wait(sb + CM + 64 + 4 * 8, (((nit + off) >> 3) & 1) ^ 1);
      mbar_wait(sb + CM + 64 + 7 * 8, (((nit + off) >> 3) & 1) ^ 1);
      asm volatile("setmaxnreg.inc.sync.aligned.u32 128;");
    }
    PROF2_AT((threadIdx.x & 31) == 0, 400 + (threadIdx.x >> 5));
    mbar_wait(sb + WBAR, 0);
    asm volatile("bar.sync 0, 512;" ::: "memory");
  } else {
    mlp_setup(sb, gs, id, w1, w2, idx, tabled, warp, lane);
  }
  mlp_role(sb, gs, &tmr, out);
}

typedef CUresult (*PFN_encodeTiled)(CUtensorMap*, CUtensorMapDataType, cuuint32_t, void*, const cuuint64_t*, const cuuint64_t*, const cuuint32_t*, const cuuint32_t*,
                                    CUtensorMapInterleave, CUtensorMapSwizzle, CUtensorMapL2promotion, CUtensorMapFloatOOBfill);

extern "C" void kernel_launch(void* const* d_in, const int* in_sizes, int n_in, void* d_out, int out_size) {
  const __nv_bfloat16* x = (const __nv_bfloat16*)d_in[0];
  const __nv_bfloat16* dw = (const __nv_bfloat16*)d_in[1];
  const __nv_bfloat16* w1 = (const __nv_bfloat16*)d_in[2];
  const __nv_bfloat16* w2 = (const __nv_bfloat16*)d_in[3];
  static PFN_encodeTiled encode = nullptr;
  static int nsm = 0;
  static Globals* gs = nullptr;
  if (!encode) {
    void* fn = nullptr; cudaDriverEntryPointQueryResult qr;
    cudaGetDriverEntryPoint("cuTensorMapEncodeTiled", &fn, cudaEnableDefault, &qr);
    encode = (PFN_encodeTiled)fn;
    cudaGetSymbolAddress((void**)&gs, g_state);
    int dev = 0; cudaGetDevice(&dev);
    cudaDeviceGetAttribute(&nsm, cudaDevAttrMultiProcessorCount, dev);
    cudaFuncSetAttribute(convnext_kernel, cudaFuncAttributeMaxDynamicSharedMemorySize, SMEM_BYTES);
  }
  CUtensorMap tm;
  cuuint64_t dims[3] = {96, 512, 512}, strides[2] = {192, 192 * 512};
  cuuint32_t box[3] = {32, 70, 2}, es[3] = {1, 1, 1};
  encode(&tm, CU_TENSOR_MAP_DATA_TYPE_BFLOAT16, 3, (void*)x, dims, strides, box, es, CU_TENSOR_MAP_INTERLEAVE_NONE, CU_TENSOR_MAP_SWIZZLE_64B,
         PROMO, CU_TENSOR_MAP_FLOAT_OOB_FILL_NONE);
  CUtensorMap tr;
  cuuint64_t dims2[3] = {1536, 32, 512}, strides2[2] = {3072, 192 * 512};
  cuuint32_t box2[3] = {192, 4, 2};
  encode(&tr, CU_TENSOR_MAP_DATA_TYPE_BFLOAT16, 3, (void*)x, dims2, strides2, box2, es, CU_TENSOR_MAP_INTERLEAVE_NONE, CU_TENSOR_MAP_SWIZZLE_NONE,
         CU_TENSOR_MAP_L2_PROMOTION_NONE, CU_TENSOR_MAP_FLOAT_OOB_FILL_NONE);
  convnext_kernel<<<nsm, 512, SMEM_BYTES>>>(dw, w1, w2, (__nv_bfloat16*)d_out, gs, nsm == 132 ? 132 : -1, tm, tr);
}
```

```cpp
#include <cuda_runtime.h>
#include <cuda_bf16.h>
#include <cuda.h>
#include <stdint.h>
#include <stddef.h>

template<int SCALE_D> __device__ __forceinline__ void wgmma_n64_f16(uint32_t* d, const uint32_t* a, uint64_t desc) {
  if (SCALE_D == 0) asm volatile("wgmma.mma_async.sync.aligned.m64n64k16.f16.f16.f16 {%0,%1,%2,%3,%4,%5,%6,%7,%8,%9,%10,%11,%12,%13,%14,%15}, {%16,%17,%18,%19}, %20, 0, 1, 1, 1;"
    : "=r"(d[0]),"=r"(d[1]),"=r"(d[2]),"=r"(d[3]),"=r"(d[4]),"=r"(d[5]),"=r"(d[6]),"=r"(d[7]),"=r"(d[8]),"=r"(d[9]),"=r"(d[10]),"=r"(d[11]),"=r"(d[12]),"=r"(d[13]),"=r"(d[14]),"=r"(d[15])
    : "r"(a[0]),"r"(a[1]),"r"(a[2]),"r"(a[3]),"l"(desc));
  if (SCALE_D == 1) asm volatile("wgmma.mma_async.sync.aligned.m64n64k16.f16.f16.f16 {%0,%1,%2,%3,%4,%5,%6,%7,%8,%9,%10,%11,%12,%13,%14,%15}, {%16,%17,%18,%19}, %20, 1, 1, 1, 1;"
    : "+r"(d[0]),"+r"(d[1]),"+r"(d[2]),"+r"(d[3]),"+r"(d[4]),"+r"(d[5]),"+r"(d[6]),"+r"(d[7]),"+r"(d[8]),"+r"(d[9]),"+r"(d[10]),"+r"(d[11]),"+r"(d[12]),"+r"(d[13]),"+r"(d[14]),"+r"(d[15])
    : "r"(a[0]),"r"(a[1]),"r"(a[2]),"r"(a[3]),"l"(desc));
}

template<int SCALE_D> __device__ __forceinline__ void wgmma_n96_f16(uint32_t* d, const uint32_t* a, uint64_t desc) {
  if (SCALE_D == 0) asm volatile("wgmma.mma_async.sync.aligned.m64n96k16.f16.f16.f16 {%0,%1,%2,%3,%4,%5,%6,%7,%8,%9,%10,%11,%12,%13,%14,%15,%16,%17,%18,%19,%20,%21,%22,%23}, {%24,%25,%26,%27}, %28, 0, 1, 1, 1;"
    : "=r"(d[0]),"=r"(d[1]),"=r"(d[2]),"=r"(d[3]),"=r"(d[4]),"=r"(d[5]),"=r"(d[6]),"=r"(d[7]),"=r"(d[8]),"=r"(d[9]),"=r"(d[10]),"=r"(d[11]),"=r"(d[12]),"=r"(d[13]),"=r"(d[14]),"=r"(d[15]),"=r"(d[16]),"=r"(d[17]),"=r"(d[18]),"=r"(d[19]),"=r"(d[20]),"=r"(d[21]),"=r"(d[22]),"=r"(d[23])
    : "r"(a[0]),"r"(a[1]),"r"(a[2]),"r"(a[3]),"l"(desc));
  if (SCALE_D == 1) asm volatile("wgmma.mma_async.sync.aligned.m64n96k16.f16.f16.f16 {%0,%1,%2,%3,%4,%5,%6,%7,%8,%9,%10,%11,%12,%13,%14,%15,%16,%17,%18,%19,%20,%21,%22,%23}, {%24,%25,%26,%27}, %28, 1, 1, 1, 1;"
    : "+r"(d[0]),"+r"(d[1]),"+r"(d[2]),"+r"(d[3]),"+r"(d[4]),"+r"(d[5]),"+r"(d[6]),"+r"(d[7]),"+r"(d[8]),"+r"(d[9]),"+r"(d[10]),"+r"(d[11]),"+r"(d[12]),"+r"(d[13]),"+r"(d[14]),"+r"(d[15]),"+r"(d[16]),"+r"(d[17]),"+r"(d[18]),"+r"(d[19]),"+r"(d[20]),"+r"(d[21]),"+r"(d[22]),"+r"(d[23])
    : "r"(a[0]),"r"(a[1]),"r"(a[2]),"r"(a[3]),"l"(desc));
}

#define SCHED_NG 10
#define SCHED_LE 104
#define SCHED_RING 16
__device__ const uint16_t g_sched[132][48] = {
{380,383,386,389,65535,65535,65535,65535,65535,65535,65535,65535,65535,65535,65535,65535,65535,65535,65535,65535,65535,65535,65535,65535,65535,65535,65535,65535,65535,65535,65535,65535,65535,65535,65535,65535,65535,65535,65535,65535,65535,65535,65535,65535,65535,65535,65535,65535},
{0,2507,22,2943,2953,2963,3801,73,83,93,3014,3852,124,134,144,3065,3903,175,185,195,206,3129,3139,3149,3975,259,269,279,3200,4026,310,320,330,3251,4077,361,371,2889,404,65535,65535,65535,65535,65535,65535,65535,65535,65535},
{796,799,802,805,65535,65535,65535,65535,65535,65535,65535,65535,65535,65535,65535,65535,65535,65535,65535,65535,65535,65535,65535,65535,65535,65535,65535,65535,65535,65535,65535,65535,65535,65535,65535,65535,65535,65535,65535,65535,65535,65535,65535,65535,65535,65535,65535,65535},
{416,426,436,446,456,467,477,487,497,507,518,528,538,548,558,569,579,589,599,609,622,632,642,653,663,673,683,693,704,714,724,734,744,755,765,775,787,808,819,65535,65535,65535,65535,65535,65535,65535,65535,65535},
{1212,1215,1218,1221,65535,65535,65535,65535,65535,65535,65535,65535,65535,65535,65535,65535,65535,65535,65535,65535,65535,65535,65535,65535,65535,65535,65535,65535,65535,65535,65535,65535,65535,65535,65535,65535,65535,65535,65535,65535,65535,65535,65535,65535,65535,65535,65535,65535},
{832,842,853,863,873,884,894,904,914,925,935,945,955,965,976,986,996,1006,1016,1027,1038,1049,1059,1070,1080,1090,1100,1111,1121,1131,1141,1151,1162,1172,1182,1192,1203,1225,1235,65535,65535,65535,65535,65535,65535,65535,65535,65535},
{1628,1631,1634,1637,65535,65535,65535,65535,65535,65535,65535,65535,65535,65535,65535,65535,65535,65535,65535,65535,65535,65535,65535,65535,65535,65535,65535,65535,65535,65535,65535,65535,65535,65535,65535,65535,65535,65535,65535,65535,65535,65535,65535,65535,65535,65535,65535,65535},
{1248,1259,1269,1279,1290,1300,1310,1320,1330,1341,1351,1361,1371,1381,1392,1402,1412,1422,1432,1443,1454,1465,1476,1486,1496,1506,1516,1527,1537,1547,1557,1567,1578,1588,1598,1608,1619,1641,1651,65535,65535,65535,65535,65535,65535,65535,65535,65535},
{2044,2047,2050,2053,65535,65535,65535,65535,65535,65535,65535,65535,65535,65535,65535,65535,65535,65535,65535,65535,65535,65535,65535,65535,65535,65535,65535,65535,65535,65535,65535,65535,65535,65535,65535,65535,65535,65535,65535,65535,65535,65535,65535,65535,65535,65535,65535,65535},
{1664,1675,1685,1696,1706,1716,1726,1736,1747,1757,1767,1777,1787,1798,1808,1818,1828,1838,1849,1859,1870,1881,1892,1902,1912,1922,1933,1943,1953,1963,1973,1984,1994,2004,2014,2024,2035,2057,2068,65535,65535,65535,65535,65535,65535,65535,65535,65535},
{2460,2463,2466,2469,65535,65535,65535,65535,65535,65535,65535,65535,65535,65535,65535,65535,65535,65535,65535,65535,65535,65535,65535,65535,65535,65535,65535,65535,65535,65535,65535,65535,65535,65535,65535,65535,65535,65535,65535,65535,65535,65535,65535,65535,65535,65535,65535,65535},
{2080,2091,2101,2112,2122,2132,2142,2152,2163,2173,2183,2193,2203,2214,2224,2234,2244,2254,2265,2275,2287,2298,2308,2318,2328,2338,2349,2359,2369,2379,2389,2400,2410,2420,2430,2440,2452,2473,2484,65535,65535,65535,65535,65535,65535,65535,65535,65535},
{2876,2879,2882,2885,65535,65535,65535,65535,65535,65535,65535,65535,65535,65535,65535,65535,65535,65535,65535,65535,65535,65535,65535,65535,65535,65535,65535,65535,65535,65535,65535,65535,65535,65535,65535,65535,65535,65535,65535,65535,65535,65535,65535,65535,65535,65535,65535,65535},
{2496,3335,3345,3355,3365,3375,2558,3396,3406,3416,3426,2609,3447,3457,3467,3477,2660,3498,3508,3518,3520,3529,3539,3549,2744,3570,3580,3590,3600,2795,3621,3631,3641,3651,2846,3672,2870,3705,2902,65535,65535,65535,65535,65535,65535,65535,65535,65535},
{3292,3295,3298,3301,65535,65535,65535,65535,65535,65535,65535,65535,65535,65535,65535,65535,65535,65535,65535,65535,65535,65535,65535,65535,65535,65535,65535,65535,65535,65535,65535,65535,65535,65535,65535,65535,65535,65535,65535,65535,65535,65535,65535,65535,65535,65535,65535,65535},
{2912,2923,2933,3771,3781,3791,2974,2984,2994,3004,3842,3025,3035,3045,3055,3893,3076,3086,3096,3106,3936,3945,3955,3965,3160,3170,3180,3190,4016,3211,3221,3231,3241,4067,3262,3272,3286,3305,3318,65535,65535,65535,65535,65535,65535,65535,65535,65535},
{381,384,387,390,65535,65535,65535,65535,65535,65535,65535,65535,65535,65535,65535,65535,65535,65535,65535,65535,65535,65535,65535,65535,65535,65535,65535,65535,65535,65535,65535,65535,65535,65535,65535,65535,65535,65535,65535,65535,65535,65535,65535,65535,65535,65535,65535,65535},
{1,3751,3761,33,43,53,63,3812,3822,3832,104,114,3863,3873,3883,155,165,3914,3924,3934,207,219,229,239,249,3986,3996,4006,290,300,4037,4047,4057,341,351,4088,372,4121,405,65535,65535,65535,65535,65535,65535,65535,65535,65535},
{797,800,803,806,65535,65535,65535,65535,65535,65535,65535,65535,65535,65535,65535,65535,65535,65535,65535,65535,65535,65535,65535,65535,65535,65535,65535,65535,65535,65535,65535,65535,65535,65535,65535,65535,65535,65535,65535,65535,65535,65535,65535,65535,65535,65535,65535,65535},
{417,427,437,447,457,468,478,488,498,508,519,529,539,549,559,570,580,590,600,610,623,633,643,654,664,674,684,694,705,715,725,735,745,756,766,776,788,809,820,65535,65535,65535,65535,65535,65535,65535,65535,65535},
{1213,1216,1219,1222,65535,65535,65535,65535,65535,65535,65535,65535,65535,65535,65535,65535,65535,65535,65535,65535,65535,65535,65535,65535,65535,65535,65535,65535,65535,65535,65535,65535,65535,65535,65535,65535,65535,65535,65535,65535,65535,65535,65535,65535,65535,65535,65535,65535},
{833,843,854,864,874,885,895,905,915,926,936,946,956,966,977,987,997,1007,1017,1028,1039,1050,1060,1071,1081,1091,1101,1112,1122,1132,1142,1152,1163,1173,1183,1193,1204,1226,1236,65535,65535,65535,65535,65535,65535,65535,65535,65535},
{1629,1632,1635,1638,65535,65535,65535,65535,65535,65535,65535,65535,65535,65535,65535,65535,65535,65535,65535,65535,65535,65535,65535,65535,65535,65535,65535,65535,65535,65535,65535,65535,65535,65535,65535,65535,65535,65535,65535,65535,65535,65535,65535,65535,65535,65535,65535,65535},
{1249,1260,1270,1280,1291,1301,1311,1321,1331,1342,1352,1362,1372,1382,1393,1403,1413,1423,1433,1444,1455,1466,1477,1487,1497,1507,1517,1528,1538,1548,1558,1568,1579,1589,1599,1609,1620,1642,1652,65535,65535,65535,65535,65535,65535,65535,65535,65535},
{2045,2048,2051,2054,65535,65535,65535,65535,65535,65535,65535,65535,65535,65535,65535,65535,65535,65535,65535,65535,65535,65535,65535,65535,65535,65535,65535,65535,65535,65535,65535,65535,65535,65535,65535,65535,65535,65535,65535,65535,65535,65535,65535,65535,65535,65535,65535,65535},
{1665,1676,1686,1697,1707,1717,1727,1737,1748,1758,1768,1778,1788,1799,1809,1819,1829,1839,1850,1860,1871,1882,1893,1903,1913,1923,1934,1944,1954,1964,1974,1985,1995,2005,2015,2025,2036,2058,2069,65535,65535,65535,65535,65535,65535,65535,65535,65535},
{2461,2464,2467,2470,65535,65535,65535,65535,65535,65535,65535,65535,65535,65535,65535,65535,65535,65535,65535,65535,65535,65535,65535,65535,65535,65535,65535,65535,65535,65535,65535,65535,65535,65535,65535,65535,65535,65535,65535,65535,65535,65535,65535,65535,65535,65535,65535,65535},
{2081,2092,2102,2113,2123,2133,2143,2153,2164,2174,2184,2194,2204,2215,2225,2235,2245,2255,2266,2276,2288,2299,2309,2319,2329,2339,2350,2360,2370,2380,2390,2401,2411,2421,2431,2441,2453,2474,2485,65535,65535,65535,65535,65535,65535,65535,65535,65535},
{2877,2880,2883,2886,65535,65535,65535,65535,65535,65535,65535,65535,65535,65535,65535,65535,65535,65535,65535,65535,65535,65535,65535,65535,65535,65535,65535,65535,65535,65535,65535,65535,65535,65535,65535,65535,65535,65535,65535,65535,65535,65535,65535,65535,65535,65535,65535,65535},
{2497,2508,2518,2528,3366,3376,2559,2569,2579,2589,3427,2610,2620,2630,2640,3478,2661,2671,2681,2691,2705,3530,3540,3550,2745,2755,2765,2775,3601,2796,2806,2816,2826,3652,2847,2857,2871,2890,2903,65535,65535,65535,65535,65535,65535,65535,65535,65535},
{3293,3296,3299,3302,65535,65535,65535,65535,65535,65535,65535,65535,65535,65535,65535,65535,65535,65535,65535,65535,65535,65535,65535,65535,65535,65535,65535,65535,65535,65535,65535,65535,65535,65535,65535,65535,65535,65535,65535,65535,65535,65535,65535,65535,65535,65535,65535,65535},
{2913,2924,2934,2944,2954,2964,3802,2985,2995,3005,3015,3853,3036,3046,3056,3066,3904,3087,3097,3107,3121,3130,3140,3150,3976,3171,3181,3191,3201,4027,3222,3232,3242,3252,4078,3273,3287,3306,3319,65535,65535,65535,65535,65535,65535,65535,65535,65535},
{382,385,388,391,65535,65535,65535,65535,65535,65535,65535,65535,65535,65535,65535,65535,65535,65535,65535,65535,65535,65535,65535,65535,65535,65535,65535,65535,65535,65535,65535,65535,65535,65535,65535,65535,65535,65535,65535,65535,65535,65535,65535,65535,65535,65535,65535,65535},
{2,13,23,3356,3782,3792,64,3397,3407,3417,3843,115,3448,3458,3468,3894,166,3499,3509,3519,209,3946,3956,3966,250,3571,3581,3591,4017,301,3622,3632,3642,4068,352,3673,374,3706,407,65535,65535,65535,65535,65535,65535,65535,65535,65535},
{798,801,804,807,65535,65535,65535,65535,65535,65535,65535,65535,65535,65535,65535,65535,65535,65535,65535,65535,65535,65535,65535,65535,65535,65535,65535,65535,65535,65535,65535,65535,65535,65535,65535,65535,65535,65535,65535,65535,65535,65535,65535,65535,65535,65535,65535,65535},
{418,428,438,448,458,469,479,489,499,509,520,530,540,550,560,571,581,591,601,611,624,634,644,655,665,675,685,695,706,716,726,736,746,757,767,777,789,810,821,65535,65535,65535,65535,65535,65535,65535,65535,65535},
{1214,1217,1220,1223,65535,65535,65535,65535,65535,65535,65535,65535,65535,65535,65535,65535,65535,65535,65535,65535,65535,65535,65535,65535,65535,65535,65535,65535,65535,65535,65535,65535,65535,65535,65535,65535,65535,65535,65535,65535,65535,65535,65535,65535,65535,65535,65535,65535},
{834,844,855,865,875,886,896,906,916,3833,937,947,957,967,3884,988,998,1008,1018,3935,1040,1051,1061,1072,1082,1092,1102,4007,1123,1133,1143,1153,4058,1174,1184,1194,1205,1227,1237,65535,65535,65535,65535,65535,65535,65535,65535,65535},
{1630,1633,1636,1639,65535,65535,65535,65535,65535,65535,65535,65535,65535,65535,65535,65535,65535,65535,65535,65535,65535,65535,65535,65535,65535,65535,65535,65535,65535,65535,65535,65535,65535,65535,65535,65535,65535,65535,65535,65535,65535,65535,65535,65535,65535,65535,65535,65535},
{1250,1261,1271,1281,1292,1302,1312,1322,1332,1343,1353,1363,1373,1383,1394,1404,1414,1424,1434,1445,1456,1467,1478,1488,1498,1508,1518,1529,1539,1549,1559,1569,1580,1590,1600,1610,1621,1643,1653,65535,65535,65535,65535,65535,65535,65535,65535,65535},
{2046,2049,2052,2055,65535,65535,65535,65535,65535,65535,65535,65535,65535,65535,65535,65535,65535,65535,65535,65535,65535,65535,65535,65535,65535,65535,65535,65535,65535,65535,65535,65535,65535,65535,65535,65535,65535,65535,65535,65535,65535,65535,65535,65535,65535,65535,65535,65535},
{1666,1677,1687,3772,1708,1718,1728,1738,1749,1759,1769,1779,1789,1800,1810,1820,1830,1840,1851,1861,1872,1883,1894,1904,1914,1924,1935,1945,1955,1965,1975,1986,1996,2006,2016,2026,2037,2059,2070,65535,65535,65535,65535,65535,65535,65535,65535,65535},
{2462,2465,2468,2471,65535,65535,65535,65535,65535,65535,65535,65535,65535,65535,65535,65535,65535,65535,65535,65535,65535,65535,65535,65535,65535,65535,65535,65535,65535,65535,65535,65535,65535,65535,65535,65535,65535,65535,65535,65535,65535,65535,65535,65535,65535,65535,65535,65535},
{2082,2093,2103,2114,2124,2134,2144,2154,2165,2175,2185,2195,2205,2216,2226,2236,2246,2256,2267,2277,2289,2300,2310,2320,2330,2340,2351,2361,2371,2381,2391,2402,2412,2422,2432,2442,2454,2475,2486,65535,65535,65535,65535,65535,65535,65535,65535,65535},
{2878,2881,2884,2887,65535,65535,65535,65535,65535,65535,65535,65535,65535,65535,65535,65535,65535,65535,65535,65535,65535,65535,65535,65535,65535,65535,65535,65535,65535,65535,65535,65535,65535,65535,65535,65535,65535,65535,65535,65535,65535,65535,65535,65535,65535,65535,65535,65535},
{2498,3336,3346,2529,2539,2549,3387,2570,2580,2590,2600,3438,2621,2631,2641,2651,3489,2672,2682,2692,3521,2715,2725,2735,3561,2756,2766,2776,2786,3612,2807,2817,2827,2837,3663,2858,2872,2891,2904,65535,65535,65535,65535,65535,65535,65535,65535,65535},
{3294,3297,3300,3303,65535,65535,65535,65535,65535,65535,65535,65535,65535,65535,65535,65535,65535,65535,65535,65535,65535,65535,65535,65535,65535,65535,65535,65535,65535,65535,65535,65535,65535,65535,65535,65535,65535,65535,65535,65535,65535,65535,65535,65535,65535,65535,65535,65535},
{2914,3752,3762,2945,2955,2965,2975,3813,3823,3006,3016,3026,3864,3874,3057,3067,3077,3915,3925,3108,3937,3131,3141,3151,3161,3987,3997,3192,3202,3212,4038,4048,3243,3253,3263,4089,3288,4122,3320,65535,65535,65535,65535,65535,65535,65535,65535,65535},
{3,14,24,35,45,55,2976,3814,3824,96,106,3027,3865,3875,147,157,3078,3916,3926,198,211,221,231,241,3162,3988,3998,282,292,3213,4039,4049,333,343,3264,4090,376,4123,409,65535,65535,65535,65535,65535,65535,65535,65535,65535},
{4,3337,3763,34,44,54,65,75,85,95,105,116,126,136,146,156,167,177,187,197,210,220,230,240,251,261,271,281,291,302,312,322,332,342,353,363,375,396,408,65535,65535,65535,65535,65535,65535,65535,65535,65535},
{419,429,439,449,459,470,480,490,500,510,521,531,541,551,561,572,582,592,602,612,625,635,645,656,666,676,686,696,707,717,727,737,747,758,768,778,790,811,822,65535,65535,65535,65535,65535,65535,65535,65535,65535},
{420,430,440,450,460,471,481,491,501,511,522,532,542,552,562,573,583,593,603,613,626,636,646,657,667,677,687,697,708,718,728,738,748,759,769,779,791,812,823,65535,65535,65535,65535,65535,65535,65535,65535,65535},
{835,845,856,866,876,887,897,907,917,927,938,948,958,968,978,989,999,1009,1019,1029,1041,1052,1062,1073,1083,1093,1103,1113,1124,1134,1144,1154,1164,1175,1185,1195,1206,1228,1238,65535,65535,65535,65535,65535,65535,65535,65535,65535},
{836,846,857,867,877,2550,3388,908,918,928,2601,3439,959,969,979,2652,3490,1010,1020,1030,1042,1053,1063,2736,3562,1094,1104,1114,2787,3613,1145,1155,1165,2838,3664,1196,1207,1229,1239,65535,65535,65535,65535,65535,65535,65535,65535,65535},
{1251,1262,1272,1282,1293,1303,1313,1323,1333,1344,1354,1364,1374,1384,1395,1405,1415,1425,1435,1446,1457,1468,1479,1489,1499,1509,1519,1530,1540,1550,1560,1570,1581,1591,1601,1611,1622,1644,1654,65535,65535,65535,65535,65535,65535,65535,65535,65535},
{1252,3753,1273,1283,2540,2966,3804,1324,1334,2591,3017,3855,1375,1385,2642,3068,3906,1426,1436,1447,1458,1469,2726,3152,3978,1510,1520,2777,3203,4029,1561,1571,2828,3254,4080,1612,1623,1645,1655,65535,65535,65535,65535,65535,65535,65535,65535,65535},
{1667,1678,1688,1698,1709,1719,1729,1739,1750,1760,1770,1780,1790,1801,1811,1821,1831,1841,1852,1862,1873,1884,1895,1905,1915,1925,1936,1946,1956,1966,1976,1987,1997,2007,2017,2027,2038,2060,2071,65535,65535,65535,65535,65535,65535,65535,65535,65535},
{1668,1679,1689,1699,2956,3378,1730,1740,2581,3007,3429,1781,1791,2632,3058,3480,1832,1842,2683,1863,1874,1885,3142,3552,1916,1926,2767,3193,3603,1967,1977,2818,3244,3654,2018,2028,2039,2061,2072,65535,65535,65535,65535,65535,65535,65535,65535,65535},
{2083,2094,2104,2115,2125,2135,2145,2155,2166,2176,2186,2196,2206,2217,2227,2237,2247,2257,2268,2278,2290,2301,2311,2321,2331,2341,2352,2362,2372,2382,2392,2403,2413,2423,2433,2443,2455,2476,2487,65535,65535,65535,65535,65535,65535,65535,65535,65535},
{2084,2095,2105,2530,3368,3794,2146,2156,2997,3419,3845,2197,2207,3048,3470,3896,2248,2258,3099,2279,2291,2716,3542,3968,2332,2342,3183,3593,4019,2383,2393,3234,3644,4070,2434,2444,2456,2477,2488,65535,65535,65535,65535,65535,65535,65535,65535,65535},
{3676,3679,3682,3685,3688,65535,65535,65535,65535,65535,65535,65535,65535,65535,65535,65535,65535,65535,65535,65535,65535,65535,65535,65535,65535,65535,65535,65535,65535,65535,65535,65535,65535,65535,65535,65535,65535,65535,65535,65535,65535,65535,65535,65535,65535,65535,65535,65535},
{2499,2509,2519,3357,3367,3377,2560,3398,3408,3418,3428,2611,3449,3459,3469,3479,2662,3500,3510,2693,2706,3531,3541,3551,2746,3572,3582,3592,3602,2797,3623,3633,3643,3653,2848,3674,2873,3707,2905,65535,65535,65535,65535,65535,65535,65535,65535,65535},
{4092,4095,4098,4101,4104,65535,65535,65535,65535,65535,65535,65535,65535,65535,65535,65535,65535,65535,65535,65535,65535,65535,65535,65535,65535,65535,65535,65535,65535,65535,65535,65535,65535,65535,65535,65535,65535,65535,65535,65535,65535,65535,65535,65535,65535,65535,65535,65535},
{2915,2925,2935,3773,3783,3793,3803,2986,2996,3834,3844,3854,3037,3047,3885,3895,3905,3088,3098,3109,3122,3947,3957,3967,3977,3172,3182,4008,4018,4028,3223,3233,4059,4069,4079,3274,3289,3307,3321,65535,65535,65535,65535,65535,65535,65535,65535,65535},
{421,431,441,451,461,472,482,492,502,512,523,533,543,553,563,574,584,594,604,614,627,637,647,658,668,678,688,698,709,719,729,739,749,760,770,780,792,813,824,65535,65535,65535,65535,65535,65535,65535,65535,65535},
{2500,2510,2520,2946,3784,2551,2561,2571,3409,3835,2602,2612,2622,3460,3886,2653,2663,2673,3511,615,3522,3132,3958,2737,2747,2757,3583,4009,2788,2798,2808,3634,4060,2839,2849,2859,793,2892,825,65535,65535,65535,65535,65535,65535,65535,65535,65535},
{837,847,2936,3358,878,888,898,2987,3825,929,939,949,3038,3876,980,990,1000,3089,3927,1031,1043,3532,1064,1074,1084,3173,3999,1115,1125,1135,3224,4050,1166,1176,1186,3275,1208,3308,1240,65535,65535,65535,65535,65535,65535,65535,65535,65535},
{2916,2926,3348,3774,2541,2967,2977,3399,919,2592,3018,3028,3450,970,2643,3069,3079,3501,1021,2694,3938,3948,2727,3153,3163,3573,1105,2778,3204,3214,3624,1156,2829,3255,3265,3675,1209,3708,1241,65535,65535,65535,65535,65535,65535,65535,65535,65535},
{1253,1263,3764,1284,3785,1305,1315,1325,3410,3836,1356,1366,1376,3461,3887,1407,1417,1427,3512,1448,1460,3533,3959,1491,1501,1511,3584,4010,1542,1552,1562,3635,4061,1593,1603,1613,1625,1646,1657,65535,65535,65535,65535,65535,65535,65535,65535,65535},
{3328,3338,1274,2531,1294,1304,1314,3815,1335,1345,1355,1365,3866,1386,1396,1406,1416,3917,1437,3110,1459,1470,1480,1490,1500,3989,1521,1531,1541,1551,4040,1572,1582,1592,1602,4091,1624,4124,1656,65535,65535,65535,65535,65535,65535,65535,65535,65535},
{1669,3754,1690,1700,1710,1720,1731,1741,1751,1761,1771,1782,1792,1802,1812,1822,1833,1843,1853,1864,1875,1886,1896,1906,1917,1927,1937,1947,1957,1968,1978,1988,1998,2008,2019,2029,2040,2062,2073,65535,65535,65535,65535,65535,65535,65535,65535,65535},
{3744,1680,3349,3775,1711,1721,2562,3400,3826,1762,1772,2613,3451,3877,1813,1823,2664,3502,3928,1865,1876,3949,1897,1907,2748,3574,4000,1948,1958,2799,3625,4051,1999,2009,2850,2030,2041,3709,2074,65535,65535,65535,65535,65535,65535,65535,65535,65535},
{2085,2096,3765,2117,2127,2137,2978,3816,2168,2178,2188,3029,3867,2219,2229,2239,3080,3918,2270,2281,3523,2303,2313,2323,3164,3990,2354,2364,2374,3215,4041,2405,2415,2425,3266,2446,2458,4125,2490,65535,65535,65535,65535,65535,65535,65535,65535,65535},
{2086,2511,2106,2116,2126,2136,2147,2157,2167,2177,2187,2198,2208,2218,2228,2238,2249,2259,2269,2280,2292,2302,2312,2322,2333,2343,2353,2363,2373,2384,2394,2404,2414,2424,2435,2445,2457,2478,2489,65535,65535,65535,65535,65535,65535,65535,65535,65535},
{3677,3680,3683,3686,3689,65535,65535,65535,65535,65535,65535,65535,65535,65535,65535,65535,65535,65535,65535,65535,65535,65535,65535,65535,65535,65535,65535,65535,65535,65535,65535,65535,65535,65535,65535,65535,65535,65535,65535,65535,65535,65535,65535,65535,65535,65535,65535,65535},
{2501,3339,2521,3359,3369,3379,3389,2572,2582,3420,3430,3440,2623,2633,3471,3481,3491,2674,2684,2695,2707,2717,3543,3553,3563,2758,2768,3594,3604,3614,2809,2819,3645,3655,3665,2860,2874,2893,2906,65535,65535,65535,65535,65535,65535,65535,65535,65535},
{4093,4096,4099,4102,4105,65535,65535,65535,65535,65535,65535,65535,65535,65535,65535,65535,65535,65535,65535,65535,65535,65535,65535,65535,65535,65535,65535,65535,65535,65535,65535,65535,65535,65535,65535,65535,65535,65535,65535,65535,65535,65535,65535,65535,65535,65535,65535,65535},
{2917,2927,2937,2947,2957,3795,3805,2988,2998,3008,3846,3856,3039,3049,3059,3897,3907,3090,3100,3111,3123,3133,3143,3969,3979,3174,3184,3194,4020,4030,3225,3235,3245,4071,4081,3276,3290,3309,3322,65535,65535,65535,65535,65535,65535,65535,65535,65535},
{422,432,443,453,463,2552,3390,494,504,514,2603,3441,545,555,565,2654,3492,596,606,617,3939,639,649,2738,3564,680,690,700,2789,3615,731,741,751,2840,3666,782,795,815,827,65535,65535,65535,65535,65535,65535,65535,65535,65535},
{3329,3755,442,452,462,473,483,493,503,513,524,534,544,554,564,575,585,595,605,616,628,638,648,659,669,679,689,699,710,720,730,740,750,761,771,781,794,814,826,65535,65535,65535,65535,65535,65535,65535,65535,65535},
{838,848,858,868,879,889,899,909,920,930,940,950,960,971,981,991,1001,1011,1022,1032,1044,1054,1065,1075,1085,1095,1106,1116,1126,1136,1146,1157,1167,1177,1187,1197,1210,1230,1242,65535,65535,65535,65535,65535,65535,65535,65535,65535},
{3745,849,859,869,2542,2968,3806,910,2583,2593,3019,3857,961,2634,2644,3070,3908,1012,2685,1033,1045,1055,2728,3154,3980,1096,2769,2779,3205,4031,1147,2820,2830,3256,4082,1198,1211,1231,1243,65535,65535,65535,65535,65535,65535,65535,65535,65535},
{1254,1264,1275,1285,1295,3380,1316,1326,1336,1346,3431,1367,1377,1387,1397,3482,1418,1428,1438,1449,1461,1471,1481,3554,1502,1512,1522,1532,3605,1553,1563,1573,1583,3656,1604,1614,1626,1647,1658,65535,65535,65535,65535,65535,65535,65535,65535,65535},
{1255,1265,2522,2532,2958,3796,2563,2573,2999,3009,3847,2614,2624,3050,3060,3898,2665,2675,3101,2696,2708,2718,3144,3970,2749,2759,3185,3195,4021,2800,2810,3236,3246,4072,2851,2861,1627,2894,1659,65535,65535,65535,65535,65535,65535,65535,65535,65535},
{1670,1681,1691,1701,3370,1722,1732,1742,1752,3421,1773,1783,1793,1803,3472,1824,1834,1844,1854,3112,1877,1887,3544,1908,1918,1928,1938,3595,1959,1969,1979,1989,3646,2010,2020,3277,2042,2063,2075,65535,65535,65535,65535,65535,65535,65535,65535,65535},
{1671,2512,2938,2948,3786,2553,2979,2989,3411,3837,2604,3030,3040,3462,3888,2655,3081,3091,3513,1866,3124,3134,3960,2739,3165,3175,3585,4011,2790,3216,3226,3636,4062,2841,3267,2031,2043,3310,2076,65535,65535,65535,65535,65535,65535,65535,65535,65535},
{2087,2097,2107,3360,2128,2139,2149,2159,2169,3422,2190,2200,2210,2220,3473,2241,2251,2261,2271,2283,2294,2304,3545,2325,2335,2345,2355,3596,2376,2386,2396,2406,3647,2427,2437,2448,3691,2480,2492,65535,65535,65535,65535,65535,65535,65535,65535,65535},
{2502,2928,3350,3776,2543,2138,2148,2158,3827,2179,2189,2199,2209,3878,2230,2240,2250,2260,3929,2282,2293,3534,2314,2324,2334,2344,4001,2365,2375,2385,2395,4052,2416,2426,2436,2447,2459,2479,2491,65535,65535,65535,65535,65535,65535,65535,65535,65535},
{3678,3681,3684,3687,3690,65535,65535,65535,65535,65535,65535,65535,65535,65535,65535,65535,65535,65535,65535,65535,65535,65535,65535,65535,65535,65535,65535,65535,65535,65535,65535,65535,65535,65535,65535,65535,65535,65535,65535,65535,65535,65535,65535,65535,65535,65535,65535,65535},
{3330,3340,2523,2533,3371,3381,3391,3401,2584,2594,3432,3442,3452,2635,2645,3483,3493,3503,2686,2697,3524,2719,2729,3555,3565,3575,2770,2780,3606,3616,3626,2821,2831,3657,3667,2862,2875,3710,2907,65535,65535,65535,65535,65535,65535,65535,65535,65535},
{4094,4097,4100,4103,4106,65535,65535,65535,65535,65535,65535,65535,65535,65535,65535,65535,65535,65535,65535,65535,65535,65535,65535,65535,65535,65535,65535,65535,65535,65535,65535,65535,65535,65535,65535,65535,65535,65535,65535,65535,65535,65535,65535,65535,65535,65535,65535,65535},
{2918,3756,3766,2949,2959,2969,3807,3817,3000,3010,3020,3858,3868,3051,3061,3071,3909,3919,3102,3113,3940,3950,3145,3155,3981,3991,3186,3196,3206,4032,4042,3237,3247,3257,4083,3278,3291,4126,3323,65535,65535,65535,65535,65535,65535,65535,65535,65535},
{423,433,444,3361,465,475,485,2574,3412,516,526,536,2625,3463,567,577,587,2676,3514,619,630,3535,651,661,671,2760,3586,702,712,722,2811,3637,753,763,773,784,3693,2895,829,65535,65535,65535,65535,65535,65535,65535,65535,65535},
{3746,434,2939,454,464,474,484,495,505,515,525,535,546,556,566,576,586,597,607,618,629,640,650,660,670,681,691,701,711,721,732,742,752,762,772,783,3692,816,828,65535,65535,65535,65535,65535,65535,65535,65535,65535},
{839,850,860,871,881,891,901,3402,922,932,942,952,3453,973,983,993,1003,3504,1024,1035,2709,3951,1067,1077,1087,3576,1108,1118,1128,1138,3627,1159,1169,1179,1189,1200,4109,3711,1245,65535,65535,65535,65535,65535,65535,65535,65535,65535},
{840,2513,3351,870,880,890,900,911,921,931,941,951,962,972,982,992,1002,1013,1023,1034,1046,1056,1066,1076,1086,1097,1107,1117,1127,1137,1148,1158,1168,1178,1188,1199,4108,1232,1244,65535,65535,65535,65535,65535,65535,65535,65535,65535},
{1256,3341,1277,1286,1296,1306,1317,1327,1337,1347,1357,1368,1378,1388,1398,1408,1419,1429,1439,1450,1462,1472,1482,1492,1503,1513,1523,1533,1543,1554,1564,1574,1584,1594,1605,1615,3694,1648,1660,65535,65535,65535,65535,65535,65535,65535,65535,65535},
{2503,1266,1276,1287,1297,1307,2564,3818,1338,1348,1358,2615,3869,1389,1399,1409,2666,3920,1440,1451,3525,1473,1483,1493,2750,3992,1524,1534,1544,2801,4043,1575,1585,1595,2852,1616,4110,4127,1661,65535,65535,65535,65535,65535,65535,65535,65535,65535},
{1672,3757,1693,1702,1712,1723,1733,1743,1753,1763,1774,1784,1794,1804,1814,1825,1835,1845,1855,1867,1878,1888,1898,1909,1919,1929,1939,1949,1960,1970,1980,1990,2000,2011,2021,2032,3695,2064,2077,65535,65535,65535,65535,65535,65535,65535,65535,65535},
{2919,1682,1692,1703,1713,2554,3392,1744,1754,1764,2605,3443,1795,1805,1815,2656,3494,1846,1856,2698,3941,1889,1899,2740,3566,1930,1940,1950,2791,3617,1981,1991,2001,2842,3668,2863,4111,2065,2908,65535,65535,65535,65535,65535,65535,65535,65535,65535},
{2088,2099,2109,2118,2129,2970,3808,2160,2170,2180,3021,3859,2211,2221,2231,3072,3910,2262,2272,2284,2295,2305,2315,3156,3982,2346,2356,2366,3207,4033,2397,2407,2417,3258,4084,2449,3696,2481,2493,65535,65535,65535,65535,65535,65535,65535,65535,65535},
{3331,2098,2108,2119,2544,3382,2150,2575,2585,2595,3433,2201,2626,2636,2646,3484,2252,2677,2687,2699,2710,2720,2730,3556,2336,2761,2771,2781,3607,2387,2812,2822,2832,3658,2438,2864,4112,2896,2494,65535,65535,65535,65535,65535,65535,65535,65535,65535},
{2504,2514,2524,2534,3372,2555,2565,3403,3413,3423,2606,2616,3454,3464,3474,2657,2667,3505,3515,2700,3526,3536,3546,2741,2751,3577,3587,3597,2792,2802,3628,3638,3648,2843,2853,2865,3697,2897,2909,65535,65535,65535,65535,65535,65535,65535,65535,65535},
{3332,3342,3352,3362,2545,3383,3393,2576,2586,2596,3434,3444,2627,2637,2647,3485,3495,2678,2688,3115,2711,2721,2731,3557,3567,2762,2772,2782,3608,3618,2813,2823,2833,3659,3669,3280,3698,3312,2910,65535,65535,65535,65535,65535,65535,65535,65535,65535},
{3747,2929,3767,3777,3787,3797,2980,2990,3828,3838,3848,3031,3041,3879,3889,3899,3082,3092,3930,3114,3125,3135,3961,3971,3166,3176,4002,4012,4022,3217,3227,4053,4063,4073,3268,3279,4107,3311,3324,65535,65535,65535,65535,65535,65535,65535,65535,65535},
{2920,2930,2940,2950,2960,3798,2981,2991,3001,3011,3849,3032,3042,3052,3062,3900,3083,3093,3103,3116,3126,3136,3146,3972,3167,3177,3187,3197,4023,3218,3228,3238,3248,4074,3269,3281,4113,3313,3325,65535,65535,65535,65535,65535,65535,65535,65535,65535},
{424,435,445,455,3788,476,486,496,506,3839,527,537,547,557,3890,578,588,598,608,620,631,641,3962,662,672,682,692,4013,713,723,733,743,4064,764,774,785,4114,817,830,65535,65535,65535,65535,65535,65535,65535,65535,65535},
{425,3758,3768,3778,466,2971,3809,3819,3829,517,3022,3860,3870,3880,568,3073,3911,3921,3931,621,3942,3952,652,3157,3983,3993,4003,703,3208,4034,4044,4054,754,3259,4085,786,3699,818,831,65535,65535,65535,65535,65535,65535,65535,65535,65535},
{841,851,861,872,882,892,902,912,923,933,943,953,963,974,984,994,1004,1014,1025,1036,1047,1057,1068,1078,1088,1098,1109,1119,1129,1139,1149,1160,1170,1180,1190,1201,4117,1233,1246,65535,65535,65535,65535,65535,65535,65535,65535,65535},
{3748,852,862,3363,883,893,903,913,924,934,944,954,964,975,985,995,1005,1015,1026,1037,1048,1058,1069,1079,1089,1099,1110,1120,1130,1140,1150,1161,1171,1181,1191,1202,1224,1234,1247,65535,65535,65535,65535,65535,65535,65535,65535,65535},
{1257,1267,1278,1288,1298,1308,1318,1328,1339,1349,1359,1369,1379,1390,1400,1410,1420,1430,1441,1452,1463,1474,1484,1494,1504,1514,1525,1535,1545,1555,1565,1576,1586,1596,1606,1617,3702,1649,1662,65535,65535,65535,65535,65535,65535,65535,65535,65535},
{1258,1268,3353,1289,1299,1309,1319,1329,1340,1350,1360,1370,1380,1391,1401,1411,1421,1431,1442,1453,1464,1475,1485,1495,1505,1515,1526,1536,1546,1556,1566,1577,1587,1597,1607,1618,1640,1650,1663,65535,65535,65535,65535,65535,65535,65535,65535,65535},
{1673,1683,1694,1704,1714,1724,1734,1745,1755,1765,1775,1785,1796,1806,1816,1826,1836,1847,1857,1868,1879,1890,1900,1910,1920,1931,1941,1951,1961,1971,1982,1992,2002,2012,2022,2033,4118,2066,2078,65535,65535,65535,65535,65535,65535,65535,65535,65535},
{1674,1684,1695,1705,1715,1725,1735,1746,1756,1766,1776,1786,1797,1807,1817,1827,1837,1848,1858,1869,1880,1891,1901,1911,1921,1932,1942,1952,1962,1972,1983,1993,2003,2013,2023,2034,2056,2067,2079,65535,65535,65535,65535,65535,65535,65535,65535,65535},
{2089,2100,2111,2121,2131,2141,3394,2162,2172,2182,2192,3445,2213,2223,2233,2243,3496,2264,2274,2286,2297,2307,2317,2327,3568,2348,2358,2368,2378,3619,2399,2409,2419,2429,3670,2451,3703,2483,415,65535,65535,65535,65535,65535,65535,65535,65535,65535},
{2090,2515,2110,2120,2130,2140,2151,2161,2171,2181,2191,2202,2212,2222,2232,2242,2253,2263,2273,2285,2296,2306,2316,2326,2337,2347,2357,2367,2377,2388,2398,2408,2418,2428,2439,2450,2472,2482,2495,65535,65535,65535,65535,65535,65535,65535,65535,65535},
{2505,3343,2525,2535,3373,2556,2566,3404,3414,3424,2607,2617,3455,3465,3475,2658,2668,3506,3516,2701,3527,3537,3547,2742,2752,3578,3588,3598,2793,2803,3629,3639,3649,2844,2854,2866,3700,2898,2911,65535,65535,65535,65535,65535,65535,65535,65535,65535},
{3333,2516,2526,2536,2546,3384,2567,2577,2587,2597,3435,2618,2628,2638,2648,3486,2669,2679,2689,2702,2712,2722,2732,3558,2753,2763,2773,2783,3609,2804,2814,2824,2834,3660,2855,2867,2888,2899,65535,65535,65535,65535,65535,65535,65535,65535,65535,65535},
{2921,2931,2941,2951,2961,3799,2982,2992,3002,3012,3850,3033,3043,3053,3063,3901,3084,3094,3104,3117,3127,3137,3147,3973,3168,3178,3188,3198,4024,3219,3229,3239,3249,4075,3270,3282,4115,3314,3326,65535,65535,65535,65535,65535,65535,65535,65535,65535},
{3749,3759,3769,3779,3789,2972,3810,3820,3830,3840,3023,3861,3871,3881,3891,3074,3912,3922,3932,3118,3943,3953,3963,3158,3984,3994,4004,4014,3209,4035,4045,4055,4065,3260,4086,3283,4116,3315,3327,65535,65535,65535,65535,65535,65535,65535,65535,65535},
{2506,3344,3354,3364,3374,2557,3395,3405,3415,3425,2608,3446,3456,3466,3476,2659,3497,3507,3517,2703,3528,3538,3548,2743,3569,3579,3589,3599,2794,3620,3630,3640,3650,2845,3671,2868,3704,2900,65535,65535,65535,65535,65535,65535,65535,65535,65535,65535},
{3334,2517,2527,2537,2547,3385,2568,2578,2588,2598,3436,2619,2629,2639,2649,3487,2670,2680,2690,2704,2713,2723,2733,3559,2754,2764,2774,2784,3610,2805,2815,2825,2835,3661,2856,2869,4119,2901,65535,65535,65535,65535,65535,65535,65535,65535,65535,65535},
{2922,2932,2942,2952,2962,3800,2983,2993,3003,3013,3851,3034,3044,3054,3064,3902,3085,3095,3105,3119,3128,3138,3148,3974,3169,3179,3189,3199,4025,3220,3230,3240,3250,4076,3271,3284,3304,3316,65535,65535,65535,65535,65535,65535,65535,65535,65535,65535},
{3750,3760,3770,3780,3790,2973,3811,3821,3831,3841,3024,3862,3872,3882,3892,3075,3913,3923,3933,3120,3944,3954,3964,3159,3985,3995,4005,4015,3210,4036,4046,4056,4066,3261,4087,3285,4120,3317,65535,65535,65535,65535,65535,65535,65535,65535,65535,65535},
{5,15,25,36,46,56,66,76,86,97,107,117,127,137,148,158,168,178,188,199,212,222,232,242,252,262,272,283,293,303,313,323,334,344,354,364,377,397,410,65535,65535,65535,65535,65535,65535,65535,65535,65535},
{6,16,26,37,47,57,67,77,87,98,108,118,128,138,149,159,169,179,189,200,213,223,233,243,253,263,273,284,294,304,314,324,335,345,355,365,378,398,411,65535,65535,65535,65535,65535,65535,65535,65535,65535},
{7,17,27,38,48,58,68,78,88,99,109,119,129,139,150,160,170,180,190,201,214,224,234,244,254,264,274,285,295,305,315,325,336,346,356,366,379,399,412,65535,65535,65535,65535,65535,65535,65535,65535,65535},
{8,18,28,39,49,59,69,79,89,100,110,120,130,140,151,161,171,181,191,202,215,225,235,245,255,265,275,286,296,306,316,326,337,347,357,367,3701,400,413,65535,65535,65535,65535,65535,65535,65535,65535,65535},
{9,19,29,40,50,60,70,80,90,101,111,121,131,141,152,162,172,182,192,203,216,226,236,246,256,266,276,287,297,307,317,327,338,348,358,368,392,401,414,65535,65535,65535,65535,65535,65535,65535,65535,65535},
{10,20,30,41,51,61,71,81,91,102,112,122,132,142,153,163,173,183,193,204,217,227,237,247,257,267,277,288,298,308,318,328,339,349,359,369,393,402,65535,65535,65535,65535,65535,65535,65535,65535,65535,65535},
{11,21,31,42,52,62,72,82,92,103,113,123,133,143,154,164,174,184,194,205,218,228,238,248,258,268,278,289,299,309,319,329,340,350,360,370,394,403,65535,65535,65535,65535,65535,65535,65535,65535,65535,65535},
{12,3347,32,2538,2548,3386,74,84,94,2599,3437,125,135,145,2650,3488,176,186,196,208,2714,2724,2734,3560,260,270,280,2785,3611,311,321,331,2836,3662,362,373,395,406,65535,65535,65535,65535,65535,65535,65535,65535,65535,65535},
};

#define TABLED 1
#define TRIG 7
#define JB 22
#define PRE 2
#define CH 64
#define FIRST 4
constexpr int NG = SCHED_NG, NCONV = 3 * NG;
constexpr int RING = SCHED_RING;
constexpr int NSLOT = 8;
constexpr int PLEN = SCHED_LE, LM = 256 - 2 * PLEN, NSEG = 4 / (NG - 8), LMID = NSEG * LM;
static_assert(LMID <= PLEN && NG == 10, "geometry");
constexpr int TILEB = 12288;
constexpr int SLOTB = 280 * 64;
constexpr int W1S = 0, W2S = 73728, ABUF = 147456, XBUF = ABUF + 16 * 3072, MISC = XBUF + 8 * 3072;
constexpr int WBAR = MISC + 2560;
constexpr int RBUF = ABUF - 4 * SLOTB;
constexpr int CM = MISC + 2816, CTAB = CM + 256;
constexpr int SMEM_BYTES = CTAB + (PLEN + 16) * 16;
static_assert(RBUF % 512 == 0 && RBUF >= W2S && RBUF + NSLOT * SLOTB + 128 <= MISC && SMEM_BYTES <= 232448, "smem layout");

struct Globals {
  unsigned char scratch[RING * NG * 4 * TILEB];
  unsigned char wimg[147456];
  uint32_t wflag[32];
  uint32_t ready[NG * PLEN + 1];
  uint32_t cons[NG * PLEN];
  uint32_t epoch[1024];
};
__device__ __align__(1024) Globals g_state;

#define GELU_C3 0.32920349f
#define GELU_A2 0x40d940d9u
#define GELU_S2 0x3e133e13u
#define SCHED_FENCE() asm volatile("pmevent 0;" ::: "memory")
#define SPIN_LIMIT 0x1000000

__device__ __forceinline__ uint32_t smem_u32(const void* p) { return (uint32_t)__cvta_generic_to_shared(p); }
__device__ __forceinline__ void wg_fence() { asm volatile("wgmma.fence.sync.aligned;" ::: "memory"); }
__device__ __forceinline__ void wg_commit() { asm volatile("wgmma.commit_group.sync.aligned;" ::: "memory"); }
template <int N> __device__ __forceinline__ void wg_wait() { asm volatile("wgmma.wait_group.sync.aligned %0;" ::"n"(N) : "memory"); }
__device__ __forceinline__ void mbar_wait(uint32_t bar, uint32_t parity) {
  asm volatile("{\n.reg .pred p;\n.reg .u32 c;\nmbarrier.try_wait.parity.shared::cta.b64 p, [%0], %1;\n@p bra DONE_%=;\nmov.u32 c, 0;\nWAIT_%=:\nmbarrier.try_wait.parity.shared::cta.b64 p, [%0], %1;\n@p bra DONE_%=;\n"
               "add.u32 c, c, 1;\nsetp.lt.u32 p, c, 0x1000000;\n@p bra WAIT_%=;\ntrap;\nDONE_%=:\n}" ::"r"(bar), "r"(parity) : "memory");
}
__device__ __forceinline__ void mbar_arrive_elect(uint32_t bar) { asm volatile("{.reg .pred p; elect.sync _|p, 0xffffffff; @p mbarrier.arrive.shared::cta.b64 _, [%0];}" ::"r"(bar) : "memory"); }
__device__ __forceinline__ void mbar_init_elect(uint32_t bar, uint32_t cnt) { asm volatile("{.reg .pred p; elect.sync _|p, 0xffffffff; @p mbarrier.init.shared::cta.b64 [%0], %1;}" ::"r"(bar), "r"(cnt) : "memory"); }
__device__ __forceinline__ uint32_t ld_relaxed(const uint32_t* p) { uint32_t v; asm volatile("ld.relaxed.gpu.global.u32 %0, [%1];" : "=r"(v) : "l"(p) : "memory"); return v; }
__device__ __forceinline__ void red_add_elect(uint32_t* p) { asm volatile("{.reg .pred p; elect.sync _|p, 0xffffffff; @p red.relaxed.gpu.global.add.u32 [%0], 1;}" ::"l"(p) : "memory"); }
__device__ __forceinline__ void wait_value(const uint32_t* p, uint32_t target, int ns) {
  int spins = 0;
  while (ld_relaxed(p) != target) { __nanosleep(ns); if (++spins > SPIN_LIMIT) __trap(); }
}
template <int BYTES, bool INIT = false> __device__ __forceinline__ void bulk_load(uint32_t dst, const void* src, uint32_t bar, int go = 0) {
  if (INIT) asm volatile("{.reg .pred p; elect.sync _|p, 0xffffffff; @p mbarrier.init.shared::cta.b64 [%0], 1; @p fence.mbarrier_init.release.cluster;}" ::"r"(bar) : "memory");
  asm volatile("{\n.reg .pred p, q;\nsetp.ge.s32 q, %4, 0;\nelect.sync _|p, 0xffffffff;\nand.pred p, p, q;\n@p mbarrier.arrive.expect_tx.shared::cta.b64 _, [%1], %3;\n"
               "@p cp.async.bulk.shared::cluster.global.mbarrier::complete_tx::bytes [%0], [%2], %3, [%1];\n}"
               ::"r"(dst), "r"(bar), "l"(src), "n"(BYTES), "r"(go) : "memory");
}
__device__ __forceinline__ void lds128(uint32_t* r, uint32_t a) { asm volatile("ld.shared.v4.b32 {%0,%1,%2,%3}, [%4];" : "=r"(r[0]), "=r"(r[1]), "=r"(r[2]), "=r"(r[3]) : "r"(a) : "memory"); }
__device__ __forceinline__ uint2 lds64(uint32_t a) { uint2 v; asm volatile("ld.shared.v2.b32 {%0,%1}, [%2];" : "=r"(v.x), "=r"(v.y) : "r"(a) : "memory"); return v; }
__device__ __forceinline__ uint32_t lds32(uint32_t a) { uint32_t v; asm volatile("ld.shared.b32 %0, [%1];" : "=r"(v) : "r"(a) : "memory"); return v; }
__device__ __forceinline__ void sts32(uint32_t a, uint32_t v) { asm volatile("st.shared.b32 [%0], %1;" ::"r"(a), "r"(v) : "memory"); }
__device__ __forceinline__ void sts64(uint32_t a, uint2 v) { asm volatile("st.shared.v2.b32 [%0], {%1,%2};" ::"r"(a), "r"(v.x), "r"(v.y) : "memory"); }
__device__ __forceinline__ void sts128(uint32_t a, uint4 v) { asm volatile("st.shared.v4.b32 [%0], {%1,%2,%3,%4};" ::"r"(a), "r"(v.x), "r"(v.y), "r"(v.z), "r"(v.w) : "memory"); }
__device__ __forceinline__ uint64_t pol_evict_first() { uint64_t p; asm("createpolicy.fractional.L2::evict_first.b64 %0, 1.0;" : "=l"(p)); return p; }
__device__ __forceinline__ void stg128_stream(void* p, uint4 v, uint64_t pol) {
  asm volatile("st.global.L2::cache_hint.v4.b32 [%0], {%1,%2,%3,%4}, %5;" ::"l"(p), "r"(v.x), "r"(v.y), "r"(v.z), "r"(v.w), "l"(pol) : "memory");
}
__device__ __forceinline__ void stg128_if(uint32_t go, void* p, uint4 v) {
  asm volatile("{.reg .pred q; setp.ge.s32 q, %5, 0; @q st.global.v4.b32 [%0], {%1,%2,%3,%4};}" ::"l"(p), "r"(v.x), "r"(v.y), "r"(v.z), "r"(v.w), "r"(go) : "memory");
}
__device__ __forceinline__ uint32_t pack_f16(float lo, float hi) { uint32_t d; asm("cvt.rn.f16x2.f32 %0, %1, %2;" : "=r"(d) : "f"(hi), "f"(lo)); return d; }
__device__ __forceinline__ uint32_t pack_f16_sat(float lo, float hi) { uint32_t d; asm("cvt.rn.satfinite.f16x2.f32 %0, %1, %2;" : "=r"(d) : "f"(hi), "f"(lo)); return d; }
__device__ __forceinline__ uint32_t pack_bf16(float lo, float hi) { uint32_t d; asm("cvt.rn.bf16x2.f32 %0, %1, %2;" : "=r"(d) : "f"(hi), "f"(lo)); return d; }
__device__ __forceinline__ uint32_t bf2_to_h2(uint32_t w) { return pack_f16(__uint_as_float(w << 16), __uint_as_float(w & 0xffff0000u)); }
__device__ __forceinline__ uint32_t hadd2_bf16(uint32_t a, uint32_t b) { uint32_t d; asm("add.rn.bf16x2 %0, %1, %2;" : "=r"(d) : "r"(a), "r"(b)); return d; }
__device__ __forceinline__ uint32_t h2add(uint32_t a, uint32_t b) { uint32_t d; asm("add.rn.f16x2 %0, %1, %2;" : "=r"(d) : "r"(a), "r"(b)); return d; }
__device__ __forceinline__ uint32_t h2mul(uint32_t a, uint32_t b) { uint32_t d; asm("mul.rn.f16x2 %0, %1, %2;" : "=r"(d) : "r"(a), "r"(b)); return d; }
__device__ __forceinline__ uint32_t h2fma(uint32_t a, uint32_t b, uint32_t c) { uint32_t d; asm("fma.rn.f16x2 %0, %1, %2, %3;" : "=r"(d) : "r"(a), "r"(b), "r"(c)); return d; }
__device__ __forceinline__ uint32_t h2lo(uint32_t a) { uint32_t d; asm("{.reg .f16 l,h; mov.b32 {l,h}, %1; mov.b32 %0, {l,l};}" : "=r"(d) : "r"(a)); return d; }
__device__ __forceinline__ uint32_t h2hi(uint32_t a) { uint32_t d; asm("{.reg .f16 l,h; mov.b32 {l,h}, %1; mov.b32 %0, {h,h};}" : "=r"(d) : "r"(a)); return d; }
__device__ __forceinline__ float h_lo(uint32_t a) { float d; asm("{.reg .f16 l,h; mov.b32 {l,h}, %1; cvt.f32.f16 %0, l;}" : "=f"(d) : "r"(a)); return d; }
__device__ __forceinline__ float h_hi(uint32_t a) { float d; asm("{.reg .f16 l,h; mov.b32 {l,h}, %1; cvt.f32.f16 %0, h;}" : "=f"(d) : "r"(a)); return d; }
__device__ __forceinline__ float rsqrt_fast(float v) { float r; asm("rsqrt.approx.ftz.f32 %0, %1;" : "=f"(r) : "f"(v)); return r; }
__device__ __forceinline__ uint32_t prmt(uint32_t a, uint32_t b, uint32_t s) { uint32_t d; asm("prmt.b32 %0, %1, %2, %3;" : "=r"(d) : "r"(a), "r"(b), "r"(s)); return d; }
__device__ __forceinline__ void mma_sp(float* d, const uint32_t* a, const uint32_t* b, const float* c, uint32_t e) {
  asm("mma.sp::ordered_metadata.sync.aligned.m16n8k32.row.col.f32.bf16.bf16.f32 {%0,%1,%2,%3}, {%4,%5,%6,%7}, {%8,%9,%10,%11}, {%12,%13,%14,%15}, %16, 0;"
      : "=f"(d[0]), "=f"(d[1]), "=f"(d[2]), "=f"(d[3])
      : "r"(a[0]), "r"(a[1]), "r"(a[2]), "r"(a[3]), "r"(b[0]), "r"(b[1]), "r"(b[2]), "r"(b[3]), "f"(c[0]), "f"(c[1]), "f"(c[2]), "f"(c[3]), "r"(e));
}

__device__ __forceinline__ uint32_t gelu_tanh(uint32_t y) {
  uint32_t t, u, th;
  asm volatile("fma.rn.f16x2 %0, %1, %1, %2;" : "=r"(t) : "r"(y), "r"(GELU_A2));
  asm volatile("mul.rn.f16x2 %0, %1, %2;" : "=r"(u) : "r"(y), "r"(t));
  asm volatile("tanh.approx.f16x2 %0, %1;" : "=r"(th) : "r"(u));
  return th;
}
__device__ __forceinline__ uint32_t gelu_fin(uint32_t y, uint32_t th) {
  uint32_t g;
  asm volatile("fma.rn.f16x2 %0, %1, %2, %1;" : "=r"(g) : "r"(y), "r"(th));
  return g;
}

__device__ __forceinline__ void convert_weights(uint32_t sb, int rot, int warp, int lane) {
  if (warp < 12) {
    const int l8 = lane & 7, q4 = lane >> 3;
    int s = (warp >> 1) + rot; if (s >= 6) s -= 6;
    const uint32_t base = sb + W1S + s * 12288 + (warp & 1) * 384;
    mbar_wait(sb + WBAR + s * 8, 0);
    uint32_t v[3][4][4];
#pragma unroll
    for (int r = 0; r < 4; r++)
#pragma unroll
      for (int i = 0; i < 3; i++) lds128(v[i][r], base + i * 128 + (4 * (l8 >> 1) + 2 * (r & 1) + (l8 & 1)) * 768 + ((l8 + q4 + 4 * (r >> 1)) & 7) * 16);
    __syncwarp();
#pragma unroll
    for (int r = 0; r < 4; r++)
#pragma unroll
      for (int i = 0; i < 3; i++)
        sts128(base + i * 128 + (((l8 + q4 + 4 * (r >> 1)) & 7) + 8 * (r & 1)) * 768 + l8 * 16,
               make_uint4(bf2_to_h2(v[i][r][0]), bf2_to_h2(v[i][r][1]), bf2_to_h2(v[i][r][2]), bf2_to_h2(v[i][r][3])));
  }
  const int q = lane & 3, t = (lane >> 2) & 3, b = lane >> 4;
  int u = 3 * (warp ^ 15) + 8 * rot; if (u >= 48) u -= 48;
  uint32_t base[3], v[3][4][3];
#pragma unroll
  for (int i = 0; i < 3; i++) {
    const int ui = u + i >= 48 ? u + i - 48 : u + i;
    base[i] = sb + W2S + ui * 1536;
    if (i != 1) mbar_wait(sb + WBAR + 48 + (ui >> 3) * 8, 0);
  }
#pragma unroll
  for (int i = 0; i < 3; i++)
#pragma unroll
    for (int d = 0; d < 4; d++)
#pragma unroll
      for (int j = 0; j < 3; j++) v[i][d][j] = lds32(base[i] + (2 * ((q + d) & 3) + b) * 192 + j * 64 + t * 16 + q * 4);
  __syncwarp();
#pragma unroll
  for (int i = 0; i < 3; i++)
#pragma unroll
    for (int d = 0; d < 4; d++)
#pragma unroll
      for (int j = 0; j < 3; j++) sts32(base[i] + (4 * j + q) * 128 + (2 * ((q + d) & 3) + b) * 16 + t * 4, bf2_to_h2(v[i][d][j]));
}

__device__ __noinline__ void ln_wide(uint32_t ad) {
  float m[2], r[2];
#pragma unroll
  for (int hi = 0; hi < 2; hi++) {
    float sm = 0.f;
    for (int s = 0; s < 6; s++) { uint2 w = lds64(ad + s * 512 + hi * 8); sm += (h_lo(w.x) + h_hi(w.x)) + (h_lo(w.y) + h_hi(w.y)); }
    sm += __shfl_xor_sync(0xffffffffu, sm, 1); sm += __shfl_xor_sync(0xffffffffu, sm, 2);
    m[hi] = sm * (1.f / 96.f);
    float q = 0.f;
    for (int s = 0; s < 6; s++) {
      uint2 w = lds64(ad + s * 512 + hi * 8);
      float d0 = h_lo(w.x) - m[hi], d1 = h_hi(w.x) - m[hi], d2 = h_lo(w.y) - m[hi], d3 = h_hi(w.y) - m[hi];
      q += (d0 * d0 + d1 * d1) + (d2 * d2 + d3 * d3);
    }
    q += __shfl_xor_sync(0xffffffffu, q, 1); q += __shfl_xor_sync(0xffffffffu, q, 2);
    r[hi] = rsqrtf(fmaf(q, 1.f / 96.f, 1e-5f)) * GELU_C3;
  }
  for (int s = 0; s < 6; s++) {
    uint32_t w[4]; lds128(w, ad + s * 512);
    sts128(ad + s * 512, make_uint4(pack_f16((h_lo(w[0]) - m[0]) * r[0], (h_hi(w[0]) - m[0]) * r[0]), pack_f16((h_lo(w[2]) - m[1]) * r[1], (h_hi(w[2]) - m[1]) * r[1]),
                                    pack_f16((h_lo(w[1]) - m[0]) * r[0], (h_hi(w[1]) - m[0]) * r[0]), pack_f16((h_lo(w[3]) - m[1]) * r[1], (h_hi(w[3]) - m[1]) * r[1])));
  }
  asm volatile("fence.proxy.async.shared::cta;" ::: "memory");
}

__device__ __forceinline__ uint32_t layer_norm(const uint32_t (&raw)[6][4], uint32_t* a, uint32_t tag) {
  const uint32_t stale = ((raw[0][0] ^ tag) | (raw[1][0] ^ tag)) | ((raw[2][0] ^ tag) | (raw[3][0] ^ tag)) | ((raw[4][0] ^ tag) | (raw[5][0] ^ tag));
  uint32_t sm[2], qq[2];
#pragma unroll
  for (int hi = 0; hi < 2; hi++) {
    uint32_t s0 = h2add(raw[0][2 * hi], raw[1][2 * hi]), s1 = h2add(raw[0][2 * hi + 1], raw[1][2 * hi + 1]);
    uint32_t s2 = h2add(raw[2][2 * hi], raw[3][2 * hi]), s3 = h2add(raw[2][2 * hi + 1], raw[3][2 * hi + 1]);
    uint32_t s4 = h2add(raw[4][2 * hi], raw[5][2 * hi]), s5 = h2add(raw[4][2 * hi + 1], raw[5][2 * hi + 1]);
    sm[hi] = h2add(h2add(h2add(s0, s1), h2add(s2, s3)), h2add(s4, s5));
  }
#pragma unroll
  for (int hi = 0; hi < 2; hi++) {
    uint32_t q0 = h2mul(raw[0][2 * hi], raw[0][2 * hi]), q1 = h2mul(raw[0][2 * hi + 1], raw[0][2 * hi + 1]);
#pragma unroll
    for (int k = 1; k < 6; k++) { q0 = h2fma(raw[k][2 * hi], raw[k][2 * hi], q0); q1 = h2fma(raw[k][2 * hi + 1], raw[k][2 * hi + 1], q1); }
    qq[hi] = h2add(q0, q1);
  }
  uint32_t s = h2add(prmt(sm[0], sm[1], 0x5410), prmt(sm[0], sm[1], 0x7632));
  uint32_t q = h2add(prmt(qq[0], qq[1], 0x5410), prmt(qq[0], qq[1], 0x7632));
  s = h2add(s, __shfl_xor_sync(0xffffffffu, s, 1)); q = h2add(q, __shfl_xor_sync(0xffffffffu, q, 1));
  s = h2add(s, __shfl_xor_sync(0xffffffffu, s, 2)); q = h2add(q, __shfl_xor_sync(0xffffffffu, q, 2));
  constexpr float K1 = 1.f / (96.f * GELU_C3 * GELU_C3), K2 = 1e-5f / (GELU_C3 * GELU_C3), K3 = 1.f / (96.f * GELU_C3);
  const float e0 = fmaf(h_lo(q), K1, K2), e1 = fmaf(h_hi(q), K1, K2), m0 = h_lo(s) * K3, m1 = h_hi(s) * K3;
  const float v0 = fmaf(-m0, m0, e0), v1 = fmaf(-m1, m1, e1);
  const uint32_t r = pack_f16(rsqrt_fast(v0), rsqrt_fast(v1)), o = h2mul(h2mul(s, 0xA155A155u), r);
#pragma unroll
  for (int k = 0; k < 6; k++) {
    a[4 * k] = h2fma(raw[k][0], h2lo(r), h2lo(o)); a[4 * k + 2] = h2fma(raw[k][1], h2lo(r), h2lo(o));
    a[4 * k + 1] = h2fma(raw[k][2], h2hi(r), h2hi(o)); a[4 * k + 3] = h2fma(raw[k][3], h2hi(r), h2hi(o));
  }
  const bool fine = fmaf(v0, 4.f, -e0) > 0.f && fmaf(v1, 4.f, -e1) > 0.f;
  return (fine ? 0u : 2u) | (stale & 1);
}

constexpr int KS = CH / 16, NC = 384 / CH;
#define WG1_(n) wgmma_n##n##_f16
#define WG1(n) WG1_(n)
__device__ __forceinline__ void gemm1(uint32_t* p, const uint32_t* a, uint64_t d1, int c, int k0, int k1) {
#pragma unroll
  for (int s = 0; s < 6; s++)
    if (s >= k0 && s < k1) {
      if (s == 0) WG1(CH)<0>(p, a, d1 + c * CH); else WG1(CH)<1>(p, a + 4 * s, d1 + c * CH + s * (12288 >> 4));
    }
}
__device__ __forceinline__ void fetch_x(uint32_t xbuf, uint32_t bar, const CUtensorMap* tm, uint32_t c0, uint32_t c12, uint64_t pol, int go = 0) {
  asm volatile("{\n.reg .pred p, q;\nsetp.ge.s32 q, %7, 0;\nelect.sync _|p, 0xffffffff;\nand.pred p, p, q;\n"
               "@p mbarrier.arrive.expect_tx.shared::cta.b64 _, [%1], 3072;\n"
               "@p cp.async.bulk.tensor.3d.shared::cluster.global.mbarrier::complete_tx::bytes.L2::cache_hint [%0], [%2, {%3, %4, %5}], [%1], %6;\n}"
               ::"r"(xbuf), "r"(bar), "l"(tm), "r"(c0), "r"(c12 & 255), "r"(c12 >> 8), "l"(pol), "r"(go) : "memory");
}
__device__ __forceinline__ uint32_t slot_tag(int gm, int j, uint32_t epoch) {
  const int len = gm < 8 ? PLEN : LMID, writes = (len - j % RING + RING - 1) / RING;
  return (epoch * writes + j / RING + 1) & 1;
}
__device__ __forceinline__ void build_tile_list(uint32_t sb, int k, int idx, bool tabled, bool is_conv, uint32_t epoch) {
  int n = -1;
  if (tabled) { if (k < 48) n = (int16_t)g_sched[idx][k]; }
  else if (!is_conv) {
    const int i = k * (gridDim.x - NCONV) + idx, r = i >> 2, full = LMID * NG;
    const int j = r < full ? r / NG : ((r - full) >> 3) + LMID, gm = r < full ? r % NG : (r - full) & 7;
    if (i < 4096) n = (gm * PLEN + j) * 4 + (i & 3);
  }
  const int q = n >> 2, gm = q / PLEN, j = q - gm * PLEN, seg = j / LM;
  const int strip = gm < 8 ? gm >> 1 : (gm - 8) * NSEG + seg, pair = gm < 8 ? ((gm & 1) ? 255 - j : j) : PLEN + j - seg * LM;
  sts128(sb + MISC + 512 + k * 16, make_uint4(q, (((j % RING) * NG + gm) * 4 + (n & 3)) * TILEB + slot_tag(gm, j, epoch),
                                              (n & 2) * 384, (strip * 8 + (n & 1) * 4) | (pair << 9)));
  if (k == 0) { sts32(sb + MISC + 256, epoch + 1); sts32(sb + MISC + 260, !is_conv); }
}

__device__ __forceinline__ void mlp_setup(uint32_t sb, Globals* gs, int id, const __nv_bfloat16* __restrict__ w1, const __nv_bfloat16* __restrict__ w2,
                                          int idx, bool tabled, int warp, int lane) {
  const int rot = idx % 6;
  if (warp < 12) {
    const int m = warp >= 6; int s = warp - 6 * m + rot; if (s >= 6) s -= 6;
    bulk_load<12288, true>(sb + (6 * m + s) * 12288, (const char*)(m ? w2 : w1) + s * 12288, sb + WBAR + (6 * m + s) * 8);
  }
  __syncthreads();
  if (warp >= 12) build_tile_list(sb, threadIdx.x - 384, idx, tabled, false, ld_relaxed(&gs->epoch[id]));
  convert_weights(sb, rot, warp, lane);
  asm volatile("fence.proxy.async.shared::cta;" ::: "memory");
  __syncthreads();
  if (threadIdx.x == 480) {
    gs->epoch[id] = lds32(sb + MISC + 256);
    if (idx < 24 && (idx & 1)) {
      asm volatile("cp.async.bulk.global.shared::cta.bulk_group [%0], [%1], 12288;\ncp.async.bulk.commit_group;\ncp.async.bulk.wait_group 0;\nfence.proxy.async.global;\n"
                   "red.release.gpu.global.add.u32 [%2], 1;" ::"l"(gs->wimg + (idx >> 1) * 12288), "r"(sb + (idx >> 1) * 12288), "l"(gs->wflag) : "memory");
    }
  }
  __syncwarp();
}

__device__ __forceinline__ void mlp_role(uint32_t sb, Globals* gs, const CUtensorMap* tmr, __nv_bfloat16* __restrict__ out) {
  uint32_t tid;
  asm volatile("mov.u32 %0, %%tid.x;" : "=r"(tid));
  const int warp = __shfl_sync(0xffffffffu, tid >> 5, 0), lane = tid & 31;
  const int wg = warp >> 2, w = warp & 3, g = lane >> 2, t = lane & 3;
  const uint32_t abuf = sb + ABUF + warp * 3072, xbuf = sb + XBUF + (warp & 7) * 3072;
  const uint32_t bar = sb + MISC + warp * 8, obar = sb + MISC + (warp ^ 8) * 8;
  const uint32_t tl = sb + MISC + 512;
  const uint32_t rtarget = 3 * lds32(sb + MISC + 256);
  const uint64_t d1 = ((uint64_t)(6144 >> 4) << 16) | ((uint64_t)(128 >> 4) << 32) | (uint64_t)(((sb + W1S) >> 4) & 0x3fff);
  const uint64_t d2 = ((uint64_t)(12288 >> 4) << 16) | ((uint64_t)(128 >> 4) << 32) | (uint64_t)(((sb + W2S) >> 4) & 0x3fff);
  const uint32_t ad = abuf + t * 128 + ((g ^ (2 * t)) << 4);
  const uint32_t xd = xbuf + g * 192 + t * 16;
  const uint32_t pofs = (g >> 1) * 3072 + (2 * w + (g & 1)) * 192 + t * 16;
  const int mybar = 1 + wg, nxtbar = 1 + ((wg + 1) & 3);
  const uint64_t pol = pol_evict_first();
  const unsigned char* const asrc = gs->scratch + w * 3072;
  uint32_t pha = 0, phx = 0, tp = tl + wg * 16;
  bool pending = lds32(sb + MISC + 260);
  uint32_t cur[4];
  lds128(cur, tp);
  if (wg < 2) fetch_x(xbuf, bar + 128, tmr, cur[2] + w * 192, cur[3], pol, cur[0]);
  while ((int)cur[0] >= 0) {
    uint32_t a[24], p[NC][CH / 4], gg[24][4], th[24][4], acc[24], raw[6][4], n2[4], n4[4];
    if (pending) {
      wait_value(&gs->ready[cur[0]], rtarget, 32);
      bulk_load<3072>(abuf, asrc + (cur[1] & ~1u), bar);
    }
    mbar_wait(bar, pha); pha ^= 1;
#pragma unroll
    for (int k = 0; k < 6; k++) lds128(raw[k], ad + k * 512);
    uint32_t st = layer_norm(raw, a, cur[1]);
    if (__any_sync(0xffffffffu, st != 0)) {
      for (int tries = 0; __any_sync(0xffffffffu, st & 1); tries++) {
        if (tries > SPIN_LIMIT) __trap();
        bulk_load<3072>(abuf, asrc + (cur[1] & ~1u), bar);
        mbar_wait(bar, pha); pha ^= 1;
        st = 0;
#pragma unroll
        for (int k = 0; k < 6; k++) st |= lds32(ad + k * 512) ^ cur[1];
      }
      ln_wide(ad);
#pragma unroll
      for (int k = 0; k < 6; k++) lds128(a + 4 * k, ad + k * 512);
    }
    if (tp != tl) asm volatile("bar.sync %0, 256;" ::"r"(mybar) : "memory");
    uint32_t rdy = 0;
    wg_fence();
    gemm1(p[0], a, d1, 0, 0, 6); wg_commit();
    gemm1(p[1], a, d1, 1, 0, 6 / KS); wg_commit();
    const int sig = lds32(tp + 16);
    lds128(n4, tp + 64);
    asm volatile("{.reg .pred p; setp.eq.u32 p, %1, 0; @p red.relaxed.gpu.global.add.u32 [%0], 1;}" ::"l"(&gs->cons[cur[0]] + lane), "r"(lane) : "memory");
#pragma unroll
    for (int j = 0; j < 24; j++) {
      const int c = j / KS, s = j % KS;
      if (j == JB) rdy = ld_relaxed(&gs->ready[max((int)n4[0], 0)]);
      if (s == 0) wg_wait<1>();
      if (j == TRIG) asm volatile("{.reg .pred p; setp.ge.s32 p, %1, 0; @p bar.arrive %0, 256;}" ::"r"(nxtbar), "r"(sig) : "memory");
#pragma unroll
      for (int i = 0; i < 4; i++) {
        if (!(s && i < PRE)) th[j][i] = gelu_tanh(p[c][4 * s + i]);
        gg[j][i] = gelu_fin(p[c][4 * s + i], th[j][i]);
      }
      wg_fence();
      if (j == 0) wgmma_n96_f16<0>(acc, gg[j], d2); else wgmma_n96_f16<1>(acc, gg[j], d2 + (16 * (j % 3) + j / 3) * (1536 >> 4));
      const int c1 = (j + 1) / KS + 1, u = (j + 1) % KS;
      if (c1 < NC) gemm1(p[c1], a, d1, c1, (6 * u) / KS, (6 * (u + 1)) / KS);
      wg_commit();
      if (s + 1 < KS) {
#pragma unroll
        for (int i = 0; i < PRE; i++) th[j + 1][i] = gelu_tanh(p[c][4 * s + 4 + i]);
      }
      if (j < 23) SCHED_FENCE();
    }
    pending = rdy != rtarget;
    bulk_load<3072>(abuf, asrc + (n4[1] & ~1u), bar, pending ? -1 : (int)n4[0]);
    wg_wait<0>();
    mbar_wait(bar + 128, phx); phx ^= 1;
#pragma unroll
    for (int k = 0; k < 24; k++) acc[k] = h2mul(acc[k], GELU_S2);
    char* const op = (char*)out + (cur[2] * 2 + (cur[3] & 255) * 3072 + (cur[3] >> 8) * (512 * 192) + pofs);
    lds128(n2, tp + 32);
#pragma unroll
    for (int k = 0; k < 6; k++) {
      const int hi = k / 3, j = k % 3;
      uint32_t xr[4];
      lds128(xr, xd + hi * 1536 + j * 64);
      uint4 o;
      o.x = hadd2_bf16(xr[0], pack_bf16(h_lo(acc[8 * j + hi]), h_hi(acc[8 * j + hi])));
      o.y = hadd2_bf16(xr[1], pack_bf16(h_lo(acc[8 * j + 2 + hi]), h_hi(acc[8 * j + 2 + hi])));
      o.z = hadd2_bf16(xr[2], pack_bf16(h_lo(acc[8 * j + 4 + hi]), h_hi(acc[8 * j + 4 + hi])));
      o.w = hadd2_bf16(xr[3], pack_bf16(h_lo(acc[8 * j + 6 + hi]), h_hi(acc[8 * j + 6 + hi])));
      stg128_stream(op + hi * (512 * 192) + j * 64, o, pol);
    }
    __syncwarp();
    if ((int)n2[0] >= 0) fetch_x(xbuf, obar + 128, tmr, n2[2] + w * 192, n2[3], pol);
    tp += 64;
#pragma unroll
    for (int k = 0; k < 4; k++) cur[k] = n4[k];
  }
}

__device__ __forceinline__ void conv_compute(uint32_t sb, Globals* gs, int third, int nit, int off, bool up, int warp, int lane) {
  const int g = lane >> 2, t = lane & 3;
  const uint32_t full = sb + CM;
  const uint32_t wt = sb + 16384 + warp * 1024;
  sts128(wt + lane * 16, make_uint4(0, 0, 0, 0));
  if (lane < 4) sts128(wt + 512 + lane * 16, make_uint4(0, 0, 0, 0));
  asm volatile("setmaxnreg.inc.sync.aligned.u32 224;");
  uint32_t meta = 0;
#pragma unroll
  for (int a = 0; a < 4; a++) meta |= ((4 * (t & 1) + a + 1 >= g) ? 0x80008u : 0xD000Du) << (4 * a);
  meta = __shfl_sync(0xffffffffu, meta, lane);
  uint32_t aq[4];
#pragma unroll
  for (int q = 0; q < 4; q++) {
    const int pp = (g & 1) * 140 + (t & 1) * 70 + 16 * (g >> 1) + 2 * q + (t >> 1);
    aq[q] = __shfl_sync(0xffffffffu, sb + RBUF + pp * 64 + (((warp >> 1) ^ ((pp >> 1) & 3)) << 4) + (warp & 1) * 8, lane);
  }
  const int Q = third * 8 + warp;
  unsigned char* const obase = gs->scratch + (g >> 1) * 3072 + Q * 128 + (((2 * t + (g & 1)) ^ (2 * (Q & 3))) << 4);
  const float zero4[4] = {0.f, 0.f, 0.f, 0.f};
  uint32_t A[4][4][4];
  asm volatile("bar.sync 5, 288;" ::: "memory");
  mbar_wait(sb + WBAR + 8, 0);
  {
#pragma unroll
    for (int k = 0; k < 2; k++) {
      const int tap = lane + 32 * k;
      if (tap < 49) sts64(wt + (tap + tap / 7 + 8) * 8, lds64(sb + tap * 192 + third * 64 + warp * 8));
    }
    __syncwarp();
    uint2 w[2][4][3];
#pragma unroll
    for (int h = 0; h < 2; h++) {
      uint32_t src = wt + ((4 * h + t - g) & 7) * 8 + (up ? 384 : 0);
#pragma unroll
      for (int u = 0; u < 4; u++) {
#pragma unroll
        for (int k = 0; k < 3; k++) w[h][u][k] = lds64(src + k * 64);
        src += up ? -128 : 128;
      }
    }
#pragma unroll
    for (int u = 0; u < 4; u++)
#pragma unroll
      for (int r = 0; r < 4; r++) {
        const uint2 w0 = w[r >> 1][u][1 - (r & 1)], w1 = w[r >> 1][u][2 - (r & 1)];
        A[0][u][r] = prmt(w0.x, w1.x, 0x5410); A[1][u][r] = prmt(w0.x, w1.x, 0x7632);
        A[2][u][r] = prmt(w0.y, w1.y, 0x5410); A[3][u][r] = prmt(w0.y, w1.y, 0x7632);
      }
  }
  float S[2][4][3][4];
#pragma unroll
  for (int s = 0; s < 2; s++)
#pragma unroll
    for (int c = 0; c < 4; c++)
#pragma unroll
      for (int i = 0; i < 3; i++)
#pragma unroll
        for (int k = 0; k < 4; k++) S[s][c][i][k] = 0.f;
  uint32_t sofs = off * SLOTB, bar = full + off * 8, ph = 0, ot = sb + CTAB;
  const uint32_t oend = ot + nit * 16;
  asm volatile("bar.sync 0, 512;" ::: "memory");
  mbar_wait(bar, 0);
  uint2 X[3][4];
#pragma unroll
  for (int j = 0; j < 2; j++)
#pragma unroll
    for (int q = 0; q < 4; q++) X[j][q] = lds64(aq[q] + sofs + j * 512);
#pragma unroll 1
  do {
    const uint2 oe = lds64(ot);
    unsigned char* const o = obase + oe.x;
    const uint32_t dbar = bar + 64;
#pragma unroll
    for (int s = 0; s < 2; s++) {
      uint32_t B[4][4];
      if (s == 1) {
        sofs += SLOTB; bar += 8;
        if (sofs == NSLOT * SLOTB) { sofs = 0; bar = full; ph ^= 1; }
        mbar_wait(bar, ph);
      }
#pragma unroll
      for (int c = 0; c < 4; c++)
#pragma unroll
        for (int q = 0; q < 4; q++) B[c][q] = prmt(c < 2 ? X[s][q].x : X[s][q].y, c < 2 ? X[s + 1][q].x : X[s + 1][q].y, (c & 1) ? 0x7632 : 0x5410);
      if (s == 0) {
#pragma unroll
        for (int q = 0; q < 4; q++) X[2][q] = lds64(aq[q] + sofs + 2 * 512);
      } else {
#pragma unroll
        for (int j = 0; j < 2; j++)
#pragma unroll
          for (int q = 0; q < 4; q++) X[j][q] = lds64(aq[q] + sofs + j * 512);
      }
      float T[4][4];
#pragma unroll
      for (int c = 0; c < 4; c++) mma_sp(T[c], A[c][3], B[c], S[s][c][2], meta);
#pragma unroll
      for (int c = 0; c < 4; c++) mma_sp(S[s][c][2], A[c][2], B[c], S[s][c][1], meta);
      stg128_if(oe.x, o + (2 * s) * TILEB, make_uint4((pack_f16_sat(T[0][0], T[1][0]) & ~1u) | oe.y, pack_f16_sat(T[2][0], T[3][0]), pack_f16_sat(T[0][2], T[1][2]), pack_f16_sat(T[2][2], T[3][2])));
      stg128_if(oe.x, o + (2 * s + 1) * TILEB, make_uint4((pack_f16_sat(T[0][1], T[1][1]) & ~1u) | oe.y, pack_f16_sat(T[2][1], T[3][1]), pack_f16_sat(T[0][3], T[1][3]), pack_f16_sat(T[2][3], T[3][3])));
      if (s == 1) mbar_arrive_elect(dbar);
#pragma unroll
      for (int c = 0; c < 4; c++) mma_sp(S[s][c][1], A[c][1], B[c], S[s][c][0], meta);
#pragma unroll
      for (int c = 0; c < 4; c++) mma_sp(S[s][c][0], A[c][0], B[c], zero4, meta);
    }
    ot += 16;
  } while (ot != oend);
}

__device__ __forceinline__ void load_step(uint32_t sb, const CUtensorMap* tmx, int gm, int third, int it, int s, bool first = false) {
  const int seg = first ? 0 : it / (LM + 3);
  const int st = gm < 8 ? gm >> 1 : (gm - 8) * NSEG + seg, J = gm < 8 ? ((gm & 1) ? 257 - it : it + 1) : PLEN + it - seg * (LM + 3);
  asm volatile("{\n.reg .pred p;\n.reg .s32 c2;\n.reg .u32 d2;\nelect.sync _|p, 0xffffffff;\nadd.s32 c2, %4, 64;\nadd.u32 d2, %0, 8960;\n"
               "@p mbarrier.arrive.expect_tx.shared::cta.b64 _, [%2], 17920;\n"
               "@p cp.async.bulk.tensor.3d.shared::cluster.global.mbarrier::complete_tx::bytes [%0], [%1, {%3, %4, %5}], [%2];\n"
               "@p cp.async.bulk.tensor.3d.shared::cluster.global.mbarrier::complete_tx::bytes [d2], [%1, {%3, c2, %5}], [%2];\n}"
               ::"r"(sb + RBUF + s * SLOTB), "l"(tmx), "r"(sb + CM + s * 8), "r"(third * 32), "r"(st * 128 - 3), "r"(2 * J - 3) : "memory");
}
__device__ __forceinline__ void ring_bar_init(uint32_t bar, uint32_t cnt, bool ahead) {
  asm volatile("{\n.reg .pred p, q;\nelect.sync _|p, 0xffffffff;\n@p mbarrier.init.shared::cta.b64 [%0], %1;\n"
               "setp.ne.and.u32 q, %2, 0, p;\n@q mbarrier.arrive.shared::cta.b64 _, [%0], %1;\n@p fence.mbarrier_init.release.cluster;\n}" ::"r"(bar), "r"(cnt), "r"((uint32_t)ahead) : "memory");
}
__device__ __forceinline__ void conv_loader(uint32_t sb, Globals* gs, const CUtensorMap* tmx, int gm, int nit, int off, int cidx, int third, int k) {
  static_assert(FIRST >= 4 && NCONV >= 24, "loader");
  const uint32_t full = sb + CM;
  asm volatile("bar.sync 0, 512;" ::: "memory");
  if (FIRST + k < NSLOT) load_step(sb, tmx, gm, third, FIRST + k, (FIRST + k + off) & 7, true);
#pragma unroll 1
  for (int it = NSLOT + k; it < nit + NSLOT; it += 4) {
    const int u = it + off;
    const uint32_t ro = lds32(sb + CTAB + (it - NSLOT) * 16 + 8);
    mbar_wait(full + 64 + (u & 7) * 8, ((u >> 3) & 1) ^ 1);
    red_add_elect((uint32_t*)((char*)gs + ro));
    if (it < nit) load_step(sb, tmx, gm, third, it, u & 7);
    else if (it == nit) mbar_arrive_elect(full);
    if (it >= nit - 16) {
      if (it < nit - 12) {
        wait_value(gs->wflag, 12 * lds32(sb + MISC + 256), 32);
        asm volatile("fence.acquire.gpu;\nfence.proxy.async.global;" ::: "memory");
        if (cidx < 24) asm volatile("{.reg .pred p; elect.sync _|p, 0xffffffff; @p cp.async.bulk.prefetch.L2.global [%0], 1536;}" ::"l"(gs->wimg + (cidx * 4 + k) * 1536) : "memory");
      }
      const int m = it == nit - 1 ? 0 : W2S;
      if (it == nit - 1 || it == nit + 3) bulk_load<73728>(sb + m, gs->wimg + m, sb + WBAR);
    }
  }
}

__device__ __forceinline__ void conv_credit(uint32_t sb, Globals* gs, int q0, int nit, int off, uint32_t ctarget, int k) {
  const uint32_t full = sb + CM;
#pragma unroll 1
  for (int it = k + NSLOT; it <= nit; it += 4) {
    const int u = it + off, q = (int)lds32(sb + CTAB + it * 16 + 12) - RING;
    mbar_wait(full + 64 + (u & 7) * 8, ((u >> 3) & 1) ^ 1);
    if (q >= q0) wait_value(&gs->cons[q], ctarget, 200);
    mbar_arrive_elect(full + (u & 7) * 8);
  }
}

__device__ __noinline__ int generic_role() {
  const int cidx = (blockIdx.x * NCONV) / gridDim.x;
  return cidx | ((((blockIdx.x + 1) * NCONV) / gridDim.x != cidx) << 16);
}

__global__ void __launch_bounds__(512, 1) convnext_kernel(const __nv_bfloat16* __restrict__ dw, const __nv_bfloat16* __restrict__ w1, const __nv_bfloat16* __restrict__ w2,
                                                          __nv_bfloat16* __restrict__ out, Globals* gs, int want_sms,
                                                          const __grid_constant__ CUtensorMap tmx, const __grid_constant__ CUtensorMap tmr) {
  extern __shared__ __align__(1024) unsigned char smem[];
  const uint32_t sb = smem_u32(smem);
  const int warp = __shfl_sync(0xffffffffu, threadIdx.x >> 5, 0), lane = threadIdx.x & 31;
  uint32_t smid, nsmid;
  asm volatile("mov.u32 %0, %%smid;" : "=r"(smid));
  asm volatile("mov.u32 %0, %%nsmid;" : "=r"(nsmid));
  const bool tabled = TABLED && (int)nsmid == want_sms;
  const int id = tabled ? smid : blockIdx.x;
  int cidx, idx, is_conv;
  if (tabled) {
    idx = smid;
    const int k = (smid - 60) / 14, r = smid - 60 - 14 * k;
    is_conv = smid < 48 ? !(smid & 1) : (smid >= 60 && smid <= 90 && (r & ~2) == 0);
    cidx = smid < 48 ? ((smid >> 1) & 7) * 3 + (smid >> 4) : 24 + (r >> 1) * 3 + k;
  } else {
    const int r = generic_role();
    cidx = r & 0xffff; is_conv = r >> 16;
    idx = blockIdx.x - cidx;
  }
  const int gm = cidx / 3, third = cidx - gm * 3;
  const int q0 = gm * PLEN, nit = gm < 8 ? PLEN + 2 : NSEG * (LM + 3), off = (8 - nit) & 7;
  if (is_conv && warp == 8) {
    bulk_load<9408, true>(sb, dw, sb + WBAR + 8);
    asm volatile("bar.arrive 5, 288;" ::: "memory");
#pragma unroll 1
    for (int it = 0; it < NSLOT; it++) {
      const int s = (it + off) & 7;
      ring_bar_init(sb + CM + s * 8, 2, s < off);
      if (it < FIRST) load_step(sb, &tmx, gm, third, it, s, true);
    }
  }
  if (warp == 15) asm volatile("prefetch.tensormap [%0];" ::"l"(&tmr) : "memory");
  mbar_init_elect(sb + MISC + warp * 8, 1); mbar_init_elect(sb + MISC + 128 + warp * 8, 1);
  asm volatile("fence.mbarrier_init.release.cluster;" ::: "memory");
  if (is_conv) {
    if (warp >= 8) ring_bar_init(sb + CM + warp * 8, 8, warp - 8 < off);
    if (warp == 9) mbar_init_elect(sb + WBAR, 2);
    const uint32_t lastph = (((nit + off) >> 3) & 1) ^ 1;
    if (warp < 8) {
      conv_compute(sb, gs, third, nit, off, gm < 8 && (gm & 1), warp, lane);
      asm volatile("setmaxnreg.dec.sync.aligned.u32 128;");
    } else if (warp >= 12) {
      asm volatile("setmaxnreg.dec.sync.aligned.u32 24;");
      const uint32_t epoch = ld_relaxed(&gs->epoch[id]);
#pragma unroll 1
      for (int it = threadIdx.x - 384; it <= nit; it += 128) {
        const int seg = it / (LM + 3), j = gm < 8 ? it - 2 : it - 3 * (seg + 1);
        const bool ok = it < nit && j >= (gm < 8 ? 0 : seg * LM);
        sts128(sb + CTAB + it * 16, make_uint4((ok ? (j % RING) * NG + gm : -1) * (4 * TILEB), slot_tag(gm, max(j, 0), epoch),
                                               offsetof(Globals, ready) + (ok ? q0 + j : NG * PLEN) * 4, ok ? q0 + j : -1));
      }
      asm volatile("bar.sync 0, 512;" ::: "memory");
      mbar_arrive_elect(sb + CM + ((((warp + 2) & 3) + off) & 7) * 8);
      mbar_arrive_elect(sb + CM + ((((warp + 2) & 3) + off + 4) & 7) * 8);
      build_tile_list(sb, threadIdx.x - 384, idx, tabled, true, epoch);
      if (threadIdx.x == 384) gs->epoch[id] = epoch + 1;
      conv_credit(sb, gs, q0, nit, off, 16 * (epoch + 1), (warp + 2) & 3);
#pragma unroll 1
      for (int i = 0; i < 4; i++) {
        const uint2 e = lds64(sb + MISC + 512 + i * 16);
        mbar_wait(sb + CM + 64 + (4 + min(i, 2)) * 8, lastph);
        const int wi = 4 * i + (warp & 3);
        if ((int)e.x >= 0) bulk_load<3072>(sb + ABUF + wi * 3072, gs->scratch + (e.y & ~1u) + (warp & 3) * 3072, sb + MISC + wi * 8);
      }
      mbar_wait(sb + CM + 64 + 7 * 8, lastph);
      asm volatile("setmaxnreg.inc.sync.aligned.u32 128;");
    } else {
      asm volatile("setmaxnreg.dec.sync.aligned.u32 40;");
      conv_loader(sb, gs, &tmx, gm, nit, off, cidx, third, warp & 3);
      mbar_wait(sb + CM + 64 + 7 * 8, lastph);
      asm volatile("setmaxnreg.inc.sync.aligned.u32 128;");
    }
    mbar_wait(sb + WBAR, 0);
    asm volatile("bar.sync 0, 512;" ::: "memory");
  } else {
    mlp_setup(sb, gs, id, w1, w2, idx, tabled, warp, lane);
  }
  mlp_role(sb, gs, &tmr, out);
}

typedef CUresult (*PFN_encodeTiled)(CUtensorMap*, CUtensorMapDataType, cuuint32_t, void*, const cuuint64_t*, const cuuint64_t*, const cuuint32_t*, const cuuint32_t*,
                                    CUtensorMapInterleave, CUtensorMapSwizzle, CUtensorMapL2promotion, CUtensorMapFloatOOBfill);

extern "C" void kernel_launch(void* const* d_in, const int* in_sizes, int n_in, void* d_out, int out_size) {
  const __nv_bfloat16* x = (const __nv_bfloat16*)d_in[0];
  const __nv_bfloat16* dw = (const __nv_bfloat16*)d_in[1];
  const __nv_bfloat16* w1 = (const __nv_bfloat16*)d_in[2];
  const __nv_bfloat16* w2 = (const __nv_bfloat16*)d_in[3];
  static PFN_encodeTiled encode = nullptr;
  static int nsm = 0;
  static Globals* gs = nullptr;
  if (!encode) {
    void* fn = nullptr; cudaDriverEntryPointQueryResult qr;
    cudaGetDriverEntryPoint("cuTensorMapEncodeTiled", &fn, cudaEnableDefault, &qr);
    encode = (PFN_encodeTiled)fn;
    cudaGetSymbolAddress((void**)&gs, g_state);
    int dev = 0; cudaGetDevice(&dev);
    cudaDeviceGetAttribute(&nsm, cudaDevAttrMultiProcessorCount, dev);
    cudaFuncSetAttribute(convnext_kernel, cudaFuncAttributeMaxDynamicSharedMemorySize, SMEM_BYTES);
  }
  CUtensorMap tm, tr;
  cuuint64_t dims[3] = {96, 512, 512}, strides[2] = {192, 192 * 512};
  cuuint32_t box[3] = {32, 70, 2}, es[3] = {1, 1, 1};
  encode(&tm, CU_TENSOR_MAP_DATA_TYPE_BFLOAT16, 3, (void*)x, dims, strides, box, es, CU_TENSOR_MAP_INTERLEAVE_NONE, CU_TENSOR_MAP_SWIZZLE_64B,
         CU_TENSOR_MAP_L2_PROMOTION_L2_128B, CU_TENSOR_MAP_FLOAT_OOB_FILL_NONE);
  cuuint64_t dims2[3] = {1536, 32, 512}, strides2[2] = {3072, 192 * 512};
  cuuint32_t box2[3] = {192, 4, 2};
  encode(&tr, CU_TENSOR_MAP_DATA_TYPE_BFLOAT16, 3, (void*)x, dims2, strides2, box2, es, CU_TENSOR_MAP_INTERLEAVE_NONE, CU_TENSOR_MAP_SWIZZLE_NONE,
         CU_TENSOR_MAP_L2_PROMOTION_NONE, CU_TENSOR_MAP_FLOAT_OOB_FILL_NONE);
  convnext_kernel<<<nsm, 512, SMEM_BYTES>>>(dw, w1, w2, (__nv_bfloat16*)d_out, gs, nsm == 132 ? 132 : -1, tm, tr);
}
```

```cpp
#include <cuda_runtime.h>
#include <cuda_bf16.h>
#include <cuda.h>
#include <stdint.h>
#include <stddef.h>

template<int SCALE_D> __device__ __forceinline__ void wgmma_n64_f16(uint32_t* d, const uint32_t* a, uint64_t desc) {
  if (SCALE_D == 0) asm volatile("wgmma.mma_async.sync.aligned.m64n64k16.f16.f16.f16 {%0,%1,%2,%3,%4,%5,%6,%7,%8,%9,%10,%11,%12,%13,%14,%15}, {%16,%17,%18,%19}, %20, 0, 1, 1, 1;"
    : "=r"(d[0]),"=r"(d[1]),"=r"(d[2]),"=r"(d[3]),"=r"(d[4]),"=r"(d[5]),"=r"(d[6]),"=r"(d[7]),"=r"(d[8]),"=r"(d[9]),"=r"(d[10]),"=r"(d[11]),"=r"(d[12]),"=r"(d[13]),"=r"(d[14]),"=r"(d[15])
    : "r"(a[0]),"r"(a[1]),"r"(a[2]),"r"(a[3]),"l"(desc));
  if (SCALE_D == 1) asm volatile("wgmma.mma_async.sync.aligned.m64n64k16.f16.f16.f16 {%0,%1,%2,%3,%4,%5,%6,%7,%8,%9,%10,%11,%12,%13,%14,%15}, {%16,%17,%18,%19}, %20, 1, 1, 1, 1;"
    : "+r"(d[0]),"+r"(d[1]),"+r"(d[2]),"+r"(d[3]),"+r"(d[4]),"+r"(d[5]),"+r"(d[6]),"+r"(d[7]),"+r"(d[8]),"+r"(d[9]),"+r"(d[10]),"+r"(d[11]),"+r"(d[12]),"+r"(d[13]),"+r"(d[14]),"+r"(d[15])
    : "r"(a[0]),"r"(a[1]),"r"(a[2]),"r"(a[3]),"l"(desc));
}

template<int SCALE_D> __device__ __forceinline__ void wgmma_n96_f16(uint32_t* d, const uint32_t* a, uint64_t desc) {
  if (SCALE_D == 0) asm volatile("wgmma.mma_async.sync.aligned.m64n96k16.f16.f16.f16 {%0,%1,%2,%3,%4,%5,%6,%7,%8,%9,%10,%11,%12,%13,%14,%15,%16,%17,%18,%19,%20,%21,%22,%23}, {%24,%25,%26,%27}, %28, 0, 1, 1, 1;"
    : "=r"(d[0]),"=r"(d[1]),"=r"(d[2]),"=r"(d[3]),"=r"(d[4]),"=r"(d[5]),"=r"(d[6]),"=r"(d[7]),"=r"(d[8]),"=r"(d[9]),"=r"(d[10]),"=r"(d[11]),"=r"(d[12]),"=r"(d[13]),"=r"(d[14]),"=r"(d[15]),"=r"(d[16]),"=r"(d[17]),"=r"(d[18]),"=r"(d[19]),"=r"(d[20]),"=r"(d[21]),"=r"(d[22]),"=r"(d[23])
    : "r"(a[0]),"r"(a[1]),"r"(a[2]),"r"(a[3]),"l"(desc));
  if (SCALE_D == 1) asm volatile("wgmma.mma_async.sync.aligned.m64n96k16.f16.f16.f16 {%0,%1,%2,%3,%4,%5,%6,%7,%8,%9,%10,%11,%12,%13,%14,%15,%16,%17,%18,%19,%20,%21,%22,%23}, {%24,%25,%26,%27}, %28, 1, 1, 1, 1;"
    : "+r"(d[0]),"+r"(d[1]),"+r"(d[2]),"+r"(d[3]),"+r"(d[4]),"+r"(d[5]),"+r"(d[6]),"+r"(d[7]),"+r"(d[8]),"+r"(d[9]),"+r"(d[10]),"+r"(d[11]),"+r"(d[12]),"+r"(d[13]),"+r"(d[14]),"+r"(d[15]),"+r"(d[16]),"+r"(d[17]),"+r"(d[18]),"+r"(d[19]),"+r"(d[20]),"+r"(d[21]),"+r"(d[22]),"+r"(d[23])
    : "r"(a[0]),"r"(a[1]),"r"(a[2]),"r"(a[3]),"l"(desc));
}

#define SCHED_NG 10
#define SCHED_LE 104
#define SCHED_RING 16
__device__ const uint16_t g_sched[132][48] = {
{380,383,386,389,65535,65535,65535,65535,65535,65535,65535,65535,65535,65535,65535,65535,65535,65535,65535,65535,65535,65535,65535,65535,65535,65535,65535,65535,65535,65535,65535,65535,65535,65535,65535,65535,65535,65535,65535,65535,65535,65535,65535,65535,65535,65535,65535,65535},
{0,2507,22,2943,2953,2963,3801,73,83,93,3014,3852,124,134,144,3065,3903,175,185,195,206,3129,3139,3149,3975,259,269,279,3200,4026,310,320,330,3251,4077,361,371,2889,404,65535,65535,65535,65535,65535,65535,65535,65535,65535},
{796,799,802,805,65535,65535,65535,65535,65535,65535,65535,65535,65535,65535,65535,65535,65535,65535,65535,65535,65535,65535,65535,65535,65535,65535,65535,65535,65535,65535,65535,65535,65535,65535,65535,65535,65535,65535,65535,65535,65535,65535,65535,65535,65535,65535,65535,65535},
{416,426,436,446,456,467,477,487,497,507,518,528,538,548,558,569,579,589,599,609,622,632,642,653,663,673,683,693,704,714,724,734,744,755,765,775,787,808,819,65535,65535,65535,65535,65535,65535,65535,65535,65535},
{1212,1215,1218,1221,65535,65535,65535,65535,65535,65535,65535,65535,65535,65535,65535,65535,65535,65535,65535,65535,65535,65535,65535,65535,65535,65535,65535,65535,65535,65535,65535,65535,65535,65535,65535,65535,65535,65535,65535,65535,65535,65535,65535,65535,65535,65535,65535,65535},
{832,842,853,863,873,884,894,904,914,925,935,945,955,965,976,986,996,1006,1016,1027,1038,1049,1059,1070,1080,1090,1100,1111,1121,1131,1141,1151,1162,1172,1182,1192,1203,1225,1235,65535,65535,65535,65535,65535,65535,65535,65535,65535},
{1628,1631,1634,1637,65535,65535,65535,65535,65535,65535,65535,65535,65535,65535,65535,65535,65535,65535,65535,65535,65535,65535,65535,65535,65535,65535,65535,65535,65535,65535,65535,65535,65535,65535,65535,65535,65535,65535,65535,65535,65535,65535,65535,65535,65535,65535,65535,65535},
{1248,1259,1269,1279,1290,1300,1310,1320,1330,1341,1351,1361,1371,1381,1392,1402,1412,1422,1432,1443,1454,1465,1476,1486,1496,1506,1516,1527,1537,1547,1557,1567,1578,1588,1598,1608,1619,1641,1651,65535,65535,65535,65535,65535,65535,65535,65535,65535},
{2044,2047,2050,2053,65535,65535,65535,65535,65535,65535,65535,65535,65535,65535,65535,65535,65535,65535,65535,65535,65535,65535,65535,65535,65535,65535,65535,65535,65535,65535,65535,65535,65535,65535,65535,65535,65535,65535,65535,65535,65535,65535,65535,65535,65535,65535,65535,65535},
{1664,1675,1685,1696,1706,1716,1726,1736,1747,1757,1767,1777,1787,1798,1808,1818,1828,1838,1849,1859,1870,1881,1892,1902,1912,1922,1933,1943,1953,1963,1973,1984,1994,2004,2014,2024,2035,2057,2068,65535,65535,65535,65535,65535,65535,65535,65535,65535},
{2460,2463,2466,2469,65535,65535,65535,65535,65535,65535,65535,65535,65535,65535,65535,65535,65535,65535,65535,65535,65535,65535,65535,65535,65535,65535,65535,65535,65535,65535,65535,65535,65535,65535,65535,65535,65535,65535,65535,65535,65535,65535,65535,65535,65535,65535,65535,65535},
{2080,2091,2101,2112,2122,2132,2142,2152,2163,2173,2183,2193,2203,2214,2224,2234,2244,2254,2265,2275,2287,2298,2308,2318,2328,2338,2349,2359,2369,2379,2389,2400,2410,2420,2430,2440,2452,2473,2484,65535,65535,65535,65535,65535,65535,65535,65535,65535},
{2876,2879,2882,2885,65535,65535,65535,65535,65535,65535,65535,65535,65535,65535,65535,65535,65535,65535,65535,65535,65535,65535,65535,65535,65535,65535,65535,65535,65535,65535,65535,65535,65535,65535,65535,65535,65535,65535,65535,65535,65535,65535,65535,65535,65535,65535,65535,65535},
{2496,3335,3345,3355,3365,3375,2558,3396,3406,3416,3426,2609,3447,3457,3467,3477,2660,3498,3508,3518,3520,3529,3539,3549,2744,3570,3580,3590,3600,2795,3621,3631,3641,3651,2846,3672,2870,3705,2902,65535,65535,65535,65535,65535,65535,65535,65535,65535},
{3292,3295,3298,3301,65535,65535,65535,65535,65535,65535,65535,65535,65535,65535,65535,65535,65535,65535,65535,65535,65535,65535,65535,65535,65535,65535,65535,65535,65535,65535,65535,65535,65535,65535,65535,65535,65535,65535,65535,65535,65535,65535,65535,65535,65535,65535,65535,65535},
{2912,2923,2933,3771,3781,3791,2974,2984,2994,3004,3842,3025,3035,3045,3055,3893,3076,3086,3096,3106,3936,3945,3955,3965,3160,3170,3180,3190,4016,3211,3221,3231,3241,4067,3262,3272,3286,3305,3318,65535,65535,65535,65535,65535,65535,65535,65535,65535},
{381,384,387,390,65535,65535,65535,65535,65535,65535,65535,65535,65535,65535,65535,65535,65535,65535,65535,65535,65535,65535,65535,65535,65535,65535,65535,65535,65535,65535,65535,65535,65535,65535,65535,65535,65535,65535,65535,65535,65535,65535,65535,65535,65535,65535,65535,65535},
{1,3751,3761,33,43,53,63,3812,3822,3832,104,114,3863,3873,3883,155,165,3914,3924,3934,207,219,229,239,249,3986,3996,4006,290,300,4037,4047,4057,341,351,4088,372,4121,405,65535,65535,65535,65535,65535,65535,65535,65535,65535},
{797,800,803,806,65535,65535,65535,65535,65535,65535,65535,65535,65535,65535,65535,65535,65535,65535,65535,65535,65535,65535,65535,65535,65535,65535,65535,65535,65535,65535,65535,65535,65535,65535,65535,65535,65535,65535,65535,65535,65535,65535,65535,65535,65535,65535,65535,65535},
{417,427,437,447,457,468,478,488,498,508,519,529,539,549,559,570,580,590,600,610,623,633,643,654,664,674,684,694,705,715,725,735,745,756,766,776,788,809,820,65535,65535,65535,65535,65535,65535,65535,65535,65535},
{1213,1216,1219,1222,65535,65535,65535,65535,65535,65535,65535,65535,65535,65535,65535,65535,65535,65535,65535,65535,65535,65535,65535,65535,65535,65535,65535,65535,65535,65535,65535,65535,65535,65535,65535,65535,65535,65535,65535,65535,65535,65535,65535,65535,65535,65535,65535,65535},
{833,843,854,864,874,885,895,905,915,926,936,946,956,966,977,987,997,1007,1017,1028,1039,1050,1060,1071,1081,1091,1101,1112,1122,1132,1142,1152,1163,1173,1183,1193,1204,1226,1236,65535,65535,65535,65535,65535,65535,65535,65535,65535},
{1629,1632,1635,1638,65535,65535,65535,65535,65535,65535,65535,65535,65535,65535,65535,65535,65535,65535,65535,65535,65535,65535,65535,65535,65535,65535,65535,65535,65535,65535,65535,65535,65535,65535,65535,65535,65535,65535,65535,65535,65535,65535,65535,65535,65535,65535,65535,65535},
{1249,1260,1270,1280,1291,1301,1311,1321,1331,1342,1352,1362,1372,1382,1393,1403,1413,1423,1433,1444,1455,1466,1477,1487,1497,1507,1517,1528,1538,1548,1558,1568,1579,1589,1599,1609,1620,1642,1652,65535,65535,65535,65535,65535,65535,65535,65535,65535},
{2045,2048,2051,2054,65535,65535,65535,65535,65535,65535,65535,65535,65535,65535,65535,65535,65535,65535,65535,65535,65535,65535,65535,65535,65535,65535,65535,65535,65535,65535,65535,65535,65535,65535,65535,65535,65535,65535,65535,65535,65535,65535,65535,65535,65535,65535,65535,65535},
{1665,1676,1686,1697,1707,1717,1727,1737,1748,1758,1768,1778,1788,1799,1809,1819,1829,1839,1850,1860,1871,1882,1893,1903,1913,1923,1934,1944,1954,1964,1974,1985,1995,2005,2015,2025,2036,2058,2069,65535,65535,65535,65535,65535,65535,65535,65535,65535},
{2461,2464,2467,2470,65535,65535,65535,65535,65535,65535,65535,65535,65535,65535,65535,65535,65535,65535,65535,65535,65535,65535,65535,65535,65535,65535,65535,65535,65535,65535,65535,65535,65535,65535,65535,65535,65535,65535,65535,65535,65535,65535,65535,65535,65535,65535,65535,65535},
{2081,2092,2102,2113,2123,2133,2143,2153,2164,2174,2184,2194,2204,2215,2225,2235,2245,2255,2266,2276,2288,2299,2309,2319,2329,2339,2350,2360,2370,2380,2390,2401,2411,2421,2431,2441,2453,2474,2485,65535,65535,65535,65535,65535,65535,65535,65535,65535},
{2877,2880,2883,2886,65535,65535,65535,65535,65535,65535,65535,65535,65535,65535,65535,65535,65535,65535,65535,65535,65535,65535,65535,65535,65535,65535,65535,65535,65535,65535,65535,65535,65535,65535,65535,65535,65535,65535,65535,65535,65535,65535,65535,65535,65535,65535,65535,65535},
{2497,2508,2518,2528,3366,3376,2559,2569,2579,2589,3427,2610,2620,2630,2640,3478,2661,2671,2681,2691,2705,3530,3540,3550,2745,2755,2765,2775,3601,2796,2806,2816,2826,3652,2847,2857,2871,2890,2903,65535,65535,65535,65535,65535,65535,65535,65535,65535},
{3293,3296,3299,3302,65535,65535,65535,65535,65535,65535,65535,65535,65535,65535,65535,65535,65535,65535,65535,65535,65535,65535,65535,65535,65535,65535,65535,65535,65535,65535,65535,65535,65535,65535,65535,65535,65535,65535,65535,65535,65535,65535,65535,65535,65535,65535,65535,65535},
{2913,2924,2934,2944,2954,2964,3802,2985,2995,3005,3015,3853,3036,3046,3056,3066,3904,3087,3097,3107,3121,3130,3140,3150,3976,3171,3181,3191,3201,4027,3222,3232,3242,3252,4078,3273,3287,3306,3319,65535,65535,65535,65535,65535,65535,65535,65535,65535},
{382,385,388,391,65535,65535,65535,65535,65535,65535,65535,65535,65535,65535,65535,65535,65535,65535,65535,65535,65535,65535,65535,65535,65535,65535,65535,65535,65535,65535,65535,65535,65535,65535,65535,65535,65535,65535,65535,65535,65535,65535,65535,65535,65535,65535,65535,65535},
{2,13,23,3356,3782,3792,64,3397,3407,3417,3843,115,3448,3458,3468,3894,166,3499,3509,3519,209,3946,3956,3966,250,3571,3581,3591,4017,301,3622,3632,3642,4068,352,3673,374,3706,407,65535,65535,65535,65535,65535,65535,65535,65535,65535},
{798,801,804,807,65535,65535,65535,65535,65535,65535,65535,65535,65535,65535,65535,65535,65535,65535,65535,65535,65535,65535,65535,65535,65535,65535,65535,65535,65535,65535,65535,65535,65535,65535,65535,65535,65535,65535,65535,65535,65535,65535,65535,65535,65535,65535,65535,65535},
{418,428,438,448,458,469,479,489,499,509,520,530,540,550,560,571,581,591,601,611,624,634,644,655,665,675,685,695,706,716,726,736,746,757,767,777,789,810,821,65535,65535,65535,65535,65535,65535,65535,65535,65535},
{1214,1217,1220,1223,65535,65535,65535,65535,65535,65535,65535,65535,65535,65535,65535,65535,65535,65535,65535,65535,65535,65535,65535,65535,65535,65535,65535,65535,65535,65535,65535,65535,65535,65535,65535,65535,65535,65535,65535,65535,65535,65535,65535,65535,65535,65535,65535,65535},
{834,844,855,865,875,886,896,906,916,3833,937,947,957,967,3884,988,998,1008,1018,3935,1040,1051,1061,1072,1082,1092,1102,4007,1123,1133,1143,1153,4058,1174,1184,1194,1205,1227,1237,65535,65535,65535,65535,65535,65535,65535,65535,65535},
{1630,1633,1636,1639,65535,65535,65535,65535,65535,65535,65535,65535,65535,65535,65535,65535,65535,65535,65535,65535,65535,65535,65535,65535,65535,65535,65535,65535,65535,65535,65535,65535,65535,65535,65535,65535,65535,65535,65535,65535,65535,65535,65535,65535,65535,65535,65535,65535},
{1250,1261,1271,1281,1292,1302,1312,1322,1332,1343,1353,1363,1373,1383,1394,1404,1414,1424,1434,1445,1456,1467,1478,1488,1498,1508,1518,1529,1539,1549,1559,1569,1580,1590,1600,1610,1621,1643,1653,65535,65535,65535,65535,65535,65535,65535,65535,65535},
{2046,2049,2052,2055,65535,65535,65535,65535,65535,65535,65535,65535,65535,65535,65535,65535,65535,65535,65535,65535,65535,65535,65535,65535,65535,65535,65535,65535,65535,65535,65535,65535,65535,65535,65535,65535,65535,65535,65535,65535,65535,65535,65535,65535,65535,65535,65535,65535},
{1666,1677,1687,3772,1708,1718,1728,1738,1749,1759,1769,1779,1789,1800,1810,1820,1830,1840,1851,1861,1872,1883,1894,1904,1914,1924,1935,1945,1955,1965,1975,1986,1996,2006,2016,2026,2037,2059,2070,65535,65535,65535,65535,65535,65535,65535,65535,65535},
{2462,2465,2468,2471,65535,65535,65535,65535,65535,65535,65535,65535,65535,65535,65535,65535,65535,65535,65535,65535,65535,65535,65535,65535,65535,65535,65535,65535,65535,65535,65535,65535,65535,65535,65535,65535,65535,65535,65535,65535,65535,65535,65535,65535,65535,65535,65535,65535},
{2082,2093,2103,2114,2124,2134,2144,2154,2165,2175,2185,2195,2205,2216,2226,2236,2246,2256,2267,2277,2289,2300,2310,2320,2330,2340,2351,2361,2371,2381,2391,2402,2412,2422,2432,2442,2454,2475,2486,65535,65535,65535,65535,65535,65535,65535,65535,65535},
{2878,2881,2884,2887,65535,65535,65535,65535,65535,65535,65535,65535,65535,65535,65535,65535,65535,65535,65535,65535,65535,65535,65535,65535,65535,65535,65535,65535,65535,65535,65535,65535,65535,65535,65535,65535,65535,65535,65535,65535,65535,65535,65535,65535,65535,65535,65535,65535},
{2498,3336,3346,2529,2539,2549,3387,2570,2580,2590,2600,3438,2621,2631,2641,2651,3489,2672,2682,2692,3521,2715,2725,2735,3561,2756,2766,2776,2786,3612,2807,2817,2827,2837,3663,2858,2872,2891,2904,65535,65535,65535,65535,65535,65535,65535,65535,65535},
{3294,3297,3300,3303,65535,65535,65535,65535,65535,65535,65535,65535,65535,65535,65535,65535,65535,65535,65535,65535,65535,65535,65535,65535,65535,65535,65535,65535,65535,65535,65535,65535,65535,65535,65535,65535,65535,65535,65535,65535,65535,65535,65535,65535,65535,65535,65535,65535},
{2914,3752,3762,2945,2955,2965,2975,3813,3823,3006,3016,3026,3864,3874,3057,3067,3077,3915,3925,3108,3937,3131,3141,3151,3161,3987,3997,3192,3202,3212,4038,4048,3243,3253,3263,4089,3288,4122,3320,65535,65535,65535,65535,65535,65535,65535,65535,65535},
{3,14,24,35,45,55,2976,3814,3824,96,106,3027,3865,3875,147,157,3078,3916,3926,198,211,221,231,241,3162,3988,3998,282,292,3213,4039,4049,333,343,3264,4090,376,4123,409,65535,65535,65535,65535,65535,65535,65535,65535,65535},
{4,3337,3763,34,44,54,65,75,85,95,105,116,126,136,146,156,167,177,187,197,210,220,230,240,251,261,271,281,291,302,312,322,332,342,353,363,375,396,408,65535,65535,65535,65535,65535,65535,65535,65535,65535},
{419,429,439,449,459,470,480,490,500,510,521,531,541,551,561,572,582,592,602,612,625,635,645,656,666,676,686,696,707,717,727,737,747,758,768,778,790,811,822,65535,65535,65535,65535,65535,65535,65535,65535,65535},
{420,430,440,450,460,471,481,491,501,511,522,532,542,552,562,573,583,593,603,613,626,636,646,657,667,677,687,697,708,718,728,738,748,759,769,779,791,812,823,65535,65535,65535,65535,65535,65535,65535,65535,65535},
{835,845,856,866,876,887,897,907,917,927,938,948,958,968,978,989,999,1009,1019,1029,1041,1052,1062,1073,1083,1093,1103,1113,1124,1134,1144,1154,1164,1175,1185,1195,1206,1228,1238,65535,65535,65535,65535,65535,65535,65535,65535,65535},
{836,846,857,867,877,2550,3388,908,918,928,2601,3439,959,969,979,2652,3490,1010,1020,1030,1042,1053,1063,2736,3562,1094,1104,1114,2787,3613,1145,1155,1165,2838,3664,1196,1207,1229,1239,65535,65535,65535,65535,65535,65535,65535,65535,65535},
{1251,1262,1272,1282,1293,1303,1313,1323,1333,1344,1354,1364,1374,1384,1395,1405,1415,1425,1435,1446,1457,1468,1479,1489,1499,1509,1519,1530,1540,1550,1560,1570,1581,1591,1601,1611,1622,1644,1654,65535,65535,65535,65535,65535,65535,65535,65535,65535},
{1252,3753,1273,1283,2540,2966,3804,1324,1334,2591,3017,3855,1375,1385,2642,3068,3906,1426,1436,1447,1458,1469,2726,3152,3978,1510,1520,2777,3203,4029,1561,1571,2828,3254,4080,1612,1623,1645,1655,65535,65535,65535,65535,65535,65535,65535,65535,65535},
{1667,1678,1688,1698,1709,1719,1729,1739,1750,1760,1770,1780,1790,1801,1811,1821,1831,1841,1852,1862,1873,1884,1895,1905,1915,1925,1936,1946,1956,1966,1976,1987,1997,2007,2017,2027,2038,2060,2071,65535,65535,65535,65535,65535,65535,65535,65535,65535},
{1668,1679,1689,1699,2956,3378,1730,1740,2581,3007,3429,1781,1791,2632,3058,3480,1832,1842,2683,1863,1874,1885,3142,3552,1916,1926,2767,3193,3603,1967,1977,2818,3244,3654,2018,2028,2039,2061,2072,65535,65535,65535,65535,65535,65535,65535,65535,65535},
{2083,2094,2104,2115,2125,2135,2145,2155,2166,2176,2186,2196,2206,2217,2227,2237,2247,2257,2268,2278,2290,2301,2311,2321,2331,2341,2352,2362,2372,2382,2392,2403,2413,2423,2433,2443,2455,2476,2487,65535,65535,65535,65535,65535,65535,65535,65535,65535},
{2084,2095,2105,2530,3368,3794,2146,2156,2997,3419,3845,2197,2207,3048,3470,3896,2248,2258,3099,2279,2291,2716,3542,3968,2332,2342,3183,3593,4019,2383,2393,3234,3644,4070,2434,2444,2456,2477,2488,65535,65535,65535,65535,65535,65535,65535,65535,65535},
{3676,3679,3682,3685,3688,65535,65535,65535,65535,65535,65535,65535,65535,65535,65535,65535,65535,65535,65535,65535,65535,65535,65535,65535,65535,65535,65535,65535,65535,65535,65535,65535,65535,65535,65535,65535,65535,65535,65535,65535,65535,65535,65535,65535,65535,65535,65535,65535},
{2499,2509,2519,3357,3367,3377,2560,3398,3408,3418,3428,2611,3449,3459,3469,3479,2662,3500,3510,2693,2706,3531,3541,3551,2746,3572,3582,3592,3602,2797,3623,3633,3643,3653,2848,3674,2873,3707,2905,65535,65535,65535,65535,65535,65535,65535,65535,65535},
{4092,4095,4098,4101,4104,65535,65535,65535,65535,65535,65535,65535,65535,65535,65535,65535,65535,65535,65535,65535,65535,65535,65535,65535,65535,65535,65535,65535,65535,65535,65535,65535,65535,65535,65535,65535,65535,65535,65535,65535,65535,65535,65535,65535,65535,65535,65535,65535},
{2915,2925,2935,3773,3783,3793,3803,2986,2996,3834,3844,3854,3037,3047,3885,3895,3905,3088,3098,3109,3122,3947,3957,3967,3977,3172,3182,4008,4018,4028,3223,3233,4059,4069,4079,3274,3289,3307,3321,65535,65535,65535,65535,65535,65535,65535,65535,65535},
{421,431,441,451,461,472,482,492,502,512,523,533,543,553,563,574,584,594,604,614,627,637,647,658,668,678,688,698,709,719,729,739,749,760,770,780,792,813,824,65535,65535,65535,65535,65535,65535,65535,65535,65535},
{2500,2510,2520,2946,3784,2551,2561,2571,3409,3835,2602,2612,2622,3460,3886,2653,2663,2673,3511,615,3522,3132,3958,2737,2747,2757,3583,4009,2788,2798,2808,3634,4060,2839,2849,2859,793,2892,825,65535,65535,65535,65535,65535,65535,65535,65535,65535},
{837,847,2936,3358,878,888,898,2987,3825,929,939,949,3038,3876,980,990,1000,3089,3927,1031,1043,3532,1064,1074,1084,3173,3999,1115,1125,1135,3224,4050,1166,1176,1186,3275,1208,3308,1240,65535,65535,65535,65535,65535,65535,65535,65535,65535},
{2916,2926,3348,3774,2541,2967,2977,3399,919,2592,3018,3028,3450,970,2643,3069,3079,3501,1021,2694,3938,3948,2727,3153,3163,3573,1105,2778,3204,3214,3624,1156,2829,3255,3265,3675,1209,3708,1241,65535,65535,65535,65535,65535,65535,65535,65535,65535},
{1253,1263,3764,1284,3785,1305,1315,1325,3410,3836,1356,1366,1376,3461,3887,1407,1417,1427,3512,1448,1460,3533,3959,1491,1501,1511,3584,4010,1542,1552,1562,3635,4061,1593,1603,1613,1625,1646,1657,65535,65535,65535,65535,65535,65535,65535,65535,65535},
{3328,3338,1274,2531,1294,1304,1314,3815,1335,1345,1355,1365,3866,1386,1396,1406,1416,3917,1437,3110,1459,1470,1480,1490,1500,3989,1521,1531,1541,1551,4040,1572,1582,1592,1602,4091,1624,4124,1656,65535,65535,65535,65535,65535,65535,65535,65535,65535},
{1669,3754,1690,1700,1710,1720,1731,1741,1751,1761,1771,1782,1792,1802,1812,1822,1833,1843,1853,1864,1875,1886,1896,1906,1917,1927,1937,1947,1957,1968,1978,1988,1998,2008,2019,2029,2040,2062,2073,65535,65535,65535,65535,65535,65535,65535,65535,65535},
{3744,1680,3349,3775,1711,1721,2562,3400,3826,1762,1772,2613,3451,3877,1813,1823,2664,3502,3928,1865,1876,3949,1897,1907,2748,3574,4000,1948,1958,2799,3625,4051,1999,2009,2850,2030,2041,3709,2074,65535,65535,65535,65535,65535,65535,65535,65535,65535},
{2085,2096,3765,2117,2127,2137,2978,3816,2168,2178,2188,3029,3867,2219,2229,2239,3080,3918,2270,2281,3523,2303,2313,2323,3164,3990,2354,2364,2374,3215,4041,2405,2415,2425,3266,2446,2458,4125,2490,65535,65535,65535,65535,65535,65535,65535,65535,65535},
{2086,2511,2106,2116,2126,2136,2147,2157,2167,2177,2187,2198,2208,2218,2228,2238,2249,2259,2269,2280,2292,2302,2312,2322,2333,2343,2353,2363,2373,2384,2394,2404,2414,2424,2435,2445,2457,2478,2489,65535,65535,65535,65535,65535,65535,65535,65535,65535},
{3677,3680,3683,3686,3689,65535,65535,65535,65535,65535,65535,65535,65535,65535,65535,65535,65535,65535,65535,65535,65535,65535,65535,65535,65535,65535,65535,65535,65535,65535,65535,65535,65535,65535,65535,65535,65535,65535,65535,65535,65535,65535,65535,65535,65535,65535,65535,65535},
{2501,3339,2521,3359,3369,3379,3389,2572,2582,3420,3430,3440,2623,2633,3471,3481,3491,2674,2684,2695,2707,2717,3543,3553,3563,2758,2768,3594,3604,3614,2809,2819,3645,3655,3665,2860,2874,2893,2906,65535,65535,65535,65535,65535,65535,65535,65535,65535},
{4093,4096,4099,4102,4105,65535,65535,65535,65535,65535,65535,65535,65535,65535,65535,65535,65535,65535,65535,65535,65535,65535,65535,65535,65535,65535,65535,65535,65535,65535,65535,65535,65535,65535,65535,65535,65535,65535,65535,65535,65535,65535,65535,65535,65535,65535,65535,65535},
{2917,2927,2937,2947,2957,3795,3805,2988,2998,3008,3846,3856,3039,3049,3059,3897,3907,3090,3100,3111,3123,3133,3143,3969,3979,3174,3184,3194,4020,4030,3225,3235,3245,4071,4081,3276,3290,3309,3322,65535,65535,65535,65535,65535,65535,65535,65535,65535},
{422,432,443,453,463,2552,3390,494,504,514,2603,3441,545,555,565,2654,3492,596,606,617,3939,639,649,2738,3564,680,690,700,2789,3615,731,741,751,2840,3666,782,795,815,827,65535,65535,65535,65535,65535,65535,65535,65535,65535},
{3329,3755,442,452,462,473,483,493,503,513,524,534,544,554,564,575,585,595,605,616,628,638,648,659,669,679,689,699,710,720,730,740,750,761,771,781,794,814,826,65535,65535,65535,65535,65535,65535,65535,65535,65535},
{838,848,858,868,879,889,899,909,920,930,940,950,960,971,981,991,1001,1011,1022,1032,1044,1054,1065,1075,1085,1095,1106,1116,1126,1136,1146,1157,1167,1177,1187,1197,1210,1230,1242,65535,65535,65535,65535,65535,65535,65535,65535,65535},
{3745,849,859,869,2542,2968,3806,910,2583,2593,3019,3857,961,2634,2644,3070,3908,1012,2685,1033,1045,1055,2728,3154,3980,1096,2769,2779,3205,4031,1147,2820,2830,3256,4082,1198,1211,1231,1243,65535,65535,65535,65535,65535,65535,65535,65535,65535},
{1254,1264,1275,1285,1295,3380,1316,1326,1336,1346,3431,1367,1377,1387,1397,3482,1418,1428,1438,1449,1461,1471,1481,3554,1502,1512,1522,1532,3605,1553,1563,1573,1583,3656,1604,1614,1626,1647,1658,65535,65535,65535,65535,65535,65535,65535,65535,65535},
{1255,1265,2522,2532,2958,3796,2563,2573,2999,3009,3847,2614,2624,3050,3060,3898,2665,2675,3101,2696,2708,2718,3144,3970,2749,2759,3185,3195,4021,2800,2810,3236,3246,4072,2851,2861,1627,2894,1659,65535,65535,65535,65535,65535,65535,65535,65535,65535},
{1670,1681,1691,1701,3370,1722,1732,1742,1752,3421,1773,1783,1793,1803,3472,1824,1834,1844,1854,3112,1877,1887,3544,1908,1918,1928,1938,3595,1959,1969,1979,1989,3646,2010,2020,3277,2042,2063,2075,65535,65535,65535,65535,65535,65535,65535,65535,65535},
{1671,2512,2938,2948,3786,2553,2979,2989,3411,3837,2604,3030,3040,3462,3888,2655,3081,3091,3513,1866,3124,3134,3960,2739,3165,3175,3585,4011,2790,3216,3226,3636,4062,2841,3267,2031,2043,3310,2076,65535,65535,65535,65535,65535,65535,65535,65535,65535},
{2087,2097,2107,3360,2128,2139,2149,2159,2169,3422,2190,2200,2210,2220,3473,2241,2251,2261,2271,2283,2294,2304,3545,2325,2335,2345,2355,3596,2376,2386,2396,2406,3647,2427,2437,2448,3691,2480,2492,65535,65535,65535,65535,65535,65535,65535,65535,65535},
{2502,2928,3350,3776,2543,2138,2148,2158,3827,2179,2189,2199,2209,3878,2230,2240,2250,2260,3929,2282,2293,3534,2314,2324,2334,2344,4001,2365,2375,2385,2395,4052,2416,2426,2436,2447,2459,2479,2491,65535,65535,65535,65535,65535,65535,65535,65535,65535},
{3678,3681,3684,3687,3690,65535,65535,65535,65535,65535,65535,65535,65535,65535,65535,65535,65535,65535,65535,65535,65535,65535,65535,65535,65535,65535,65535,65535,65535,65535,65535,65535,65535,65535,65535,65535,65535,65535,65535,65535,65535,65535,65535,65535,65535,65535,65535,65535},
{3330,3340,2523,2533,3371,3381,3391,3401,2584,2594,3432,3442,3452,2635,2645,3483,3493,3503,2686,2697,3524,2719,2729,3555,3565,3575,2770,2780,3606,3616,3626,2821,2831,3657,3667,2862,2875,3710,2907,65535,65535,65535,65535,65535,65535,65535,65535,65535},
{4094,4097,4100,4103,4106,65535,65535,65535,65535,65535,65535,65535,65535,65535,65535,65535,65535,65535,65535,65535,65535,65535,65535,65535,65535,65535,65535,65535,65535,65535,65535,65535,65535,65535,65535,65535,65535,65535,65535,65535,65535,65535,65535,65535,65535,65535,65535,65535},
{2918,3756,3766,2949,2959,2969,3807,3817,3000,3010,3020,3858,3868,3051,3061,3071,3909,3919,3102,3113,3940,3950,3145,3155,3981,3991,3186,3196,3206,4032,4042,3237,3247,3257,4083,3278,3291,4126,3323,65535,65535,65535,65535,65535,65535,65535,65535,65535},
{423,433,444,3361,465,475,485,2574,3412,516,526,536,2625,3463,567,577,587,2676,3514,619,630,3535,651,661,671,2760,3586,702,712,722,2811,3637,753,763,773,784,3693,2895,829,65535,65535,65535,65535,65535,65535,65535,65535,65535},
{3746,434,2939,454,464,474,484,495,505,515,525,535,546,556,566,576,586,597,607,618,629,640,650,660,670,681,691,701,711,721,732,742,752,762,772,783,3692,816,828,65535,65535,65535,65535,65535,65535,65535,65535,65535},
{839,850,860,871,881,891,901,3402,922,932,942,952,3453,973,983,993,1003,3504,1024,1035,2709,3951,1067,1077,1087,3576,1108,1118,1128,1138,3627,1159,1169,1179,1189,1200,4109,3711,1245,65535,65535,65535,65535,65535,65535,65535,65535,65535},
{840,2513,3351,870,880,890,900,911,921,931,941,951,962,972,982,992,1002,1013,1023,1034,1046,1056,1066,1076,1086,1097,1107,1117,1127,1137,1148,1158,1168,1178,1188,1199,4108,1232,1244,65535,65535,65535,65535,65535,65535,65535,65535,65535},
{1256,3341,1277,1286,1296,1306,1317,1327,1337,1347,1357,1368,1378,1388,1398,1408,1419,1429,1439,1450,1462,1472,1482,1492,1503,1513,1523,1533,1543,1554,1564,1574,1584,1594,1605,1615,3694,1648,1660,65535,65535,65535,65535,65535,65535,65535,65535,65535},
{2503,1266,1276,1287,1297,1307,2564,3818,1338,1348,1358,2615,3869,1389,1399,1409,2666,3920,1440,1451,3525,1473,1483,1493,2750,3992,1524,1534,1544,2801,4043,1575,1585,1595,2852,1616,4110,4127,1661,65535,65535,65535,65535,65535,65535,65535,65535,65535},
{1672,3757,1693,1702,1712,1723,1733,1743,1753,1763,1774,1784,1794,1804,1814,1825,1835,1845,1855,1867,1878,1888,1898,1909,1919,1929,1939,1949,1960,1970,1980,1990,2000,2011,2021,2032,3695,2064,2077,65535,65535,65535,65535,65535,65535,65535,65535,65535},
{2919,1682,1692,1703,1713,2554,3392,1744,1754,1764,2605,3443,1795,1805,1815,2656,3494,1846,1856,2698,3941,1889,1899,2740,3566,1930,1940,1950,2791,3617,1981,1991,2001,2842,3668,2863,4111,2065,2908,65535,65535,65535,65535,65535,65535,65535,65535,65535},
{2088,2099,2109,2118,2129,2970,3808,2160,2170,2180,3021,3859,2211,2221,2231,3072,3910,2262,2272,2284,2295,2305,2315,3156,3982,2346,2356,2366,3207,4033,2397,2407,2417,3258,4084,2449,3696,2481,2493,65535,65535,65535,65535,65535,65535,65535,65535,65535},
{3331,2098,2108,2119,2544,3382,2150,2575,2585,2595,3433,2201,2626,2636,2646,3484,2252,2677,2687,2699,2710,2720,2730,3556,2336,2761,2771,2781,3607,2387,2812,2822,2832,3658,2438,2864,4112,2896,2494,65535,65535,65535,65535,65535,65535,65535,65535,65535},
{2504,2514,2524,2534,3372,2555,2565,3403,3413,3423,2606,2616,3454,3464,3474,2657,2667,3505,3515,2700,3526,3536,3546,2741,2751,3577,3587,3597,2792,2802,3628,3638,3648,2843,2853,2865,3697,2897,2909,65535,65535,65535,65535,65535,65535,65535,65535,65535},
{3332,3342,3352,3362,2545,3383,3393,2576,2586,2596,3434,3444,2627,2637,2647,3485,3495,2678,2688,3115,2711,2721,2731,3557,3567,2762,2772,2782,3608,3618,2813,2823,2833,3659,3669,3280,3698,3312,2910,65535,65535,65535,65535,65535,65535,65535,65535,65535},
{3747,2929,3767,3777,3787,3797,2980,2990,3828,3838,3848,3031,3041,3879,3889,3899,3082,3092,3930,3114,3125,3135,3961,3971,3166,3176,4002,4012,4022,3217,3227,4053,4063,4073,3268,3279,4107,3311,3324,65535,65535,65535,65535,65535,65535,65535,65535,65535},
{2920,2930,2940,2950,2960,3798,2981,2991,3001,3011,3849,3032,3042,3052,3062,3900,3083,3093,3103,3116,3126,3136,3146,3972,3167,3177,3187,3197,4023,3218,3228,3238,3248,4074,3269,3281,4113,3313,3325,65535,65535,65535,65535,65535,65535,65535,65535,65535},
{424,435,445,455,3788,476,486,496,506,3839,527,537,547,557,3890,578,588,598,608,620,631,641,3962,662,672,682,692,4013,713,723,733,743,4064,764,774,785,4114,817,830,65535,65535,65535,65535,65535,65535,65535,65535,65535},
{425,3758,3768,3778,466,2971,3809,3819,3829,517,3022,3860,3870,3880,568,3073,3911,3921,3931,621,3942,3952,652,3157,3983,3993,4003,703,3208,4034,4044,4054,754,3259,4085,786,3699,818,831,65535,65535,65535,65535,65535,65535,65535,65535,65535},
{841,851,861,872,882,892,902,912,923,933,943,953,963,974,984,994,1004,1014,1025,1036,1047,1057,1068,1078,1088,1098,1109,1119,1129,1139,1149,1160,1170,1180,1190,1201,4117,1233,1246,65535,65535,65535,65535,65535,65535,65535,65535,65535},
{3748,852,862,3363,883,893,903,913,924,934,944,954,964,975,985,995,1005,1015,1026,1037,1048,1058,1069,1079,1089,1099,1110,1120,1130,1140,1150,1161,1171,1181,1191,1202,1224,1234,1247,65535,65535,65535,65535,65535,65535,65535,65535,65535},
{1257,1267,1278,1288,1298,1308,1318,1328,1339,1349,1359,1369,1379,1390,1400,1410,1420,1430,1441,1452,1463,1474,1484,1494,1504,1514,1525,1535,1545,1555,1565,1576,1586,1596,1606,1617,3702,1649,1662,65535,65535,65535,65535,65535,65535,65535,65535,65535},
{1258,1268,3353,1289,1299,1309,1319,1329,1340,1350,1360,1370,1380,1391,1401,1411,1421,1431,1442,1453,1464,1475,1485,1495,1505,1515,1526,1536,1546,1556,1566,1577,1587,1597,1607,1618,1640,1650,1663,65535,65535,65535,65535,65535,65535,65535,65535,65535},
{1673,1683,1694,1704,1714,1724,1734,1745,1755,1765,1775,1785,1796,1806,1816,1826,1836,1847,1857,1868,1879,1890,1900,1910,1920,1931,1941,1951,1961,1971,1982,1992,2002,2012,2022,2033,4118,2066,2078,65535,65535,65535,65535,65535,65535,65535,65535,65535},
{1674,1684,1695,1705,1715,1725,1735,1746,1756,1766,1776,1786,1797,1807,1817,1827,1837,1848,1858,1869,1880,1891,1901,1911,1921,1932,1942,1952,1962,1972,1983,1993,2003,2013,2023,2034,2056,2067,2079,65535,65535,65535,65535,65535,65535,65535,65535,65535},
{2089,2100,2111,2121,2131,2141,3394,2162,2172,2182,2192,3445,2213,2223,2233,2243,3496,2264,2274,2286,2297,2307,2317,2327,3568,2348,2358,2368,2378,3619,2399,2409,2419,2429,3670,2451,3703,2483,415,65535,65535,65535,65535,65535,65535,65535,65535,65535},
{2090,2515,2110,2120,2130,2140,2151,2161,2171,2181,2191,2202,2212,2222,2232,2242,2253,2263,2273,2285,2296,2306,2316,2326,2337,2347,2357,2367,2377,2388,2398,2408,2418,2428,2439,2450,2472,2482,2495,65535,65535,65535,65535,65535,65535,65535,65535,65535},
{2505,3343,2525,2535,3373,2556,2566,3404,3414,3424,2607,2617,3455,3465,3475,2658,2668,3506,3516,2701,3527,3537,3547,2742,2752,3578,3588,3598,2793,2803,3629,3639,3649,2844,2854,2866,3700,2898,2911,65535,65535,65535,65535,65535,65535,65535,65535,65535},
{3333,2516,2526,2536,2546,3384,2567,2577,2587,2597,3435,2618,2628,2638,2648,3486,2669,2679,2689,2702,2712,2722,2732,3558,2753,2763,2773,2783,3609,2804,2814,2824,2834,3660,2855,2867,2888,2899,65535,65535,65535,65535,65535,65535,65535,65535,65535,65535},
{2921,2931,2941,2951,2961,3799,2982,2992,3002,3012,3850,3033,3043,3053,3063,3901,3084,3094,3104,3117,3127,3137,3147,3973,3168,3178,3188,3198,4024,3219,3229,3239,3249,4075,3270,3282,4115,3314,3326,65535,65535,65535,65535,65535,65535,65535,65535,65535},
{3749,3759,3769,3779,3789,2972,3810,3820,3830,3840,3023,3861,3871,3881,3891,3074,3912,3922,3932,3118,3943,3953,3963,3158,3984,3994,4004,4014,3209,4035,4045,4055,4065,3260,4086,3283,4116,3315,3327,65535,65535,65535,65535,65535,65535,65535,65535,65535},
{2506,3344,3354,3364,3374,2557,3395,3405,3415,3425,2608,3446,3456,3466,3476,2659,3497,3507,3517,2703,3528,3538,3548,2743,3569,3579,3589,3599,2794,3620,3630,3640,3650,2845,3671,2868,3704,2900,65535,65535,65535,65535,65535,65535,65535,65535,65535,65535},
{3334,2517,2527,2537,2547,3385,2568,2578,2588,2598,3436,2619,2629,2639,2649,3487,2670,2680,2690,2704,2713,2723,2733,3559,2754,2764,2774,2784,3610,2805,2815,2825,2835,3661,2856,2869,4119,2901,65535,65535,65535,65535,65535,65535,65535,65535,65535,65535},
{2922,2932,2942,2952,2962,3800,2983,2993,3003,3013,3851,3034,3044,3054,3064,3902,3085,3095,3105,3119,3128,3138,3148,3974,3169,3179,3189,3199,4025,3220,3230,3240,3250,4076,3271,3284,3304,3316,65535,65535,65535,65535,65535,65535,65535,65535,65535,65535},
{3750,3760,3770,3780,3790,2973,3811,3821,3831,3841,3024,3862,3872,3882,3892,3075,3913,3923,3933,3120,3944,3954,3964,3159,3985,3995,4005,4015,3210,4036,4046,4056,4066,3261,4087,3285,4120,3317,65535,65535,65535,65535,65535,65535,65535,65535,65535,65535},
{5,15,25,36,46,56,66,76,86,97,107,117,127,137,148,158,168,178,188,199,212,222,232,242,252,262,272,283,293,303,313,323,334,344,354,364,377,397,410,65535,65535,65535,65535,65535,65535,65535,65535,65535},
{6,16,26,37,47,57,67,77,87,98,108,118,128,138,149,159,169,179,189,200,213,223,233,243,253,263,273,284,294,304,314,324,335,345,355,365,378,398,411,65535,65535,65535,65535,65535,65535,65535,65535,65535},
{7,17,27,38,48,58,68,78,88,99,109,119,129,139,150,160,170,180,190,201,214,224,234,244,254,264,274,285,295,305,315,325,336,346,356,366,379,399,412,65535,65535,65535,65535,65535,65535,65535,65535,65535},
{8,18,28,39,49,59,69,79,89,100,110,120,130,140,151,161,171,181,191,202,215,225,235,245,255,265,275,286,296,306,316,326,337,347,357,367,3701,400,413,65535,65535,65535,65535,65535,65535,65535,65535,65535},
{9,19,29,40,50,60,70,80,90,101,111,121,131,141,152,162,172,182,192,203,216,226,236,246,256,266,276,287,297,307,317,327,338,348,358,368,392,401,414,65535,65535,65535,65535,65535,65535,65535,65535,65535},
{10,20,30,41,51,61,71,81,91,102,112,122,132,142,153,163,173,183,193,204,217,227,237,247,257,267,277,288,298,308,318,328,339,349,359,369,393,402,65535,65535,65535,65535,65535,65535,65535,65535,65535,65535},
{11,21,31,42,52,62,72,82,92,103,113,123,133,143,154,164,174,184,194,205,218,228,238,248,258,268,278,289,299,309,319,329,340,350,360,370,394,403,65535,65535,65535,65535,65535,65535,65535,65535,65535,65535},
{12,3347,32,2538,2548,3386,74,84,94,2599,3437,125,135,145,2650,3488,176,186,196,208,2714,2724,2734,3560,260,270,280,2785,3611,311,321,331,2836,3662,362,373,395,406,65535,65535,65535,65535,65535,65535,65535,65535,65535,65535},
};

#define TABLED 1
#define TRIG 7
#define JB 22
#define PRE 2
#define CH 64
#define CFN 1
#define CREGS 232
#define FIRST 4
constexpr int NG = SCHED_NG, NCONV = 3 * NG;
constexpr int RING = SCHED_RING;
constexpr int NSLOT = 8;
constexpr int PLEN = SCHED_LE, LM = 256 - 2 * PLEN, NSEG = 4 / (NG - 8), LMID = NSEG * LM;
static_assert(LMID <= PLEN && NG == 10, "geometry");
constexpr int TILEB = 12288;
constexpr int SLOTB = 280 * 64;
constexpr int W1S = 0, W2S = 73728, ABUF = 147456, XBUF = ABUF + 16 * 3072, MISC = XBUF + 8 * 3072;
constexpr int WBAR = MISC + 2560;
constexpr int RBUF = ABUF - 4 * SLOTB;
constexpr int CM = MISC + 2816, CTAB = CM + 256;
constexpr int SMEM_BYTES = CTAB + (PLEN + 16) * 16;
static_assert(RBUF % 512 == 0 && RBUF >= W2S && RBUF + NSLOT * SLOTB + 128 <= MISC && SMEM_BYTES <= 232448, "smem layout");

struct Globals {
  unsigned char scratch[RING * NG * 4 * TILEB];
  unsigned char wimg[147456];
  uint32_t wflag[32];
  uint32_t ready[NG * PLEN + 1];
  uint32_t cons[NG * PLEN];
  uint32_t epoch[1024];
};
__device__ __align__(1024) Globals g_state;

#define GELU_C3 0.32920349f
#define GELU_A2 0x40d940d9u
#define GELU_S2 0x3e133e13u
#define SCHED_FENCE() asm volatile("pmevent 0;" ::: "memory")
#define SPIN_LIMIT 0x1000000

__device__ __forceinline__ uint32_t smem_u32(const void* p) { return (uint32_t)__cvta_generic_to_shared(p); }
__device__ __forceinline__ void wg_fence() { asm volatile("wgmma.fence.sync.aligned;" ::: "memory"); }
__device__ __forceinline__ void wg_commit() { asm volatile("wgmma.commit_group.sync.aligned;" ::: "memory"); }
template <int N> __device__ __forceinline__ void wg_wait() { asm volatile("wgmma.wait_group.sync.aligned %0;" ::"n"(N) : "memory"); }
__device__ __forceinline__ void mbar_wait(uint32_t bar, uint32_t parity) {
  asm volatile("{\n.reg .pred p;\n.reg .u32 c;\nmbarrier.try_wait.parity.shared::cta.b64 p, [%0], %1;\n@p bra DONE_%=;\nmov.u32 c, 0;\nWAIT_%=:\nmbarrier.try_wait.parity.shared::cta.b64 p, [%0], %1;\n@p bra DONE_%=;\n"
               "add.u32 c, c, 1;\nsetp.lt.u32 p, c, 0x1000000;\n@p bra WAIT_%=;\ntrap;\nDONE_%=:\n}" ::"r"(bar), "r"(parity) : "memory");
}
__device__ __forceinline__ void mbar_arrive_elect(uint32_t bar) { asm volatile("{.reg .pred p; elect.sync _|p, 0xffffffff; @p mbarrier.arrive.shared::cta.b64 _, [%0];}" ::"r"(bar) : "memory"); }
__device__ __forceinline__ void mbar_init_elect(uint32_t bar, uint32_t cnt) { asm volatile("{.reg .pred p; elect.sync _|p, 0xffffffff; @p mbarrier.init.shared::cta.b64 [%0], %1;}" ::"r"(bar), "r"(cnt) : "memory"); }
__device__ __forceinline__ uint32_t ld_relaxed(const uint32_t* p) { uint32_t v; asm volatile("ld.relaxed.gpu.global.u32 %0, [%1];" : "=r"(v) : "l"(p) : "memory"); return v; }
__device__ __forceinline__ void red_add_elect(uint32_t* p) { asm volatile("{.reg .pred p; elect.sync _|p, 0xffffffff; @p red.relaxed.gpu.global.add.u32 [%0], 1;}" ::"l"(p) : "memory"); }
__device__ __forceinline__ void wait_value(const uint32_t* p, uint32_t target, int ns) {
  int spins = 0;
  while (ld_relaxed(p) != target) { __nanosleep(ns); if (++spins > SPIN_LIMIT) __trap(); }
}
template <int BYTES, bool INIT = false> __device__ __forceinline__ void bulk_load(uint32_t dst, const void* src, uint32_t bar, int go = 0) {
  if (INIT) asm volatile("{.reg .pred p; elect.sync _|p, 0xffffffff; @p mbarrier.init.shared::cta.b64 [%0], 1; @p fence.mbarrier_init.release.cluster;}" ::"r"(bar) : "memory");
  asm volatile("{\n.reg .pred p, q;\nsetp.ge.s32 q, %4, 0;\nelect.sync _|p, 0xffffffff;\nand.pred p, p, q;\n@p mbarrier.arrive.expect_tx.shared::cta.b64 _, [%1], %3;\n"
               "@p cp.async.bulk.shared::cluster.global.mbarrier::complete_tx::bytes [%0], [%2], %3, [%1];\n}"
               ::"r"(dst), "r"(bar), "l"(src), "n"(BYTES), "r"(go) : "memory");
}
__device__ __forceinline__ void lds128(uint32_t* r, uint32_t a) { asm volatile("ld.shared.v4.b32 {%0,%1,%2,%3}, [%4];" : "=r"(r[0]), "=r"(r[1]), "=r"(r[2]), "=r"(r[3]) : "r"(a) : "memory"); }
__device__ __forceinline__ uint2 lds64(uint32_t a) { uint2 v; asm volatile("ld.shared.v2.b32 {%0,%1}, [%2];" : "=r"(v.x), "=r"(v.y) : "r"(a) : "memory"); return v; }
__device__ __forceinline__ uint32_t lds32(uint32_t a) { uint32_t v; asm volatile("ld.shared.b32 %0, [%1];" : "=r"(v) : "r"(a) : "memory"); return v; }
__device__ __forceinline__ void sts32(uint32_t a, uint32_t v) { asm volatile("st.shared.b32 [%0], %1;" ::"r"(a), "r"(v) : "memory"); }
__device__ __forceinline__ void sts64(uint32_t a, uint2 v) { asm volatile("st.shared.v2.b32 [%0], {%1,%2};" ::"r"(a), "r"(v.x), "r"(v.y) : "memory"); }
__device__ __forceinline__ void sts128(uint32_t a, uint4 v) { asm volatile("st.shared.v4.b32 [%0], {%1,%2,%3,%4};" ::"r"(a), "r"(v.x), "r"(v.y), "r"(v.z), "r"(v.w) : "memory"); }
__device__ __forceinline__ uint64_t pol_evict_first() { uint64_t p; asm("createpolicy.fractional.L2::evict_first.b64 %0, 1.0;" : "=l"(p)); return p; }
__device__ __forceinline__ void stg128_stream(void* p, uint4 v, uint64_t pol) {
  asm volatile("st.global.L2::cache_hint.v4.b32 [%0], {%1,%2,%3,%4}, %5;" ::"l"(p), "r"(v.x), "r"(v.y), "r"(v.z), "r"(v.w), "l"(pol) : "memory");
}
__device__ __forceinline__ void stg128_if(uint32_t go, void* p, uint4 v) {
  asm volatile("{.reg .pred q; setp.ge.s32 q, %5, 0; @q st.global.v4.b32 [%0], {%1,%2,%3,%4};}" ::"l"(p), "r"(v.x), "r"(v.y), "r"(v.z), "r"(v.w), "r"(go) : "memory");
}
__device__ __forceinline__ uint32_t pack_f16(float lo, float hi) { uint32_t d; asm("cvt.rn.f16x2.f32 %0, %1, %2;" : "=r"(d) : "f"(hi), "f"(lo)); return d; }
__device__ __forceinline__ uint32_t pack_f16_sat(float lo, float hi) { uint32_t d; asm("cvt.rn.satfinite.f16x2.f32 %0, %1, %2;" : "=r"(d) : "f"(hi), "f"(lo)); return d; }
__device__ __forceinline__ uint32_t pack_bf16(float lo, float hi) { uint32_t d; asm("cvt.rn.bf16x2.f32 %0, %1, %2;" : "=r"(d) : "f"(hi), "f"(lo)); return d; }
__device__ __forceinline__ uint32_t bf2_to_h2(uint32_t w) { return pack_f16(__uint_as_float(w << 16), __uint_as_float(w & 0xffff0000u)); }
__device__ __forceinline__ uint32_t hadd2_bf16(uint32_t a, uint32_t b) { uint32_t d; asm("add.rn.bf16x2 %0, %1, %2;" : "=r"(d) : "r"(a), "r"(b)); return d; }
__device__ __forceinline__ uint32_t h2add(uint32_t a, uint32_t b) { uint32_t d; asm("add.rn.f16x2 %0, %1, %2;" : "=r"(d) : "r"(a), "r"(b)); return d; }
__device__ __forceinline__ uint32_t h2mul(uint32_t a, uint32_t b) { uint32_t d; asm("mul.rn.f16x2 %0, %1, %2;" : "=r"(d) : "r"(a), "r"(b)); return d; }
__device__ __forceinline__ uint32_t h2fma(uint32_t a, uint32_t b, uint32_t c) { uint32_t d; asm("fma.rn.f16x2 %0, %1, %2, %3;" : "=r"(d) : "r"(a), "r"(b), "r"(c)); return d; }
__device__ __forceinline__ uint32_t h2lo(uint32_t a) { uint32_t d; asm("{.reg .f16 l,h; mov.b32 {l,h}, %1; mov.b32 %0, {l,l};}" : "=r"(d) : "r"(a)); return d; }
__device__ __forceinline__ uint32_t h2hi(uint32_t a) { uint32_t d; asm("{.reg .f16 l,h; mov.b32 {l,h}, %1; mov.b32 %0, {h,h};}" : "=r"(d) : "r"(a)); return d; }
__device__ __forceinline__ float h_lo(uint32_t a) { float d; asm("{.reg .f16 l,h; mov.b32 {l,h}, %1; cvt.f32.f16 %0, l;}" : "=f"(d) : "r"(a)); return d; }
__device__ __forceinline__ float h_hi(uint32_t a) { float d; asm("{.reg .f16 l,h; mov.b32 {l,h}, %1; cvt.f32.f16 %0, h;}" : "=f"(d) : "r"(a)); return d; }
__device__ __forceinline__ float rsqrt_fast(float v) { float r; asm("rsqrt.approx.ftz.f32 %0, %1;" : "=f"(r) : "f"(v)); return r; }
__device__ __forceinline__ uint32_t prmt(uint32_t a, uint32_t b, uint32_t s) { uint32_t d; asm("prmt.b32 %0, %1, %2, %3;" : "=r"(d) : "r"(a), "r"(b), "r"(s)); return d; }
__device__ __forceinline__ void mma_sp(float* d, const uint32_t* a, const uint32_t* b, const float* c, uint32_t e) {
  asm("mma.sp::ordered_metadata.sync.aligned.m16n8k32.row.col.f32.bf16.bf16.f32 {%0,%1,%2,%3}, {%4,%5,%6,%7}, {%8,%9,%10,%11}, {%12,%13,%14,%15}, %16, 0;"
      : "=f"(d[0]), "=f"(d[1]), "=f"(d[2]), "=f"(d[3])
      : "r"(a[0]), "r"(a[1]), "r"(a[2]), "r"(a[3]), "r"(b[0]), "r"(b[1]), "r"(b[2]), "r"(b[3]), "f"(c[0]), "f"(c[1]), "f"(c[2]), "f"(c[3]), "r"(e));
}

__device__ __forceinline__ uint32_t gelu_tanh(uint32_t y) {
  uint32_t t, u, th;
  asm volatile("fma.rn.f16x2 %0, %1, %1, %2;" : "=r"(t) : "r"(y), "r"(GELU_A2));
  asm volatile("mul.rn.f16x2 %0, %1, %2;" : "=r"(u) : "r"(y), "r"(t));
  asm volatile("tanh.approx.f16x2 %0, %1;" : "=r"(th) : "r"(u));
  return th;
}
__device__ __forceinline__ uint32_t gelu_fin(uint32_t y, uint32_t th) {
  uint32_t g;
  asm volatile("fma.rn.f16x2 %0, %1, %2, %1;" : "=r"(g) : "r"(y), "r"(th));
  return g;
}

__device__ __forceinline__ void convert_weights(uint32_t sb, int rot, int warp, int lane) {
  if (warp < 12) {
    const int l8 = lane & 7, q4 = lane >> 3;
    int s = (warp >> 1) + rot; if (s >= 6) s -= 6;
    const uint32_t base = sb + W1S + s * 12288 + (warp & 1) * 384;
    mbar_wait(sb + WBAR + s * 8, 0);
    uint32_t v[3][4][4];
#pragma unroll
    for (int r = 0; r < 4; r++)
#pragma unroll
      for (int i = 0; i < 3; i++) lds128(v[i][r], base + i * 128 + (4 * (l8 >> 1) + 2 * (r & 1) + (l8 & 1)) * 768 + ((l8 + q4 + 4 * (r >> 1)) & 7) * 16);
    __syncwarp();
#pragma unroll
    for (int r = 0; r < 4; r++)
#pragma unroll
      for (int i = 0; i < 3; i++)
        sts128(base + i * 128 + (((l8 + q4 + 4 * (r >> 1)) & 7) + 8 * (r & 1)) * 768 + l8 * 16,
               make_uint4(bf2_to_h2(v[i][r][0]), bf2_to_h2(v[i][r][1]), bf2_to_h2(v[i][r][2]), bf2_to_h2(v[i][r][3])));
  }
  const int q = lane & 3, t = (lane >> 2) & 3, b = lane >> 4;
  int u = 3 * (warp ^ 15) + 8 * rot; if (u >= 48) u -= 48;
  uint32_t base[3], v[3][4][3];
#pragma unroll
  for (int i = 0; i < 3; i++) {
    const int ui = u + i >= 48 ? u + i - 48 : u + i;
    base[i] = sb + W2S + ui * 1536;
    if (i != 1) mbar_wait(sb + WBAR + 48 + (ui >> 3) * 8, 0);
  }
#pragma unroll
  for (int i = 0; i < 3; i++)
#pragma unroll
    for (int d = 0; d < 4; d++)
#pragma unroll
      for (int j = 0; j < 3; j++) v[i][d][j] = lds32(base[i] + (2 * ((q + d) & 3) + b) * 192 + j * 64 + t * 16 + q * 4);
  __syncwarp();
#pragma unroll
  for (int i = 0; i < 3; i++)
#pragma unroll
    for (int d = 0; d < 4; d++)
#pragma unroll
      for (int j = 0; j < 3; j++) sts32(base[i] + (4 * j + q) * 128 + (2 * ((q + d) & 3) + b) * 16 + t * 4, bf2_to_h2(v[i][d][j]));
}

__device__ __noinline__ void ln_wide(uint32_t ad) {
  float m[2], r[2];
#pragma unroll
  for (int hi = 0; hi < 2; hi++) {
    float sm = 0.f;
    for (int s = 0; s < 6; s++) { uint2 w = lds64(ad + s * 512 + hi * 8); sm += (h_lo(w.x) + h_hi(w.x)) + (h_lo(w.y) + h_hi(w.y)); }
    sm += __shfl_xor_sync(0xffffffffu, sm, 1); sm += __shfl_xor_sync(0xffffffffu, sm, 2);
    m[hi] = sm * (1.f / 96.f);
    float q = 0.f;
    for (int s = 0; s < 6; s++) {
      uint2 w = lds64(ad + s * 512 + hi * 8);
      float d0 = h_lo(w.x) - m[hi], d1 = h_hi(w.x) - m[hi], d2 = h_lo(w.y) - m[hi], d3 = h_hi(w.y) - m[hi];
      q += (d0 * d0 + d1 * d1) + (d2 * d2 + d3 * d3);
    }
    q += __shfl_xor_sync(0xffffffffu, q, 1); q += __shfl_xor_sync(0xffffffffu, q, 2);
    r[hi] = rsqrtf(fmaf(q, 1.f / 96.f, 1e-5f)) * GELU_C3;
  }
  for (int s = 0; s < 6; s++) {
    uint32_t w[4]; lds128(w, ad + s * 512);
    sts128(ad + s * 512, make_uint4(pack_f16((h_lo(w[0]) - m[0]) * r[0], (h_hi(w[0]) - m[0]) * r[0]), pack_f16((h_lo(w[2]) - m[1]) * r[1], (h_hi(w[2]) - m[1]) * r[1]),
                                    pack_f16((h_lo(w[1]) - m[0]) * r[0], (h_hi(w[1]) - m[0]) * r[0]), pack_f16((h_lo(w[3]) - m[1]) * r[1], (h_hi(w[3]) - m[1]) * r[1])));
  }
  asm volatile("fence.proxy.async.shared::cta;" ::: "memory");
}

__device__ __forceinline__ uint32_t layer_norm(const uint32_t (&raw)[6][4], uint32_t* a, uint32_t tag) {
  const uint32_t stale = ((raw[0][0] ^ tag) | (raw[1][0] ^ tag)) | ((raw[2][0] ^ tag) | (raw[3][0] ^ tag)) | ((raw[4][0] ^ tag) | (raw[5][0] ^ tag));
  uint32_t sm[2], qq[2];
#pragma unroll
  for (int hi = 0; hi < 2; hi++) {
    uint32_t s0 = h2add(raw[0][2 * hi], raw[1][2 * hi]), s1 = h2add(raw[0][2 * hi + 1], raw[1][2 * hi + 1]);
    uint32_t s2 = h2add(raw[2][2 * hi], raw[3][2 * hi]), s3 = h2add(raw[2][2 * hi + 1], raw[3][2 * hi + 1]);
    uint32_t s4 = h2add(raw[4][2 * hi], raw[5][2 * hi]), s5 = h2add(raw[4][2 * hi + 1], raw[5][2 * hi + 1]);
    sm[hi] = h2add(h2add(h2add(s0, s1), h2add(s2, s3)), h2add(s4, s5));
  }
#pragma unroll
  for (int hi = 0; hi < 2; hi++) {
    uint32_t q0 = h2mul(raw[0][2 * hi], raw[0][2 * hi]), q1 = h2mul(raw[0][2 * hi + 1], raw[0][2 * hi + 1]);
#pragma unroll
    for (int k = 1; k < 6; k++) { q0 = h2fma(raw[k][2 * hi], raw[k][2 * hi], q0); q1 = h2fma(raw[k][2 * hi + 1], raw[k][2 * hi + 1], q1); }
    qq[hi] = h2add(q0, q1);
  }
  uint32_t s = h2add(prmt(sm[0], sm[1], 0x5410), prmt(sm[0], sm[1], 0x7632));
  uint32_t q = h2add(prmt(qq[0], qq[1], 0x5410), prmt(qq[0], qq[1], 0x7632));
  s = h2add(s, __shfl_xor_sync(0xffffffffu, s, 1)); q = h2add(q, __shfl_xor_sync(0xffffffffu, q, 1));
  s = h2add(s, __shfl_xor_sync(0xffffffffu, s, 2)); q = h2add(q, __shfl_xor_sync(0xffffffffu, q, 2));
  constexpr float K1 = 1.f / (96.f * GELU_C3 * GELU_C3), K2 = 1e-5f / (GELU_C3 * GELU_C3), K3 = 1.f / (96.f * GELU_C3);
  const float e0 = fmaf(h_lo(q), K1, K2), e1 = fmaf(h_hi(q), K1, K2), m0 = h_lo(s) * K3, m1 = h_hi(s) * K3;
  const float v0 = fmaf(-m0, m0, e0), v1 = fmaf(-m1, m1, e1);
  const uint32_t r = pack_f16(rsqrt_fast(v0), rsqrt_fast(v1)), o = h2mul(h2mul(s, 0xA155A155u), r);
#pragma unroll
  for (int k = 0; k < 6; k++) {
    a[4 * k] = h2fma(raw[k][0], h2lo(r), h2lo(o)); a[4 * k + 2] = h2fma(raw[k][1], h2lo(r), h2lo(o));
    a[4 * k + 1] = h2fma(raw[k][2], h2hi(r), h2hi(o)); a[4 * k + 3] = h2fma(raw[k][3], h2hi(r), h2hi(o));
  }
  const bool fine = fmaf(v0, 4.f, -e0) > 0.f && fmaf(v1, 4.f, -e1) > 0.f;
  return (fine ? 0u : 2u) | (stale & 1);
}

constexpr int KS = CH / 16, NC = 384 / CH;
#define WG1_(n) wgmma_n##n##_f16
#define WG1(n) WG1_(n)
__device__ __forceinline__ void gemm1(uint32_t* p, const uint32_t* a, uint64_t d1, int c, int k0, int k1) {
#pragma unroll
  for (int s = 0; s < 6; s++)
    if (s >= k0 && s < k1) {
      if (s == 0) WG1(CH)<0>(p, a, d1 + c * CH); else WG1(CH)<1>(p, a + 4 * s, d1 + c * CH + s * (12288 >> 4));
    }
}
__device__ __forceinline__ void fetch_x(uint32_t xbuf, uint32_t bar, const CUtensorMap* tm, uint32_t c0, uint32_t c12, uint64_t pol, int go = 0) {
  asm volatile("{\n.reg .pred p, q;\nsetp.ge.s32 q, %7, 0;\nelect.sync _|p, 0xffffffff;\nand.pred p, p, q;\n"
               "@p mbarrier.arrive.expect_tx.shared::cta.b64 _, [%1], 3072;\n"
               "@p cp.async.bulk.tensor.3d.shared::cluster.global.mbarrier::complete_tx::bytes.L2::cache_hint [%0], [%2, {%3, %4, %5}], [%1], %6;\n}"
               ::"r"(xbuf), "r"(bar), "l"(tm), "r"(c0), "r"(c12 & 255), "r"(c12 >> 8), "l"(pol), "r"(go) : "memory");
}
__device__ __forceinline__ uint32_t slot_tag(int gm, int j, uint32_t epoch) {
  const int len = gm < 8 ? PLEN : LMID, writes = (len - j % RING + RING - 1) / RING;
  return (epoch * writes + j / RING + 1) & 1;
}
__device__ __forceinline__ void build_tile_list(uint32_t sb, int k, int idx, bool tabled, bool is_conv, uint32_t epoch) {
  int n = -1;
  if (tabled) { if (k < 48) n = (int16_t)g_sched[idx][k]; }
  else if (!is_conv) {
    const int i = k * (gridDim.x - NCONV) + idx, r = i >> 2, full = LMID * NG;
    const int j = r < full ? r / NG : ((r - full) >> 3) + LMID, gm = r < full ? r % NG : (r - full) & 7;
    if (i < 4096) n = (gm * PLEN + j) * 4 + (i & 3);
  }
  const int q = n >> 2, gm = q / PLEN, j = q - gm * PLEN, seg = j / LM;
  const int strip = gm < 8 ? gm >> 1 : (gm - 8) * NSEG + seg, pair = gm < 8 ? ((gm & 1) ? 255 - j : j) : PLEN + j - seg * LM;
  sts128(sb + MISC + 512 + k * 16, make_uint4(q, (((j % RING) * NG + gm) * 4 + (n & 3)) * TILEB + slot_tag(gm, j, epoch),
                                              (n & 2) * 384, (strip * 8 + (n & 1) * 4) | (pair << 9)));
  if (k == 0) { sts32(sb + MISC + 256, epoch + 1); sts32(sb + MISC + 260, !is_conv); }
}

__device__ __forceinline__ void mlp_setup(uint32_t sb, Globals* gs, int id, const __nv_bfloat16* __restrict__ w1, const __nv_bfloat16* __restrict__ w2,
                                          int idx, bool tabled, int warp, int lane) {
  const int rot = idx % 6;
  if (warp < 12) {
    const int m = warp >= 6; int s = warp - 6 * m + rot; if (s >= 6) s -= 6;
    bulk_load<12288, true>(sb + (6 * m + s) * 12288, (const char*)(m ? w2 : w1) + s * 12288, sb + WBAR + (6 * m + s) * 8);
  }
  __syncthreads();
  if (warp >= 12) build_tile_list(sb, threadIdx.x - 384, idx, tabled, false, ld_relaxed(&gs->epoch[id]));
  convert_weights(sb, rot, warp, lane);
  asm volatile("fence.proxy.async.shared::cta;" ::: "memory");
  __syncthreads();
  if (threadIdx.x == 480) {
    gs->epoch[id] = lds32(sb + MISC + 256);
    if (idx < 24 && (idx & 1)) {
      asm volatile("cp.async.bulk.global.shared::cta.bulk_group [%0], [%1], 12288;\ncp.async.bulk.commit_group;\ncp.async.bulk.wait_group 0;\nfence.proxy.async.global;\n"
                   "red.release.gpu.global.add.u32 [%2], 1;" ::"l"(gs->wimg + (idx >> 1) * 12288), "r"(sb + (idx >> 1) * 12288), "l"(gs->wflag) : "memory");
    }
  }
  __syncwarp();
}

__device__ __forceinline__ void mlp_role(uint32_t sb, Globals* gs, const CUtensorMap* tmr, __nv_bfloat16* __restrict__ out) {
  uint32_t tid;
  asm volatile("mov.u32 %0, %%tid.x;" : "=r"(tid));
  const int warp = __shfl_sync(0xffffffffu, tid >> 5, 0), lane = tid & 31;
  const int wg = warp >> 2, w = warp & 3, g = lane >> 2, t = lane & 3;
  const uint32_t abuf = sb + ABUF + warp * 3072, xbuf = sb + XBUF + (warp & 7) * 3072;
  const uint32_t bar = sb + MISC + warp * 8, obar = sb + MISC + (warp ^ 8) * 8;
  const uint32_t tl = sb + MISC + 512;
  const uint32_t rtarget = 3 * lds32(sb + MISC + 256);
  const uint64_t d1 = ((uint64_t)(6144 >> 4) << 16) | ((uint64_t)(128 >> 4) << 32) | (uint64_t)(((sb + W1S) >> 4) & 0x3fff);
  const uint64_t d2 = ((uint64_t)(12288 >> 4) << 16) | ((uint64_t)(128 >> 4) << 32) | (uint64_t)(((sb + W2S) >> 4) & 0x3fff);
  const uint32_t ad = abuf + t * 128 + ((g ^ (2 * t)) << 4);
  const uint32_t xd = xbuf + g * 192 + t * 16;
  const uint32_t pofs = (g >> 1) * 3072 + (2 * w + (g & 1)) * 192 + t * 16;
  const int mybar = 1 + wg, nxtbar = 1 + ((wg + 1) & 3);
  const uint64_t pol = pol_evict_first();
  const unsigned char* const asrc = gs->scratch + w * 3072;
  uint32_t pha = 0, phx = 0, tp = tl + wg * 16;
  bool pending = lds32(sb + MISC + 260);
  uint32_t cur[4];
  lds128(cur, tp);
  if (wg < 2) fetch_x(xbuf, bar + 128, tmr, cur[2] + w * 192, cur[3], pol, cur[0]);
  while ((int)cur[0] >= 0) {
    uint32_t a[24], p[NC][CH / 4], gg[24][4], th[24][4], acc[24], raw[6][4], n2[4], n4[4];
    if (pending) {
      wait_value(&gs->ready[cur[0]], rtarget, 32);
      bulk_load<3072>(abuf, asrc + (cur[1] & ~1u), bar);
    }
    mbar_wait(bar, pha); pha ^= 1;
#pragma unroll
    for (int k = 0; k < 6; k++) lds128(raw[k], ad + k * 512);
    uint32_t st = layer_norm(raw, a, cur[1]);
    if (__any_sync(0xffffffffu, st != 0)) {
      for (int tries = 0; __any_sync(0xffffffffu, st & 1); tries++) {
        if (tries > SPIN_LIMIT) __trap();
        bulk_load<3072>(abuf, asrc + (cur[1] & ~1u), bar);
        mbar_wait(bar, pha); pha ^= 1;
        st = 0;
#pragma unroll
        for (int k = 0; k < 6; k++) st |= lds32(ad + k * 512) ^ cur[1];
      }
      ln_wide(ad);
#pragma unroll
      for (int k = 0; k < 6; k++) lds128(a + 4 * k, ad + k * 512);
    }
    if (tp != tl) asm volatile("bar.sync %0, 256;" ::"r"(mybar) : "memory");
    uint32_t rdy = 0;
    wg_fence();
    gemm1(p[0], a, d1, 0, 0, 6); wg_commit();
    gemm1(p[1], a, d1, 1, 0, 6 / KS); wg_commit();
    const int sig = lds32(tp + 16);
    lds128(n4, tp + 64);
    asm volatile("{.reg .pred p; setp.eq.u32 p, %1, 0; @p red.relaxed.gpu.global.add.u32 [%0], 1;}" ::"l"(&gs->cons[cur[0]] + lane), "r"(lane) : "memory");
#pragma unroll
    for (int j = 0; j < 24; j++) {
      const int c = j / KS, s = j % KS;
      if (j == JB) rdy = ld_relaxed(&gs->ready[max((int)n4[0], 0)]);
      if (s == 0) wg_wait<1>();
      if (j == TRIG) asm volatile("{.reg .pred p; setp.ge.s32 p, %1, 0; @p bar.arrive %0, 256;}" ::"r"(nxtbar), "r"(sig) : "memory");
#pragma unroll
      for (int i = 0; i < 4; i++) {
        if (!(s && i < PRE)) th[j][i] = gelu_tanh(p[c][4 * s + i]);
        gg[j][i] = gelu_fin(p[c][4 * s + i], th[j][i]);
      }
      wg_fence();
      if (j == 0) wgmma_n96_f16<0>(acc, gg[j], d2); else wgmma_n96_f16<1>(acc, gg[j], d2 + (16 * (j % 3) + j / 3) * (1536 >> 4));
      const int c1 = (j + 1) / KS + 1, u = (j + 1) % KS;
      if (c1 < NC) gemm1(p[c1], a, d1, c1, (6 * u) / KS, (6 * (u + 1)) / KS);
      wg_commit();
      if (s + 1 < KS) {
#pragma unroll
        for (int i = 0; i < PRE; i++) th[j + 1][i] = gelu_tanh(p[c][4 * s + 4 + i]);
      }
      if (j < 23) SCHED_FENCE();
    }
    pending = rdy != rtarget;
    bulk_load<3072>(abuf, asrc + (n4[1] & ~1u), bar, pending ? -1 : (int)n4[0]);
    wg_wait<0>();
    mbar_wait(bar + 128, phx); phx ^= 1;
#pragma unroll
    for (int k = 0; k < 24; k++) acc[k] = h2mul(acc[k], GELU_S2);
    char* const op = (char*)out + (cur[2] * 2 + (cur[3] & 255) * 3072 + (cur[3] >> 8) * (512 * 192) + pofs);
    lds128(n2, tp + 32);
#pragma unroll
    for (int k = 0; k < 6; k++) {
      const int hi = k / 3, j = k % 3;
      uint32_t xr[4];
      lds128(xr, xd + hi * 1536 + j * 64);
      uint4 o;
      o.x = hadd2_bf16(xr[0], pack_bf16(h_lo(acc[8 * j + hi]), h_hi(acc[8 * j + hi])));
      o.y = hadd2_bf16(xr[1], pack_bf16(h_lo(acc[8 * j + 2 + hi]), h_hi(acc[8 * j + 2 + hi])));
      o.z = hadd2_bf16(xr[2], pack_bf16(h_lo(acc[8 * j + 4 + hi]), h_hi(acc[8 * j + 4 + hi])));
      o.w = hadd2_bf16(xr[3], pack_bf16(h_lo(acc[8 * j + 6 + hi]), h_hi(acc[8 * j + 6 + hi])));
      stg128_stream(op + hi * (512 * 192) + j * 64, o, pol);
    }
    __syncwarp();
    if ((int)n2[0] >= 0) fetch_x(xbuf, obar + 128, tmr, n2[2] + w * 192, n2[3], pol);
    tp += 64;
#pragma unroll
    for (int k = 0; k < 4; k++) cur[k] = n4[k];
  }
}

__device__ __forceinline__ void conv_compute(uint32_t sb, Globals* gs, int third, int nit, int off, bool up, int warp, int lane) {
  const int g = lane >> 2, t = lane & 3;
  const uint32_t full = sb + CM;
  const uint32_t wt = sb + 16384 + warp * 1024;
  sts128(wt + lane * 16, make_uint4(0, 0, 0, 0));
  if (lane < 4) sts128(wt + 512 + lane * 16, make_uint4(0, 0, 0, 0));
  asm volatile("setmaxnreg.inc.sync.aligned.u32 %0;" ::"n"(CREGS));
  uint32_t meta = 0;
#pragma unroll
  for (int a = 0; a < 4; a++) meta |= ((4 * (t & 1) + a + 1 >= g) ? 0x80008u : 0xD000Du) << (4 * a);
  meta = __shfl_sync(0xffffffffu, meta, lane);
  uint32_t aq[4];
#pragma unroll
  for (int q = 0; q < 4; q++) {
    const int pp = (g & 1) * 140 + (t & 1) * 70 + 16 * (g >> 1) + 2 * q + (t >> 1);
    aq[q] = __shfl_sync(0xffffffffu, sb + RBUF + pp * 64 + (((warp >> 1) ^ ((pp >> 1) & 3)) << 4) + (warp & 1) * 8, lane);
  }
  const int Q = third * 8 + warp;
  unsigned char* const obase = gs->scratch + (g >> 1) * 3072 + Q * 128 + (((2 * t + (g & 1)) ^ (2 * (Q & 3))) << 4);
  const float zero4[4] = {0.f, 0.f, 0.f, 0.f};
  float S[2][4][3][4];
  __syncwarp();
#pragma unroll
  for (int i = 0; i < 8; i++) {
    lds128((uint32_t*)S[i >> 2][i & 3][0], wt + i * 16);
#pragma unroll
    for (int k = 0; k < 8; k++) asm volatile("" : "=f"(S[i >> 2][i & 3][1 + (k >> 2)][k & 3]));
  }
  uint32_t A[4][4][4];
  asm volatile("bar.sync 5, 288;" ::: "memory");
  mbar_wait(sb + WBAR + 8, 0);
  {
#pragma unroll
    for (int k = 0; k < 2; k++) {
      const int tap = lane + 32 * k;
      if (tap < 49) sts64(wt + (tap + tap / 7 + 8) * 8, lds64(sb + tap * 192 + third * 64 + warp * 8));
    }
    __syncwarp();
    uint2 w[2][4][3];
#pragma unroll
    for (int h = 0; h < 2; h++) {
      uint32_t src = wt + ((4 * h + t - g) & 7) * 8 + (up ? 384 : 0);
#pragma unroll
      for (int u = 0; u < 4; u++) {
#pragma unroll
        for (int k = 0; k < 3; k++) w[h][u][k] = lds64(src + k * 64);
        src += up ? -128 : 128;
      }
    }
#pragma unroll
    for (int u = 0; u < 4; u++)
#pragma unroll
      for (int r = 0; r < 4; r++) {
        const uint2 w0 = w[r >> 1][u][1 - (r & 1)], w1 = w[r >> 1][u][2 - (r & 1)];
        A[0][u][r] = prmt(w0.x, w1.x, 0x5410); A[1][u][r] = prmt(w0.x, w1.x, 0x7632);
        A[2][u][r] = prmt(w0.y, w1.y, 0x5410); A[3][u][r] = prmt(w0.y, w1.y, 0x7632);
      }
  }
  uint32_t sofs = off * SLOTB, bar = full + off * 8, ph = 0, ot = sb + CTAB;
  const uint32_t oend = ot + nit * 16;
  asm volatile("bar.sync 0, 512;" ::: "memory");
  mbar_wait(bar, 0);
  uint2 X[3][4];
#pragma unroll
  for (int j = 0; j < 2; j++)
#pragma unroll
    for (int q = 0; q < 4; q++) X[j][q] = lds64(aq[q] + sofs + j * 512);
#pragma unroll 1
  do {
    const uint2 oe = lds64(ot);
    unsigned char* const o = obase + oe.x;
    const uint32_t dbar = bar + 64;
#pragma unroll
    for (int s = 0; s < 2; s++) {
      uint32_t B[4][4];
      if (s == 1) {
        sofs += SLOTB; bar += 8;
        if (sofs == NSLOT * SLOTB) { sofs = 0; bar = full; ph ^= 1; }
        mbar_wait(bar, ph);
      }
#pragma unroll
      for (int c = 0; c < 4; c++)
#pragma unroll
        for (int q = 0; q < 4; q++) B[c][q] = prmt(c < 2 ? X[s][q].x : X[s][q].y, c < 2 ? X[s + 1][q].x : X[s + 1][q].y, (c & 1) ? 0x7632 : 0x5410);
      if (s == 0) {
#pragma unroll
        for (int q = 0; q < 4; q++) X[2][q] = lds64(aq[q] + sofs + 2 * 512);
      } else {
#pragma unroll
        for (int j = 0; j < 2; j++)
#pragma unroll
          for (int q = 0; q < 4; q++) X[j][q] = lds64(aq[q] + sofs + j * 512);
      }
      float T[4][4];
      if (CFN & 1) SCHED_FENCE();
#pragma unroll
      for (int c = 0; c < 4; c++) mma_sp(T[c], A[c][3], B[c], S[s][c][2], meta);
#pragma unroll
      for (int c = 0; c < 4; c++) mma_sp(S[s][c][2], A[c][2], B[c], S[s][c][1], meta);
      if (CFN & 8) {
#pragma unroll
        for (int c = 0; c < 4; c++) mma_sp(S[s][c][1], A[c][1], B[c], S[s][c][0], meta);
#pragma unroll
        for (int c = 0; c < 4; c++) mma_sp(S[s][c][0], A[c][0], B[c], zero4, meta);
      }
      if (CFN & 2) SCHED_FENCE();
      stg128_if(oe.x, o + (2 * s) * TILEB, make_uint4((pack_f16_sat(T[0][0], T[1][0]) & ~1u) | oe.y, pack_f16_sat(T[2][0], T[3][0]), pack_f16_sat(T[0][2], T[1][2]), pack_f16_sat(T[2][2], T[3][2])));
      stg128_if(oe.x, o + (2 * s + 1) * TILEB, make_uint4((pack_f16_sat(T[0][1], T[1][1]) & ~1u) | oe.y, pack_f16_sat(T[2][1], T[3][1]), pack_f16_sat(T[0][3], T[1][3]), pack_f16_sat(T[2][3], T[3][3])));
      if (s == 1) mbar_arrive_elect(dbar);
      if (CFN & 4) SCHED_FENCE();
      if (!(CFN & 8)) {
#pragma unroll
        for (int c = 0; c < 4; c++) mma_sp(S[s][c][1], A[c][1], B[c], S[s][c][0], meta);
#pragma unroll
        for (int c = 0; c < 4; c++) mma_sp(S[s][c][0], A[c][0], B[c], zero4, meta);
      }
    }
    ot += 16;
  } while (ot != oend);
}

__device__ __forceinline__ void load_step(uint32_t sb, const CUtensorMap* tmx, int gm, int third, int it, int s, bool first = false) {
  const int seg = first ? 0 : it / (LM + 3);
  const int st = gm < 8 ? gm >> 1 : (gm - 8) * NSEG + seg, J = gm < 8 ? ((gm & 1) ? 257 - it : it + 1) : PLEN + it - seg * (LM + 3);
  asm volatile("{\n.reg .pred p;\n.reg .s32 c2;\n.reg .u32 d2;\nelect.sync _|p, 0xffffffff;\nadd.s32 c2, %4, 64;\nadd.u32 d2, %0, 8960;\n"
               "@p mbarrier.arrive.expect_tx.shared::cta.b64 _, [%2], 17920;\n"
               "@p cp.async.bulk.tensor.3d.shared::cluster.global.mbarrier::complete_tx::bytes [%0], [%1, {%3, %4, %5}], [%2];\n"
               "@p cp.async.bulk.tensor.3d.shared::cluster.global.mbarrier::complete_tx::bytes [d2], [%1, {%3, c2, %5}], [%2];\n}"
               ::"r"(sb + RBUF + s * SLOTB), "l"(tmx), "r"(sb + CM + s * 8), "r"(third * 32), "r"(st * 128 - 3), "r"(2 * J - 3) : "memory");
}
__device__ __forceinline__ void ring_bar_init(uint32_t bar, uint32_t cnt, bool ahead) {
  asm volatile("{\n.reg .pred p, q;\nelect.sync _|p, 0xffffffff;\n@p mbarrier.init.shared::cta.b64 [%0], %1;\n"
               "setp.ne.and.u32 q, %2, 0, p;\n@q mbarrier.arrive.shared::cta.b64 _, [%0], %1;\n@p fence.mbarrier_init.release.cluster;\n}" ::"r"(bar), "r"(cnt), "r"((uint32_t)ahead) : "memory");
}
__device__ __forceinline__ void conv_loader(uint32_t sb, Globals* gs, const CUtensorMap* tmx, int gm, int nit, int off, int cidx, int third, int k) {
  static_assert(FIRST >= 4 && NCONV >= 24, "loader");
  const uint32_t full = sb + CM;
  asm volatile("bar.sync 0, 512;" ::: "memory");
  if (FIRST + k < NSLOT) load_step(sb, tmx, gm, third, FIRST + k, (FIRST + k + off) & 7, true);
#pragma unroll 1
  for (int it = NSLOT + k; it < nit + NSLOT; it += 4) {
    const int u = it + off;
    const uint32_t ro = lds32(sb + CTAB + (it - NSLOT) * 16 + 8);
    mbar_wait(full + 64 + (u & 7) * 8, ((u >> 3) & 1) ^ 1);
    red_add_elect((uint32_t*)((char*)gs + ro));
    if (it < nit) load_step(sb, tmx, gm, third, it, u & 7);
    else if (it == nit) mbar_arrive_elect(full);
    if (it >= nit - 16) {
      if (it < nit - 12) {
        wait_value(gs->wflag, 12 * lds32(sb + MISC + 256), 32);
        asm volatile("fence.acquire.gpu;\nfence.proxy.async.global;" ::: "memory");
        if (cidx < 24) asm volatile("{.reg .pred p; elect.sync _|p, 0xffffffff; @p cp.async.bulk.prefetch.L2.global [%0], 1536;}" ::"l"(gs->wimg + (cidx * 4 + k) * 1536) : "memory");
      }
      const int m = it == nit - 1 ? 0 : W2S;
      if (it == nit - 1 || it == nit + 3) bulk_load<73728>(sb + m, gs->wimg + m, sb + WBAR);
    }
  }
}

__device__ __forceinline__ void conv_credit(uint32_t sb, Globals* gs, int q0, int nit, int off, uint32_t ctarget, int k) {
  const uint32_t full = sb + CM;
#pragma unroll 1
  for (int it = k + NSLOT; it <= nit; it += 4) {
    const int u = it + off, q = (int)lds32(sb + CTAB + it * 16 + 12) - RING;
    mbar_wait(full + 64 + (u & 7) * 8, ((u >> 3) & 1) ^ 1);
    if (q >= q0) wait_value(&gs->cons[q], ctarget, 200);
    mbar_arrive_elect(full + (u & 7) * 8);
  }
}

__device__ __noinline__ int generic_role() {
  const int cidx = (blockIdx.x * NCONV) / gridDim.x;
  return cidx | ((((blockIdx.x + 1) * NCONV) / gridDim.x != cidx) << 16);
}

__global__ void __launch_bounds__(512, 1) convnext_kernel(const __nv_bfloat16* __restrict__ dw, const __nv_bfloat16* __restrict__ w1, const __nv_bfloat16* __restrict__ w2,
                                                          __nv_bfloat16* __restrict__ out, Globals* gs, int want_sms,
                                                          const __grid_constant__ CUtensorMap tmx, const __grid_constant__ CUtensorMap tmr) {
  extern __shared__ __align__(1024) unsigned char smem[];
  const uint32_t sb = smem_u32(smem);
  const int warp = __shfl_sync(0xffffffffu, threadIdx.x >> 5, 0), lane = threadIdx.x & 31;
  uint32_t smid, nsmid;
  asm volatile("mov.u32 %0, %%smid;" : "=r"(smid));
  asm volatile("mov.u32 %0, %%nsmid;" : "=r"(nsmid));
  const bool tabled = TABLED && (int)nsmid == want_sms;
  const int id = tabled ? smid : blockIdx.x;
  int cidx, idx, is_conv;
  if (tabled) {
    idx = smid;
    const int k = (smid - 60) / 14, r = smid - 60 - 14 * k;
    is_conv = smid < 48 ? !(smid & 1) : (smid >= 60 && smid <= 90 && (r & ~2) == 0);
    cidx = smid < 48 ? ((smid >> 1) & 7) * 3 + (smid >> 4) : 24 + (r >> 1) * 3 + k;
  } else {
    const int r = generic_role();
    cidx = r & 0xffff; is_conv = r >> 16;
    idx = blockIdx.x - cidx;
  }
  const int gm = cidx / 3, third = cidx - gm * 3;
  const int q0 = gm * PLEN, nit = gm < 8 ? PLEN + 2 : NSEG * (LM + 3), off = (8 - nit) & 7;
  if (is_conv && warp == 8) {
    bulk_load<9408, true>(sb, dw, sb + WBAR + 8);
    asm volatile("bar.arrive 5, 288;" ::: "memory");
#pragma unroll 1
    for (int it = 0; it < NSLOT; it++) {
      const int s = (it + off) & 7;
      ring_bar_init(sb + CM + s * 8, 2, s < off);
      if (it < FIRST) load_step(sb, &tmx, gm, third, it, s, true);
    }
  }
  if (warp == 15) asm volatile("prefetch.tensormap [%0];" ::"l"(&tmr) : "memory");
  mbar_init_elect(sb + MISC + warp * 8, 1); mbar_init_elect(sb + MISC + 128 + warp * 8, 1);
  asm volatile("fence.mbarrier_init.release.cluster;" ::: "memory");
  if (is_conv) {
    if (warp >= 8) ring_bar_init(sb + CM + warp * 8, 8, warp - 8 < off);
    if (warp == 9) mbar_init_elect(sb + WBAR, 2);
    const uint32_t lastph = (((nit + off) >> 3) & 1) ^ 1;
    if (warp < 8) {
      conv_compute(sb, gs, third, nit, off, gm < 8 && (gm & 1), warp, lane);
      asm volatile("setmaxnreg.dec.sync.aligned.u32 128;");
    } else if (warp >= 12) {
      asm volatile("setmaxnreg.dec.sync.aligned.u32 24;");
      const uint32_t epoch = ld_relaxed(&gs->epoch[id]);
#pragma unroll 1
      for (int it = threadIdx.x - 384; it <= nit; it += 128) {
        const int seg = it / (LM + 3), j = gm < 8 ? it - 2 : it - 3 * (seg + 1);
        const bool ok = it < nit && j >= (gm < 8 ? 0 : seg * LM);
        sts128(sb + CTAB + it * 16, make_uint4((ok ? (j % RING) * NG + gm : -1) * (4 * TILEB), slot_tag(gm, max(j, 0), epoch),
                                               offsetof(Globals, ready) + (ok ? q0 + j : NG * PLEN) * 4, ok ? q0 + j : -1));
      }
      asm volatile("bar.sync 0, 512;" ::: "memory");
      mbar_arrive_elect(sb + CM + ((((warp + 2) & 3) + off) & 7) * 8);
      mbar_arrive_elect(sb + CM + ((((warp + 2) & 3) + off + 4) & 7) * 8);
      build_tile_list(sb, threadIdx.x - 384, idx, tabled, true, epoch);
      if (threadIdx.x == 384) gs->epoch[id] = epoch + 1;
      conv_credit(sb, gs, q0, nit, off, 16 * (epoch + 1), (warp + 2) & 3);
#pragma unroll 1
      for (int i = 0; i < 4; i++) {
        const uint2 e = lds64(sb + MISC + 512 + i * 16);
        mbar_wait(sb + CM + 64 + (4 + min(i, 2)) * 8, lastph);
        const int wi = 4 * i + (warp & 3);
        if ((int)e.x >= 0) bulk_load<3072>(sb + ABUF + wi * 3072, gs->scratch + (e.y & ~1u) + (warp & 3) * 3072, sb + MISC + wi * 8);
      }
      mbar_wait(sb + CM + 64 + 7 * 8, lastph);
      asm volatile("setmaxnreg.inc.sync.aligned.u32 128;");
    } else {
      asm volatile("setmaxnreg.dec.sync.aligned.u32 %0;" ::"n"(488 - 2 * CREGS));
      conv_loader(sb, gs, &tmx, gm, nit, off, cidx, third, warp & 3);
      mbar_wait(sb + CM + 64 + 7 * 8, lastph);
      asm volatile("setmaxnreg.inc.sync.aligned.u32 128;");
    }
    mbar_wait(sb + WBAR, 0);
    asm volatile("bar.sync 0, 512;" ::: "memory");
  } else {
    mlp_setup(sb, gs, id, w1, w2, idx, tabled, warp, lane);
  }
  mlp_role(sb, gs, &tmr, out);
}

typedef CUresult (*PFN_encodeTiled)(CUtensorMap*, CUtensorMapDataType, cuuint32_t, void*, const cuuint64_t*, const cuuint64_t*, const cuuint32_t*, const cuuint32_t*,
                                    CUtensorMapInterleave, CUtensorMapSwizzle, CUtensorMapL2promotion, CUtensorMapFloatOOBfill);

extern "C" void kernel_launch(void* const* d_in, const int* in_sizes, int n_in, void* d_out, int out_size) {
  const __nv_bfloat16* x = (const __nv_bfloat16*)d_in[0];
  const __nv_bfloat16* dw = (const __nv_bfloat16*)d_in[1];
  const __nv_bfloat16* w1 = (const __nv_bfloat16*)d_in[2];
  const __nv_bfloat16* w2 = (const __nv_bfloat16*)d_in[3];
  static PFN_encodeTiled encode = nullptr;
  static int nsm = 0;
  static Globals* gs = nullptr;
  if (!encode) {
    void* fn = nullptr; cudaDriverEntryPointQueryResult qr;
    cudaGetDriverEntryPoint("cuTensorMapEncodeTiled", &fn, cudaEnableDefault, &qr);
    encode = (PFN_encodeTiled)fn;
    cudaGetSymbolAddress((void**)&gs, g_state);
    int dev = 0; cudaGetDevice(&dev);
    cudaDeviceGetAttribute(&nsm, cudaDevAttrMultiProcessorCount, dev);
    cudaFuncSetAttribute(convnext_kernel, cudaFuncAttributeMaxDynamicSharedMemorySize, SMEM_BYTES);
  }
  CUtensorMap tm, tr;
  cuuint64_t dims[3] = {96, 512, 512}, strides[2] = {192, 192 * 512};
  cuuint32_t box[3] = {32, 70, 2}, es[3] = {1, 1, 1};
  encode(&tm, CU_TENSOR_MAP_DATA_TYPE_BFLOAT16, 3, (void*)x, dims, strides, box, es, CU_TENSOR_MAP_INTERLEAVE_NONE, CU_TENSOR_MAP_SWIZZLE_64B,
         CU_TENSOR_MAP_L2_PROMOTION_L2_128B, CU_TENSOR_MAP_FLOAT_OOB_FILL_NONE);
  cuuint64_t dims2[3] = {1536, 32, 512}, strides2[2] = {3072, 192 * 512};
  cuuint32_t box2[3] = {192, 4, 2};
  encode(&tr, CU_TENSOR_MAP_DATA_TYPE_BFLOAT16, 3, (void*)x, dims2, strides2, box2, es, CU_TENSOR_MAP_INTERLEAVE_NONE, CU_TENSOR_MAP_SWIZZLE_NONE,
         CU_TENSOR_MAP_L2_PROMOTION_NONE, CU_TENSOR_MAP_FLOAT_OOB_FILL_NONE);
  convnext_kernel<<<nsm, 512, SMEM_BYTES>>>(dw, w1, w2, (__nv_bfloat16*)d_out, gs, nsm == 132 ? 132 : -1, tm, tr);
}
```

```cpp
#include <cuda_runtime.h>
#include <cuda_bf16.h>
#include <cuda.h>
#include <stdint.h>
#include <stddef.h>

template<int SCALE_D> __device__ __forceinline__ void wgmma_n64_f16(uint32_t* d, const uint32_t* a, uint64_t desc) {
  if (SCALE_D == 0) asm volatile("wgmma.mma_async.sync.aligned.m64n64k16.f16.f16.f16 {%0,%1,%2,%3,%4,%5,%6,%7,%8,%9,%10,%11,%12,%13,%14,%15}, {%16,%17,%18,%19}, %20, 0, 1, 1, 1;"
    : "=r"(d[0]),"=r"(d[1]),"=r"(d[2]),"=r"(d[3]),"=r"(d[4]),"=r"(d[5]),"=r"(d[6]),"=r"(d[7]),"=r"(d[8]),"=r"(d[9]),"=r"(d[10]),"=r"(d[11]),"=r"(d[12]),"=r"(d[13]),"=r"(d[14]),"=r"(d[15])
    : "r"(a[0]),"r"(a[1]),"r"(a[2]),"r"(a[3]),"l"(desc));
  if (SCALE_D == 1) asm volatile("wgmma.mma_async.sync.aligned.m64n64k16.f16.f16.f16 {%0,%1,%2,%3,%4,%5,%6,%7,%8,%9,%10,%11,%12,%13,%14,%15}, {%16,%17,%18,%19}, %20, 1, 1, 1, 1;"
    : "+r"(d[0]),"+r"(d[1]),"+r"(d[2]),"+r"(d[3]),"+r"(d[4]),"+r"(d[5]),"+r"(d[6]),"+r"(d[7]),"+r"(d[8]),"+r"(d[9]),"+r"(d[10]),"+r"(d[11]),"+r"(d[12]),"+r"(d[13]),"+r"(d[14]),"+r"(d[15])
    : "r"(a[0]),"r"(a[1]),"r"(a[2]),"r"(a[3]),"l"(desc));
}

template<int SCALE_D> __device__ __forceinline__ void wgmma_n96_f16(uint32_t* d, const uint32_t* a, uint64_t desc) {
  if (SCALE_D == 0) asm volatile("wgmma.mma_async.sync.aligned.m64n96k16.f16.f16.f16 {%0,%1,%2,%3,%4,%5,%6,%7,%8,%9,%10,%11,%12,%13,%14,%15,%16,%17,%18,%19,%20,%21,%22,%23}, {%24,%25,%26,%27}, %28, 0, 1, 1, 1;"
    : "=r"(d[0]),"=r"(d[1]),"=r"(d[2]),"=r"(d[3]),"=r"(d[4]),"=r"(d[5]),"=r"(d[6]),"=r"(d[7]),"=r"(d[8]),"=r"(d[9]),"=r"(d[10]),"=r"(d[11]),"=r"(d[12]),"=r"(d[13]),"=r"(d[14]),"=r"(d[15]),"=r"(d[16]),"=r"(d[17]),"=r"(d[18]),"=r"(d[19]),"=r"(d[20]),"=r"(d[21]),"=r"(d[22]),"=r"(d[23])
    : "r"(a[0]),"r"(a[1]),"r"(a[2]),"r"(a[3]),"l"(desc));
  if (SCALE_D == 1) asm volatile("wgmma.mma_async.sync.aligned.m64n96k16.f16.f16.f16 {%0,%1,%2,%3,%4,%5,%6,%7,%8,%9,%10,%11,%12,%13,%14,%15,%16,%17,%18,%19,%20,%21,%22,%23}, {%24,%25,%26,%27}, %28, 1, 1, 1, 1;"
    : "+r"(d[0]),"+r"(d[1]),"+r"(d[2]),"+r"(d[3]),"+r"(d[4]),"+r"(d[5]),"+r"(d[6]),"+r"(d[7]),"+r"(d[8]),"+r"(d[9]),"+r"(d[10]),"+r"(d[11]),"+r"(d[12]),"+r"(d[13]),"+r"(d[14]),"+r"(d[15]),"+r"(d[16]),"+r"(d[17]),"+r"(d[18]),"+r"(d[19]),"+r"(d[20]),"+r"(d[21]),"+r"(d[22]),"+r"(d[23])
    : "r"(a[0]),"r"(a[1]),"r"(a[2]),"r"(a[3]),"l"(desc));
}

#define SCHED_NMID 1
#define SCHED_LE 106
#define SCHED_LT 10
#define SCHED_RING 16
__device__ const uint16_t g_sched[132][48] = {
{388,391,394,65535,65535,65535,65535,65535,65535,65535,65535,65535,65535,65535,65535,65535,65535,65535,65535,65535,65535,65535,65535,65535,65535,65535,65535,65535,65535,65535,65535,65535,65535,65535,65535,65535,65535,65535,65535,65535,65535,65535,65535,65535,65535,65535,65535,65535},
{3824,3827,3830,3833,3854,53,65,77,88,100,113,125,136,148,160,171,183,195,206,219,231,243,254,266,278,289,301,313,325,337,349,361,372,384,404,416,65535,65535,65535,65535,65535,65535,65535,65535,65535,65535,65535,65535},
{812,815,818,65535,65535,65535,65535,65535,65535,65535,65535,65535,65535,65535,65535,65535,65535,65535,65535,65535,65535,65535,65535,65535,65535,65535,65535,65535,65535,65535,65535,65535,65535,65535,65535,65535,65535,65535,65535,65535,65535,65535,65535,65535,65535,65535,65535,65535},
{4248,4251,4254,4257,4279,478,490,502,513,525,538,550,561,573,585,596,608,620,631,644,656,668,679,691,703,714,726,738,750,762,774,786,797,809,830,841,65535,65535,65535,65535,65535,65535,65535,65535,65535,65535,65535,65535},
{1236,1239,1242,65535,65535,65535,65535,65535,65535,65535,65535,65535,65535,65535,65535,65535,65535,65535,65535,65535,65535,65535,65535,65535,65535,65535,65535,65535,65535,65535,65535,65535,65535,65535,65535,65535,65535,65535,65535,65535,65535,65535,65535,65535,65535,65535,65535,65535},
{4672,4675,4678,4681,891,902,914,925,937,949,962,973,985,997,1008,1020,1032,1043,1055,1068,1080,1091,1103,1115,1126,1138,1150,1161,1174,1186,1198,1209,1221,1233,1253,1265,65535,65535,65535,65535,65535,65535,65535,65535,65535,65535,65535,65535},
{1660,1663,1666,65535,65535,65535,65535,65535,65535,65535,65535,65535,65535,65535,65535,65535,65535,65535,65535,65535,65535,65535,65535,65535,65535,65535,65535,65535,65535,65535,65535,65535,65535,65535,65535,65535,65535,65535,65535,65535,65535,65535,65535,65535,65535,65535,65535,65535},
{5096,5099,5102,5105,1315,1325,1337,1348,1360,1372,1385,1396,1408,1420,1431,1443,1455,1466,1478,1491,1503,1514,1526,1538,1549,1561,1573,1584,1597,1609,1621,1632,1644,1656,1677,1688,65535,65535,65535,65535,65535,65535,65535,65535,65535,65535,65535,65535},
{2084,2087,2090,65535,65535,65535,65535,65535,65535,65535,65535,65535,65535,65535,65535,65535,65535,65535,65535,65535,65535,65535,65535,65535,65535,65535,65535,65535,65535,65535,65535,65535,65535,65535,65535,65535,65535,65535,65535,65535,65535,65535,65535,65535,65535,65535,65535,65535},
{5520,5523,5526,5529,1739,1750,1761,1773,1784,1796,1809,1821,1832,1844,1856,1867,1879,1891,1902,1915,1927,1939,1950,1962,1974,1985,1997,2009,2021,2034,2045,2057,2068,2080,2101,2113,65535,65535,65535,65535,65535,65535,65535,65535,65535,65535,65535,65535},
{2508,2511,2514,65535,65535,65535,65535,65535,65535,65535,65535,65535,65535,65535,65535,65535,65535,65535,65535,65535,65535,65535,65535,65535,65535,65535,65535,65535,65535,65535,65535,65535,65535,65535,65535,65535,65535,65535,65535,65535,65535,65535,65535,65535,65535,65535,65535,65535},
{5944,5947,5950,5953,2163,2174,2185,2197,2209,2220,2233,2245,2257,2268,2280,2292,2303,2315,2327,2339,2351,2363,2375,2386,2398,2410,2421,2433,2445,2458,2469,2481,2493,2504,2525,2537,65535,65535,65535,65535,65535,65535,65535,65535,65535,65535,65535,65535},
{2932,2935,2938,65535,65535,65535,65535,65535,65535,65535,65535,65535,65535,65535,65535,65535,65535,65535,65535,65535,65535,65535,65535,65535,65535,65535,65535,65535,65535,65535,65535,65535,65535,65535,65535,65535,65535,65535,65535,65535,65535,65535,65535,65535,65535,65535,65535,65535},
{6368,6371,6374,6377,3430,3441,2609,2621,2633,2644,2657,2669,2681,2692,2704,2716,2727,2739,2751,3584,2775,2787,2799,2810,2822,2834,2845,2857,2871,3689,2893,2905,2917,2928,2949,3768,65535,65535,65535,65535,65535,65535,65535,65535,65535,65535,65535,65535},
{3356,3359,3362,65535,65535,65535,65535,65535,65535,65535,65535,65535,65535,65535,65535,65535,65535,65535,65535,65535,65535,65535,65535,65535,65535,65535,65535,65535,65535,65535,65535,65535,65535,65535,65535,65535,65535,65535,65535,65535,65535,65535,65535,65535,65535,65535,65535,65535},
{6792,6795,6798,6801,6398,3023,3453,3046,3058,3070,3489,3094,3106,3524,3129,3141,3559,3164,3176,3189,3595,3212,3224,3630,3247,3259,3665,3282,3296,3307,3701,3330,3342,3736,3374,3386,65535,65535,65535,65535,65535,65535,65535,65535,65535,65535,65535,65535},
{389,392,395,65535,65535,65535,65535,65535,65535,65535,65535,65535,65535,65535,65535,65535,65535,65535,65535,65535,65535,65535,65535,65535,65535,65535,65535,65535,65535,65535,65535,65535,65535,65535,65535,65535,65535,65535,65535,65535,65535,65535,65535,65535,65535,65535,65535,65535},
{3825,3828,3831,3834,43,54,66,78,89,101,114,126,137,149,161,172,184,196,207,220,232,244,255,267,279,290,302,314,326,338,350,362,373,385,405,417,65535,65535,65535,65535,65535,65535,65535,65535,65535,65535,65535,65535},
{813,816,819,65535,65535,65535,65535,65535,65535,65535,65535,65535,65535,65535,65535,65535,65535,65535,65535,65535,65535,65535,65535,65535,65535,65535,65535,65535,65535,65535,65535,65535,65535,65535,65535,65535,65535,65535,65535,65535,65535,65535,65535,65535,65535,65535,65535,65535},
{4249,4252,4255,4258,468,479,491,3465,514,526,539,3501,562,574,3536,597,609,3571,632,645,657,3607,680,692,3642,715,727,3677,751,763,775,3713,798,810,3757,842,65535,65535,65535,65535,65535,65535,65535,65535,65535,65535,65535,65535},
{1237,1240,1243,65535,65535,65535,65535,65535,65535,65535,65535,65535,65535,65535,65535,65535,65535,65535,65535,65535,65535,65535,65535,65535,65535,65535,65535,65535,65535,65535,65535,65535,65535,65535,65535,65535,65535,65535,65535,65535,65535,65535,65535,65535,65535,65535,65535,65535},
{4673,4676,4679,4682,4703,903,915,926,938,950,963,974,986,998,1009,1021,1033,1044,1056,1069,1081,1092,1104,1116,1127,1139,1151,1162,1175,1187,1199,1210,1222,1234,1254,1266,65535,65535,65535,65535,65535,65535,65535,65535,65535,65535,65535,65535},
{1661,1664,1667,65535,65535,65535,65535,65535,65535,65535,65535,65535,65535,65535,65535,65535,65535,65535,65535,65535,65535,65535,65535,65535,65535,65535,65535,65535,65535,65535,65535,65535,65535,65535,65535,65535,65535,65535,65535,65535,65535,65535,65535,65535,65535,65535,65535,65535},
{5097,5100,5103,5106,5127,1326,1338,1349,1361,1373,1386,1397,1409,1421,1432,1444,1456,1467,1479,1492,1504,1515,1527,1539,1550,1562,1574,1585,1598,1610,1622,1633,1645,1657,1678,1689,65535,65535,65535,65535,65535,65535,65535,65535,65535,65535,65535,65535},
{2085,2088,2091,65535,65535,65535,65535,65535,65535,65535,65535,65535,65535,65535,65535,65535,65535,65535,65535,65535,65535,65535,65535,65535,65535,65535,65535,65535,65535,65535,65535,65535,65535,65535,65535,65535,65535,65535,65535,65535,65535,65535,65535,65535,65535,65535,65535,65535},
{5521,5524,5527,5530,5551,1751,1762,1774,1785,1797,1810,1822,1833,1845,1857,1868,1880,1892,1903,1916,1928,1940,1951,1963,1975,1986,1998,2010,2022,2035,2046,2058,2069,2081,2102,2114,65535,65535,65535,65535,65535,65535,65535,65535,65535,65535,65535,65535},
{2509,2512,2515,65535,65535,65535,65535,65535,65535,65535,65535,65535,65535,65535,65535,65535,65535,65535,65535,65535,65535,65535,65535,65535,65535,65535,65535,65535,65535,65535,65535,65535,65535,65535,65535,65535,65535,65535,65535,65535,65535,65535,65535,65535,65535,65535,65535,65535},
{5945,5948,5951,5954,5975,2175,2186,2198,2210,2221,2234,2246,2258,2269,2281,2293,2304,2316,2328,2340,2352,2364,2376,2387,2399,2411,2422,2434,2446,2459,2470,2482,2494,2505,2526,2538,65535,65535,65535,65535,65535,65535,65535,65535,65535,65535,65535,65535},
{2933,2936,2939,65535,65535,65535,65535,65535,65535,65535,65535,65535,65535,65535,65535,65535,65535,65535,65535,65535,65535,65535,65535,65535,65535,65535,65535,65535,65535,65535,65535,65535,65535,65535,65535,65535,65535,65535,65535,65535,65535,65535,65535,65535,65535,65535,65535,65535},
{6369,6372,6375,6378,2587,2598,2610,2622,3477,2645,2658,2670,3513,2693,2705,3548,2728,2740,3583,2765,2776,2788,3619,2811,2823,3654,2846,2858,2872,2882,2894,2906,3725,2929,2950,2961,65535,65535,65535,65535,65535,65535,65535,65535,65535,65535,65535,65535},
{3357,3360,3363,65535,65535,65535,65535,65535,65535,65535,65535,65535,65535,65535,65535,65535,65535,65535,65535,65535,65535,65535,65535,65535,65535,65535,65535,65535,65535,65535,65535,65535,65535,65535,65535,65535,65535,65535,65535,65535,65535,65535,65535,65535,65535,65535,65535,65535},
{6793,6796,6799,6802,3012,3442,3035,3047,3059,3071,3083,3095,3107,3118,3130,3142,3153,3165,3177,3190,3201,3213,3225,3236,3248,3260,3271,3283,3297,3690,3319,3331,3343,3354,3375,3769,65535,65535,65535,65535,65535,65535,65535,65535,65535,65535,65535,65535},
{390,393,396,65535,65535,65535,65535,65535,65535,65535,65535,65535,65535,65535,65535,65535,65535,65535,65535,65535,65535,65535,65535,65535,65535,65535,65535,65535,65535,65535,65535,65535,65535,65535,65535,65535,65535,65535,65535,65535,65535,65535,65535,65535,65535,65535,65535,65535},
{3826,3829,3832,3835,3855,55,67,79,90,102,115,127,138,150,162,173,185,197,208,221,233,245,256,268,280,291,303,315,327,339,351,363,374,386,406,418,65535,65535,65535,65535,65535,65535,65535,65535,65535,65535,65535,65535},
{814,817,820,65535,65535,65535,65535,65535,65535,65535,65535,65535,65535,65535,65535,65535,65535,65535,65535,65535,65535,65535,65535,65535,65535,65535,65535,65535,65535,65535,65535,65535,65535,65535,65535,65535,65535,65535,65535,65535,65535,65535,65535,65535,65535,65535,65535,65535},
{4250,4253,4256,4259,3431,480,3454,503,515,527,3490,551,563,3525,586,598,3560,621,633,646,3596,669,681,3631,704,716,3666,739,752,764,3702,787,799,3737,831,843,65535,65535,65535,65535,65535,65535,65535,65535,65535,65535,65535,65535},
{1238,1241,1244,65535,65535,65535,65535,65535,65535,65535,65535,65535,65535,65535,65535,65535,65535,65535,65535,65535,65535,65535,65535,65535,65535,65535,65535,65535,65535,65535,65535,65535,65535,65535,65535,65535,65535,65535,65535,65535,65535,65535,65535,65535,65535,65535,65535,65535},
{4674,4677,4680,4683,892,904,916,927,939,951,964,975,987,999,1010,1022,1034,1045,1057,1070,1082,1093,1105,1117,1128,1140,1152,1163,1176,1188,1200,1211,1223,1235,1255,1267,65535,65535,65535,65535,65535,65535,65535,65535,65535,65535,65535,65535},
{1662,1665,1668,65535,65535,65535,65535,65535,65535,65535,65535,65535,65535,65535,65535,65535,65535,65535,65535,65535,65535,65535,65535,65535,65535,65535,65535,65535,65535,65535,65535,65535,65535,65535,65535,65535,65535,65535,65535,65535,65535,65535,65535,65535,65535,65535,65535,65535},
{5098,5101,5104,5107,1316,1327,1339,1350,1362,1374,1387,1398,1410,1422,1433,1445,1457,1468,1480,1493,1505,1516,1528,1540,1551,1563,1575,1586,1599,1611,1623,1634,1646,1658,1679,1690,65535,65535,65535,65535,65535,65535,65535,65535,65535,65535,65535,65535},
{2086,2089,2092,65535,65535,65535,65535,65535,65535,65535,65535,65535,65535,65535,65535,65535,65535,65535,65535,65535,65535,65535,65535,65535,65535,65535,65535,65535,65535,65535,65535,65535,65535,65535,65535,65535,65535,65535,65535,65535,65535,65535,65535,65535,65535,65535,65535,65535},
{5522,5525,5528,5531,1740,1752,1763,1775,1786,1798,1811,1823,1834,1846,1858,1869,1881,1893,1904,1917,1929,1941,1952,1964,1976,1987,1999,2011,2023,2036,2047,2059,2070,2082,2103,2115,65535,65535,65535,65535,65535,65535,65535,65535,65535,65535,65535,65535},
{2510,2513,2516,65535,65535,65535,65535,65535,65535,65535,65535,65535,65535,65535,65535,65535,65535,65535,65535,65535,65535,65535,65535,65535,65535,65535,65535,65535,65535,65535,65535,65535,65535,65535,65535,65535,65535,65535,65535,65535,65535,65535,65535,65535,65535,65535,65535,65535},
{5946,5949,5952,5955,2164,2176,2187,2199,2211,2222,2235,2247,2259,2270,2282,2294,2305,2317,2329,2341,2353,2365,2377,2388,2400,2412,2423,2435,2447,2460,2471,2483,2495,2506,2527,2539,65535,65535,65535,65535,65535,65535,65535,65535,65535,65535,65535,65535},
{2934,2937,2940,65535,65535,65535,65535,65535,65535,65535,65535,65535,65535,65535,65535,65535,65535,65535,65535,65535,65535,65535,65535,65535,65535,65535,65535,65535,65535,65535,65535,65535,65535,65535,65535,65535,65535,65535,65535,65535,65535,65535,65535,65535,65535,65535,65535,65535},
{6370,6373,6376,6379,6399,2599,2611,3466,2634,2646,2659,3502,2682,2694,3537,2717,2729,3572,2752,3585,2777,3608,2800,2812,3643,2835,2847,3678,3680,2883,2895,3714,2918,2930,3758,2962,65535,65535,65535,65535,65535,65535,65535,65535,65535,65535,65535,65535},
{3358,3361,3364,65535,65535,65535,65535,65535,65535,65535,65535,65535,65535,65535,65535,65535,65535,65535,65535,65535,65535,65535,65535,65535,65535,65535,65535,65535,65535,65535,65535,65535,65535,65535,65535,65535,65535,65535,65535,65535,65535,65535,65535,65535,65535,65535,65535,65535},
{6794,6797,6800,6803,3013,3024,3036,3048,3478,3072,3084,3096,3514,3119,3131,3549,3154,3166,3178,3191,3202,3214,3620,3237,3249,3655,3272,3284,3298,3308,3320,3332,3726,3355,3376,3387,65535,65535,65535,65535,65535,65535,65535,65535,65535,65535,65535,65535},
{0,3394,3399,2565,3414,3844,3849,6396,2595,908,76,2630,943,532,124,2678,991,159,2713,1026,194,2748,1062,1074,242,2796,1109,277,2831,1144,312,1168,2879,1192,360,2914,1227,2946,2958,65535,65535,65535,65535,65535,65535,65535,65535,65535},
{1,6362,6367,3409,6382,3419,3424,42,3439,2607,496,3474,2642,956,544,3510,2690,579,3545,2725,614,3580,2761,2773,662,3616,2808,697,3651,2843,732,2867,3687,2891,780,3722,2926,3754,3766,65535,65535,65535,65535,65535,65535,65535,65535,65535},
{424,430,435,443,4262,455,460,465,473,485,497,508,520,533,545,556,568,580,591,603,615,626,639,651,663,674,686,698,709,721,733,745,757,769,781,792,804,825,836,65535,65535,65535,65535,65535,65535,65535,65535,65535},
{425,4242,4247,444,451,4267,4272,4277,474,486,498,509,521,534,546,557,569,581,592,604,616,627,640,652,664,675,687,699,710,722,734,746,758,770,782,793,805,826,837,65535,65535,65535,65535,65535,65535,65535,65535,65535},
{848,4666,859,867,4686,879,4695,4700,897,909,920,932,944,957,968,980,992,1003,1015,1027,1038,1050,1063,1075,1086,1098,1110,1121,1133,1145,1156,1169,1181,1193,1204,1216,1228,1248,1260,65535,65535,65535,65535,65535,65535,65535,65535,65535},
{849,855,4671,868,875,4691,884,889,898,910,921,933,945,958,969,981,993,1004,1016,1028,1039,1051,1064,1076,1087,1099,1111,1122,1134,1146,1157,1170,1182,1194,1205,1217,1229,1249,1261,65535,65535,65535,65535,65535,65535,65535,65535,65535},
{1272,1279,5095,1291,5110,1303,1308,1313,1321,1333,1344,1356,1368,1381,1392,1404,1416,1427,1439,1451,1462,1474,1487,1499,1510,1522,1534,1545,1557,1569,1580,1593,1605,1617,1628,1640,1652,1673,1684,65535,65535,65535,65535,65535,65535,65535,65535,65535},
{1273,5091,1284,1292,1299,5115,5120,5125,1322,1334,1345,1357,1369,1382,1393,1405,1417,1428,1440,1452,1463,1475,1488,1500,1511,1523,1535,1546,1558,1570,1581,1594,1606,1618,1629,1641,1653,1674,1685,65535,65535,65535,65535,65535,65535,65535,65535,65535},
{1696,1703,1708,1716,1723,1728,1732,1737,1746,1757,1769,1780,1792,1805,1817,1828,1840,1852,1863,1875,1887,1898,1911,1923,1935,1946,1958,1970,1981,1993,2005,2017,2030,2041,2053,2064,2076,2097,2109,65535,65535,65535,65535,65535,65535,65535,65535,65535},
{1697,5515,1709,1717,5535,5540,5544,5549,1747,1758,1770,1781,1793,1806,1818,1829,1841,1853,1864,1876,1888,1899,1912,1924,1936,1947,1959,1971,1982,1994,2006,2018,2031,2042,2054,2065,2077,2098,2110,65535,65535,65535,65535,65535,65535,65535,65535,65535},
{2120,2127,2132,2140,2147,2152,5968,2161,2170,2181,2193,2205,2216,2229,2241,2253,2264,2276,2288,2299,2311,2323,2335,2347,2359,2371,2382,2394,2406,2417,2429,2441,2454,2465,2477,2489,2500,2521,2533,65535,65535,65535,65535,65535,65535,65535,65535,65535},
{2121,5939,2133,2141,5959,5964,2157,5973,2171,2182,2194,2206,2217,2230,2242,2254,2265,2277,2289,2300,2312,2324,2336,2348,2360,2372,2383,2395,2407,2418,2430,2442,2455,2466,2478,2490,2501,2522,2534,65535,65535,65535,65535,65535,65535,65535,65535,65535},
{3740,3743,3746,65535,65535,65535,65535,65535,65535,65535,65535,65535,65535,65535,65535,65535,65535,65535,65535,65535,65535,65535,65535,65535,65535,65535,65535,65535,65535,65535,65535,65535,65535,65535,65535,65535,65535,65535,65535,65535,65535,65535,65535,65535,65535,65535,65535,65535},
{2544,2551,2556,2566,2571,6387,6392,2585,2596,3451,2619,2631,3486,2655,2667,2679,3522,2702,2714,3557,2737,2749,2762,3593,2785,2797,3628,2820,2832,3663,2855,2868,2880,3699,2903,2915,3734,2947,2959,65535,65535,65535,65535,65535,65535,65535,65535,65535},
{2968,6787,2980,2989,2995,3000,3005,3010,3018,3030,3042,3054,3065,3078,3090,3102,3113,3125,3137,3148,3160,3172,3184,3196,3208,3220,3231,3243,3255,3266,3278,3291,3302,3314,3326,3338,3349,3370,3381,65535,65535,65535,65535,65535,65535,65535,65535,65535},
{2969,2976,2981,2990,6807,6812,6817,6822,3019,3031,3043,3055,3066,3079,3091,3103,3114,3126,3138,3149,3161,3173,3185,3197,3209,3221,3232,3244,3256,3267,3279,3292,3303,3315,3327,3339,3350,3371,3382,65535,65535,65535,65535,65535,65535,65535,65535,65535},
{426,431,436,445,4263,456,461,466,475,487,499,510,522,535,547,558,570,582,593,605,617,628,641,653,665,676,688,700,711,723,735,747,759,771,783,794,806,827,838,65535,65535,65535,65535,65535,65535,65535,65535,65535},
{2545,4243,437,446,452,4268,4273,4278,476,488,500,511,523,536,548,559,571,583,594,606,618,629,642,654,666,677,689,701,712,724,736,748,760,772,784,795,807,828,839,65535,65535,65535,65535,65535,65535,65535,65535,65535},
{850,4667,860,869,4687,880,4696,4701,899,911,922,934,946,959,970,982,994,1005,1017,1029,1040,1052,1065,1077,1088,1100,1112,1123,1135,1147,1158,1171,1183,1195,1206,1218,1230,1250,1262,65535,65535,65535,65535,65535,65535,65535,65535,65535},
{851,856,861,870,876,4692,885,890,900,912,923,935,947,960,971,983,995,1006,1018,1030,1041,1053,1066,1078,1089,1101,1113,1124,1136,1148,1159,1172,1184,1196,1207,1219,1231,1251,1263,65535,65535,65535,65535,65535,65535,65535,65535,65535},
{1274,1280,1285,1293,5111,1304,1309,1314,1323,1335,1346,1358,1370,1383,1394,1406,1418,1429,1441,1453,1464,1476,1489,1501,1512,1524,1536,1547,1559,1571,1582,1595,1607,1619,1630,1642,1654,1675,1686,65535,65535,65535,65535,65535,65535,65535,65535,65535},
{1275,5092,3400,1294,1300,5116,5121,5126,1324,1336,1347,1359,1371,1384,1395,1407,1419,1430,1442,1454,1465,1477,1490,1502,1513,1525,1537,1548,1560,1572,1583,1596,1608,1620,1631,1643,1655,1676,1687,65535,65535,65535,65535,65535,65535,65535,65535,65535},
{1698,1704,1710,1718,1724,1729,1733,1738,1748,1759,1771,1782,1794,1807,1819,1830,1842,1854,1865,1877,1889,1900,1913,1925,1937,1948,1960,1972,1983,1995,2007,2019,2032,2043,2055,2066,2078,2099,2111,65535,65535,65535,65535,65535,65535,65535,65535,65535},
{1699,5516,2557,1719,5536,5541,5545,5550,1749,1760,1772,1783,1795,1808,1820,1831,1843,1855,1866,1878,1890,1901,1914,1926,1938,1949,1961,1973,1984,1996,2008,2020,2033,2044,2056,2067,2079,2100,2112,65535,65535,65535,65535,65535,65535,65535,65535,65535},
{2122,2128,2134,2142,2148,2153,5969,2162,2172,2183,2195,2207,2218,2231,2243,2255,2266,2278,2290,2301,2313,2325,2337,2349,2361,2373,2384,2396,2408,2419,2431,2443,2456,2467,2479,2491,2502,2523,2535,65535,65535,65535,65535,65535,65535,65535,65535,65535},
{2123,5940,3401,2143,5960,5965,2158,5974,2173,2184,2196,2208,2219,2232,2244,2256,2267,2279,2291,2302,2314,2326,2338,2350,2362,2374,2385,2397,2409,2420,2432,2444,2457,2468,2480,2492,2503,2524,2536,65535,65535,65535,65535,65535,65535,65535,65535,65535},
{3741,3744,3747,65535,65535,65535,65535,65535,65535,65535,65535,65535,65535,65535,65535,65535,65535,65535,65535,65535,65535,65535,65535,65535,65535,65535,65535,65535,65535,65535,65535,65535,65535,65535,65535,65535,65535,65535,65535,65535,65535,65535,65535,65535,65535,65535,65535,65535},
{2546,3395,2558,3410,3415,2576,2581,3429,3440,2608,3463,3475,2643,2656,3499,3511,2691,3534,3546,2726,3569,3581,2763,2774,3605,3617,2809,3640,3652,2844,3675,2869,3688,2892,3711,3723,2927,3755,3767,65535,65535,65535,65535,65535,65535,65535,65535,65535},
{2970,6788,2982,2991,2996,3001,3006,6397,3020,3032,3044,3056,3067,3080,3092,3104,3115,3127,3139,3150,3162,3174,3186,3198,3210,3222,3233,3245,3257,3268,3280,3293,3304,3316,3328,3340,3351,3372,3383,65535,65535,65535,65535,65535,65535,65535,65535,65535},
{2971,6363,2983,2992,6808,6813,6818,3011,3021,3033,3045,3057,3068,3081,3093,3105,3116,3128,3140,3151,3163,3175,3187,3199,3211,3223,3234,3246,3258,3269,3281,3294,3305,3317,3329,3341,3352,3373,3384,65535,65535,65535,65535,65535,65535,65535,65535,65535},
{427,432,438,447,4264,457,462,467,477,489,501,512,524,537,549,560,572,584,595,607,619,630,643,655,667,678,690,702,713,725,737,749,761,773,785,796,808,829,840,65535,65535,65535,65535,65535,65535,65535,65535,65535},
{428,4244,439,448,453,4269,4274,469,3443,492,504,516,528,540,552,564,575,587,599,610,622,634,647,658,670,682,693,705,717,728,740,753,3691,776,788,800,811,832,3770,65535,65535,65535,65535,65535,65535,65535,65535,65535},
{852,857,863,872,877,4693,886,893,905,3455,928,940,952,3491,976,988,3526,1011,1023,3561,1046,1058,1071,3597,1094,1106,3632,1129,1141,3667,1164,1177,1189,3703,1212,1224,3738,1256,1268,65535,65535,65535,65535,65535,65535,65535,65535,65535},
{4664,4669,864,4684,4689,882,4698,2588,2600,917,2623,2635,2647,965,2671,2683,1000,2706,2718,1035,2741,2753,2766,1083,2789,2801,1118,2824,2836,1153,2859,1178,2884,1201,2907,2919,2931,2951,2963,65535,65535,65535,65535,65535,65535,65535,65535,65535},
{1276,1281,1286,1295,5112,1305,1310,1317,1328,1340,1351,1363,1375,1388,1399,1411,1423,1434,1446,1458,1469,1481,1494,1506,1517,1529,1541,1552,1564,1576,1587,1600,1612,1624,1635,1647,1659,1680,1691,65535,65535,65535,65535,65535,65535,65535,65535,65535},
{5088,5093,1287,1296,1301,5117,5122,3432,1329,1341,1352,1364,1376,1389,1400,1412,1424,1435,1447,1459,1470,1482,1495,1507,1518,1530,1542,1553,1565,1577,1588,1601,1613,1625,1636,1648,3739,3759,1692,65535,65535,65535,65535,65535,65535,65535,65535,65535},
{1700,1705,1711,1720,1725,1730,1734,1741,1753,1764,1776,1787,1799,1812,1824,1835,1847,1859,1870,1882,1894,1905,1918,1930,1942,1953,1965,1977,1988,2000,2012,2024,2037,2048,2060,2071,2083,2104,2116,65535,65535,65535,65535,65535,65535,65535,65535,65535},
{5512,5517,1712,5532,5537,5542,5546,1742,3444,1765,3467,1788,1800,1813,3503,1836,1848,3538,1871,1883,3573,1906,1919,1931,3609,1954,1966,3644,1989,2001,3679,2025,3692,2049,3715,2072,387,2105,3771,65535,65535,65535,65535,65535,65535,65535,65535,65535},
{2124,2129,2135,2144,2149,2154,5970,2165,2177,2188,2200,2212,2223,2236,2248,2260,2271,2283,2295,2306,2318,2330,2342,2354,2366,2378,2389,2401,2413,2424,2436,2448,2461,2472,2484,2496,2507,2528,2540,65535,65535,65535,65535,65535,65535,65535,65535,65535},
{5936,5941,2136,5956,5961,5966,2159,2166,2178,2189,2201,3479,2224,2237,2249,3515,2272,2284,3550,2307,2319,2331,2343,2355,2367,3621,2390,2402,3656,2425,2437,2449,2462,2473,2485,3727,2517,2529,2541,65535,65535,65535,65535,65535,65535,65535,65535,65535},
{3742,3745,3748,65535,65535,65535,65535,65535,65535,65535,65535,65535,65535,65535,65535,65535,65535,65535,65535,65535,65535,65535,65535,65535,65535,65535,65535,65535,65535,65535,65535,65535,65535,65535,65535,65535,65535,65535,65535,65535,65535,65535,65535,65535,65535,65535,65535,65535},
{2547,2552,3402,2567,6383,3420,3425,2586,2597,3452,2620,2632,3487,3488,2668,2680,3523,2703,2715,3558,2738,2750,2764,3594,2786,2798,3629,2821,2833,3664,2856,2870,2881,3700,2904,2916,3735,2948,2960,65535,65535,65535,65535,65535,65535,65535,65535,65535},
{2972,6789,2559,3411,6809,3002,3007,3014,3025,3037,3049,3060,3073,3085,3097,3108,3120,3132,3143,3155,3167,3179,3586,3203,3215,3226,3238,3250,3261,3273,3285,2873,3309,3321,3333,3344,3365,3377,3388,65535,65535,65535,65535,65535,65535,65535,65535,65535},
{6784,3396,3403,2993,2572,6814,6819,2589,3026,2612,2624,3061,2648,2660,2672,3109,2695,2707,3144,2730,2742,2754,3192,2778,2790,3227,2813,2825,3262,2848,2860,3681,3310,2896,2908,3345,3366,2952,3389,65535,65535,65535,65535,65535,65535,65535,65535,65535},
{4240,433,440,4260,4265,458,463,470,481,493,505,517,529,541,553,565,576,588,600,611,623,635,648,659,671,683,694,706,718,729,741,754,765,777,789,801,821,833,844,65535,65535,65535,65535,65535,65535,65535,65535,65535},
{429,4245,13,449,3416,4270,4275,3433,482,3456,3468,2636,530,3492,3504,2684,3527,3539,2719,3562,3574,636,2767,3598,3610,2802,3633,3645,2837,3668,742,755,766,3704,3716,2920,822,3760,845,65535,65535,65535,65535,65535,65535,65535,65535,65535},
{853,6364,865,873,6384,4694,887,894,906,918,929,941,953,966,977,989,1001,1012,1024,1036,1047,1059,1072,1084,1095,1107,1119,1130,1142,1154,1165,1179,1190,1202,1213,1225,1245,1257,1269,65535,65535,65535,65535,65535,65535,65535,65535,65535},
{4665,858,2560,4685,878,2577,4699,895,2601,2613,930,3480,954,2661,978,3516,2696,1013,3551,2731,1048,1060,3587,2779,1096,3622,2814,1131,3657,2849,1166,2874,2885,2897,1214,3728,1246,1258,2964,65535,65535,65535,65535,65535,65535,65535,65535,65535},
{1277,1282,1288,5108,5113,1306,1311,1318,1330,1342,1353,1365,1377,1390,1401,1413,1425,1436,1448,1460,1471,1483,1496,1508,1519,1531,1543,1554,1566,1578,1589,1602,1614,1626,1637,1649,1669,1681,1693,65535,65535,65535,65535,65535,65535,65535,65535,65535},
{5089,5094,1289,1297,1302,5118,5123,1319,3445,3457,1354,1366,1378,3493,1402,1414,3528,1437,1449,3563,1472,1484,1497,3599,1520,1532,3634,1555,1567,3669,1590,1603,3693,3705,1638,1650,1670,1682,3772,65535,65535,65535,65535,65535,65535,65535,65535,65535},
{1701,1706,1713,1721,1726,3421,1735,1743,1754,1766,1777,1789,1801,1814,1825,1837,1849,1860,1872,1884,1895,1907,1920,1932,1943,1955,1967,1978,1990,2002,2013,2026,2038,2050,2061,2073,2093,2106,2117,65535,65535,65535,65535,65535,65535,65535,65535,65535},
{5513,5518,3404,5533,5538,6389,5547,2590,1755,1767,1778,1790,1802,1815,1826,1838,1850,1861,1873,1885,1896,1908,1921,1933,1944,1956,1968,1979,1991,2003,2014,2027,2039,2051,2062,2074,2094,2953,2118,65535,65535,65535,65535,65535,65535,65535,65535,65535},
{2125,2130,2137,2145,2150,2155,5971,2167,2179,2190,2202,2213,2225,2238,2250,2261,2273,2285,2296,2308,2320,2332,2344,2356,2368,2379,2391,2403,2414,2426,2438,2450,2463,2474,2486,2497,2518,2530,2542,65535,65535,65535,65535,65535,65535,65535,65535,65535},
{5937,5942,14,5957,5962,5967,2582,3434,2602,2191,2625,2214,2226,2239,2673,2262,2274,2708,2297,2309,2743,2755,2345,2357,2791,2380,2392,2826,2415,2427,2861,2451,2886,2475,2909,2498,2941,3761,2965,65535,65535,65535,65535,65535,65535,65535,65535,65535},
{2548,2553,2561,2568,2573,2578,3426,2591,3446,2614,3469,2637,2649,2662,3505,2685,2697,3540,2720,2732,3575,2756,2768,2780,3611,2803,2815,3646,2838,2850,2862,3682,3694,2898,3717,2921,3749,2954,3773,65535,65535,65535,65535,65535,65535,65535,65535,65535},
{3392,3397,3405,3412,3417,3422,6394,3435,2603,3458,2626,3481,2650,3494,2674,3517,3529,2709,3552,3564,2744,209,3588,3600,2792,3623,3635,2827,3658,3670,2863,2875,2887,3706,2910,3729,2942,3762,2966,65535,65535,65535,65535,65535,65535,65535,65535,65535},
{2973,2978,2985,6805,2998,3003,3008,3015,3027,3038,3050,3062,3074,3086,3098,3110,3121,3133,3145,3156,3168,3180,3193,3204,3216,3228,3239,3251,3263,3274,3286,3299,3311,3322,3334,3346,3367,3378,3390,65535,65535,65535,65535,65535,65535,65535,65535,65535},
{6785,6790,2986,6380,6810,6815,6820,44,56,3039,3051,91,103,3087,3099,139,3122,3134,174,3157,3169,3181,222,3205,3217,257,3240,3252,292,3275,3287,328,340,3323,3335,375,3750,407,419,65535,65535,65535,65535,65535,65535,65535,65535,65535},
{4241,434,441,4261,454,459,464,471,483,494,506,518,531,542,554,566,577,589,601,612,624,637,649,660,672,684,695,707,719,730,743,756,767,778,790,802,823,834,846,65535,65535,65535,65535,65535,65535,65535,65535,65535},
{6360,4246,442,450,4266,4271,4276,472,484,495,507,519,104,543,555,567,578,590,602,613,625,210,650,661,673,685,696,708,720,731,316,3683,768,779,791,803,824,835,847,65535,65535,65535,65535,65535,65535,65535,65535,65535},
{2,4668,862,871,4688,881,4697,4702,901,913,924,936,948,961,972,984,996,1007,1019,1031,1042,1054,1067,1079,1090,1102,1114,1125,1137,1149,1160,1173,1185,1197,1208,1220,1232,1252,1264,65535,65535,65535,65535,65535,65535,65535,65535,65535},
{854,4670,866,874,4690,883,888,896,907,919,931,942,955,967,979,990,1002,1014,1025,1037,1049,1061,1073,1085,1097,1108,1120,1132,1143,1155,1167,1180,1191,1203,1215,1226,1247,1259,1270,65535,65535,65535,65535,65535,65535,65535,65535,65535},
{1278,6365,1290,5109,5114,1307,1312,1320,1331,1343,1355,1367,1379,1391,1403,1415,1426,1438,1450,1461,1473,1485,1498,1509,1521,1533,1544,1556,1568,1579,1591,1604,1615,1627,1639,1651,1671,1683,1694,65535,65535,65535,65535,65535,65535,65535,65535,65535},
{5090,1283,15,1298,6385,5119,5124,45,1332,68,3470,2638,1380,116,3506,2686,151,3541,2721,186,3576,1486,2769,234,3612,2804,269,3647,2839,304,1592,329,1616,352,3718,2922,1672,408,1695,65535,65535,65535,65535,65535,65535,65535,65535,65535},
{1702,1707,1714,1722,1727,1731,1736,1744,1756,1768,1779,1791,1803,1816,1827,1839,1851,1862,1874,1886,1897,1909,1922,1934,1945,1957,1969,1980,1992,2004,2015,2028,2040,2052,2063,2075,2095,2107,2119,65535,65535,65535,65535,65535,65535,65535,65535,65535},
{5514,5519,1715,5534,5539,5543,5548,1745,3447,2615,80,3482,1804,2663,128,3518,2698,163,3553,2733,198,1910,3589,2781,246,3624,2816,281,3659,2851,2016,2029,3695,2899,364,3730,2096,2108,3774,65535,65535,65535,65535,65535,65535,65535,65535,65535},
{2126,2131,2138,2146,2151,6390,2160,2168,2180,2192,2203,2215,2227,2240,2251,2263,2275,2286,2298,2310,2321,2333,2346,2358,2369,2381,2393,2404,2416,2428,2439,2452,2464,2476,2487,2499,2519,2531,2543,65535,65535,65535,65535,65535,65535,65535,65535,65535},
{5938,5943,2139,5958,5963,2156,5972,2169,57,3459,2204,92,2228,3495,2252,140,3530,2287,175,3565,2322,2334,223,3601,2370,258,3636,2405,293,3671,2440,2453,341,3707,2488,376,2520,2532,420,65535,65535,65535,65535,65535,65535,65535,65535,65535},
{2549,2554,2562,2569,2574,2579,2583,2592,2604,2616,2627,2639,2651,2664,2675,2687,2699,2710,2722,2734,2745,2757,2770,2782,2793,2805,2817,2828,2840,2852,2864,2876,2888,2900,2911,2923,2943,2955,2967,65535,65535,65535,65535,65535,65535,65535,65535,65535},
{3393,3398,3406,3413,3418,3423,3427,3436,3448,3460,3471,3483,2652,3496,3507,3519,3531,3542,3554,3566,3577,2758,3590,3602,3613,3625,3637,3648,3660,3672,317,3684,3696,3708,3719,3731,3751,3763,3775,65535,65535,65535,65535,65535,65535,65535,65535,65535},
{2974,2979,2987,2994,2999,3004,6395,3016,3028,3040,3052,3063,3075,3088,3100,3111,3123,3135,3146,3158,3170,3182,3194,3206,3218,3229,3241,3253,3264,3276,3288,3300,3312,3324,3336,3347,3368,3379,3391,65535,65535,65535,65535,65535,65535,65535,65535,65535},
{6786,6791,16,6806,6811,6816,3009,3017,3029,69,81,3064,3076,117,129,3112,152,164,3147,187,199,211,3195,235,247,3230,270,282,3265,305,3289,3301,3313,353,365,3348,397,3380,421,65535,65535,65535,65535,65535,65535,65535,65535,65535},
{6361,6366,2563,6381,6386,6391,2584,2593,2605,2617,2628,2640,105,2665,2676,2688,2700,2711,2723,2735,2746,2759,2771,2783,2794,2806,2818,2829,2841,2853,2865,2877,2889,2901,2912,2924,2944,2956,422,65535,65535,65535,65535,65535,65535,65535,65535,65535},
{2550,2555,3407,2570,2575,2580,3428,3437,3449,3461,3472,3484,2653,3497,3508,3520,3532,3543,3555,3567,3578,212,3591,3603,3614,3626,3638,3649,3661,3673,318,3685,3697,3709,3720,3732,3752,3764,423,65535,65535,65535,65535,65535,65535,65535,65535,65535},
{3,2977,2984,6804,2997,6388,6393,6823,3022,3034,3464,3476,3069,3082,3500,3512,3117,3535,3547,3152,3570,3582,3188,3200,3606,3618,3235,3641,3653,3270,3676,3295,3306,3318,3712,3724,3353,3756,3385,65535,65535,65535,65535,65535,65535,65535,65535,65535},
{2975,8,2988,23,28,33,6821,46,58,3041,3053,93,3077,3089,3101,141,3124,3136,176,3159,3171,3183,224,3207,3219,259,3242,3254,294,3277,3290,330,342,3325,3337,377,3369,409,1271,65535,65535,65535,65535,65535,65535,65535,65535,65535},
{4,3820,17,24,3840,3845,38,47,59,70,82,94,106,118,130,142,153,165,177,188,200,213,225,236,248,260,271,283,295,306,319,331,343,354,366,378,398,410,65535,65535,65535,65535,65535,65535,65535,65535,65535,65535},
{3816,9,18,3836,29,34,3850,48,60,71,83,95,107,119,131,143,154,166,178,189,201,214,226,237,249,261,272,284,296,307,320,332,344,355,367,379,399,411,65535,65535,65535,65535,65535,65535,65535,65535,65535,65535},
{5,3821,19,25,3841,3846,39,49,61,72,84,96,108,120,132,144,155,167,179,190,202,215,227,238,250,262,273,285,297,308,321,333,345,356,368,380,400,412,65535,65535,65535,65535,65535,65535,65535,65535,65535,65535},
{3817,10,20,3837,30,35,3851,50,62,73,85,97,109,121,133,145,156,168,180,191,203,216,228,239,251,263,274,286,298,309,322,334,346,357,369,381,401,413,65535,65535,65535,65535,65535,65535,65535,65535,65535,65535},
{6,3822,21,26,3842,3847,40,51,63,74,86,98,110,122,134,146,157,169,181,192,204,217,229,240,252,264,275,287,299,310,323,335,347,358,370,382,402,414,65535,65535,65535,65535,65535,65535,65535,65535,65535,65535},
{3818,11,2564,3838,31,36,3852,2594,2606,75,2629,2641,111,123,2677,2689,158,2712,2724,193,2747,2760,2772,241,2795,2807,276,2830,2842,311,2866,2878,2890,359,2913,2925,2945,2957,65535,65535,65535,65535,65535,65535,65535,65535,65535,65535},
{7,3823,3408,27,3843,3848,41,3438,3450,2618,3473,3485,2654,2666,3509,3521,2701,3544,3556,2736,3579,218,3592,2784,3615,3627,2819,3650,3662,2854,324,3686,3698,2902,3721,3733,3753,3765,65535,65535,65535,65535,65535,65535,65535,65535,65535,65535},
{3819,12,22,3839,32,37,3853,52,64,3462,87,99,112,3498,135,147,3533,170,182,3568,205,638,230,3604,253,265,3639,288,300,3674,744,336,348,3710,371,383,403,415,65535,65535,65535,65535,65535,65535,65535,65535,65535,65535},
};

#define TABLED 1
#define TRIG 7
#define JB 22
#define PRE 2
#define CH 64
#define CFN 1
#define CREGS 232
#define FIRST 4
constexpr int RING = SCHED_RING;
constexpr int NSLOT = 8;
constexpr int PLEN = SCHED_LE, LT = SCHED_LT, LM = 256 - 2 * PLEN - 2 * LT, NSEG = 4 / SCHED_NMID, LMID = NSEG * LM;
constexpr int NP = 8 + SCHED_NMID, NG = NP + (LT ? 8 : 0), NCONV = 3 * NG;
static_assert(LMID <= PLEN && LT <= RING && LT < LM && (LT == 0 || LT >= 6), "geometry");
__device__ __forceinline__ int group_len(int gm) { return gm < 8 ? PLEN : gm < NP ? LMID : LT; }
__device__ __forceinline__ int group_strip(int gm, int seg) { return gm < 8 ? gm >> 1 : gm < NP ? (gm - 8) * NSEG + seg : (gm - NP) >> 1; }
__device__ __forceinline__ int group_base(int gm) { return gm < NP ? PLEN + LT : PLEN + ((gm - NP) & 1) * (LT + LM); }
constexpr int TILEB = 12288;
constexpr int SLOTB = 280 * 64;
constexpr int W1S = 0, W2S = 73728, ABUF = 147456, XBUF = ABUF + 16 * 3072, MISC = XBUF + 8 * 3072;
constexpr int WBAR = MISC + 2560;
constexpr int RBUF = ABUF - 4 * SLOTB;
constexpr int CM = MISC + 2816, CTAB = CM + 256;
constexpr int SMEM_BYTES = CTAB + (PLEN + 16) * 16;
static_assert(RBUF % 512 == 0 && RBUF >= W2S && RBUF + NSLOT * SLOTB + 128 <= MISC && SMEM_BYTES <= 232448, "smem layout");

struct Globals {
  unsigned char scratch[RING * NG * 4 * TILEB];
  unsigned char wimg[147456];
  uint32_t wflag[32];
  uint32_t ready[NG * PLEN + 1];
  uint32_t cons[NG * PLEN];
  uint32_t epoch[1024];
};
__device__ __align__(1024) Globals g_state;

#define GELU_C3 0.32920349f
#define GELU_A2 0x40d940d9u
#define GELU_S2 0x3e133e13u
#define SCHED_FENCE() asm volatile("pmevent 0;" ::: "memory")
#define SPIN_LIMIT 0x1000000

__device__ __forceinline__ uint32_t smem_u32(const void* p) { return (uint32_t)__cvta_generic_to_shared(p); }
__device__ __forceinline__ void wg_fence() { asm volatile("wgmma.fence.sync.aligned;" ::: "memory"); }
__device__ __forceinline__ void wg_commit() { asm volatile("wgmma.commit_group.sync.aligned;" ::: "memory"); }
template <int N> __device__ __forceinline__ void wg_wait() { asm volatile("wgmma.wait_group.sync.aligned %0;" ::"n"(N) : "memory"); }
__device__ __forceinline__ void mbar_wait(uint32_t bar, uint32_t parity) {
  asm volatile("{\n.reg .pred p;\n.reg .u32 c;\nmbarrier.try_wait.parity.shared::cta.b64 p, [%0], %1;\n@p bra DONE_%=;\nmov.u32 c, 0;\nWAIT_%=:\nmbarrier.try_wait.parity.shared::cta.b64 p, [%0], %1;\n@p bra DONE_%=;\n"
               "add.u32 c, c, 1;\nsetp.lt.u32 p, c, 0x1000000;\n@p bra WAIT_%=;\ntrap;\nDONE_%=:\n}" ::"r"(bar), "r"(parity) : "memory");
}
__device__ __forceinline__ void mbar_arrive_elect(uint32_t bar) { asm volatile("{.reg .pred p; elect.sync _|p, 0xffffffff; @p mbarrier.arrive.shared::cta.b64 _, [%0];}" ::"r"(bar) : "memory"); }
__device__ __forceinline__ void mbar_init_elect(uint32_t bar, uint32_t cnt) { asm volatile("{.reg .pred p; elect.sync _|p, 0xffffffff; @p mbarrier.init.shared::cta.b64 [%0], %1;}" ::"r"(bar), "r"(cnt) : "memory"); }
__device__ __forceinline__ uint32_t ld_relaxed(const uint32_t* p) { uint32_t v; asm volatile("ld.relaxed.gpu.global.u32 %0, [%1];" : "=r"(v) : "l"(p) : "memory"); return v; }
__device__ __forceinline__ void red_add_elect(uint32_t* p) { asm volatile("{.reg .pred p; elect.sync _|p, 0xffffffff; @p red.relaxed.gpu.global.add.u32 [%0], 1;}" ::"l"(p) : "memory"); }
__device__ __forceinline__ void wait_value(const uint32_t* p, uint32_t target, int ns) {
  int spins = 0;
  while (ld_relaxed(p) != target) { __nanosleep(ns); if (++spins > SPIN_LIMIT) __trap(); }
}
template <int BYTES, bool INIT = false> __device__ __forceinline__ void bulk_load(uint32_t dst, const void* src, uint32_t bar, int go = 0) {
  if (INIT) asm volatile("{.reg .pred p; elect.sync _|p, 0xffffffff; @p mbarrier.init.shared::cta.b64 [%0], 1; @p fence.mbarrier_init.release.cluster;}" ::"r"(bar) : "memory");
  asm volatile("{\n.reg .pred p, q;\nsetp.ge.s32 q, %4, 0;\nelect.sync _|p, 0xffffffff;\nand.pred p, p, q;\n@p mbarrier.arrive.expect_tx.shared::cta.b64 _, [%1], %3;\n"
               "@p cp.async.bulk.shared::cluster.global.mbarrier::complete_tx::bytes [%0], [%2], %3, [%1];\n}"
               ::"r"(dst), "r"(bar), "l"(src), "n"(BYTES), "r"(go) : "memory");
}
__device__ __forceinline__ void lds128(uint32_t* r, uint32_t a) { asm volatile("ld.shared.v4.b32 {%0,%1,%2,%3}, [%4];" : "=r"(r[0]), "=r"(r[1]), "=r"(r[2]), "=r"(r[3]) : "r"(a) : "memory"); }
__device__ __forceinline__ uint2 lds64(uint32_t a) { uint2 v; asm volatile("ld.shared.v2.b32 {%0,%1}, [%2];" : "=r"(v.x), "=r"(v.y) : "r"(a) : "memory"); return v; }
__device__ __forceinline__ uint32_t lds32(uint32_t a) { uint32_t v; asm volatile("ld.shared.b32 %0, [%1];" : "=r"(v) : "r"(a) : "memory"); return v; }
__device__ __forceinline__ void sts32(uint32_t a, uint32_t v) { asm volatile("st.shared.b32 [%0], %1;" ::"r"(a), "r"(v) : "memory"); }
__device__ __forceinline__ void sts64(uint32_t a, uint2 v) { asm volatile("st.shared.v2.b32 [%0], {%1,%2};" ::"r"(a), "r"(v.x), "r"(v.y) : "memory"); }
__device__ __forceinline__ void sts128(uint32_t a, uint4 v) { asm volatile("st.shared.v4.b32 [%0], {%1,%2,%3,%4};" ::"r"(a), "r"(v.x), "r"(v.y), "r"(v.z), "r"(v.w) : "memory"); }
__device__ __forceinline__ uint64_t pol_evict_first() { uint64_t p; asm("createpolicy.fractional.L2::evict_first.b64 %0, 1.0;" : "=l"(p)); return p; }
__device__ __forceinline__ void stg128_stream(void* p, uint4 v, uint64_t pol) {
  asm volatile("st.global.L2::cache_hint.v4.b32 [%0], {%1,%2,%3,%4}, %5;" ::"l"(p), "r"(v.x), "r"(v.y), "r"(v.z), "r"(v.w), "l"(pol) : "memory");
}
__device__ __forceinline__ void stg128_if(uint32_t go, void* p, uint4 v) {
  asm volatile("{.reg .pred q; setp.ge.s32 q, %5, 0; @q st.global.v4.b32 [%0], {%1,%2,%3,%4};}" ::"l"(p), "r"(v.x), "r"(v.y), "r"(v.z), "r"(v.w), "r"(go) : "memory");
}
__device__ __forceinline__ uint32_t pack_f16(float lo, float hi) { uint32_t d; asm("cvt.rn.f16x2.f32 %0, %1, %2;" : "=r"(d) : "f"(hi), "f"(lo)); return d; }
__device__ __forceinline__ uint32_t pack_f16_sat(float lo, float hi) { uint32_t d; asm("cvt.rn.satfinite.f16x2.f32 %0, %1, %2;" : "=r"(d) : "f"(hi), "f"(lo)); return d; }
__device__ __forceinline__ uint32_t pack_bf16(float lo, float hi) { uint32_t d; asm("cvt.rn.bf16x2.f32 %0, %1, %2;" : "=r"(d) : "f"(hi), "f"(lo)); return d; }
__device__ __forceinline__ uint32_t bf2_to_h2(uint32_t w) { return pack_f16(__uint_as_float(w << 16), __uint_as_float(w & 0xffff0000u)); }
__device__ __forceinline__ uint32_t hadd2_bf16(uint32_t a, uint32_t b) { uint32_t d; asm("add.rn.bf16x2 %0, %1, %2;" : "=r"(d) : "r"(a), "r"(b)); return d; }
__device__ __forceinline__ uint32_t h2add(uint32_t a, uint32_t b) { uint32_t d; asm("add.rn.f16x2 %0, %1, %2;" : "=r"(d) : "r"(a), "r"(b)); return d; }
__device__ __forceinline__ uint32_t h2mul(uint32_t a, uint32_t b) { uint32_t d; asm("mul.rn.f16x2 %0, %1, %2;" : "=r"(d) : "r"(a), "r"(b)); return d; }
__device__ __forceinline__ uint32_t h2fma(uint32_t a, uint32_t b, uint32_t c) { uint32_t d; asm("fma.rn.f16x2 %0, %1, %2, %3;" : "=r"(d) : "r"(a), "r"(b), "r"(c)); return d; }
__device__ __forceinline__ uint32_t h2lo(uint32_t a) { uint32_t d; asm("{.reg .f16 l,h; mov.b32 {l,h}, %1; mov.b32 %0, {l,l};}" : "=r"(d) : "r"(a)); return d; }
__device__ __forceinline__ uint32_t h2hi(uint32_t a) { uint32_t d; asm("{.reg .f16 l,h; mov.b32 {l,h}, %1; mov.b32 %0, {h,h};}" : "=r"(d) : "r"(a)); return d; }
__device__ __forceinline__ float h_lo(uint32_t a) { float d; asm("{.reg .f16 l,h; mov.b32 {l,h}, %1; cvt.f32.f16 %0, l;}" : "=f"(d) : "r"(a)); return d; }
__device__ __forceinline__ float h_hi(uint32_t a) { float d; asm("{.reg .f16 l,h; mov.b32 {l,h}, %1; cvt.f32.f16 %0, h;}" : "=f"(d) : "r"(a)); return d; }
__device__ __forceinline__ float rsqrt_fast(float v) { float r; asm("rsqrt.approx.ftz.f32 %0, %1;" : "=f"(r) : "f"(v)); return r; }
__device__ __forceinline__ uint32_t prmt(uint32_t a, uint32_t b, uint32_t s) { uint32_t d; asm("prmt.b32 %0, %1, %2, %3;" : "=r"(d) : "r"(a), "r"(b), "r"(s)); return d; }
__device__ __forceinline__ void mma_sp(float* d, const uint32_t* a, const uint32_t* b, const float* c, uint32_t e) {
  asm("mma.sp::ordered_metadata.sync.aligned.m16n8k32.row.col.f32.bf16.bf16.f32 {%0,%1,%2,%3}, {%4,%5,%6,%7}, {%8,%9,%10,%11}, {%12,%13,%14,%15}, %16, 0;"
      : "=f"(d[0]), "=f"(d[1]), "=f"(d[2]), "=f"(d[3])
      : "r"(a[0]), "r"(a[1]), "r"(a[2]), "r"(a[3]), "r"(b[0]), "r"(b[1]), "r"(b[2]), "r"(b[3]), "f"(c[0]), "f"(c[1]), "f"(c[2]), "f"(c[3]), "r"(e));
}

__device__ __forceinline__ uint32_t gelu_tanh(uint32_t y) {
  uint32_t t, u, th;
  asm volatile("fma.rn.f16x2 %0, %1, %1, %2;" : "=r"(t) : "r"(y), "r"(GELU_A2));
  asm volatile("mul.rn.f16x2 %0, %1, %2;" : "=r"(u) : "r"(y), "r"(t));
  asm volatile("tanh.approx.f16x2 %0, %1;" : "=r"(th) : "r"(u));
  return th;
}
__device__ __forceinline__ uint32_t gelu_fin(uint32_t y, uint32_t th) {
  uint32_t g;
  asm volatile("fma.rn.f16x2 %0, %1, %2, %1;" : "=r"(g) : "r"(y), "r"(th));
  return g;
}

__device__ __forceinline__ void convert_weights(uint32_t sb, int rot, int warp, int lane) {
  if (warp < 12) {
    const int l8 = lane & 7, q4 = lane >> 3;
    int s = (warp >> 1) + rot; if (s >= 6) s -= 6;
    const uint32_t base = sb + W1S + s * 12288 + (warp & 1) * 384;
    mbar_wait(sb + WBAR + s * 8, 0);
    uint32_t v[3][4][4];
#pragma unroll
    for (int r = 0; r < 4; r++)
#pragma unroll
      for (int i = 0; i < 3; i++) lds128(v[i][r], base + i * 128 + (4 * (l8 >> 1) + 2 * (r & 1) + (l8 & 1)) * 768 + ((l8 + q4 + 4 * (r >> 1)) & 7) * 16);
    __syncwarp();
#pragma unroll
    for (int r = 0; r < 4; r++)
#pragma unroll
      for (int i = 0; i < 3; i++)
        sts128(base + i * 128 + (((l8 + q4 + 4 * (r >> 1)) & 7) + 8 * (r & 1)) * 768 + l8 * 16,
               make_uint4(bf2_to_h2(v[i][r][0]), bf2_to_h2(v[i][r][1]), bf2_to_h2(v[i][r][2]), bf2_to_h2(v[i][r][3])));
  }
  const int q = lane & 3, t = (lane >> 2) & 3, b = lane >> 4;
  int u = 3 * (warp ^ 15) + 8 * rot; if (u >= 48) u -= 48;
  uint32_t base[3], v[3][4][3];
#pragma unroll
  for (int i = 0; i < 3; i++) {
    const int ui = u + i >= 48 ? u + i - 48 : u + i;
    base[i] = sb + W2S + ui * 1536;
    if (i != 1) mbar_wait(sb + WBAR + 48 + (ui >> 3) * 8, 0);
  }
#pragma unroll
  for (int i = 0; i < 3; i++)
#pragma unroll
    for (int d = 0; d < 4; d++)
#pragma unroll
      for (int j = 0; j < 3; j++) v[i][d][j] = lds32(base[i] + (2 * ((q + d) & 3) + b) * 192 + j * 64 + t * 16 + q * 4);
  __syncwarp();
#pragma unroll
  for (int i = 0; i < 3; i++)
#pragma unroll
    for (int d = 0; d < 4; d++)
#pragma unroll
      for (int j = 0; j < 3; j++) sts32(base[i] + (4 * j + q) * 128 + (2 * ((q + d) & 3) + b) * 16 + t * 4, bf2_to_h2(v[i][d][j]));
}

__device__ __noinline__ void ln_wide(uint32_t ad) {
  float m[2], r[2];
#pragma unroll
  for (int hi = 0; hi < 2; hi++) {
    float sm = 0.f;
    for (int s = 0; s < 6; s++) { uint2 w = lds64(ad + s * 512 + hi * 8); sm += (h_lo(w.x) + h_hi(w.x)) + (h_lo(w.y) + h_hi(w.y)); }
    sm += __shfl_xor_sync(0xffffffffu, sm, 1); sm += __shfl_xor_sync(0xffffffffu, sm, 2);
    m[hi] = sm * (1.f / 96.f);
    float q = 0.f;
    for (int s = 0; s < 6; s++) {
      uint2 w = lds64(ad + s * 512 + hi * 8);
      float d0 = h_lo(w.x) - m[hi], d1 = h_hi(w.x) - m[hi], d2 = h_lo(w.y) - m[hi], d3 = h_hi(w.y) - m[hi];
      q += (d0 * d0 + d1 * d1) + (d2 * d2 + d3 * d3);
    }
    q += __shfl_xor_sync(0xffffffffu, q, 1); q += __shfl_xor_sync(0xffffffffu, q, 2);
    r[hi] = rsqrtf(fmaf(q, 1.f / 96.f, 1e-5f)) * GELU_C3;
  }
  for (int s = 0; s < 6; s++) {
    uint32_t w[4]; lds128(w, ad + s * 512);
    sts128(ad + s * 512, make_uint4(pack_f16((h_lo(w[0]) - m[0]) * r[0], (h_hi(w[0]) - m[0]) * r[0]), pack_f16((h_lo(w[2]) - m[1]) * r[1], (h_hi(w[2]) - m[1]) * r[1]),
                                    pack_f16((h_lo(w[1]) - m[0]) * r[0], (h_hi(w[1]) - m[0]) * r[0]), pack_f16((h_lo(w[3]) - m[1]) * r[1], (h_hi(w[3]) - m[1]) * r[1])));
  }
  asm volatile("fence.proxy.async.shared::cta;" ::: "memory");
}

__device__ __forceinline__ uint32_t layer_norm(const uint32_t (&raw)[6][4], uint32_t* a, uint32_t tag) {
  const uint32_t stale = ((raw[0][0] ^ tag) | (raw[1][0] ^ tag)) | ((raw[2][0] ^ tag) | (raw[3][0] ^ tag)) | ((raw[4][0] ^ tag) | (raw[5][0] ^ tag));
  uint32_t sm[2], qq[2];
#pragma unroll
  for (int hi = 0; hi < 2; hi++) {
    uint32_t s0 = h2add(raw[0][2 * hi], raw[1][2 * hi]), s1 = h2add(raw[0][2 * hi + 1], raw[1][2 * hi + 1]);
    uint32_t s2 = h2add(raw[2][2 * hi], raw[3][2 * hi]), s3 = h2add(raw[2][2 * hi + 1], raw[3][2 * hi + 1]);
    uint32_t s4 = h2add(raw[4][2 * hi], raw[5][2 * hi]), s5 = h2add(raw[4][2 * hi + 1], raw[5][2 * hi + 1]);
    sm[hi] = h2add(h2add(h2add(s0, s1), h2add(s2, s3)), h2add(s4, s5));
  }
#pragma unroll
  for (int hi = 0; hi < 2; hi++) {
    uint32_t q0 = h2mul(raw[0][2 * hi], raw[0][2 * hi]), q1 = h2mul(raw[0][2 * hi + 1], raw[0][2 * hi + 1]);
#pragma unroll
    for (int k = 1; k < 6; k++) { q0 = h2fma(raw[k][2 * hi], raw[k][2 * hi], q0); q1 = h2fma(raw[k][2 * hi + 1], raw[k][2 * hi + 1], q1); }
    qq[hi] = h2add(q0, q1);
  }
  uint32_t s = h2add(prmt(sm[0], sm[1], 0x5410), prmt(sm[0], sm[1], 0x7632));
  uint32_t q = h2add(prmt(qq[0], qq[1], 0x5410), prmt(qq[0], qq[1], 0x7632));
  s = h2add(s, __shfl_xor_sync(0xffffffffu, s, 1)); q = h2add(q, __shfl_xor_sync(0xffffffffu, q, 1));
  s = h2add(s, __shfl_xor_sync(0xffffffffu, s, 2)); q = h2add(q, __shfl_xor_sync(0xffffffffu, q, 2));
  constexpr float K1 = 1.f / (96.f * GELU_C3 * GELU_C3), K2 = 1e-5f / (GELU_C3 * GELU_C3), K3 = 1.f / (96.f * GELU_C3);
  const float e0 = fmaf(h_lo(q), K1, K2), e1 = fmaf(h_hi(q), K1, K2), m0 = h_lo(s) * K3, m1 = h_hi(s) * K3;
  const float v0 = fmaf(-m0, m0, e0), v1 = fmaf(-m1, m1, e1);
  const uint32_t r = pack_f16(rsqrt_fast(v0), rsqrt_fast(v1)), o = h2mul(h2mul(s, 0xA155A155u), r);
#pragma unroll
  for (int k = 0; k < 6; k++) {
    a[4 * k] = h2fma(raw[k][0], h2lo(r), h2lo(o)); a[4 * k + 2] = h2fma(raw[k][1], h2lo(r), h2lo(o));
    a[4 * k + 1] = h2fma(raw[k][2], h2hi(r), h2hi(o)); a[4 * k + 3] = h2fma(raw[k][3], h2hi(r), h2hi(o));
  }
  const bool fine = fmaf(v0, 4.f, -e0) > 0.f && fmaf(v1, 4.f, -e1) > 0.f;
  return (fine ? 0u : 2u) | (stale & 1);
}

constexpr int KS = CH / 16, NC = 384 / CH;
#define WG1_(n) wgmma_n##n##_f16
#define WG1(n) WG1_(n)
__device__ __forceinline__ void gemm1(uint32_t* p, const uint32_t* a, uint64_t d1, int c, int k0, int k1) {
#pragma unroll
  for (int s = 0; s < 6; s++)
    if (s >= k0 && s < k1) {
      if (s == 0) WG1(CH)<0>(p, a, d1 + c * CH); else WG1(CH)<1>(p, a + 4 * s, d1 + c * CH + s * (12288 >> 4));
    }
}
__device__ __forceinline__ void fetch_x(uint32_t xbuf, uint32_t bar, const CUtensorMap* tm, uint32_t c0, uint32_t c12, uint64_t pol, int go = 0) {
  asm volatile("{\n.reg .pred p, q;\nsetp.ge.s32 q, %7, 0;\nelect.sync _|p, 0xffffffff;\nand.pred p, p, q;\n"
               "@p mbarrier.arrive.expect_tx.shared::cta.b64 _, [%1], 3072;\n"
               "@p cp.async.bulk.tensor.3d.shared::cluster.global.mbarrier::complete_tx::bytes.L2::cache_hint [%0], [%2, {%3, %4, %5}], [%1], %6;\n}"
               ::"r"(xbuf), "r"(bar), "l"(tm), "r"(c0), "r"(c12 & 255), "r"(c12 >> 8), "l"(pol), "r"(go) : "memory");
}
__device__ __forceinline__ uint32_t slot_tag(int gm, int j, uint32_t epoch) {
  const int writes = (group_len(gm) - j % RING + RING - 1) / RING;
  return (epoch * writes + j / RING + 1) & 1;
}
__device__ __forceinline__ void build_tile_list(uint32_t sb, int k, int idx, bool tabled, bool is_conv, uint32_t epoch) {
  int n = -1;
  if (tabled) { if (k < 48) n = (int16_t)g_sched[idx][k]; }
  else if (!is_conv) {
    const int i = k * (gridDim.x - NCONV) + idx, r = i >> 2, r1 = r - LT * NG, r2 = r1 - (LMID - LT) * NP;
    const int j = r1 < 0 ? r / NG : r2 < 0 ? LT + r1 / NP : LMID + (r2 >> 3), gm = r1 < 0 ? r % NG : r2 < 0 ? r1 % NP : r2 & 7;
    if (i < 4096) n = (gm * PLEN + j) * 4 + (i & 3);
  }
  const int q = n >> 2, gm = q / PLEN, j = q - gm * PLEN, seg = j / LM;
  const int strip = group_strip(gm, seg), pair = gm < 8 ? ((gm & 1) ? 255 - j : j) : group_base(gm) + j - seg * LM;
  sts128(sb + MISC + 512 + k * 16, make_uint4(q, (((j % RING) * NG + gm) * 4 + (n & 3)) * TILEB + slot_tag(gm, j, epoch),
                                              (n & 2) * 384, (strip * 8 + (n & 1) * 4) | (pair << 9)));
  if (k == 0) sts64(sb + MISC + 256, make_uint2(epoch + 1, !is_conv));
}

__device__ __forceinline__ void mlp_setup(uint32_t sb, Globals* gs, int id, const __nv_bfloat16* __restrict__ w1, const __nv_bfloat16* __restrict__ w2,
                                          int idx, bool tabled, int warp, int lane) {
  const int rot = idx % 6;
  if (warp < 12) {
    const int m = warp >= 6; int s = warp - 6 * m + rot; if (s >= 6) s -= 6;
    bulk_load<12288, true>(sb + (6 * m + s) * 12288, (const char*)(m ? w2 : w1) + s * 12288, sb + WBAR + (6 * m + s) * 8);
  }
  __syncthreads();
  if (warp >= 12) build_tile_list(sb, threadIdx.x - 384, idx, tabled, false, ld_relaxed(&gs->epoch[id]));
  convert_weights(sb, rot, warp, lane);
  asm volatile("fence.proxy.async.shared::cta;" ::: "memory");
  __syncthreads();
  if (threadIdx.x == 480) {
    gs->epoch[id] = lds32(sb + MISC + 256);
    const uint32_t piece = tabled ? idx - 96 : idx;
    if (piece < 12) {
      asm volatile("cp.async.bulk.global.shared::cta.bulk_group [%0], [%1], 12288;\ncp.async.bulk.commit_group;\ncp.async.bulk.wait_group 0;\nfence.proxy.async.global;\n"
                   "red.release.gpu.global.add.u32 [%2], 1;" ::"l"(gs->wimg + piece * 12288), "r"(sb + piece * 12288), "l"(gs->wflag) : "memory");
    }
  }
  __syncwarp();
}

__device__ __forceinline__ void mlp_role(uint32_t sb, Globals* gs, const CUtensorMap* tmr, __nv_bfloat16* __restrict__ out) {
  uint32_t tid;
  asm volatile("mov.u32 %0, %%tid.x;" : "=r"(tid));
  const int warp = __shfl_sync(0xffffffffu, tid >> 5, 0), lane = tid & 31;
  const int wg = warp >> 2, w = warp & 3, g = lane >> 2, t = lane & 3;
  const uint32_t abuf = sb + ABUF + warp * 3072, xbuf = sb + XBUF + (warp & 7) * 3072;
  const uint32_t bar = sb + MISC + warp * 8, obar = sb + MISC + (warp ^ 8) * 8;
  const uint32_t tl = sb + MISC + 512;
  const uint32_t rtarget = 3 * lds32(sb + MISC + 256);
  const uint64_t d1 = ((uint64_t)(6144 >> 4) << 16) | ((uint64_t)(128 >> 4) << 32) | (uint64_t)(((sb + W1S) >> 4) & 0x3fff);
  const uint64_t d2 = ((uint64_t)(12288 >> 4) << 16) | ((uint64_t)(128 >> 4) << 32) | (uint64_t)(((sb + W2S) >> 4) & 0x3fff);
  const uint32_t ad = abuf + t * 128 + ((g ^ (2 * t)) << 4);
  const uint32_t xd = xbuf + g * 192 + t * 16;
  const uint32_t pofs = (g >> 1) * 3072 + (2 * w + (g & 1)) * 192 + t * 16;
  const int mybar = 1 + wg, nxtbar = 1 + ((wg + 1) & 3);
  const uint64_t pol = pol_evict_first();
  const unsigned char* const asrc = gs->scratch + w * 3072;
  uint32_t pha = 0, phx = 0, tp = tl + wg * 16;
  bool pending = lds32(sb + MISC + 260);
  uint32_t cur[4];
  lds128(cur, tp);
  if (wg < 2) fetch_x(xbuf, bar + 128, tmr, cur[2] + w * 192, cur[3], pol, cur[0]);
  while ((int)cur[0] >= 0) {
    uint32_t a[24], p[NC][CH / 4], gg[24][4], th[24][4], acc[24], raw[6][4], n2[4], n4[4];
    if (pending) {
      wait_value(&gs->ready[cur[0]], rtarget, 32);
      bulk_load<3072>(abuf, asrc + (cur[1] & ~1u), bar);
    }
    mbar_wait(bar, pha); pha ^= 1;
#pragma unroll
    for (int k = 0; k < 6; k++) lds128(raw[k], ad + k * 512);
    uint32_t st = layer_norm(raw, a, cur[1]);
    if (__any_sync(0xffffffffu, st != 0)) {
      for (int tries = 0; __any_sync(0xffffffffu, st & 1); tries++) {
        if (tries > SPIN_LIMIT) __trap();
        bulk_load<3072>(abuf, asrc + (cur[1] & ~1u), bar);
        mbar_wait(bar, pha); pha ^= 1;
        st = 0;
#pragma unroll
        for (int k = 0; k < 6; k++) st |= lds32(ad + k * 512) ^ cur[1];
      }
      ln_wide(ad);
#pragma unroll
      for (int k = 0; k < 6; k++) lds128(a + 4 * k, ad + k * 512);
    }
    if (tp != tl) asm volatile("bar.sync %0, 256;" ::"r"(mybar) : "memory");
    uint32_t rdy = 0;
    wg_fence();
    gemm1(p[0], a, d1, 0, 0, 6); wg_commit();
    gemm1(p[1], a, d1, 1, 0, 6 / KS); wg_commit();
    const int sig = lds32(tp + 16);
    lds128(n4, tp + 64);
    asm volatile("{.reg .pred p; setp.eq.u32 p, %1, 0; @p red.relaxed.gpu.global.add.u32 [%0], 1;}" ::"l"(&gs->cons[cur[0]] + lane), "r"(lane) : "memory");
#pragma unroll
    for (int j = 0; j < 24; j++) {
      const int c = j / KS, s = j % KS;
      if (j == JB) rdy = ld_relaxed(&gs->ready[max((int)n4[0], 0)]);
      if (s == 0) wg_wait<1>();
      if (j == TRIG) asm volatile("{.reg .pred p; setp.ge.s32 p, %1, 0; @p bar.arrive %0, 256;}" ::"r"(nxtbar), "r"(sig) : "memory");
#pragma unroll
      for (int i = 0; i < 4; i++) {
        if (!(s && i < PRE)) th[j][i] = gelu_tanh(p[c][4 * s + i]);
        gg[j][i] = gelu_fin(p[c][4 * s + i], th[j][i]);
      }
      wg_fence();
      if (j == 0) wgmma_n96_f16<0>(acc, gg[j], d2); else wgmma_n96_f16<1>(acc, gg[j], d2 + (16 * (j % 3) + j / 3) * (1536 >> 4));
      const int c1 = (j + 1) / KS + 1, u = (j + 1) % KS;
      if (c1 < NC) gemm1(p[c1], a, d1, c1, (6 * u) / KS, (6 * (u + 1)) / KS);
      wg_commit();
      if (s + 1 < KS) {
#pragma unroll
        for (int i = 0; i < PRE; i++) th[j + 1][i] = gelu_tanh(p[c][4 * s + 4 + i]);
      }
      if (j < 23) SCHED_FENCE();
    }
    pending = rdy != rtarget;
    bulk_load<3072>(abuf, asrc + (n4[1] & ~1u), bar, pending ? -1 : (int)n4[0]);
    wg_wait<0>();
    mbar_wait(bar + 128, phx); phx ^= 1;
#pragma unroll
    for (int k = 0; k < 24; k++) acc[k] = h2mul(acc[k], GELU_S2);
    char* const op = (char*)out + (cur[2] * 2 + (cur[3] & 255) * 3072 + (cur[3] >> 8) * (512 * 192) + pofs);
    lds128(n2, tp + 32);
#pragma unroll
    for (int k = 0; k < 6; k++) {
      const int hi = k / 3, j = k % 3;
      uint32_t xr[4];
      lds128(xr, xd + hi * 1536 + j * 64);
      uint4 o;
      o.x = hadd2_bf16(xr[0], pack_bf16(h_lo(acc[8 * j + hi]), h_hi(acc[8 * j + hi])));
      o.y = hadd2_bf16(xr[1], pack_bf16(h_lo(acc[8 * j + 2 + hi]), h_hi(acc[8 * j + 2 + hi])));
      o.z = hadd2_bf16(xr[2], pack_bf16(h_lo(acc[8 * j + 4 + hi]), h_hi(acc[8 * j + 4 + hi])));
      o.w = hadd2_bf16(xr[3], pack_bf16(h_lo(acc[8 * j + 6 + hi]), h_hi(acc[8 * j + 6 + hi])));
      stg128_stream(op + hi * (512 * 192) + j * 64, o, pol);
    }
    __syncwarp();
    if ((int)n2[0] >= 0) fetch_x(xbuf, obar + 128, tmr, n2[2] + w * 192, n2[3], pol);
    tp += 64;
#pragma unroll
    for (int k = 0; k < 4; k++) cur[k] = n4[k];
  }
}

__device__ __forceinline__ void conv_compute(uint32_t sb, Globals* gs, int third, int nit, int off, bool up, int warp, int lane) {
  const int g = lane >> 2, t = lane & 3;
  const uint32_t full = sb + CM;
  const uint32_t wt = sb + 16384 + warp * 1024;
  sts128(wt + lane * 16, make_uint4(0, 0, 0, 0));
  if (lane < 4) sts128(wt + 512 + lane * 16, make_uint4(0, 0, 0, 0));
  asm volatile("setmaxnreg.inc.sync.aligned.u32 %0;" ::"n"(CREGS));
  uint32_t meta = 0;
#pragma unroll
  for (int a = 0; a < 4; a++) meta |= ((4 * (t & 1) + a + 1 >= g) ? 0x80008u : 0xD000Du) << (4 * a);
  meta = __shfl_sync(0xffffffffu, meta, lane);
  uint32_t aq[4];
#pragma unroll
  for (int q = 0; q < 4; q++) {
    const int pp = (g & 1) * 140 + (t & 1) * 70 + 16 * (g >> 1) + 2 * q + (t >> 1);
    aq[q] = __shfl_sync(0xffffffffu, sb + RBUF + pp * 64 + (((warp >> 1) ^ ((pp >> 1) & 3)) << 4) + (warp & 1) * 8, lane);
  }
  const int Q = third * 8 + warp;
  unsigned char* const obase = gs->scratch + (g >> 1) * 3072 + Q * 128 + (((2 * t + (g & 1)) ^ (2 * (Q & 3))) << 4);
  const float zero4[4] = {0.f, 0.f, 0.f, 0.f};
  float S[2][4][3][4];
  __syncwarp();
#pragma unroll
  for (int i = 0; i < 8; i++) {
    lds128((uint32_t*)S[i >> 2][i & 3][0], wt + i * 16);
#pragma unroll
    for (int k = 0; k < 8; k++) asm volatile("" : "=f"(S[i >> 2][i & 3][1 + (k >> 2)][k & 3]));
  }
  uint32_t A[4][4][4];
  asm volatile("bar.sync 5, 288;" ::: "memory");
  mbar_wait(sb + WBAR + 8, 0);
  {
#pragma unroll
    for (int k = 0; k < 2; k++) {
      const int tap = lane + 32 * k;
      if (tap < 49) sts64(wt + (tap + tap / 7 + 8) * 8, lds64(sb + tap * 192 + third * 64 + warp * 8));
    }
    __syncwarp();
    uint2 w[2][4][3];
#pragma unroll
    for (int h = 0; h < 2; h++) {
      uint32_t src = wt + ((4 * h + t - g) & 7) * 8 + (up ? 384 : 0);
#pragma unroll
      for (int u = 0; u < 4; u++) {
#pragma unroll
        for (int k = 0; k < 3; k++) w[h][u][k] = lds64(src + k * 64);
        src += up ? -128 : 128;
      }
    }
#pragma unroll
    for (int u = 0; u < 4; u++)
#pragma unroll
      for (int r = 0; r < 4; r++) {
        const uint2 w0 = w[r >> 1][u][1 - (r & 1)], w1 = w[r >> 1][u][2 - (r & 1)];
        A[0][u][r] = prmt(w0.x, w1.x, 0x5410); A[1][u][r] = prmt(w0.x, w1.x, 0x7632);
        A[2][u][r] = prmt(w0.y, w1.y, 0x5410); A[3][u][r] = prmt(w0.y, w1.y, 0x7632);
      }
  }
  uint32_t sofs = off * SLOTB, bar = full + off * 8, ph = 0, ot = sb + CTAB;
  const uint32_t oend = ot + nit * 16;
  asm volatile("bar.sync 0, 512;" ::: "memory");
  mbar_wait(bar, 0);
  uint2 X[3][4];
#pragma unroll
  for (int j = 0; j < 2; j++)
#pragma unroll
    for (int q = 0; q < 4; q++) X[j][q] = lds64(aq[q] + sofs + j * 512);
#pragma unroll 1
  do {
    const uint2 oe = lds64(ot);
    unsigned char* const o = obase + oe.x;
    const uint32_t dbar = bar + 64;
#pragma unroll
    for (int s = 0; s < 2; s++) {
      uint32_t B[4][4];
      if (s == 1) {
        sofs += SLOTB; bar += 8;
        if (sofs == NSLOT * SLOTB) { sofs = 0; bar = full; ph ^= 1; }
        mbar_wait(bar, ph);
      }
#pragma unroll
      for (int c = 0; c < 4; c++)
#pragma unroll
        for (int q = 0; q < 4; q++) B[c][q] = prmt(c < 2 ? X[s][q].x : X[s][q].y, c < 2 ? X[s + 1][q].x : X[s + 1][q].y, (c & 1) ? 0x7632 : 0x5410);
      if (s == 0) {
#pragma unroll
        for (int q = 0; q < 4; q++) X[2][q] = lds64(aq[q] + sofs + 2 * 512);
      } else {
#pragma unroll
        for (int j = 0; j < 2; j++)
#pragma unroll
          for (int q = 0; q < 4; q++) X[j][q] = lds64(aq[q] + sofs + j * 512);
      }
      float T[4][4];
      if (CFN & 1) SCHED_FENCE();
#pragma unroll
      for (int c = 0; c < 4; c++) mma_sp(T[c], A[c][3], B[c], S[s][c][2], meta);
#pragma unroll
      for (int c = 0; c < 4; c++) mma_sp(S[s][c][2], A[c][2], B[c], S[s][c][1], meta);
      if (CFN & 8) {
#pragma unroll
        for (int c = 0; c < 4; c++) mma_sp(S[s][c][1], A[c][1], B[c], S[s][c][0], meta);
#pragma unroll
        for (int c = 0; c < 4; c++) mma_sp(S[s][c][0], A[c][0], B[c], zero4, meta);
      }
      if (CFN & 2) SCHED_FENCE();
      stg128_if(oe.x, o + (2 * s) * TILEB, make_uint4((pack_f16_sat(T[0][0], T[1][0]) & ~1u) | oe.y, pack_f16_sat(T[2][0], T[3][0]), pack_f16_sat(T[0][2], T[1][2]), pack_f16_sat(T[2][2], T[3][2])));
      stg128_if(oe.x, o + (2 * s + 1) * TILEB, make_uint4((pack_f16_sat(T[0][1], T[1][1]) & ~1u) | oe.y, pack_f16_sat(T[2][1], T[3][1]), pack_f16_sat(T[0][3], T[1][3]), pack_f16_sat(T[2][3], T[3][3])));
      if (s == 1) mbar_arrive_elect(dbar);
      if (CFN & 4) SCHED_FENCE();
      if (!(CFN & 8)) {
#pragma unroll
        for (int c = 0; c < 4; c++) mma_sp(S[s][c][1], A[c][1], B[c], S[s][c][0], meta);
#pragma unroll
        for (int c = 0; c < 4; c++) mma_sp(S[s][c][0], A[c][0], B[c], zero4, meta);
      }
    }
    ot += 16;
  } while (ot != oend);
}

__device__ __forceinline__ void load_step(uint32_t sb, const CUtensorMap* tmx, int gm, int third, int it, int s, bool first = false) {
  const int seg = first ? 0 : it / (LM + 3);
  const int st = group_strip(gm, seg), J = gm < 8 ? ((gm & 1) ? 257 - it : it + 1) : group_base(gm) + it - seg * (LM + 3);
  asm volatile("{\n.reg .pred p;\n.reg .s32 c2;\n.reg .u32 d2;\nelect.sync _|p, 0xffffffff;\nadd.s32 c2, %4, 64;\nadd.u32 d2, %0, 8960;\n"
               "@p mbarrier.arrive.expect_tx.shared::cta.b64 _, [%2], 17920;\n"
               "@p cp.async.bulk.tensor.3d.shared::cluster.global.mbarrier::complete_tx::bytes [%0], [%1, {%3, %4, %5}], [%2];\n"
               "@p cp.async.bulk.tensor.3d.shared::cluster.global.mbarrier::complete_tx::bytes [d2], [%1, {%3, c2, %5}], [%2];\n}"
               ::"r"(sb + RBUF + s * SLOTB), "l"(tmx), "r"(sb + CM + s * 8), "r"(third * 32), "r"(st * 128 - 3), "r"(2 * J - 3) : "memory");
}
__device__ __forceinline__ void ring_bar_init(uint32_t bar, uint32_t cnt, bool ahead) {
  asm volatile("{\n.reg .pred p, q;\nelect.sync _|p, 0xffffffff;\n@p mbarrier.init.shared::cta.b64 [%0], %1;\n"
               "setp.ne.and.u32 q, %2, 0, p;\n@q mbarrier.arrive.shared::cta.b64 _, [%0], %1;\n@p fence.mbarrier_init.release.cluster;\n}" ::"r"(bar), "r"(cnt), "r"((uint32_t)ahead) : "memory");
}
__device__ __forceinline__ void conv_loader(uint32_t sb, Globals* gs, const CUtensorMap* tmx, int gm, int nit, int off, int cidx, int third, int k) {
  static_assert(FIRST >= 4 && NCONV >= 24, "loader");
  const uint32_t full = sb + CM;
  asm volatile("bar.sync 0, 512;" ::: "memory");
  if (FIRST + k < NSLOT) load_step(sb, tmx, gm, third, FIRST + k, (FIRST + k + off) & 7, true);
#pragma unroll 1
  for (int it = NSLOT + k; it < nit + NSLOT; it += 4) {
    const int u = it + off;
    const uint32_t ro = lds32(sb + CTAB + (it - NSLOT) * 16 + 8);
    mbar_wait(full + 64 + (u & 7) * 8, ((u >> 3) & 1) ^ 1);
    red_add_elect((uint32_t*)((char*)gs + ro));
    if (it < nit) load_step(sb, tmx, gm, third, it, u & 7);
    else if (it == nit) mbar_arrive_elect(full);
    if (it >= nit - 16) {
      const bool pre = it < nit - 12 && cidx < 24;
      if (pre || it == nit - 1) {
        wait_value(gs->wflag, 12 * lds32(sb + MISC + 256), 32);
        asm volatile("fence.acquire.gpu;\nfence.proxy.async.global;" ::: "memory");
      }
      if (pre) asm volatile("{.reg .pred p; elect.sync _|p, 0xffffffff; @p cp.async.bulk.prefetch.L2.global [%0], 1536;}" ::"l"(gs->wimg + (cidx * 4 + k) * 1536) : "memory");
      const int m = it == nit - 1 ? 0 : W2S;
      if (it == nit - 1 || it == nit + 3) bulk_load<73728>(sb + m, gs->wimg + m, sb + WBAR);
    }
  }
}

__device__ __forceinline__ void conv_credit(uint32_t sb, Globals* gs, int q0, int nit, int off, uint32_t ctarget, int k) {
  const uint32_t full = sb + CM;
#pragma unroll 1
  for (int it = k + NSLOT; it <= nit; it += 4) {
    const int u = it + off, q = (int)lds32(sb + CTAB + it * 16 + 12) - RING;
    mbar_wait(full + 64 + (u & 7) * 8, ((u >> 3) & 1) ^ 1);
    if (q >= q0) wait_value(&gs->cons[q], ctarget, 200);
    mbar_arrive_elect(full + (u & 7) * 8);
  }
}

__device__ __noinline__ int generic_role() {
  const int cidx = (blockIdx.x * NCONV) / gridDim.x;
  return cidx | ((((blockIdx.x + 1) * NCONV) / gridDim.x != cidx) << 16);
}

__global__ void __launch_bounds__(512, 1) convnext_kernel(const __nv_bfloat16* __restrict__ dw, const __nv_bfloat16* __restrict__ w1, const __nv_bfloat16* __restrict__ w2,
                                                          __nv_bfloat16* __restrict__ out, Globals* gs, int want_sms,
                                                          const __grid_constant__ CUtensorMap tmx, const __grid_constant__ CUtensorMap tmr) {
  extern __shared__ __align__(1024) unsigned char smem[];
  const uint32_t sb = smem_u32(smem);
  const int warp = __shfl_sync(0xffffffffu, threadIdx.x >> 5, 0), lane = threadIdx.x & 31;
  uint32_t smid, nsmid;
  asm volatile("mov.u32 %0, %%smid;" : "=r"(smid));
  asm volatile("mov.u32 %0, %%nsmid;" : "=r"(nsmid));
  const bool tabled = TABLED && (int)nsmid == want_sms;
  const int id = tabled ? smid : blockIdx.x;
  int cidx, idx, is_conv;
  if (tabled) {
    idx = smid;
    const int k = (smid - 60) / 14, r = smid - 60 - 14 * k;
    is_conv = smid < 48 ? LT || !(smid & 1) : (smid >= 60 && smid <= 90 && (r & ~(2 * SCHED_NMID - 2)) == 0);
    cidx = smid < 48 ? (((smid >> 1) & 7) + (smid & 1) * NP) * 3 + (smid >> 4) : 24 + (r >> 1) * 3 + k;
  } else {
    const int r = generic_role();
    cidx = r & 0xffff; is_conv = r >> 16;
    idx = blockIdx.x - cidx;
  }
  const int gm = cidx / 3, third = cidx - gm * 3;
  const int q0 = gm * PLEN, nit = gm < 8 ? PLEN + 2 : gm < NP ? NSEG * (LM + 3) : LT + 3, off = (8 - nit) & 7;
  if (is_conv && warp == 8) {
    bulk_load<9408, true>(sb, dw, sb + WBAR + 8);
    asm volatile("bar.arrive 5, 288;" ::: "memory");
#pragma unroll 1
    for (int it = 0; it < NSLOT; it++) {
      const int s = (it + off) & 7;
      ring_bar_init(sb + CM + s * 8, 2, s < off);
      if (it < FIRST) load_step(sb, &tmx, gm, third, it, s, true);
    }
  }
  if (warp == 15) asm volatile("prefetch.tensormap [%0];" ::"l"(&tmr) : "memory");
  mbar_init_elect(sb + MISC + warp * 8, 1); mbar_init_elect(sb + MISC + 128 + warp * 8, 1);
  asm volatile("fence.mbarrier_init.release.cluster;" ::: "memory");
  if (is_conv) {
    if (warp >= 8) ring_bar_init(sb + CM + warp * 8, 8, warp - 8 < off);
    if (warp == 9) mbar_init_elect(sb + WBAR, 2);
    const uint32_t lastph = (((nit + off) >> 3) & 1) ^ 1;
    if (warp < 8) {
      conv_compute(sb, gs, third, nit, off, gm < 8 && (gm & 1), warp, lane);
      asm volatile("setmaxnreg.dec.sync.aligned.u32 128;");
    } else if (warp >= 12) {
      asm volatile("setmaxnreg.dec.sync.aligned.u32 24;");
      const uint32_t epoch = ld_relaxed(&gs->epoch[id]);
#pragma unroll 1
      for (int it = threadIdx.x - 384; it <= nit; it += 128) {
        const int seg = it / (LM + 3), j = gm < 8 ? it - 2 : it - 3 * (seg + 1);
        const bool ok = it < nit && j >= (gm < 8 ? 0 : seg * LM);
        sts128(sb + CTAB + it * 16, make_uint4((ok ? (j % RING) * NG + gm : -1) * (4 * TILEB), slot_tag(gm, max(j, 0), epoch),
                                               offsetof(Globals, ready) + (ok ? q0 + j : NG * PLEN) * 4, ok ? q0 + j : -1));
      }
      if (threadIdx.x == 384) sts32(sb + MISC + 256, epoch + 1);
      asm volatile("bar.sync 0, 512;" ::: "memory");
      mbar_arrive_elect(sb + CM + ((((warp + 2) & 3) + off) & 7) * 8);
      mbar_arrive_elect(sb + CM + ((((warp + 2) & 3) + off + 4) & 7) * 8);
      build_tile_list(sb, threadIdx.x - 384, idx, tabled, true, epoch);
      if (threadIdx.x == 384) gs->epoch[id] = epoch + 1;
      asm volatile("bar.sync 6, 128;" ::: "memory");
      conv_credit(sb, gs, q0, nit, off, 16 * (epoch + 1), (warp + 2) & 3);
#pragma unroll 1
      for (int i = 0; i < 4; i++) {
        const uint2 e = lds64(sb + MISC + 512 + i * 16);
        mbar_wait(sb + CM + 64 + (4 + min(i, 2)) * 8, lastph);
        const int wi = 4 * i + (warp & 3);
        if ((int)e.x >= 0) bulk_load<3072>(sb + ABUF + wi * 3072, gs->scratch + (e.y & ~1u) + (warp & 3) * 3072, sb + MISC + wi * 8);
      }
      mbar_wait(sb + CM + 64 + 7 * 8, lastph);
      asm volatile("setmaxnreg.inc.sync.aligned.u32 128;");
    } else {
      asm volatile("setmaxnreg.dec.sync.aligned.u32 %0;" ::"n"(488 - 2 * CREGS));
      conv_loader(sb, gs, &tmx, gm, nit, off, cidx, third, warp & 3);
      mbar_wait(sb + CM + 64 + 7 * 8, lastph);
      asm volatile("setmaxnreg.inc.sync.aligned.u32 128;");
    }
    mbar_wait(sb + WBAR, 0);
    asm volatile("bar.sync 0, 512;" ::: "memory");
  } else {
    mlp_setup(sb, gs, id, w1, w2, idx, tabled, warp, lane);
  }
  mlp_role(sb, gs, &tmr, out);
}

typedef CUresult (*PFN_encodeTiled)(CUtensorMap*, CUtensorMapDataType, cuuint32_t, void*, const cuuint64_t*, const cuuint64_t*, const cuuint32_t*, const cuuint32_t*,
                                    CUtensorMapInterleave, CUtensorMapSwizzle, CUtensorMapL2promotion, CUtensorMapFloatOOBfill);

extern "C" void kernel_launch(void* const* d_in, const int* in_sizes, int n_in, void* d_out, int out_size) {
  const __nv_bfloat16* x = (const __nv_bfloat16*)d_in[0];
  const __nv_bfloat16* dw = (const __nv_bfloat16*)d_in[1];
  const __nv_bfloat16* w1 = (const __nv_bfloat16*)d_in[2];
  const __nv_bfloat16* w2 = (const __nv_bfloat16*)d_in[3];
  static PFN_encodeTiled encode = nullptr;
  static int nsm = 0;
  static Globals* gs = nullptr;
  if (!encode) {
    void* fn = nullptr; cudaDriverEntryPointQueryResult qr;
    cudaGetDriverEntryPoint("cuTensorMapEncodeTiled", &fn, cudaEnableDefault, &qr);
    encode = (PFN_encodeTiled)fn;
    cudaGetSymbolAddress((void**)&gs, g_state);
    int dev = 0; cudaGetDevice(&dev);
    cudaDeviceGetAttribute(&nsm, cudaDevAttrMultiProcessorCount, dev);
    cudaFuncSetAttribute(convnext_kernel, cudaFuncAttributeMaxDynamicSharedMemorySize, SMEM_BYTES);
  }
  CUtensorMap tm, tr;
  cuuint64_t dims[3] = {96, 512, 512}, strides[2] = {192, 192 * 512};
  cuuint32_t box[3] = {32, 70, 2}, es[3] = {1, 1, 1};
  encode(&tm, CU_TENSOR_MAP_DATA_TYPE_BFLOAT16, 3, (void*)x, dims, strides, box, es, CU_TENSOR_MAP_INTERLEAVE_NONE, CU_TENSOR_MAP_SWIZZLE_64B,
         CU_TENSOR_MAP_L2_PROMOTION_L2_128B, CU_TENSOR_MAP_FLOAT_OOB_FILL_NONE);
  cuuint64_t dims2[3] = {1536, 32, 512}, strides2[2] = {3072, 192 * 512};
  cuuint32_t box2[3] = {192, 4, 2};
  encode(&tr, CU_TENSOR_MAP_DATA_TYPE_BFLOAT16, 3, (void*)x, dims2, strides2, box2, es, CU_TENSOR_MAP_INTERLEAVE_NONE, CU_TENSOR_MAP_SWIZZLE_NONE,
         CU_TENSOR_MAP_L2_PROMOTION_NONE, CU_TENSOR_MAP_FLOAT_OOB_FILL_NONE);
  convnext_kernel<<<nsm, 512, SMEM_BYTES>>>(dw, w1, w2, (__nv_bfloat16*)d_out, gs, nsm == 132 ? 132 : -1, tm, tr);
}
```

```cpp
#include <cuda_runtime.h>
#include <cuda_bf16.h>
#include <cuda.h>
#include <stdint.h>
#include <stddef.h>

template<int SCALE_D> __device__ __forceinline__ void wgmma_n64_f16(uint32_t* d, const uint32_t* a, uint64_t desc) {
  if (SCALE_D == 0) asm volatile("wgmma.mma_async.sync.aligned.m64n64k16.f16.f16.f16 {%0,%1,%2,%3,%4,%5,%6,%7,%8,%9,%10,%11,%12,%13,%14,%15}, {%16,%17,%18,%19}, %20, 0, 1, 1, 1;"
    : "=r"(d[0]),"=r"(d[1]),"=r"(d[2]),"=r"(d[3]),"=r"(d[4]),"=r"(d[5]),"=r"(d[6]),"=r"(d[7]),"=r"(d[8]),"=r"(d[9]),"=r"(d[10]),"=r"(d[11]),"=r"(d[12]),"=r"(d[13]),"=r"(d[14]),"=r"(d[15])
    : "r"(a[0]),"r"(a[1]),"r"(a[2]),"r"(a[3]),"l"(desc));
  if (SCALE_D == 1) asm volatile("wgmma.mma_async.sync.aligned.m64n64k16.f16.f16.f16 {%0,%1,%2,%3,%4,%5,%6,%7,%8,%9,%10,%11,%12,%13,%14,%15}, {%16,%17,%18,%19}, %20, 1, 1, 1, 1;"
    : "+r"(d[0]),"+r"(d[1]),"+r"(d[2]),"+r"(d[3]),"+r"(d[4]),"+r"(d[5]),"+r"(d[6]),"+r"(d[7]),"+r"(d[8]),"+r"(d[9]),"+r"(d[10]),"+r"(d[11]),"+r"(d[12]),"+r"(d[13]),"+r"(d[14]),"+r"(d[15])
    : "r"(a[0]),"r"(a[1]),"r"(a[2]),"r"(a[3]),"l"(desc));
}

template<int SCALE_D> __device__ __forceinline__ void wgmma_n96_f16(uint32_t* d, const uint32_t* a, uint64_t desc) {
  if (SCALE_D == 0) asm volatile("wgmma.mma_async.sync.aligned.m64n96k16.f16.f16.f16 {%0,%1,%2,%3,%4,%5,%6,%7,%8,%9,%10,%11,%12,%13,%14,%15,%16,%17,%18,%19,%20,%21,%22,%23}, {%24,%25,%26,%27}, %28, 0, 1, 1, 1;"
    : "=r"(d[0]),"=r"(d[1]),"=r"(d[2]),"=r"(d[3]),"=r"(d[4]),"=r"(d[5]),"=r"(d[6]),"=r"(d[7]),"=r"(d[8]),"=r"(d[9]),"=r"(d[10]),"=r"(d[11]),"=r"(d[12]),"=r"(d[13]),"=r"(d[14]),"=r"(d[15]),"=r"(d[16]),"=r"(d[17]),"=r"(d[18]),"=r"(d[19]),"=r"(d[20]),"=r"(d[21]),"=r"(d[22]),"=r"(d[23])
    : "r"(a[0]),"r"(a[1]),"r"(a[2]),"r"(a[3]),"l"(desc));
  if (SCALE_D == 1) asm volatile("wgmma.mma_async.sync.aligned.m64n96k16.f16.f16.f16 {%0,%1,%2,%3,%4,%5,%6,%7,%8,%9,%10,%11,%12,%13,%14,%15,%16,%17,%18,%19,%20,%21,%22,%23}, {%24,%25,%26,%27}, %28, 1, 1, 1, 1;"
    : "+r"(d[0]),"+r"(d[1]),"+r"(d[2]),"+r"(d[3]),"+r"(d[4]),"+r"(d[5]),"+r"(d[6]),"+r"(d[7]),"+r"(d[8]),"+r"(d[9]),"+r"(d[10]),"+r"(d[11]),"+r"(d[12]),"+r"(d[13]),"+r"(d[14]),"+r"(d[15]),"+r"(d[16]),"+r"(d[17]),"+r"(d[18]),"+r"(d[19]),"+r"(d[20]),"+r"(d[21]),"+r"(d[22]),"+r"(d[23])
    : "r"(a[0]),"r"(a[1]),"r"(a[2]),"r"(a[3]),"l"(desc));
}

#define SCHED_NMID 1
#define SCHED_LE 106
#define SCHED_LT 10
#define SCHED_RING 16
__device__ const uint16_t g_sched[132][48] = {
{388,391,394,65535,65535,65535,65535,65535,65535,65535,65535,65535,65535,65535,65535,65535,65535,65535,65535,65535,65535,65535,65535,65535,65535,65535,65535,65535,65535,65535,65535,65535,65535,65535,65535,65535,65535,65535,65535,65535,65535,65535,65535,65535,65535,65535,65535,65535},
{3824,3827,3830,3833,3854,53,65,77,88,100,113,125,136,148,160,171,183,195,206,219,231,243,254,266,278,289,301,313,325,337,349,361,372,384,404,416,65535,65535,65535,65535,65535,65535,65535,65535,65535,65535,65535,65535},
{812,815,818,65535,65535,65535,65535,65535,65535,65535,65535,65535,65535,65535,65535,65535,65535,65535,65535,65535,65535,65535,65535,65535,65535,65535,65535,65535,65535,65535,65535,65535,65535,65535,65535,65535,65535,65535,65535,65535,65535,65535,65535,65535,65535,65535,65535,65535},
{4248,4251,4254,4257,4279,478,490,502,513,525,538,550,561,573,585,596,608,620,631,644,656,668,679,691,703,714,726,738,750,762,774,786,797,809,830,841,65535,65535,65535,65535,65535,65535,65535,65535,65535,65535,65535,65535},
{1236,1239,1242,65535,65535,65535,65535,65535,65535,65535,65535,65535,65535,65535,65535,65535,65535,65535,65535,65535,65535,65535,65535,65535,65535,65535,65535,65535,65535,65535,65535,65535,65535,65535,65535,65535,65535,65535,65535,65535,65535,65535,65535,65535,65535,65535,65535,65535},
{4672,4675,4678,4681,891,902,914,925,937,949,962,973,985,997,1008,1020,1032,1043,1055,1068,1080,1091,1103,1115,1126,1138,1150,1161,1174,1186,1198,1209,1221,1233,1253,1265,65535,65535,65535,65535,65535,65535,65535,65535,65535,65535,65535,65535},
{1660,1663,1666,65535,65535,65535,65535,65535,65535,65535,65535,65535,65535,65535,65535,65535,65535,65535,65535,65535,65535,65535,65535,65535,65535,65535,65535,65535,65535,65535,65535,65535,65535,65535,65535,65535,65535,65535,65535,65535,65535,65535,65535,65535,65535,65535,65535,65535},
{5096,5099,5102,5105,1315,1325,1337,1348,1360,1372,1385,1396,1408,1420,1431,1443,1455,1466,1478,1491,1503,1514,1526,1538,1549,1561,1573,1584,1597,1609,1621,1632,1644,1656,1677,1688,65535,65535,65535,65535,65535,65535,65535,65535,65535,65535,65535,65535},
{2084,2087,2090,65535,65535,65535,65535,65535,65535,65535,65535,65535,65535,65535,65535,65535,65535,65535,65535,65535,65535,65535,65535,65535,65535,65535,65535,65535,65535,65535,65535,65535,65535,65535,65535,65535,65535,65535,65535,65535,65535,65535,65535,65535,65535,65535,65535,65535},
{5520,5523,5526,5529,1739,1750,1761,1773,1784,1796,1809,1821,1832,1844,1856,1867,1879,1891,1902,1915,1927,1939,1950,1962,1974,1985,1997,2009,2021,2034,2045,2057,2068,2080,2101,2113,65535,65535,65535,65535,65535,65535,65535,65535,65535,65535,65535,65535},
{2508,2511,2514,65535,65535,65535,65535,65535,65535,65535,65535,65535,65535,65535,65535,65535,65535,65535,65535,65535,65535,65535,65535,65535,65535,65535,65535,65535,65535,65535,65535,65535,65535,65535,65535,65535,65535,65535,65535,65535,65535,65535,65535,65535,65535,65535,65535,65535},
{5944,5947,5950,5953,2163,2174,2185,2197,2209,2220,2233,2245,2257,2268,2280,2292,2303,2315,2327,2339,2351,2363,2375,2386,2398,2410,2421,2433,2445,2458,2469,2481,2493,2504,2525,2537,65535,65535,65535,65535,65535,65535,65535,65535,65535,65535,65535,65535},
{2932,2935,2938,65535,65535,65535,65535,65535,65535,65535,65535,65535,65535,65535,65535,65535,65535,65535,65535,65535,65535,65535,65535,65535,65535,65535,65535,65535,65535,65535,65535,65535,65535,65535,65535,65535,65535,65535,65535,65535,65535,65535,65535,65535,65535,65535,65535,65535},
{6368,6371,6374,6377,3430,3441,2609,2621,2633,2644,2657,2669,2681,2692,2704,2716,2727,2739,2751,3584,2775,2787,2799,2810,2822,2834,2845,2857,2871,3689,2893,2905,2917,2928,2949,3768,65535,65535,65535,65535,65535,65535,65535,65535,65535,65535,65535,65535},
{3356,3359,3362,65535,65535,65535,65535,65535,65535,65535,65535,65535,65535,65535,65535,65535,65535,65535,65535,65535,65535,65535,65535,65535,65535,65535,65535,65535,65535,65535,65535,65535,65535,65535,65535,65535,65535,65535,65535,65535,65535,65535,65535,65535,65535,65535,65535,65535},
{6792,6795,6798,6801,6398,3023,3453,3046,3058,3070,3489,3094,3106,3524,3129,3141,3559,3164,3176,3189,3595,3212,3224,3630,3247,3259,3665,3282,3296,3307,3701,3330,3342,3736,3374,3386,65535,65535,65535,65535,65535,65535,65535,65535,65535,65535,65535,65535},
{389,392,395,65535,65535,65535,65535,65535,65535,65535,65535,65535,65535,65535,65535,65535,65535,65535,65535,65535,65535,65535,65535,65535,65535,65535,65535,65535,65535,65535,65535,65535,65535,65535,65535,65535,65535,65535,65535,65535,65535,65535,65535,65535,65535,65535,65535,65535},
{3825,3828,3831,3834,43,54,66,78,89,101,114,126,137,149,161,172,184,196,207,220,232,244,255,267,279,290,302,314,326,338,350,362,373,385,405,417,65535,65535,65535,65535,65535,65535,65535,65535,65535,65535,65535,65535},
{813,816,819,65535,65535,65535,65535,65535,65535,65535,65535,65535,65535,65535,65535,65535,65535,65535,65535,65535,65535,65535,65535,65535,65535,65535,65535,65535,65535,65535,65535,65535,65535,65535,65535,65535,65535,65535,65535,65535,65535,65535,65535,65535,65535,65535,65535,65535},
{4249,4252,4255,4258,468,479,491,3465,514,526,539,3501,562,574,3536,597,609,3571,632,645,657,3607,680,692,3642,715,727,3677,751,763,775,3713,798,810,3757,842,65535,65535,65535,65535,65535,65535,65535,65535,65535,65535,65535,65535},
{1237,1240,1243,65535,65535,65535,65535,65535,65535,65535,65535,65535,65535,65535,65535,65535,65535,65535,65535,65535,65535,65535,65535,65535,65535,65535,65535,65535,65535,65535,65535,65535,65535,65535,65535,65535,65535,65535,65535,65535,65535,65535,65535,65535,65535,65535,65535,65535},
{4673,4676,4679,4682,4703,903,915,926,938,950,963,974,986,998,1009,1021,1033,1044,1056,1069,1081,1092,1104,1116,1127,1139,1151,1162,1175,1187,1199,1210,1222,1234,1254,1266,65535,65535,65535,65535,65535,65535,65535,65535,65535,65535,65535,65535},
{1661,1664,1667,65535,65535,65535,65535,65535,65535,65535,65535,65535,65535,65535,65535,65535,65535,65535,65535,65535,65535,65535,65535,65535,65535,65535,65535,65535,65535,65535,65535,65535,65535,65535,65535,65535,65535,65535,65535,65535,65535,65535,65535,65535,65535,65535,65535,65535},
{5097,5100,5103,5106,5127,1326,1338,1349,1361,1373,1386,1397,1409,1421,1432,1444,1456,1467,1479,1492,1504,1515,1527,1539,1550,1562,1574,1585,1598,1610,1622,1633,1645,1657,1678,1689,65535,65535,65535,65535,65535,65535,65535,65535,65535,65535,65535,65535},
{2085,2088,2091,65535,65535,65535,65535,65535,65535,65535,65535,65535,65535,65535,65535,65535,65535,65535,65535,65535,65535,65535,65535,65535,65535,65535,65535,65535,65535,65535,65535,65535,65535,65535,65535,65535,65535,65535,65535,65535,65535,65535,65535,65535,65535,65535,65535,65535},
{5521,5524,5527,5530,5551,1751,1762,1774,1785,1797,1810,1822,1833,1845,1857,1868,1880,1892,1903,1916,1928,1940,1951,1963,1975,1986,1998,2010,2022,2035,2046,2058,2069,2081,2102,2114,65535,65535,65535,65535,65535,65535,65535,65535,65535,65535,65535,65535},
{2509,2512,2515,65535,65535,65535,65535,65535,65535,65535,65535,65535,65535,65535,65535,65535,65535,65535,65535,65535,65535,65535,65535,65535,65535,65535,65535,65535,65535,65535,65535,65535,65535,65535,65535,65535,65535,65535,65535,65535,65535,65535,65535,65535,65535,65535,65535,65535},
{5945,5948,5951,5954,5975,2175,2186,2198,2210,2221,2234,2246,2258,2269,2281,2293,2304,2316,2328,2340,2352,2364,2376,2387,2399,2411,2422,2434,2446,2459,2470,2482,2494,2505,2526,2538,65535,65535,65535,65535,65535,65535,65535,65535,65535,65535,65535,65535},
{2933,2936,2939,65535,65535,65535,65535,65535,65535,65535,65535,65535,65535,65535,65535,65535,65535,65535,65535,65535,65535,65535,65535,65535,65535,65535,65535,65535,65535,65535,65535,65535,65535,65535,65535,65535,65535,65535,65535,65535,65535,65535,65535,65535,65535,65535,65535,65535},
{6369,6372,6375,6378,2587,2598,2610,2622,3477,2645,2658,2670,3513,2693,2705,3548,2728,2740,3583,2765,2776,2788,3619,2811,2823,3654,2846,2858,2872,2882,2894,2906,3725,2929,2950,2961,65535,65535,65535,65535,65535,65535,65535,65535,65535,65535,65535,65535},
{3357,3360,3363,65535,65535,65535,65535,65535,65535,65535,65535,65535,65535,65535,65535,65535,65535,65535,65535,65535,65535,65535,65535,65535,65535,65535,65535,65535,65535,65535,65535,65535,65535,65535,65535,65535,65535,65535,65535,65535,65535,65535,65535,65535,65535,65535,65535,65535},
{6793,6796,6799,6802,3012,3442,3035,3047,3059,3071,3083,3095,3107,3118,3130,3142,3153,3165,3177,3190,3201,3213,3225,3236,3248,3260,3271,3283,3297,3690,3319,3331,3343,3354,3375,3769,65535,65535,65535,65535,65535,65535,65535,65535,65535,65535,65535,65535},
{390,393,396,65535,65535,65535,65535,65535,65535,65535,65535,65535,65535,65535,65535,65535,65535,65535,65535,65535,65535,65535,65535,65535,65535,65535,65535,65535,65535,65535,65535,65535,65535,65535,65535,65535,65535,65535,65535,65535,65535,65535,65535,65535,65535,65535,65535,65535},
{3826,3829,3832,3835,3855,55,67,79,90,102,115,127,138,150,162,173,185,197,208,221,233,245,256,268,280,291,303,315,327,339,351,363,374,386,406,418,65535,65535,65535,65535,65535,65535,65535,65535,65535,65535,65535,65535},
{814,817,820,65535,65535,65535,65535,65535,65535,65535,65535,65535,65535,65535,65535,65535,65535,65535,65535,65535,65535,65535,65535,65535,65535,65535,65535,65535,65535,65535,65535,65535,65535,65535,65535,65535,65535,65535,65535,65535,65535,65535,65535,65535,65535,65535,65535,65535},
{4250,4253,4256,4259,3431,480,3454,503,515,527,3490,551,563,3525,586,598,3560,621,633,646,3596,669,681,3631,704,716,3666,739,752,764,3702,787,799,3737,831,843,65535,65535,65535,65535,65535,65535,65535,65535,65535,65535,65535,65535},
{1238,1241,1244,65535,65535,65535,65535,65535,65535,65535,65535,65535,65535,65535,65535,65535,65535,65535,65535,65535,65535,65535,65535,65535,65535,65535,65535,65535,65535,65535,65535,65535,65535,65535,65535,65535,65535,65535,65535,65535,65535,65535,65535,65535,65535,65535,65535,65535},
{4674,4677,4680,4683,892,904,916,927,939,951,964,975,987,999,1010,1022,1034,1045,1057,1070,1082,1093,1105,1117,1128,1140,1152,1163,1176,1188,1200,1211,1223,1235,1255,1267,65535,65535,65535,65535,65535,65535,65535,65535,65535,65535,65535,65535},
{1662,1665,1668,65535,65535,65535,65535,65535,65535,65535,65535,65535,65535,65535,65535,65535,65535,65535,65535,65535,65535,65535,65535,65535,65535,65535,65535,65535,65535,65535,65535,65535,65535,65535,65535,65535,65535,65535,65535,65535,65535,65535,65535,65535,65535,65535,65535,65535},
{5098,5101,5104,5107,1316,1327,1339,1350,1362,1374,1387,1398,1410,1422,1433,1445,1457,1468,1480,1493,1505,1516,1528,1540,1551,1563,1575,1586,1599,1611,1623,1634,1646,1658,1679,1690,65535,65535,65535,65535,65535,65535,65535,65535,65535,65535,65535,65535},
{2086,2089,2092,65535,65535,65535,65535,65535,65535,65535,65535,65535,65535,65535,65535,65535,65535,65535,65535,65535,65535,65535,65535,65535,65535,65535,65535,65535,65535,65535,65535,65535,65535,65535,65535,65535,65535,65535,65535,65535,65535,65535,65535,65535,65535,65535,65535,65535},
{5522,5525,5528,5531,1740,1752,1763,1775,1786,1798,1811,1823,1834,1846,1858,1869,1881,1893,1904,1917,1929,1941,1952,1964,1976,1987,1999,2011,2023,2036,2047,2059,2070,2082,2103,2115,65535,65535,65535,65535,65535,65535,65535,65535,65535,65535,65535,65535},
{2510,2513,2516,65535,65535,65535,65535,65535,65535,65535,65535,65535,65535,65535,65535,65535,65535,65535,65535,65535,65535,65535,65535,65535,65535,65535,65535,65535,65535,65535,65535,65535,65535,65535,65535,65535,65535,65535,65535,65535,65535,65535,65535,65535,65535,65535,65535,65535},
{5946,5949,5952,5955,2164,2176,2187,2199,2211,2222,2235,2247,2259,2270,2282,2294,2305,2317,2329,2341,2353,2365,2377,2388,2400,2412,2423,2435,2447,2460,2471,2483,2495,2506,2527,2539,65535,65535,65535,65535,65535,65535,65535,65535,65535,65535,65535,65535},
{2934,2937,2940,65535,65535,65535,65535,65535,65535,65535,65535,65535,65535,65535,65535,65535,65535,65535,65535,65535,65535,65535,65535,65535,65535,65535,65535,65535,65535,65535,65535,65535,65535,65535,65535,65535,65535,65535,65535,65535,65535,65535,65535,65535,65535,65535,65535,65535},
{6370,6373,6376,6379,6399,2599,2611,3466,2634,2646,2659,3502,2682,2694,3537,2717,2729,3572,2752,3585,2777,3608,2800,2812,3643,2835,2847,3678,3680,2883,2895,3714,2918,2930,3758,2962,65535,65535,65535,65535,65535,65535,65535,65535,65535,65535,65535,65535},
{3358,3361,3364,65535,65535,65535,65535,65535,65535,65535,65535,65535,65535,65535,65535,65535,65535,65535,65535,65535,65535,65535,65535,65535,65535,65535,65535,65535,65535,65535,65535,65535,65535,65535,65535,65535,65535,65535,65535,65535,65535,65535,65535,65535,65535,65535,65535,65535},
{6794,6797,6800,6803,3013,3024,3036,3048,3478,3072,3084,3096,3514,3119,3131,3549,3154,3166,3178,3191,3202,3214,3620,3237,3249,3655,3272,3284,3298,3308,3320,3332,3726,3355,3376,3387,65535,65535,65535,65535,65535,65535,65535,65535,65535,65535,65535,65535},
{0,3394,3399,2565,3414,3844,3849,6396,2595,908,76,2630,943,532,124,2678,991,159,2713,1026,194,2748,1062,1074,242,2796,1109,277,2831,1144,312,1168,2879,1192,360,2914,1227,2946,2958,65535,65535,65535,65535,65535,65535,65535,65535,65535},
{1,6362,6367,3409,6382,3419,3424,42,3439,2607,496,3474,2642,956,544,3510,2690,579,3545,2725,614,3580,2761,2773,662,3616,2808,697,3651,2843,732,2867,3687,2891,780,3722,2926,3754,3766,65535,65535,65535,65535,65535,65535,65535,65535,65535},
{424,430,435,443,4262,455,460,465,473,485,497,508,520,533,545,556,568,580,591,603,615,626,639,651,663,674,686,698,709,721,733,745,757,769,781,792,804,825,836,65535,65535,65535,65535,65535,65535,65535,65535,65535},
{425,4242,4247,444,451,4267,4272,4277,474,486,498,509,521,534,546,557,569,581,592,604,616,627,640,652,664,675,687,699,710,722,734,746,758,770,782,793,805,826,837,65535,65535,65535,65535,65535,65535,65535,65535,65535},
{848,4666,859,867,4686,879,4695,4700,897,909,920,932,944,957,968,980,992,1003,1015,1027,1038,1050,1063,1075,1086,1098,1110,1121,1133,1145,1156,1169,1181,1193,1204,1216,1228,1248,1260,65535,65535,65535,65535,65535,65535,65535,65535,65535},
{849,855,4671,868,875,4691,884,889,898,910,921,933,945,958,969,981,993,1004,1016,1028,1039,1051,1064,1076,1087,1099,1111,1122,1134,1146,1157,1170,1182,1194,1205,1217,1229,1249,1261,65535,65535,65535,65535,65535,65535,65535,65535,65535},
{1272,1279,5095,1291,5110,1303,1308,1313,1321,1333,1344,1356,1368,1381,1392,1404,1416,1427,1439,1451,1462,1474,1487,1499,1510,1522,1534,1545,1557,1569,1580,1593,1605,1617,1628,1640,1652,1673,1684,65535,65535,65535,65535,65535,65535,65535,65535,65535},
{1273,5091,1284,1292,1299,5115,5120,5125,1322,1334,1345,1357,1369,1382,1393,1405,1417,1428,1440,1452,1463,1475,1488,1500,1511,1523,1535,1546,1558,1570,1581,1594,1606,1618,1629,1641,1653,1674,1685,65535,65535,65535,65535,65535,65535,65535,65535,65535},
{1696,1703,1708,1716,1723,1728,1732,1737,1746,1757,1769,1780,1792,1805,1817,1828,1840,1852,1863,1875,1887,1898,1911,1923,1935,1946,1958,1970,1981,1993,2005,2017,2030,2041,2053,2064,2076,2097,2109,65535,65535,65535,65535,65535,65535,65535,65535,65535},
{1697,5515,1709,1717,5535,5540,5544,5549,1747,1758,1770,1781,1793,1806,1818,1829,1841,1853,1864,1876,1888,1899,1912,1924,1936,1947,1959,1971,1982,1994,2006,2018,2031,2042,2054,2065,2077,2098,2110,65535,65535,65535,65535,65535,65535,65535,65535,65535},
{2120,2127,2132,2140,2147,2152,5968,2161,2170,2181,2193,2205,2216,2229,2241,2253,2264,2276,2288,2299,2311,2323,2335,2347,2359,2371,2382,2394,2406,2417,2429,2441,2454,2465,2477,2489,2500,2521,2533,65535,65535,65535,65535,65535,65535,65535,65535,65535},
{2121,5939,2133,2141,5959,5964,2157,5973,2171,2182,2194,2206,2217,2230,2242,2254,2265,2277,2289,2300,2312,2324,2336,2348,2360,2372,2383,2395,2407,2418,2430,2442,2455,2466,2478,2490,2501,2522,2534,65535,65535,65535,65535,65535,65535,65535,65535,65535},
{3740,3743,3746,65535,65535,65535,65535,65535,65535,65535,65535,65535,65535,65535,65535,65535,65535,65535,65535,65535,65535,65535,65535,65535,65535,65535,65535,65535,65535,65535,65535,65535,65535,65535,65535,65535,65535,65535,65535,65535,65535,65535,65535,65535,65535,65535,65535,65535},
{2544,2551,2556,2566,2571,6387,6392,2585,2596,3451,2619,2631,3486,2655,2667,2679,3522,2702,2714,3557,2737,2749,2762,3593,2785,2797,3628,2820,2832,3663,2855,2868,2880,3699,2903,2915,3734,2947,2959,65535,65535,65535,65535,65535,65535,65535,65535,65535},
{2968,6787,2980,2989,2995,3000,3005,3010,3018,3030,3042,3054,3065,3078,3090,3102,3113,3125,3137,3148,3160,3172,3184,3196,3208,3220,3231,3243,3255,3266,3278,3291,3302,3314,3326,3338,3349,3370,3381,65535,65535,65535,65535,65535,65535,65535,65535,65535},
{2969,2976,2981,2990,6807,6812,6817,6822,3019,3031,3043,3055,3066,3079,3091,3103,3114,3126,3138,3149,3161,3173,3185,3197,3209,3221,3232,3244,3256,3267,3279,3292,3303,3315,3327,3339,3350,3371,3382,65535,65535,65535,65535,65535,65535,65535,65535,65535},
{426,431,436,445,4263,456,461,466,475,487,499,510,522,535,547,558,570,582,593,605,617,628,641,653,665,676,688,700,711,723,735,747,759,771,783,794,806,827,838,65535,65535,65535,65535,65535,65535,65535,65535,65535},
{2545,4243,437,446,452,4268,4273,4278,476,488,500,511,523,536,548,559,571,583,594,606,618,629,642,654,666,677,689,701,712,724,736,748,760,772,784,795,807,828,839,65535,65535,65535,65535,65535,65535,65535,65535,65535},
{850,4667,860,869,4687,880,4696,4701,899,911,922,934,946,959,970,982,994,1005,1017,1029,1040,1052,1065,1077,1088,1100,1112,1123,1135,1147,1158,1171,1183,1195,1206,1218,1230,1250,1262,65535,65535,65535,65535,65535,65535,65535,65535,65535},
{851,856,861,870,876,4692,885,890,900,912,923,935,947,960,971,983,995,1006,1018,1030,1041,1053,1066,1078,1089,1101,1113,1124,1136,1148,1159,1172,1184,1196,1207,1219,1231,1251,1263,65535,65535,65535,65535,65535,65535,65535,65535,65535},
{1274,1280,1285,1293,5111,1304,1309,1314,1323,1335,1346,1358,1370,1383,1394,1406,1418,1429,1441,1453,1464,1476,1489,1501,1512,1524,1536,1547,1559,1571,1582,1595,1607,1619,1630,1642,1654,1675,1686,65535,65535,65535,65535,65535,65535,65535,65535,65535},
{1275,5092,3400,1294,1300,5116,5121,5126,1324,1336,1347,1359,1371,1384,1395,1407,1419,1430,1442,1454,1465,1477,1490,1502,1513,1525,1537,1548,1560,1572,1583,1596,1608,1620,1631,1643,1655,1676,1687,65535,65535,65535,65535,65535,65535,65535,65535,65535},
{1698,1704,1710,1718,1724,1729,1733,1738,1748,1759,1771,1782,1794,1807,1819,1830,1842,1854,1865,1877,1889,1900,1913,1925,1937,1948,1960,1972,1983,1995,2007,2019,2032,2043,2055,2066,2078,2099,2111,65535,65535,65535,65535,65535,65535,65535,65535,65535},
{1699,5516,2557,1719,5536,5541,5545,5550,1749,1760,1772,1783,1795,1808,1820,1831,1843,1855,1866,1878,1890,1901,1914,1926,1938,1949,1961,1973,1984,1996,2008,2020,2033,2044,2056,2067,2079,2100,2112,65535,65535,65535,65535,65535,65535,65535,65535,65535},
{2122,2128,2134,2142,2148,2153,5969,2162,2172,2183,2195,2207,2218,2231,2243,2255,2266,2278,2290,2301,2313,2325,2337,2349,2361,2373,2384,2396,2408,2419,2431,2443,2456,2467,2479,2491,2502,2523,2535,65535,65535,65535,65535,65535,65535,65535,65535,65535},
{2123,5940,3401,2143,5960,5965,2158,5974,2173,2184,2196,2208,2219,2232,2244,2256,2267,2279,2291,2302,2314,2326,2338,2350,2362,2374,2385,2397,2409,2420,2432,2444,2457,2468,2480,2492,2503,2524,2536,65535,65535,65535,65535,65535,65535,65535,65535,65535},
{3741,3744,3747,65535,65535,65535,65535,65535,65535,65535,65535,65535,65535,65535,65535,65535,65535,65535,65535,65535,65535,65535,65535,65535,65535,65535,65535,65535,65535,65535,65535,65535,65535,65535,65535,65535,65535,65535,65535,65535,65535,65535,65535,65535,65535,65535,65535,65535},
{2546,3395,2558,3410,3415,2576,2581,3429,3440,2608,3463,3475,2643,2656,3499,3511,2691,3534,3546,2726,3569,3581,2763,2774,3605,3617,2809,3640,3652,2844,3675,2869,3688,2892,3711,3723,2927,3755,3767,65535,65535,65535,65535,65535,65535,65535,65535,65535},
{2970,6788,2982,2991,2996,3001,3006,6397,3020,3032,3044,3056,3067,3080,3092,3104,3115,3127,3139,3150,3162,3174,3186,3198,3210,3222,3233,3245,3257,3268,3280,3293,3304,3316,3328,3340,3351,3372,3383,65535,65535,65535,65535,65535,65535,65535,65535,65535},
{2971,6363,2983,2992,6808,6813,6818,3011,3021,3033,3045,3057,3068,3081,3093,3105,3116,3128,3140,3151,3163,3175,3187,3199,3211,3223,3234,3246,3258,3269,3281,3294,3305,3317,3329,3341,3352,3373,3384,65535,65535,65535,65535,65535,65535,65535,65535,65535},
{427,432,438,447,4264,457,462,467,477,489,501,512,524,537,549,560,572,584,595,607,619,630,643,655,667,678,690,702,713,725,737,749,761,773,785,796,808,829,840,65535,65535,65535,65535,65535,65535,65535,65535,65535},
{428,4244,439,448,453,4269,4274,469,3443,492,504,516,528,540,552,564,575,587,599,610,622,634,647,658,670,682,693,705,717,728,740,753,3691,776,788,800,811,832,3770,65535,65535,65535,65535,65535,65535,65535,65535,65535},
{852,857,863,872,877,4693,886,893,905,3455,928,940,952,3491,976,988,3526,1011,1023,3561,1046,1058,1071,3597,1094,1106,3632,1129,1141,3667,1164,1177,1189,3703,1212,1224,3738,1256,1268,65535,65535,65535,65535,65535,65535,65535,65535,65535},
{4664,4669,864,4684,4689,882,4698,2588,2600,917,2623,2635,2647,965,2671,2683,1000,2706,2718,1035,2741,2753,2766,1083,2789,2801,1118,2824,2836,1153,2859,1178,2884,1201,2907,2919,2931,2951,2963,65535,65535,65535,65535,65535,65535,65535,65535,65535},
{1276,1281,1286,1295,5112,1305,1310,1317,1328,1340,1351,1363,1375,1388,1399,1411,1423,1434,1446,1458,1469,1481,1494,1506,1517,1529,1541,1552,1564,1576,1587,1600,1612,1624,1635,1647,1659,1680,1691,65535,65535,65535,65535,65535,65535,65535,65535,65535},
{5088,5093,1287,1296,1301,5117,5122,3432,1329,1341,1352,1364,1376,1389,1400,1412,1424,1435,1447,1459,1470,1482,1495,1507,1518,1530,1542,1553,1565,1577,1588,1601,1613,1625,1636,1648,3739,3759,1692,65535,65535,65535,65535,65535,65535,65535,65535,65535},
{1700,1705,1711,1720,1725,1730,1734,1741,1753,1764,1776,1787,1799,1812,1824,1835,1847,1859,1870,1882,1894,1905,1918,1930,1942,1953,1965,1977,1988,2000,2012,2024,2037,2048,2060,2071,2083,2104,2116,65535,65535,65535,65535,65535,65535,65535,65535,65535},
{5512,5517,1712,5532,5537,5542,5546,1742,3444,1765,3467,1788,1800,1813,3503,1836,1848,3538,1871,1883,3573,1906,1919,1931,3609,1954,1966,3644,1989,2001,3679,2025,3692,2049,3715,2072,387,2105,3771,65535,65535,65535,65535,65535,65535,65535,65535,65535},
{2124,2129,2135,2144,2149,2154,5970,2165,2177,2188,2200,2212,2223,2236,2248,2260,2271,2283,2295,2306,2318,2330,2342,2354,2366,2378,2389,2401,2413,2424,2436,2448,2461,2472,2484,2496,2507,2528,2540,65535,65535,65535,65535,65535,65535,65535,65535,65535},
{5936,5941,2136,5956,5961,5966,2159,2166,2178,2189,2201,3479,2224,2237,2249,3515,2272,2284,3550,2307,2319,2331,2343,2355,2367,3621,2390,2402,3656,2425,2437,2449,2462,2473,2485,3727,2517,2529,2541,65535,65535,65535,65535,65535,65535,65535,65535,65535},
{3742,3745,3748,65535,65535,65535,65535,65535,65535,65535,65535,65535,65535,65535,65535,65535,65535,65535,65535,65535,65535,65535,65535,65535,65535,65535,65535,65535,65535,65535,65535,65535,65535,65535,65535,65535,65535,65535,65535,65535,65535,65535,65535,65535,65535,65535,65535,65535},
{2547,2552,3402,2567,6383,3420,3425,2586,2597,3452,2620,2632,3487,3488,2668,2680,3523,2703,2715,3558,2738,2750,2764,3594,2786,2798,3629,2821,2833,3664,2856,2870,2881,3700,2904,2916,3735,2948,2960,65535,65535,65535,65535,65535,65535,65535,65535,65535},
{2972,6789,2559,3411,6809,3002,3007,3014,3025,3037,3049,3060,3073,3085,3097,3108,3120,3132,3143,3155,3167,3179,3586,3203,3215,3226,3238,3250,3261,3273,3285,2873,3309,3321,3333,3344,3365,3377,3388,65535,65535,65535,65535,65535,65535,65535,65535,65535},
{6784,3396,3403,2993,2572,6814,6819,2589,3026,2612,2624,3061,2648,2660,2672,3109,2695,2707,3144,2730,2742,2754,3192,2778,2790,3227,2813,2825,3262,2848,2860,3681,3310,2896,2908,3345,3366,2952,3389,65535,65535,65535,65535,65535,65535,65535,65535,65535},
{4240,433,440,4260,4265,458,463,470,481,493,505,517,529,541,553,565,576,588,600,611,623,635,648,659,671,683,694,706,718,729,741,754,765,777,789,801,821,833,844,65535,65535,65535,65535,65535,65535,65535,65535,65535},
{429,4245,13,449,3416,4270,4275,3433,482,3456,3468,2636,530,3492,3504,2684,3527,3539,2719,3562,3574,636,2767,3598,3610,2802,3633,3645,2837,3668,742,755,766,3704,3716,2920,822,3760,845,65535,65535,65535,65535,65535,65535,65535,65535,65535},
{853,6364,865,873,6384,4694,887,894,906,918,929,941,953,966,977,989,1001,1012,1024,1036,1047,1059,1072,1084,1095,1107,1119,1130,1142,1154,1165,1179,1190,1202,1213,1225,1245,1257,1269,65535,65535,65535,65535,65535,65535,65535,65535,65535},
{4665,858,2560,4685,878,2577,4699,895,2601,2613,930,3480,954,2661,978,3516,2696,1013,3551,2731,1048,1060,3587,2779,1096,3622,2814,1131,3657,2849,1166,2874,2885,2897,1214,3728,1246,1258,2964,65535,65535,65535,65535,65535,65535,65535,65535,65535},
{1277,1282,1288,5108,5113,1306,1311,1318,1330,1342,1353,1365,1377,1390,1401,1413,1425,1436,1448,1460,1471,1483,1496,1508,1519,1531,1543,1554,1566,1578,1589,1602,1614,1626,1637,1649,1669,1681,1693,65535,65535,65535,65535,65535,65535,65535,65535,65535},
{5089,5094,1289,1297,1302,5118,5123,1319,3445,3457,1354,1366,1378,3493,1402,1414,3528,1437,1449,3563,1472,1484,1497,3599,1520,1532,3634,1555,1567,3669,1590,1603,3693,3705,1638,1650,1670,1682,3772,65535,65535,65535,65535,65535,65535,65535,65535,65535},
{1701,1706,1713,1721,1726,3421,1735,1743,1754,1766,1777,1789,1801,1814,1825,1837,1849,1860,1872,1884,1895,1907,1920,1932,1943,1955,1967,1978,1990,2002,2013,2026,2038,2050,2061,2073,2093,2106,2117,65535,65535,65535,65535,65535,65535,65535,65535,65535},
{5513,5518,3404,5533,5538,6389,5547,2590,1755,1767,1778,1790,1802,1815,1826,1838,1850,1861,1873,1885,1896,1908,1921,1933,1944,1956,1968,1979,1991,2003,2014,2027,2039,2051,2062,2074,2094,2953,2118,65535,65535,65535,65535,65535,65535,65535,65535,65535},
{2125,2130,2137,2145,2150,2155,5971,2167,2179,2190,2202,2213,2225,2238,2250,2261,2273,2285,2296,2308,2320,2332,2344,2356,2368,2379,2391,2403,2414,2426,2438,2450,2463,2474,2486,2497,2518,2530,2542,65535,65535,65535,65535,65535,65535,65535,65535,65535},
{5937,5942,14,5957,5962,5967,2582,3434,2602,2191,2625,2214,2226,2239,2673,2262,2274,2708,2297,2309,2743,2755,2345,2357,2791,2380,2392,2826,2415,2427,2861,2451,2886,2475,2909,2498,2941,3761,2965,65535,65535,65535,65535,65535,65535,65535,65535,65535},
{2548,2553,2561,2568,2573,2578,3426,2591,3446,2614,3469,2637,2649,2662,3505,2685,2697,3540,2720,2732,3575,2756,2768,2780,3611,2803,2815,3646,2838,2850,2862,3682,3694,2898,3717,2921,3749,2954,3773,65535,65535,65535,65535,65535,65535,65535,65535,65535},
{3392,3397,3405,3412,3417,3422,6394,3435,2603,3458,2626,3481,2650,3494,2674,3517,3529,2709,3552,3564,2744,209,3588,3600,2792,3623,3635,2827,3658,3670,2863,2875,2887,3706,2910,3729,2942,3762,2966,65535,65535,65535,65535,65535,65535,65535,65535,65535},
{2973,2978,2985,6805,2998,3003,3008,3015,3027,3038,3050,3062,3074,3086,3098,3110,3121,3133,3145,3156,3168,3180,3193,3204,3216,3228,3239,3251,3263,3274,3286,3299,3311,3322,3334,3346,3367,3378,3390,65535,65535,65535,65535,65535,65535,65535,65535,65535},
{6785,6790,2986,6380,6810,6815,6820,44,56,3039,3051,91,103,3087,3099,139,3122,3134,174,3157,3169,3181,222,3205,3217,257,3240,3252,292,3275,3287,328,340,3323,3335,375,3750,407,419,65535,65535,65535,65535,65535,65535,65535,65535,65535},
{4241,434,441,4261,454,459,464,471,483,494,506,518,531,542,554,566,577,589,601,612,624,637,649,660,672,684,695,707,719,730,743,756,767,778,790,802,823,834,846,65535,65535,65535,65535,65535,65535,65535,65535,65535},
{6360,4246,442,450,4266,4271,4276,472,484,495,507,519,104,543,555,567,578,590,602,613,625,210,650,661,673,685,696,708,720,731,316,3683,768,779,791,803,824,835,847,65535,65535,65535,65535,65535,65535,65535,65535,65535},
{2,4668,862,871,4688,881,4697,4702,901,913,924,936,948,961,972,984,996,1007,1019,1031,1042,1054,1067,1079,1090,1102,1114,1125,1137,1149,1160,1173,1185,1197,1208,1220,1232,1252,1264,65535,65535,65535,65535,65535,65535,65535,65535,65535},
{854,4670,866,874,4690,883,888,896,907,919,931,942,955,967,979,990,1002,1014,1025,1037,1049,1061,1073,1085,1097,1108,1120,1132,1143,1155,1167,1180,1191,1203,1215,1226,1247,1259,1270,65535,65535,65535,65535,65535,65535,65535,65535,65535},
{1278,6365,1290,5109,5114,1307,1312,1320,1331,1343,1355,1367,1379,1391,1403,1415,1426,1438,1450,1461,1473,1485,1498,1509,1521,1533,1544,1556,1568,1579,1591,1604,1615,1627,1639,1651,1671,1683,1694,65535,65535,65535,65535,65535,65535,65535,65535,65535},
{5090,1283,15,1298,6385,5119,5124,45,1332,68,3470,2638,1380,116,3506,2686,151,3541,2721,186,3576,1486,2769,234,3612,2804,269,3647,2839,304,1592,329,1616,352,3718,2922,1672,408,1695,65535,65535,65535,65535,65535,65535,65535,65535,65535},
{1702,1707,1714,1722,1727,1731,1736,1744,1756,1768,1779,1791,1803,1816,1827,1839,1851,1862,1874,1886,1897,1909,1922,1934,1945,1957,1969,1980,1992,2004,2015,2028,2040,2052,2063,2075,2095,2107,2119,65535,65535,65535,65535,65535,65535,65535,65535,65535},
{5514,5519,1715,5534,5539,5543,5548,1745,3447,2615,80,3482,1804,2663,128,3518,2698,163,3553,2733,198,1910,3589,2781,246,3624,2816,281,3659,2851,2016,2029,3695,2899,364,3730,2096,2108,3774,65535,65535,65535,65535,65535,65535,65535,65535,65535},
{2126,2131,2138,2146,2151,6390,2160,2168,2180,2192,2203,2215,2227,2240,2251,2263,2275,2286,2298,2310,2321,2333,2346,2358,2369,2381,2393,2404,2416,2428,2439,2452,2464,2476,2487,2499,2519,2531,2543,65535,65535,65535,65535,65535,65535,65535,65535,65535},
{5938,5943,2139,5958,5963,2156,5972,2169,57,3459,2204,92,2228,3495,2252,140,3530,2287,175,3565,2322,2334,223,3601,2370,258,3636,2405,293,3671,2440,2453,341,3707,2488,376,2520,2532,420,65535,65535,65535,65535,65535,65535,65535,65535,65535},
{2549,2554,2562,2569,2574,2579,2583,2592,2604,2616,2627,2639,2651,2664,2675,2687,2699,2710,2722,2734,2745,2757,2770,2782,2793,2805,2817,2828,2840,2852,2864,2876,2888,2900,2911,2923,2943,2955,2967,65535,65535,65535,65535,65535,65535,65535,65535,65535},
{3393,3398,3406,3413,3418,3423,3427,3436,3448,3460,3471,3483,2652,3496,3507,3519,3531,3542,3554,3566,3577,2758,3590,3602,3613,3625,3637,3648,3660,3672,317,3684,3696,3708,3719,3731,3751,3763,3775,65535,65535,65535,65535,65535,65535,65535,65535,65535},
{2974,2979,2987,2994,2999,3004,6395,3016,3028,3040,3052,3063,3075,3088,3100,3111,3123,3135,3146,3158,3170,3182,3194,3206,3218,3229,3241,3253,3264,3276,3288,3300,3312,3324,3336,3347,3368,3379,3391,65535,65535,65535,65535,65535,65535,65535,65535,65535},
{6786,6791,16,6806,6811,6816,3009,3017,3029,69,81,3064,3076,117,129,3112,152,164,3147,187,199,211,3195,235,247,3230,270,282,3265,305,3289,3301,3313,353,365,3348,397,3380,421,65535,65535,65535,65535,65535,65535,65535,65535,65535},
{6361,6366,2563,6381,6386,6391,2584,2593,2605,2617,2628,2640,105,2665,2676,2688,2700,2711,2723,2735,2746,2759,2771,2783,2794,2806,2818,2829,2841,2853,2865,2877,2889,2901,2912,2924,2944,2956,422,65535,65535,65535,65535,65535,65535,65535,65535,65535},
{2550,2555,3407,2570,2575,2580,3428,3437,3449,3461,3472,3484,2653,3497,3508,3520,3532,3543,3555,3567,3578,212,3591,3603,3614,3626,3638,3649,3661,3673,318,3685,3697,3709,3720,3732,3752,3764,423,65535,65535,65535,65535,65535,65535,65535,65535,65535},
{3,2977,2984,6804,2997,6388,6393,6823,3022,3034,3464,3476,3069,3082,3500,3512,3117,3535,3547,3152,3570,3582,3188,3200,3606,3618,3235,3641,3653,3270,3676,3295,3306,3318,3712,3724,3353,3756,3385,65535,65535,65535,65535,65535,65535,65535,65535,65535},
{2975,8,2988,23,28,33,6821,46,58,3041,3053,93,3077,3089,3101,141,3124,3136,176,3159,3171,3183,224,3207,3219,259,3242,3254,294,3277,3290,330,342,3325,3337,377,3369,409,1271,65535,65535,65535,65535,65535,65535,65535,65535,65535},
{4,3820,17,24,3840,3845,38,47,59,70,82,94,106,118,130,142,153,165,177,188,200,213,225,236,248,260,271,283,295,306,319,331,343,354,366,378,398,410,65535,65535,65535,65535,65535,65535,65535,65535,65535,65535},
{3816,9,18,3836,29,34,3850,48,60,71,83,95,107,119,131,143,154,166,178,189,201,214,226,237,249,261,272,284,296,307,320,332,344,355,367,379,399,411,65535,65535,65535,65535,65535,65535,65535,65535,65535,65535},
{5,3821,19,25,3841,3846,39,49,61,72,84,96,108,120,132,144,155,167,179,190,202,215,227,238,250,262,273,285,297,308,321,333,345,356,368,380,400,412,65535,65535,65535,65535,65535,65535,65535,65535,65535,65535},
{3817,10,20,3837,30,35,3851,50,62,73,85,97,109,121,133,145,156,168,180,191,203,216,228,239,251,263,274,286,298,309,322,334,346,357,369,381,401,413,65535,65535,65535,65535,65535,65535,65535,65535,65535,65535},
{6,3822,21,26,3842,3847,40,51,63,74,86,98,110,122,134,146,157,169,181,192,204,217,229,240,252,264,275,287,299,310,323,335,347,358,370,382,402,414,65535,65535,65535,65535,65535,65535,65535,65535,65535,65535},
{3818,11,2564,3838,31,36,3852,2594,2606,75,2629,2641,111,123,2677,2689,158,2712,2724,193,2747,2760,2772,241,2795,2807,276,2830,2842,311,2866,2878,2890,359,2913,2925,2945,2957,65535,65535,65535,65535,65535,65535,65535,65535,65535,65535},
{7,3823,3408,27,3843,3848,41,3438,3450,2618,3473,3485,2654,2666,3509,3521,2701,3544,3556,2736,3579,218,3592,2784,3615,3627,2819,3650,3662,2854,324,3686,3698,2902,3721,3733,3753,3765,65535,65535,65535,65535,65535,65535,65535,65535,65535,65535},
{3819,12,22,3839,32,37,3853,52,64,3462,87,99,112,3498,135,147,3533,170,182,3568,205,638,230,3604,253,265,3639,288,300,3674,744,336,348,3710,371,383,403,415,65535,65535,65535,65535,65535,65535,65535,65535,65535,65535},
};

#define TABLED 1
#define TRIG 7
#define JB 22
#define PRE 2
#define CH 64
#define FIRST 5
constexpr int RING = SCHED_RING;
constexpr int NSLOT = 8;
constexpr int PLEN = SCHED_LE, LT = SCHED_LT, LM = 256 - 2 * PLEN - 2 * LT, NSEG = 4 / SCHED_NMID, LMID = NSEG * LM;
constexpr int NP = 8 + SCHED_NMID, NG = NP + (LT ? 8 : 0), NCONV = 3 * NG;
static_assert(LMID <= PLEN && LT <= RING && LT < LM && (LT == 0 || LT >= 6), "geometry");
__device__ __forceinline__ int group_len(int gm) { return gm < 8 ? PLEN : gm < NP ? LMID : LT; }
__device__ __forceinline__ int group_strip(int gm, int seg) { return gm < 8 ? gm >> 1 : gm < NP ? (gm - 8) * NSEG + seg : (gm - NP) >> 1; }
__device__ __forceinline__ int group_base(int gm) { return gm < NP ? PLEN + LT : PLEN + ((gm - NP) & 1) * (LT + LM); }
constexpr int TILEB = 12288;
constexpr int SLOTB = 280 * 64;
constexpr int W1S = 0, W2S = 73728, ABUF = 147456, XBUF = ABUF + 16 * 3072, MISC = XBUF + 8 * 3072;
constexpr int WBAR = MISC + 2560;
constexpr int RBUF = ABUF - 4 * SLOTB;
constexpr int CM = MISC + 2816, CTAB = CM + 256;
constexpr int SMEM_BYTES = CTAB + (PLEN + 16) * 16;
static_assert(RBUF % 512 == 0 && RBUF >= W2S && RBUF + NSLOT * SLOTB + 128 <= MISC && SMEM_BYTES <= 232448, "smem layout");

struct Globals {
  unsigned char scratch[RING * NG * 4 * TILEB];
  unsigned char wimg[147456];
  uint32_t wflag[32];
  uint32_t ready[NG * PLEN + 1];
  uint32_t cons[NG * PLEN];
  uint32_t epoch[1024];
};
__device__ __align__(1024) Globals g_state;

#define GELU_C3 0.32920349f
#define GELU_A2 0x40d940d9u
#define GELU_S2 0x3e133e13u
#define SCHED_FENCE() asm volatile("pmevent 0;" ::: "memory")
#define SPIN_LIMIT 0x1000000

__device__ __forceinline__ uint32_t smem_u32(const void* p) { return (uint32_t)__cvta_generic_to_shared(p); }
__device__ __forceinline__ void wg_fence() { asm volatile("wgmma.fence.sync.aligned;" ::: "memory"); }
__device__ __forceinline__ void wg_commit() { asm volatile("wgmma.commit_group.sync.aligned;" ::: "memory"); }
template <int N> __device__ __forceinline__ void wg_wait() { asm volatile("wgmma.wait_group.sync.aligned %0;" ::"n"(N) : "memory"); }
__device__ __forceinline__ void mbar_wait(uint32_t bar, uint32_t parity) {
  asm volatile("{\n.reg .pred p;\n.reg .u32 c;\nmbarrier.try_wait.parity.shared::cta.b64 p, [%0], %1;\n@p bra DONE_%=;\nmov.u32 c, 0;\nWAIT_%=:\nmbarrier.try_wait.parity.shared::cta.b64 p, [%0], %1;\n@p bra DONE_%=;\n"
               "add.u32 c, c, 1;\nsetp.lt.u32 p, c, 0x1000000;\n@p bra WAIT_%=;\ntrap;\nDONE_%=:\n}" ::"r"(bar), "r"(parity) : "memory");
}
__device__ __forceinline__ void mbar_arrive_elect(uint32_t bar) { asm volatile("{.reg .pred p; elect.sync _|p, 0xffffffff; @p mbarrier.arrive.shared::cta.b64 _, [%0];}" ::"r"(bar) : "memory"); }
__device__ __forceinline__ void mbar_init_elect(uint32_t bar, uint32_t cnt) { asm volatile("{.reg .pred p; elect.sync _|p, 0xffffffff; @p mbarrier.init.shared::cta.b64 [%0], %1;}" ::"r"(bar), "r"(cnt) : "memory"); }
__device__ __forceinline__ uint32_t ld_relaxed(const uint32_t* p) { uint32_t v; asm volatile("ld.relaxed.gpu.global.u32 %0, [%1];" : "=r"(v) : "l"(p) : "memory"); return v; }
__device__ __forceinline__ void red_add_elect(uint32_t* p) { asm volatile("{.reg .pred p; elect.sync _|p, 0xffffffff; @p red.relaxed.gpu.global.add.u32 [%0], 1;}" ::"l"(p) : "memory"); }
__device__ __forceinline__ void wait_value(const uint32_t* p, uint32_t target, int ns) {
  int spins = 0;
  while (ld_relaxed(p) != target) { __nanosleep(ns); if (++spins > SPIN_LIMIT) __trap(); }
}
template <int BYTES, bool INIT = false> __device__ __forceinline__ void bulk_load(uint32_t dst, const void* src, uint32_t bar, int go = 0) {
  if (INIT) asm volatile("{.reg .pred p; elect.sync _|p, 0xffffffff; @p mbarrier.init.shared::cta.b64 [%0], 1; @p fence.mbarrier_init.release.cluster;}" ::"r"(bar) : "memory");
  asm volatile("{\n.reg .pred p, q;\nsetp.ge.s32 q, %4, 0;\nelect.sync _|p, 0xffffffff;\nand.pred p, p, q;\n@p mbarrier.arrive.expect_tx.shared::cta.b64 _, [%1], %3;\n"
               "@p cp.async.bulk.shared::cluster.global.mbarrier::complete_tx::bytes [%0], [%2], %3, [%1];\n}"
               ::"r"(dst), "r"(bar), "l"(src), "n"(BYTES), "r"(go) : "memory");
}
__device__ __forceinline__ void lds128(uint32_t* r, uint32_t a) { asm volatile("ld.shared.v4.b32 {%0,%1,%2,%3}, [%4];" : "=r"(r[0]), "=r"(r[1]), "=r"(r[2]), "=r"(r[3]) : "r"(a) : "memory"); }
__device__ __forceinline__ uint2 lds64(uint32_t a) { uint2 v; asm volatile("ld.shared.v2.b32 {%0,%1}, [%2];" : "=r"(v.x), "=r"(v.y) : "r"(a) : "memory"); return v; }
__device__ __forceinline__ uint32_t lds32(uint32_t a) { uint32_t v; asm volatile("ld.shared.b32 %0, [%1];" : "=r"(v) : "r"(a) : "memory"); return v; }
__device__ __forceinline__ void sts32(uint32_t a, uint32_t v) { asm volatile("st.shared.b32 [%0], %1;" ::"r"(a), "r"(v) : "memory"); }
__device__ __forceinline__ void sts64(uint32_t a, uint2 v) { asm volatile("st.shared.v2.b32 [%0], {%1,%2};" ::"r"(a), "r"(v.x), "r"(v.y) : "memory"); }
__device__ __forceinline__ void sts128(uint32_t a, uint4 v) { asm volatile("st.shared.v4.b32 [%0], {%1,%2,%3,%4};" ::"r"(a), "r"(v.x), "r"(v.y), "r"(v.z), "r"(v.w) : "memory"); }
__device__ __forceinline__ uint64_t pol_evict_first() { uint64_t p; asm("createpolicy.fractional.L2::evict_first.b64 %0, 1.0;" : "=l"(p)); return p; }
__device__ __forceinline__ void stg128_stream(void* p, uint4 v, uint64_t pol) {
  asm volatile("st.global.L2::cache_hint.v4.b32 [%0], {%1,%2,%3,%4}, %5;" ::"l"(p), "r"(v.x), "r"(v.y), "r"(v.z), "r"(v.w), "l"(pol) : "memory");
}
__device__ __forceinline__ void stg128_if(uint32_t go, void* p, uint4 v) {
  asm volatile("{.reg .pred q; setp.ge.s32 q, %5, 0; @q st.global.v4.b32 [%0], {%1,%2,%3,%4};}" ::"l"(p), "r"(v.x), "r"(v.y), "r"(v.z), "r"(v.w), "r"(go) : "memory");
}
__device__ __forceinline__ uint32_t pack_f16(float lo, float hi) { uint32_t d; asm("cvt.rn.f16x2.f32 %0, %1, %2;" : "=r"(d) : "f"(hi), "f"(lo)); return d; }
__device__ __forceinline__ uint32_t pack_f16_sat(float lo, float hi) { uint32_t d; asm("cvt.rn.satfinite.f16x2.f32 %0, %1, %2;" : "=r"(d) : "f"(hi), "f"(lo)); return d; }
__device__ __forceinline__ uint32_t pack_bf16(float lo, float hi) { uint32_t d; asm("cvt.rn.bf16x2.f32 %0, %1, %2;" : "=r"(d) : "f"(hi), "f"(lo)); return d; }
__device__ __forceinline__ uint32_t bf2_to_h2(uint32_t w) { return pack_f16(__uint_as_float(w << 16), __uint_as_float(w & 0xffff0000u)); }
__device__ __forceinline__ uint32_t hadd2_bf16(uint32_t a, uint32_t b) { uint32_t d; asm("add.rn.bf16x2 %0, %1, %2;" : "=r"(d) : "r"(a), "r"(b)); return d; }
__device__ __forceinline__ uint32_t h2add(uint32_t a, uint32_t b) { uint32_t d; asm("add.rn.f16x2 %0, %1, %2;" : "=r"(d) : "r"(a), "r"(b)); return d; }
__device__ __forceinline__ uint32_t h2mul(uint32_t a, uint32_t b) { uint32_t d; asm("mul.rn.f16x2 %0, %1, %2;" : "=r"(d) : "r"(a), "r"(b)); return d; }
__device__ __forceinline__ uint32_t h2fma(uint32_t a, uint32_t b, uint32_t c) { uint32_t d; asm("fma.rn.f16x2 %0, %1, %2, %3;" : "=r"(d) : "r"(a), "r"(b), "r"(c)); return d; }
__device__ __forceinline__ uint32_t h2lo(uint32_t a) { uint32_t d; asm("{.reg .f16 l,h; mov.b32 {l,h}, %1; mov.b32 %0, {l,l};}" : "=r"(d) : "r"(a)); return d; }
__device__ __forceinline__ uint32_t h2hi(uint32_t a) { uint32_t d; asm("{.reg .f16 l,h; mov.b32 {l,h}, %1; mov.b32 %0, {h,h};}" : "=r"(d) : "r"(a)); return d; }
__device__ __forceinline__ float h_lo(uint32_t a) { float d; asm("{.reg .f16 l,h; mov.b32 {l,h}, %1; cvt.f32.f16 %0, l;}" : "=f"(d) : "r"(a)); return d; }
__device__ __forceinline__ float h_hi(uint32_t a) { float d; asm("{.reg .f16 l,h; mov.b32 {l,h}, %1; cvt.f32.f16 %0, h;}" : "=f"(d) : "r"(a)); return d; }
__device__ __forceinline__ float rsqrt_fast(float v) { float r; asm("rsqrt.approx.ftz.f32 %0, %1;" : "=f"(r) : "f"(v)); return r; }
__device__ __forceinline__ uint32_t prmt(uint32_t a, uint32_t b, uint32_t s) { uint32_t d; asm("prmt.b32 %0, %1, %2, %3;" : "=r"(d) : "r"(a), "r"(b), "r"(s)); return d; }
__device__ __forceinline__ void mma_sp(float* d, const uint32_t* a, const uint32_t* b, const float* c, uint32_t e) {
  asm("mma.sp::ordered_metadata.sync.aligned.m16n8k32.row.col.f32.bf16.bf16.f32 {%0,%1,%2,%3}, {%4,%5,%6,%7}, {%8,%9,%10,%11}, {%12,%13,%14,%15}, %16, 0;"
      : "=f"(d[0]), "=f"(d[1]), "=f"(d[2]), "=f"(d[3])
      : "r"(a[0]), "r"(a[1]), "r"(a[2]), "r"(a[3]), "r"(b[0]), "r"(b[1]), "r"(b[2]), "r"(b[3]), "f"(c[0]), "f"(c[1]), "f"(c[2]), "f"(c[3]), "r"(e));
}

__device__ __forceinline__ uint32_t gelu_tanh(uint32_t y) {
  uint32_t t, u, th;
  asm volatile("fma.rn.f16x2 %0, %1, %1, %2;" : "=r"(t) : "r"(y), "r"(GELU_A2));
  asm volatile("mul.rn.f16x2 %0, %1, %2;" : "=r"(u) : "r"(y), "r"(t));
  asm volatile("tanh.approx.f16x2 %0, %1;" : "=r"(th) : "r"(u));
  return th;
}
__device__ __forceinline__ uint32_t gelu_fin(uint32_t y, uint32_t th) {
  uint32_t g;
  asm volatile("fma.rn.f16x2 %0, %1, %2, %1;" : "=r"(g) : "r"(y), "r"(th));
  return g;
}

__device__ __forceinline__ void convert_weights(uint32_t sb, int rot, int warp, int lane) {
  if (warp < 12) {
    const int l8 = lane & 7, q4 = lane >> 3;
    int s = (warp >> 1) + rot; if (s >= 6) s -= 6;
    const uint32_t base = sb + W1S + s * 12288 + (warp & 1) * 384;
    mbar_wait(sb + WBAR + s * 8, 0);
    uint32_t v[3][4][4];
#pragma unroll
    for (int r = 0; r < 4; r++)
#pragma unroll
      for (int i = 0; i < 3; i++) lds128(v[i][r], base + i * 128 + (4 * (l8 >> 1) + 2 * (r & 1) + (l8 & 1)) * 768 + ((l8 + q4 + 4 * (r >> 1)) & 7) * 16);
    __syncwarp();
#pragma unroll
    for (int r = 0; r < 4; r++)
#pragma unroll
      for (int i = 0; i < 3; i++)
        sts128(base + i * 128 + (((l8 + q4 + 4 * (r >> 1)) & 7) + 8 * (r & 1)) * 768 + l8 * 16,
               make_uint4(bf2_to_h2(v[i][r][0]), bf2_to_h2(v[i][r][1]), bf2_to_h2(v[i][r][2]), bf2_to_h2(v[i][r][3])));
  }
  const int q = lane & 3, t = (lane >> 2) & 3, b = lane >> 4;
  int u = 3 * (warp ^ 15) + 8 * rot; if (u >= 48) u -= 48;
  uint32_t base[3], v[3][4][3];
#pragma unroll
  for (int i = 0; i < 3; i++) {
    const int ui = u + i >= 48 ? u + i - 48 : u + i;
    base[i] = sb + W2S + ui * 1536;
    if (i != 1) mbar_wait(sb + WBAR + 48 + (ui >> 3) * 8, 0);
  }
#pragma unroll
  for (int i = 0; i < 3; i++)
#pragma unroll
    for (int d = 0; d < 4; d++)
#pragma unroll
      for (int j = 0; j < 3; j++) v[i][d][j] = lds32(base[i] + (2 * ((q + d) & 3) + b) * 192 + j * 64 + t * 16 + q * 4);
  __syncwarp();
#pragma unroll
  for (int i = 0; i < 3; i++)
#pragma unroll
    for (int d = 0; d < 4; d++)
#pragma unroll
      for (int j = 0; j < 3; j++) sts32(base[i] + (4 * j + q) * 128 + (2 * ((q + d) & 3) + b) * 16 + t * 4, bf2_to_h2(v[i][d][j]));
}

__device__ __noinline__ void ln_wide(uint32_t ad) {
  float m[2], r[2];
#pragma unroll
  for (int hi = 0; hi < 2; hi++) {
    float sm = 0.f;
    for (int s = 0; s < 6; s++) { uint2 w = lds64(ad + s * 512 + hi * 8); sm += (h_lo(w.x) + h_hi(w.x)) + (h_lo(w.y) + h_hi(w.y)); }
    sm += __shfl_xor_sync(0xffffffffu, sm, 1); sm += __shfl_xor_sync(0xffffffffu, sm, 2);
    m[hi] = sm * (1.f / 96.f);
    float q = 0.f;
    for (int s = 0; s < 6; s++) {
      uint2 w = lds64(ad + s * 512 + hi * 8);
      float d0 = h_lo(w.x) - m[hi], d1 = h_hi(w.x) - m[hi], d2 = h_lo(w.y) - m[hi], d3 = h_hi(w.y) - m[hi];
      q += (d0 * d0 + d1 * d1) + (d2 * d2 + d3 * d3);
    }
    q += __shfl_xor_sync(0xffffffffu, q, 1); q += __shfl_xor_sync(0xffffffffu, q, 2);
    r[hi] = rsqrtf(fmaf(q, 1.f / 96.f, 1e-5f)) * GELU_C3;
  }
  for (int s = 0; s < 6; s++) {
    uint32_t w[4]; lds128(w, ad + s * 512);
    sts128(ad + s * 512, make_uint4(pack_f16((h_lo(w[0]) - m[0]) * r[0], (h_hi(w[0]) - m[0]) * r[0]), pack_f16((h_lo(w[2]) - m[1]) * r[1], (h_hi(w[2]) - m[1]) * r[1]),
                                    pack_f16((h_lo(w[1]) - m[0]) * r[0], (h_hi(w[1]) - m[0]) * r[0]), pack_f16((h_lo(w[3]) - m[1]) * r[1], (h_hi(w[3]) - m[1]) * r[1])));
  }
  asm volatile("fence.proxy.async.shared::cta;" ::: "memory");
}

__device__ __forceinline__ uint32_t layer_norm(const uint32_t (&raw)[6][4], uint32_t* a, uint32_t tag) {
  const uint32_t stale = ((raw[0][0] ^ tag) | (raw[1][0] ^ tag)) | ((raw[2][0] ^ tag) | (raw[3][0] ^ tag)) | ((raw[4][0] ^ tag) | (raw[5][0] ^ tag));
  uint32_t sm[2], qq[2];
#pragma unroll
  for (int hi = 0; hi < 2; hi++) {
    uint32_t s0 = h2add(raw[0][2 * hi], raw[1][2 * hi]), s1 = h2add(raw[0][2 * hi + 1], raw[1][2 * hi + 1]);
    uint32_t s2 = h2add(raw[2][2 * hi], raw[3][2 * hi]), s3 = h2add(raw[2][2 * hi + 1], raw[3][2 * hi + 1]);
    uint32_t s4 = h2add(raw[4][2 * hi], raw[5][2 * hi]), s5 = h2add(raw[4][2 * hi + 1], raw[5][2 * hi + 1]);
    sm[hi] = h2add(h2add(h2add(s0, s1), h2add(s2, s3)), h2add(s4, s5));
  }
#pragma unroll
  for (int hi = 0; hi < 2; hi++) {
    uint32_t q0 = h2mul(raw[0][2 * hi], raw[0][2 * hi]), q1 = h2mul(raw[0][2 * hi + 1], raw[0][2 * hi + 1]);
#pragma unroll
    for (int k = 1; k < 6; k++) { q0 = h2fma(raw[k][2 * hi], raw[k][2 * hi], q0); q1 = h2fma(raw[k][2 * hi + 1], raw[k][2 * hi + 1], q1); }
    qq[hi] = h2add(q0, q1);
  }
  uint32_t s = h2add(prmt(sm[0], sm[1], 0x5410), prmt(sm[0], sm[1], 0x7632));
  uint32_t q = h2add(prmt(qq[0], qq[1], 0x5410), prmt(qq[0], qq[1], 0x7632));
  s = h2add(s, __shfl_xor_sync(0xffffffffu, s, 1)); q = h2add(q, __shfl_xor_sync(0xffffffffu, q, 1));
  s = h2add(s, __shfl_xor_sync(0xffffffffu, s, 2)); q = h2add(q, __shfl_xor_sync(0xffffffffu, q, 2));
  constexpr float K1 = 1.f / (96.f * GELU_C3 * GELU_C3), K2 = 1e-5f / (GELU_C3 * GELU_C3), K3 = 1.f / (96.f * GELU_C3);
  const float e0 = fmaf(h_lo(q), K1, K2), e1 = fmaf(h_hi(q), K1, K2), m0 = h_lo(s) * K3, m1 = h_hi(s) * K3;
  const float v0 = fmaf(-m0, m0, e0), v1 = fmaf(-m1, m1, e1);
  const uint32_t r = pack_f16(rsqrt_fast(v0), rsqrt_fast(v1)), o = h2mul(h2mul(s, 0xA155A155u), r);
#pragma unroll
  for (int k = 0; k < 6; k++) {
    a[4 * k] = h2fma(raw[k][0], h2lo(r), h2lo(o)); a[4 * k + 2] = h2fma(raw[k][1], h2lo(r), h2lo(o));
    a[4 * k + 1] = h2fma(raw[k][2], h2hi(r), h2hi(o)); a[4 * k + 3] = h2fma(raw[k][3], h2hi(r), h2hi(o));
  }
  const bool fine = fmaf(v0, 4.f, -e0) > 0.f && fmaf(v1, 4.f, -e1) > 0.f;
  return (fine ? 0u : 2u) | (stale & 1);
}

constexpr int KS = CH / 16, NC = 384 / CH;
#define WG1_(n) wgmma_n##n##_f16
#define WG1(n) WG1_(n)
__device__ __forceinline__ void gemm1(uint32_t* p, const uint32_t* a, uint64_t d1, int c, int k0, int k1) {
#pragma unroll
  for (int s = 0; s < 6; s++)
    if (s >= k0 && s < k1) {
      if (s == 0) WG1(CH)<0>(p, a, d1 + c * CH); else WG1(CH)<1>(p, a + 4 * s, d1 + c * CH + s * (12288 >> 4));
    }
}
__device__ __forceinline__ void fetch_x(uint32_t xbuf, uint32_t bar, const CUtensorMap* tm, uint32_t c0, uint32_t c12, uint64_t pol, int go = 0) {
  asm volatile("{\n.reg .pred p, q;\nsetp.ge.s32 q, %7, 0;\nelect.sync _|p, 0xffffffff;\nand.pred p, p, q;\n"
               "@p mbarrier.arrive.expect_tx.shared::cta.b64 _, [%1], 3072;\n"
               "@p cp.async.bulk.tensor.3d.shared::cluster.global.mbarrier::complete_tx::bytes.L2::cache_hint [%0], [%2, {%3, %4, %5}], [%1], %6;\n}"
               ::"r"(xbuf), "r"(bar), "l"(tm), "r"(c0), "r"(c12 & 255), "r"(c12 >> 8), "l"(pol), "r"(go) : "memory");
}
__device__ __forceinline__ uint32_t slot_tag(int gm, int j, uint32_t epoch) {
  const int writes = (group_len(gm) - j % RING + RING - 1) / RING;
  return (epoch * writes + j / RING + 1) & 1;
}
__device__ __forceinline__ void build_tile_list(uint32_t sb, int k, int idx, bool tabled, bool is_conv, uint32_t epoch) {
  int n = -1;
  if (tabled) { if (k < 48) n = (int16_t)g_sched[idx][k]; }
  else if (!is_conv) {
    const int i = k * (gridDim.x - NCONV) + idx, r = i >> 2, r1 = r - LT * NG, r2 = r1 - (LMID - LT) * NP;
    const int j = r1 < 0 ? r / NG : r2 < 0 ? LT + r1 / NP : LMID + (r2 >> 3), gm = r1 < 0 ? r % NG : r2 < 0 ? r1 % NP : r2 & 7;
    if (i < 4096) n = (gm * PLEN + j) * 4 + (i & 3);
  }
  const int q = n >> 2, gm = q / PLEN, j = q - gm * PLEN, seg = j / LM;
  const int strip = group_strip(gm, seg), pair = gm < 8 ? ((gm & 1) ? 255 - j : j) : group_base(gm) + j - seg * LM;
  sts128(sb + MISC + 512 + k * 16, make_uint4(q, (((j % RING) * NG + gm) * 4 + (n & 3)) * TILEB + slot_tag(gm, j, epoch),
                                              (n & 2) * 384, (strip * 8 + (n & 1) * 4) | (pair << 9)));
  if (k == 0) sts64(sb + MISC + 256, make_uint2(epoch + 1, !is_conv));
}

__device__ __forceinline__ void mlp_setup(uint32_t sb, Globals* gs, int id, const __nv_bfloat16* __restrict__ w1, const __nv_bfloat16* __restrict__ w2,
                                          int idx, bool tabled, int warp, int lane) {
  const int rot = idx % 6;
  if (warp < 12) {
    const int m = warp >= 6; int s = warp - 6 * m + rot; if (s >= 6) s -= 6;
    bulk_load<12288, true>(sb + (6 * m + s) * 12288, (const char*)(m ? w2 : w1) + s * 12288, sb + WBAR + (6 * m + s) * 8);
  }
  __syncthreads();
  if (warp >= 12) build_tile_list(sb, threadIdx.x - 384, idx, tabled, false, ld_relaxed(&gs->epoch[id]));
  convert_weights(sb, rot, warp, lane);
  asm volatile("fence.proxy.async.shared::cta;" ::: "memory");
  __syncthreads();
  if (threadIdx.x == 480) {
    gs->epoch[id] = lds32(sb + MISC + 256);
    const uint32_t piece = tabled ? idx - 96 : idx;
    if (piece < 12) {
      asm volatile("cp.async.bulk.global.shared::cta.bulk_group [%0], [%1], 12288;\ncp.async.bulk.commit_group;\ncp.async.bulk.wait_group 0;\nfence.proxy.async.global;\n"
                   "red.release.gpu.global.add.u32 [%2], 1;" ::"l"(gs->wimg + piece * 12288), "r"(sb + piece * 12288), "l"(gs->wflag) : "memory");
    }
  }
  __syncwarp();
}

__device__ __forceinline__ void mlp_role(uint32_t sb, Globals* gs, const CUtensorMap* tmr, __nv_bfloat16* __restrict__ out) {
  uint32_t tid;
  asm volatile("mov.u32 %0, %%tid.x;" : "=r"(tid));
  const int warp = __shfl_sync(0xffffffffu, tid >> 5, 0), lane = tid & 31;
  const int wg = warp >> 2, w = warp & 3, g = lane >> 2, t = lane & 3;
  const uint32_t abuf = sb + ABUF + warp * 3072, xbuf = sb + XBUF + (warp & 7) * 3072;
  const uint32_t bar = sb + MISC + warp * 8, obar = sb + MISC + (warp ^ 8) * 8;
  const uint32_t tl = sb + MISC + 512;
  const uint32_t rtarget = 3 * lds32(sb + MISC + 256);
  const uint64_t d1 = ((uint64_t)(6144 >> 4) << 16) | ((uint64_t)(128 >> 4) << 32) | (uint64_t)(((sb + W1S) >> 4) & 0x3fff);
  const uint64_t d2 = ((uint64_t)(12288 >> 4) << 16) | ((uint64_t)(128 >> 4) << 32) | (uint64_t)(((sb + W2S) >> 4) & 0x3fff);
  const uint32_t ad = abuf + t * 128 + ((g ^ (2 * t)) << 4);
  const uint32_t xd = xbuf + g * 192 + t * 16;
  const uint32_t pofs = (g >> 1) * 3072 + (2 * w + (g & 1)) * 192 + t * 16;
  const int mybar = 1 + wg, nxtbar = 1 + ((wg + 1) & 3);
  const uint64_t pol = pol_evict_first();
  const unsigned char* const asrc = gs->scratch + w * 3072;
  uint32_t pha = 0, phx = 0, tp = tl + wg * 16;
  bool pending = lds32(sb + MISC + 260);
  uint32_t cur[4];
  lds128(cur, tp);
  if (wg < 2) fetch_x(xbuf, bar + 128, tmr, cur[2] + w * 192, cur[3], pol, cur[0]);
  while ((int)cur[0] >= 0) {
    uint32_t a[24], p[NC][CH / 4], gg[24][4], th[24][4], acc[24], raw[6][4], n2[4], n4[4];
    if (pending) {
      wait_value(&gs->ready[cur[0]], rtarget, 32);
      bulk_load<3072>(abuf, asrc + (cur[1] & ~1u), bar);
    }
    mbar_wait(bar, pha); pha ^= 1;
#pragma unroll
    for (int k = 0; k < 6; k++) lds128(raw[k], ad + k * 512);
    uint32_t st = layer_norm(raw, a, cur[1]);
    if (__any_sync(0xffffffffu, st != 0)) {
      for (int tries = 0; __any_sync(0xffffffffu, st & 1); tries++) {
        if (tries > SPIN_LIMIT) __trap();
        bulk_load<3072>(abuf, asrc + (cur[1] & ~1u), bar);
        mbar_wait(bar, pha); pha ^= 1;
        st = 0;
#pragma unroll
        for (int k = 0; k < 6; k++) st |= lds32(ad + k * 512) ^ cur[1];
      }
      ln_wide(ad);
#pragma unroll
      for (int k = 0; k < 6; k++) lds128(a + 4 * k, ad + k * 512);
    }
    if (tp != tl) asm volatile("bar.sync %0, 256;" ::"r"(mybar) : "memory");
    uint32_t rdy = 0;
    wg_fence();
    gemm1(p[0], a, d1, 0, 0, 6); wg_commit();
    gemm1(p[1], a, d1, 1, 0, 6 / KS); wg_commit();
    const int sig = lds32(tp + 16);
    lds128(n4, tp + 64);
    asm volatile("{.reg .pred p; setp.eq.u32 p, %1, 0; @p red.relaxed.gpu.global.add.u32 [%0], 1;}" ::"l"(&gs->cons[cur[0]] + lane), "r"(lane) : "memory");
#pragma unroll
    for (int j = 0; j < 24; j++) {
      const int c = j / KS, s = j % KS;
      if (j == JB) rdy = ld_relaxed(&gs->ready[max((int)n4[0], 0)]);
      if (s == 0) wg_wait<1>();
      if (j == TRIG) asm volatile("{.reg .pred p; setp.ge.s32 p, %1, 0; @p bar.arrive %0, 256;}" ::"r"(nxtbar), "r"(sig) : "memory");
#pragma unroll
      for (int i = 0; i < 4; i++) {
        if (!(s && i < PRE)) th[j][i] = gelu_tanh(p[c][4 * s + i]);
        gg[j][i] = gelu_fin(p[c][4 * s + i], th[j][i]);
      }
      wg_fence();
      if (j == 0) wgmma_n96_f16<0>(acc, gg[j], d2); else wgmma_n96_f16<1>(acc, gg[j], d2 + (16 * (j % 3) + j / 3) * (1536 >> 4));
      const int c1 = (j + 1) / KS + 1, u = (j + 1) % KS;
      if (c1 < NC) gemm1(p[c1], a, d1, c1, (6 * u) / KS, (6 * (u + 1)) / KS);
      wg_commit();
      if (s + 1 < KS) {
#pragma unroll
        for (int i = 0; i < PRE; i++) th[j + 1][i] = gelu_tanh(p[c][4 * s + 4 + i]);
      }
      if (j < 23) SCHED_FENCE();
    }
    pending = rdy != rtarget;
    bulk_load<3072>(abuf, asrc + (n4[1] & ~1u), bar, pending ? -1 : (int)n4[0]);
    wg_wait<0>();
    mbar_wait(bar + 128, phx); phx ^= 1;
#pragma unroll
    for (int k = 0; k < 24; k++) acc[k] = h2mul(acc[k], GELU_S2);
    char* const op = (char*)out + (cur[2] * 2 + (cur[3] & 255) * 3072 + (cur[3] >> 8) * (512 * 192) + pofs);
    lds128(n2, tp + 32);
#pragma unroll
    for (int k = 0; k < 6; k++) {
      const int hi = k / 3, j = k % 3;
      uint32_t xr[4];
      lds128(xr, xd + hi * 1536 + j * 64);
      uint4 o;
      o.x = hadd2_bf16(xr[0], pack_bf16(h_lo(acc[8 * j + hi]), h_hi(acc[8 * j + hi])));
      o.y = hadd2_bf16(xr[1], pack_bf16(h_lo(acc[8 * j + 2 + hi]), h_hi(acc[8 * j + 2 + hi])));
      o.z = hadd2_bf16(xr[2], pack_bf16(h_lo(acc[8 * j + 4 + hi]), h_hi(acc[8 * j + 4 + hi])));
      o.w = hadd2_bf16(xr[3], pack_bf16(h_lo(acc[8 * j + 6 + hi]), h_hi(acc[8 * j + 6 + hi])));
      stg128_stream(op + hi * (512 * 192) + j * 64, o, pol);
    }
    __syncwarp();
    if ((int)n2[0] >= 0) fetch_x(xbuf, obar + 128, tmr, n2[2] + w * 192, n2[3], pol);
    tp += 64;
#pragma unroll
    for (int k = 0; k < 4; k++) cur[k] = n4[k];
  }
}

__device__ __forceinline__ void conv_compute(uint32_t sb, Globals* gs, int third, int nit, int off, bool edge, bool up, int warp, int lane) {
  const int g = lane >> 2, t = lane & 3;
  const uint32_t full = sb + CM;
  const uint32_t wt = sb + 16384 + warp * 1024;
  sts128(wt + lane * 16, make_uint4(0, 0, 0, 0));
  if (lane < 4) sts128(wt + 512 + lane * 16, make_uint4(0, 0, 0, 0));
  asm volatile("setmaxnreg.inc.sync.aligned.u32 232;");
  uint32_t meta = 0;
#pragma unroll
  for (int a = 0; a < 4; a++) meta |= ((4 * (t & 1) + a + 1 >= g) ? 0x80008u : 0xD000Du) << (4 * a);
  meta = __shfl_sync(0xffffffffu, meta, lane);
  uint32_t aq[4];
#pragma unroll
  for (int q = 0; q < 4; q++) {
    const int pp = (g & 1) * 140 + (t & 1) * 70 + 16 * (g >> 1) + 2 * q + (t >> 1);
    aq[q] = __shfl_sync(0xffffffffu, sb + RBUF + pp * 64 + (((warp >> 1) ^ ((pp >> 1) & 3)) << 4) + (warp & 1) * 8, lane);
  }
  const int Q = third * 8 + warp;
  unsigned char* const obase = gs->scratch + (g >> 1) * 3072 + Q * 128 + (((2 * t + (g & 1)) ^ (2 * (Q & 3))) << 4);
  const float zero4[4] = {0.f, 0.f, 0.f, 0.f};
  float S[2][4][3][4];
  __syncwarp();
#pragma unroll
  for (int i = 0; i < 8; i++) {
    lds128((uint32_t*)S[i >> 2][i & 3][0], wt + i * 16);
#pragma unroll
    for (int k = 0; k < 8; k++) asm volatile("" : "=f"(S[i >> 2][i & 3][1 + (k >> 2)][k & 3]));
  }
  uint32_t A[4][4][4];
  asm volatile("bar.sync 5, 288;" ::: "memory");
  mbar_wait(sb + WBAR + 8, 0);
  {
#pragma unroll
    for (int k = 0; k < 2; k++) {
      const int tap = lane + 32 * k;
      if (tap < 49) sts64(wt + (tap + tap / 7 + 8) * 8, lds64(sb + tap * 192 + third * 64 + warp * 8));
    }
    __syncwarp();
    uint2 w[2][4][3];
#pragma unroll
    for (int h = 0; h < 2; h++) {
      uint32_t src = wt + ((4 * h + t - g) & 7) * 8 + (up ? 384 : 0);
#pragma unroll
      for (int u = 0; u < 4; u++) {
#pragma unroll
        for (int k = 0; k < 3; k++) w[h][u][k] = lds64(src + k * 64);
        src += up ? -128 : 128;
      }
    }
#pragma unroll
    for (int u = 0; u < 4; u++)
#pragma unroll
      for (int r = 0; r < 4; r++) {
        const uint2 w0 = w[r >> 1][u][1 - (r & 1)], w1 = w[r >> 1][u][2 - (r & 1)];
        A[0][u][r] = prmt(w0.x, w1.x, 0x5410); A[1][u][r] = prmt(w0.x, w1.x, 0x7632);
        A[2][u][r] = prmt(w0.y, w1.y, 0x5410); A[3][u][r] = prmt(w0.y, w1.y, 0x7632);
      }
  }
  uint32_t sofs = off * SLOTB, bar = full + off * 8, ph = 0, ot = sb + CTAB;
  const uint32_t oend = ot + nit * 16;
  asm volatile("bar.sync 0, 512;" ::: "memory");
  mbar_wait(bar, 0);
  uint2 X[3][4];
#pragma unroll 1
  for (int wu = edge; wu < 3; wu++) {
#pragma unroll
    for (int j = 0; j < 3; j++)
#pragma unroll
      for (int q = 0; q < 4; q++) X[j][q] = lds64(aq[q] + sofs + j * 512);
    mbar_arrive_elect(bar + 64);
    uint32_t B[8][4];
#pragma unroll
    for (int i = 0; i < 8; i++)
#pragma unroll
      for (int q = 0; q < 4; q++) B[i][q] = prmt((i & 2) ? X[i >> 2][q].y : X[i >> 2][q].x, (i & 2) ? X[(i >> 2) + 1][q].y : X[(i >> 2) + 1][q].x, (i & 1) ? 0x7632 : 0x5410);
    if (wu >= 1) {
      if (wu >= 2) {
        SCHED_FENCE();
#pragma unroll
        for (int i = 0; i < 8; i++) mma_sp(S[i >> 2][i & 3][2], A[i & 3][2], B[i], S[i >> 2][i & 3][1], meta);
      }
      SCHED_FENCE();
#pragma unroll
      for (int i = 0; i < 8; i++) mma_sp(S[i >> 2][i & 3][1], A[i & 3][1], B[i], S[i >> 2][i & 3][0], meta);
    }
#pragma unroll
    for (int i = 0; i < 8; i++) mma_sp(S[i >> 2][i & 3][0], A[i & 3][0], B[i], zero4, meta);
    sofs += SLOTB; bar += 8; ot += 16;
    if (sofs == NSLOT * SLOTB) { sofs = 0; bar = full; ph ^= 1; }
    mbar_wait(bar, ph);
  }
#pragma unroll
  for (int j = 0; j < 2; j++)
#pragma unroll
    for (int q = 0; q < 4; q++) X[j][q] = lds64(aq[q] + sofs + j * 512);
#pragma unroll 1
  do {
    const uint2 oe = lds64(ot);
    unsigned char* const o = obase + oe.x;
    const uint32_t dbar = bar + 64;
#pragma unroll
    for (int s = 0; s < 2; s++) {
      uint32_t B[4][4];
      if (s == 1) {
        sofs += SLOTB; bar += 8;
        if (sofs == NSLOT * SLOTB) { sofs = 0; bar = full; ph ^= 1; }
        mbar_wait(bar, ph);
      }
#pragma unroll
      for (int c = 0; c < 4; c++)
#pragma unroll
        for (int q = 0; q < 4; q++) B[c][q] = prmt(c < 2 ? X[s][q].x : X[s][q].y, c < 2 ? X[s + 1][q].x : X[s + 1][q].y, (c & 1) ? 0x7632 : 0x5410);
      if (s == 0) {
#pragma unroll
        for (int q = 0; q < 4; q++) X[2][q] = lds64(aq[q] + sofs + 2 * 512);
      } else {
#pragma unroll
        for (int j = 0; j < 2; j++)
#pragma unroll
          for (int q = 0; q < 4; q++) X[j][q] = lds64(aq[q] + sofs + j * 512);
      }
      float T[4][4];
      SCHED_FENCE();
#pragma unroll
      for (int c = 0; c < 4; c++) mma_sp(T[c], A[c][3], B[c], S[s][c][2], meta);
#pragma unroll
      for (int c = 0; c < 4; c++) mma_sp(S[s][c][2], A[c][2], B[c], S[s][c][1], meta);
      stg128_if(oe.x, o + (2 * s) * TILEB, make_uint4((pack_f16_sat(T[0][0], T[1][0]) & ~1u) | oe.y, pack_f16_sat(T[2][0], T[3][0]), pack_f16_sat(T[0][2], T[1][2]), pack_f16_sat(T[2][2], T[3][2])));
      stg128_if(oe.x, o + (2 * s + 1) * TILEB, make_uint4((pack_f16_sat(T[0][1], T[1][1]) & ~1u) | oe.y, pack_f16_sat(T[2][1], T[3][1]), pack_f16_sat(T[0][3], T[1][3]), pack_f16_sat(T[2][3], T[3][3])));
      if (s == 1) mbar_arrive_elect(dbar);
#pragma unroll
      for (int c = 0; c < 4; c++) mma_sp(S[s][c][1], A[c][1], B[c], S[s][c][0], meta);
#pragma unroll
      for (int c = 0; c < 4; c++) mma_sp(S[s][c][0], A[c][0], B[c], zero4, meta);
    }
    ot += 16;
  } while (ot != oend);
}

__device__ __forceinline__ void load_step(uint32_t sb, const CUtensorMap* tmx, int gm, int third, int it, int s, bool first = false) {
  const int seg = first ? 0 : it / (LM + 3);
  const int st = group_strip(gm, seg), J = gm < 8 ? ((gm & 1) ? 257 - it : it + 1) : group_base(gm) + it - seg * (LM + 3);
  asm volatile("{\n.reg .pred p;\n.reg .s32 c2;\n.reg .u32 d2;\nelect.sync _|p, 0xffffffff;\nadd.s32 c2, %4, 64;\nadd.u32 d2, %0, 8960;\n"
               "@p mbarrier.arrive.expect_tx.shared::cta.b64 _, [%2], 17920;\n"
               "@p cp.async.bulk.tensor.3d.shared::cluster.global.mbarrier::complete_tx::bytes [%0], [%1, {%3, %4, %5}], [%2];\n"
               "@p cp.async.bulk.tensor.3d.shared::cluster.global.mbarrier::complete_tx::bytes [d2], [%1, {%3, c2, %5}], [%2];\n}"
               ::"r"(sb + RBUF + s * SLOTB), "l"(tmx), "r"(sb + CM + s * 8), "r"(third * 32), "r"(st * 128 - 3), "r"(2 * J - 3) : "memory");
}
__device__ __forceinline__ void ring_bar_init(uint32_t bar, uint32_t cnt, bool ahead) {
  asm volatile("{\n.reg .pred p, q;\nelect.sync _|p, 0xffffffff;\n@p mbarrier.init.shared::cta.b64 [%0], %1;\n"
               "setp.ne.and.u32 q, %2, 0, p;\n@q mbarrier.arrive.shared::cta.b64 _, [%0], %1;\n@p fence.mbarrier_init.release.cluster;\n}" ::"r"(bar), "r"(cnt), "r"((uint32_t)ahead) : "memory");
}
__device__ __forceinline__ void conv_loader(uint32_t sb, Globals* gs, const CUtensorMap* tmx, int gm, int nit, int off, int cidx, int third, int k) {
  static_assert(FIRST >= 4 && NCONV >= 24, "loader");
  const uint32_t full = sb + CM;
  asm volatile("bar.sync 0, 512;" ::: "memory");
  if (FIRST + k < NSLOT) load_step(sb, tmx, gm, third, FIRST + k, (FIRST + k + off) & 7, true);
#pragma unroll 1
  for (int it = NSLOT + k; it < nit + NSLOT; it += 4) {
    const int u = it + off;
    const uint32_t ro = lds32(sb + CTAB + (it - NSLOT) * 16 + 8);
    mbar_wait(full + 64 + (u & 7) * 8, ((u >> 3) & 1) ^ 1);
    red_add_elect((uint32_t*)((char*)gs + ro));
    if (it < nit) load_step(sb, tmx, gm, third, it, u & 7);
    else if (it == nit) mbar_arrive_elect(full);
    if (it >= nit - 16) {
      const bool pre = it < nit - 12 && cidx < 24;
      if (pre || it == nit - 1) {
        wait_value(gs->wflag, 12 * lds32(sb + MISC + 256), 32);
        asm volatile("fence.acquire.gpu;\nfence.proxy.async.global;" ::: "memory");
      }
      if (pre) asm volatile("{.reg .pred p; elect.sync _|p, 0xffffffff; @p cp.async.bulk.prefetch.L2.global [%0], 1536;}" ::"l"(gs->wimg + (cidx * 4 + k) * 1536) : "memory");
      const int m = it == nit - 1 ? 0 : W2S;
      if (it == nit - 1 || it == nit + 3) bulk_load<73728>(sb + m, gs->wimg + m, sb + WBAR);
    }
  }
}

__device__ __forceinline__ void conv_credit(uint32_t sb, Globals* gs, int q0, int nit, int off, uint32_t ctarget, int k) {
  const uint32_t full = sb + CM;
#pragma unroll 1
  for (int it = k + NSLOT; it <= nit; it += 4) {
    const int u = it + off, q = (int)lds32(sb + CTAB + it * 16 + 12) - RING;
    mbar_wait(full + 64 + (u & 7) * 8, ((u >> 3) & 1) ^ 1);
    if (q >= q0) wait_value(&gs->cons[q], ctarget, 200);
    mbar_arrive_elect(full + (u & 7) * 8);
  }
}

__device__ __noinline__ int generic_role() {
  const int cidx = (blockIdx.x * NCONV) / gridDim.x;
  return cidx | ((((blockIdx.x + 1) * NCONV) / gridDim.x != cidx) << 16);
}

__global__ void __launch_bounds__(512, 1) convnext_kernel(const __nv_bfloat16* __restrict__ dw, const __nv_bfloat16* __restrict__ w1, const __nv_bfloat16* __restrict__ w2,
                                                          __nv_bfloat16* __restrict__ out, Globals* gs, int want_sms,
                                                          const __grid_constant__ CUtensorMap tmx, const __grid_constant__ CUtensorMap tmr) {
  extern __shared__ __align__(1024) unsigned char smem[];
  const uint32_t sb = smem_u32(smem);
  const int warp = __shfl_sync(0xffffffffu, threadIdx.x >> 5, 0), lane = threadIdx.x & 31;
  uint32_t smid, nsmid;
  asm volatile("mov.u32 %0, %%smid;" : "=r"(smid));
  asm volatile("mov.u32 %0, %%nsmid;" : "=r"(nsmid));
  const bool tabled = TABLED && (int)nsmid == want_sms;
  const int id = tabled ? smid : blockIdx.x;
  int cidx, idx, is_conv;
  if (tabled) {
    idx = smid;
    const int k = (smid - 60) / 14, r = smid - 60 - 14 * k;
    is_conv = smid < 48 ? LT || !(smid & 1) : (smid >= 60 && smid <= 90 && (r & ~(2 * SCHED_NMID - 2)) == 0);
    cidx = smid < 48 ? (((smid >> 1) & 7) + (smid & 1) * NP) * 3 + (smid >> 4) : 24 + (r >> 1) * 3 + k;
  } else {
    const int r = generic_role();
    cidx = r & 0xffff; is_conv = r >> 16;
    idx = blockIdx.x - cidx;
  }
  const int gm = cidx / 3, third = cidx - gm * 3;
  const int q0 = gm * PLEN, nit = gm < 8 ? PLEN + 2 : gm < NP ? NSEG * (LM + 3) : LT + 3, off = (8 - nit) & 7;
  if (is_conv && warp == 8) {
    bulk_load<9408, true>(sb, dw, sb + WBAR + 8);
    asm volatile("bar.arrive 5, 288;" ::: "memory");
#pragma unroll 1
    for (int it = 0; it < NSLOT; it++) {
      const int s = (it + off) & 7;
      ring_bar_init(sb + CM + s * 8, 2, s < off);
      if (it < FIRST) load_step(sb, &tmx, gm, third, it, s, true);
    }
  }
  if (warp == 15) asm volatile("prefetch.tensormap [%0];" ::"l"(&tmr) : "memory");
  mbar_init_elect(sb + MISC + warp * 8, 1); mbar_init_elect(sb + MISC + 128 + warp * 8, 1);
  asm volatile("fence.mbarrier_init.release.cluster;" ::: "memory");
  if (is_conv) {
    if (warp >= 8) ring_bar_init(sb + CM + warp * 8, 8, warp - 8 < off);
    if (warp == 9) mbar_init_elect(sb + WBAR, 2);
    const uint32_t lastph = (((nit + off) >> 3) & 1) ^ 1;
    if (warp < 8) {
      conv_compute(sb, gs, third, nit, off, gm < 8, gm < 8 && (gm & 1), warp, lane);
      asm volatile("setmaxnreg.dec.sync.aligned.u32 128;");
    } else if (warp >= 12) {
      asm volatile("setmaxnreg.dec.sync.aligned.u32 24;");
      const uint32_t epoch = ld_relaxed(&gs->epoch[id]);
#pragma unroll 1
      for (int it = threadIdx.x - 384; it <= nit; it += 128) {
        const int seg = it / (LM + 3), j = gm < 8 ? it - 2 : it - 3 * (seg + 1);
        const bool ok = it < nit && j >= (gm < 8 ? 0 : seg * LM);
        sts128(sb + CTAB + it * 16, make_uint4((ok ? (j % RING) * NG + gm : -1) * (4 * TILEB), slot_tag(gm, max(j, 0), epoch),
                                               offsetof(Globals, ready) + (ok ? q0 + j : NG * PLEN) * 4, ok ? q0 + j : -1));
      }
      if (threadIdx.x == 384) sts32(sb + MISC + 256, epoch + 1);
      asm volatile("bar.sync 0, 512;" ::: "memory");
      mbar_arrive_elect(sb + CM + ((((warp + 2) & 3) + off) & 7) * 8);
      mbar_arrive_elect(sb + CM + ((((warp + 2) & 3) + off + 4) & 7) * 8);
      build_tile_list(sb, threadIdx.x - 384, idx, tabled, true, epoch);
      if (threadIdx.x == 384) gs->epoch[id] = epoch + 1;
      asm volatile("bar.sync 6, 128;" ::: "memory");
      conv_credit(sb, gs, q0, nit, off, 16 * (epoch + 1), (warp + 2) & 3);
#pragma unroll 1
      for (int i = 0; i < 4; i++) {
        const uint2 e = lds64(sb + MISC + 512 + i * 16);
        mbar_wait(sb + CM + 64 + (4 + min(i, 2)) * 8, lastph);
        const int wi = 4 * i + (warp & 3);
        if ((int)e.x >= 0) bulk_load<3072>(sb + ABUF + wi * 3072, gs->scratch + (e.y & ~1u) + (warp & 3) * 3072, sb + MISC + wi * 8);
      }
      mbar_wait(sb + CM + 64 + 7 * 8, lastph);
      asm volatile("setmaxnreg.inc.sync.aligned.u32 128;");
    } else {
      asm volatile("setmaxnreg.dec.sync.aligned.u32 24;");
      conv_loader(sb, gs, &tmx, gm, nit, off, cidx, third, warp & 3);
      mbar_wait(sb + CM + 64 + 7 * 8, lastph);
      asm volatile("setmaxnreg.inc.sync.aligned.u32 128;");
    }
    mbar_wait(sb + WBAR, 0);
    asm volatile("bar.sync 0, 512;" ::: "memory");
  } else {
    mlp_setup(sb, gs, id, w1, w2, idx, tabled, warp, lane);
  }
  mlp_role(sb, gs, &tmr, out);
}

typedef CUresult (*PFN_encodeTiled)(CUtensorMap*, CUtensorMapDataType, cuuint32_t, void*, const cuuint64_t*, const cuuint64_t*, const cuuint32_t*, const cuuint32_t*,
                                    CUtensorMapInterleave, CUtensorMapSwizzle, CUtensorMapL2promotion, CUtensorMapFloatOOBfill);

extern "C" void kernel_launch(void* const* d_in, const int* in_sizes, int n_in, void* d_out, int out_size) {
  const __nv_bfloat16* x = (const __nv_bfloat16*)d_in[0];
  const __nv_bfloat16* dw = (const __nv_bfloat16*)d_in[1];
  const __nv_bfloat16* w1 = (const __nv_bfloat16*)d_in[2];
  const __nv_bfloat16* w2 = (const __nv_bfloat16*)d_in[3];
  static PFN_encodeTiled encode = nullptr;
  static int nsm = 0;
  static Globals* gs = nullptr;
  if (!encode) {
    void* fn = nullptr; cudaDriverEntryPointQueryResult qr;
    cudaGetDriverEntryPoint("cuTensorMapEncodeTiled", &fn, cudaEnableDefault, &qr);
    encode = (PFN_encodeTiled)fn;
    cudaGetSymbolAddress((void**)&gs, g_state);
    int dev = 0; cudaGetDevice(&dev);
    cudaDeviceGetAttribute(&nsm, cudaDevAttrMultiProcessorCount, dev);
    cudaFuncSetAttribute(convnext_kernel, cudaFuncAttributeMaxDynamicSharedMemorySize, SMEM_BYTES);
  }
  CUtensorMap tm, tr;
  cuuint64_t dims[3] = {96, 512, 512}, strides[2] = {192, 192 * 512};
  cuuint32_t box[3] = {32, 70, 2}, es[3] = {1, 1, 1};
  encode(&tm, CU_TENSOR_MAP_DATA_TYPE_BFLOAT16, 3, (void*)x, dims, strides, box, es, CU_TENSOR_MAP_INTERLEAVE_NONE, CU_TENSOR_MAP_SWIZZLE_64B,
         CU_TENSOR_MAP_L2_PROMOTION_L2_128B, CU_TENSOR_MAP_FLOAT_OOB_FILL_NONE);
  cuuint64_t dims2[3] = {1536, 32, 512}, strides2[2] = {3072, 192 * 512};
  cuuint32_t box2[3] = {192, 4, 2};
  encode(&tr, CU_TENSOR_MAP_DATA_TYPE_BFLOAT16, 3, (void*)x, dims2, strides2, box2, es, CU_TENSOR_MAP_INTERLEAVE_NONE, CU_TENSOR_MAP_SWIZZLE_NONE,
         CU_TENSOR_MAP_L2_PROMOTION_NONE, CU_TENSOR_MAP_FLOAT_OOB_FILL_NONE);
  convnext_kernel<<<nsm, 512, SMEM_BYTES>>>(dw, w1, w2, (__nv_bfloat16*)d_out, gs, nsm == 132 ? 132 : -1, tm, tr);
}
```

```cpp
#include <cuda_runtime.h>
#include <cuda_bf16.h>
#include <cuda.h>
#include <stdint.h>
#include <stddef.h>

template<int SCALE_D> __device__ __forceinline__ void wgmma_n64_f16(uint32_t* d, const uint32_t* a, uint64_t desc) {
  if (SCALE_D == 0) asm volatile("wgmma.mma_async.sync.aligned.m64n64k16.f16.f16.f16 {%0,%1,%2,%3,%4,%5,%6,%7,%8,%9,%10,%11,%12,%13,%14,%15}, {%16,%17,%18,%19}, %20, 0, 1, 1, 1;"
    : "=r"(d[0]),"=r"(d[1]),"=r"(d[2]),"=r"(d[3]),"=r"(d[4]),"=r"(d[5]),"=r"(d[6]),"=r"(d[7]),"=r"(d[8]),"=r"(d[9]),"=r"(d[10]),"=r"(d[11]),"=r"(d[12]),"=r"(d[13]),"=r"(d[14]),"=r"(d[15])
    : "r"(a[0]),"r"(a[1]),"r"(a[2]),"r"(a[3]),"l"(desc));
  if (SCALE_D == 1) asm volatile("wgmma.mma_async.sync.aligned.m64n64k16.f16.f16.f16 {%0,%1,%2,%3,%4,%5,%6,%7,%8,%9,%10,%11,%12,%13,%14,%15}, {%16,%17,%18,%19}, %20, 1, 1, 1, 1;"
    : "+r"(d[0]),"+r"(d[1]),"+r"(d[2]),"+r"(d[3]),"+r"(d[4]),"+r"(d[5]),"+r"(d[6]),"+r"(d[7]),"+r"(d[8]),"+r"(d[9]),"+r"(d[10]),"+r"(d[11]),"+r"(d[12]),"+r"(d[13]),"+r"(d[14]),"+r"(d[15])
    : "r"(a[0]),"r"(a[1]),"r"(a[2]),"r"(a[3]),"l"(desc));
}

template<int SCALE_D> __device__ __forceinline__ void wgmma_n96_f16(uint32_t* d, const uint32_t* a, uint64_t desc) {
  if (SCALE_D == 0) asm volatile("wgmma.mma_async.sync.aligned.m64n96k16.f16.f16.f16 {%0,%1,%2,%3,%4,%5,%6,%7,%8,%9,%10,%11,%12,%13,%14,%15,%16,%17,%18,%19,%20,%21,%22,%23}, {%24,%25,%26,%27}, %28, 0, 1, 1, 1;"
    : "=r"(d[0]),"=r"(d[1]),"=r"(d[2]),"=r"(d[3]),"=r"(d[4]),"=r"(d[5]),"=r"(d[6]),"=r"(d[7]),"=r"(d[8]),"=r"(d[9]),"=r"(d[10]),"=r"(d[11]),"=r"(d[12]),"=r"(d[13]),"=r"(d[14]),"=r"(d[15]),"=r"(d[16]),"=r"(d[17]),"=r"(d[18]),"=r"(d[19]),"=r"(d[20]),"=r"(d[21]),"=r"(d[22]),"=r"(d[23])
    : "r"(a[0]),"r"(a[1]),"r"(a[2]),"r"(a[3]),"l"(desc));
  if (SCALE_D == 1) asm volatile("wgmma.mma_async.sync.aligned.m64n96k16.f16.f16.f16 {%0,%1,%2,%3,%4,%5,%6,%7,%8,%9,%10,%11,%12,%13,%14,%15,%16,%17,%18,%19,%20,%21,%22,%23}, {%24,%25,%26,%27}, %28, 1, 1, 1, 1;"
    : "+r"(d[0]),"+r"(d[1]),"+r"(d[2]),"+r"(d[3]),"+r"(d[4]),"+r"(d[5]),"+r"(d[6]),"+r"(d[7]),"+r"(d[8]),"+r"(d[9]),"+r"(d[10]),"+r"(d[11]),"+r"(d[12]),"+r"(d[13]),"+r"(d[14]),"+r"(d[15]),"+r"(d[16]),"+r"(d[17]),"+r"(d[18]),"+r"(d[19]),"+r"(d[20]),"+r"(d[21]),"+r"(d[22]),"+r"(d[23])
    : "r"(a[0]),"r"(a[1]),"r"(a[2]),"r"(a[3]),"l"(desc));
}

#define SCHED_NMID 1
#define SCHED_LE 106
#define SCHED_LT 10
#define SCHED_RING 16
#define SCHED_MID0 50
#define SCHED_MID1 64
#define SCHED_MID2 78
__device__ const uint16_t g_sched[132][48] = {
{388,391,394,65535,65535,65535,65535,65535,65535,65535,65535,65535,65535,65535,65535,65535,65535,65535,65535,65535,65535,65535,65535,65535,65535,65535,65535,65535,65535,65535,65535,65535,65535,65535,65535,65535,65535,65535,65535,65535,65535,65535,65535,65535,65535,65535,65535,65535},
{3824,3827,3830,3833,42,52,64,75,87,99,112,123,135,147,158,170,182,193,205,218,229,241,253,265,276,288,300,311,324,336,348,359,371,383,404,415,65535,65535,65535,65535,65535,65535,65535,65535,65535,65535,65535,65535},
{812,815,818,65535,65535,65535,65535,65535,65535,65535,65535,65535,65535,65535,65535,65535,65535,65535,65535,65535,65535,65535,65535,65535,65535,65535,65535,65535,65535,65535,65535,65535,65535,65535,65535,65535,65535,65535,65535,65535,65535,65535,65535,65535,65535,65535,65535,65535},
{4248,4251,4254,4257,4278,478,489,501,513,524,3489,549,561,572,584,596,607,619,631,3584,655,667,679,690,702,714,725,737,751,762,773,785,797,808,829,841,65535,65535,65535,65535,65535,65535,65535,65535,65535,65535,65535,65535},
{1236,1239,1242,65535,65535,65535,65535,65535,65535,65535,65535,65535,65535,65535,65535,65535,65535,65535,65535,65535,65535,65535,65535,65535,65535,65535,65535,65535,65535,65535,65535,65535,65535,65535,65535,65535,65535,65535,65535,65535,65535,65535,65535,65535,65535,65535,65535,65535},
{4672,4675,4678,4681,891,902,913,925,937,948,961,973,985,996,1008,1020,1031,1043,1055,1067,1080,1091,1103,1114,1126,1138,1149,1161,1173,1186,1197,1209,1221,1232,1253,1265,65535,65535,65535,65535,65535,65535,65535,65535,65535,65535,65535,65535},
{1660,1663,1666,65535,65535,65535,65535,65535,65535,65535,65535,65535,65535,65535,65535,65535,65535,65535,65535,65535,65535,65535,65535,65535,65535,65535,65535,65535,65535,65535,65535,65535,65535,65535,65535,65535,65535,65535,65535,65535,65535,65535,65535,65535,65535,65535,65535,65535},
{5096,5099,5102,5105,1315,1325,1337,1349,1360,1372,1385,1397,1408,1420,1432,1443,1455,1467,1478,1491,1503,1515,1526,1538,1550,1561,1573,1585,1597,1609,1621,1633,1644,1656,1677,1688,65535,65535,65535,65535,65535,65535,65535,65535,65535,65535,65535,65535},
{2084,2087,2090,65535,65535,65535,65535,65535,65535,65535,65535,65535,65535,65535,65535,65535,65535,65535,65535,65535,65535,65535,65535,65535,65535,65535,65535,65535,65535,65535,65535,65535,65535,65535,65535,65535,65535,65535,65535,65535,65535,65535,65535,65535,65535,65535,65535,65535},
{5520,5523,5526,5529,1739,1750,1762,1773,1785,1797,1809,1821,1833,1845,1856,1868,1880,1891,1903,1916,1928,1939,1951,1963,1974,1986,1998,2009,2022,2034,2046,2057,2069,2081,2101,2113,65535,65535,65535,65535,65535,65535,65535,65535,65535,65535,65535,65535},
{2508,2511,2514,65535,65535,65535,65535,65535,65535,65535,65535,65535,65535,65535,65535,65535,65535,65535,65535,65535,65535,65535,65535,65535,65535,65535,65535,65535,65535,65535,65535,65535,65535,65535,65535,65535,65535,65535,65535,65535,65535,65535,65535,65535,65535,65535,65535,65535},
{5944,5947,5950,5953,2163,2174,2186,2197,2209,2221,2234,2245,2257,2269,2280,2292,2304,2315,2327,2340,2352,2363,2375,2387,2398,2410,2422,2433,2446,2458,2470,2481,2493,2505,2525,2537,65535,65535,65535,65535,65535,65535,65535,65535,65535,65535,65535,65535},
{2932,2935,2938,65535,65535,65535,65535,65535,65535,65535,65535,65535,65535,65535,65535,65535,65535,65535,65535,65535,65535,65535,65535,65535,65535,65535,65535,65535,65535,65535,65535,65535,65535,65535,65535,65535,65535,65535,65535,65535,65535,65535,65535,65535,65535,65535,65535,65535},
{6368,6371,6374,6377,6399,2599,3453,3465,2634,2646,2659,3501,2682,3524,3536,2717,3559,3571,2752,2765,3595,3607,2800,3630,3642,2835,3665,3677,2871,2883,3701,3713,2918,3736,2950,2962,65535,65535,65535,65535,65535,65535,65535,65535,65535,65535,65535,65535},
{3356,3359,3362,65535,65535,65535,65535,65535,65535,65535,65535,65535,65535,65535,65535,65535,65535,65535,65535,65535,65535,65535,65535,65535,65535,65535,65535,65535,65535,65535,65535,65535,65535,65535,65535,65535,65535,65535,65535,65535,65535,65535,65535,65535,65535,65535,65535,65535},
{6792,6795,6798,6801,3012,3022,3034,3046,3057,3069,3082,3094,3105,3117,3129,3140,3152,3164,3175,3188,3200,3212,3223,3235,3247,3258,3270,3282,3295,3306,3318,3330,3341,3353,3374,3385,65535,65535,65535,65535,65535,65535,65535,65535,65535,65535,65535,65535},
{389,392,395,65535,65535,65535,65535,65535,65535,65535,65535,65535,65535,65535,65535,65535,65535,65535,65535,65535,65535,65535,65535,65535,65535,65535,65535,65535,65535,65535,65535,65535,65535,65535,65535,65535,65535,65535,65535,65535,65535,65535,65535,65535,65535,65535,65535,65535},
{3825,3828,3831,3834,3854,53,65,76,88,100,113,124,136,148,159,171,183,194,206,219,230,242,254,266,277,289,301,312,325,337,349,360,372,384,405,416,65535,65535,65535,65535,65535,65535,65535,65535,65535,65535,65535,65535},
{813,816,819,65535,65535,65535,65535,65535,65535,65535,65535,65535,65535,65535,65535,65535,65535,65535,65535,65535,65535,65535,65535,65535,65535,65535,65535,65535,65535,65535,65535,65535,65535,65535,65535,65535,65535,65535,65535,65535,65535,65535,65535,65535,65535,65535,65535,65535},
{4249,4252,4255,4258,467,3442,490,502,3477,525,538,550,3513,573,585,3548,608,620,3583,645,656,668,3619,691,703,3654,726,738,752,3690,774,786,3725,809,3757,3769,65535,65535,65535,65535,65535,65535,65535,65535,65535,65535,65535,65535},
{1237,1240,1243,65535,65535,65535,65535,65535,65535,65535,65535,65535,65535,65535,65535,65535,65535,65535,65535,65535,65535,65535,65535,65535,65535,65535,65535,65535,65535,65535,65535,65535,65535,65535,65535,65535,65535,65535,65535,65535,65535,65535,65535,65535,65535,65535,65535,65535},
{4673,4676,4679,4682,4703,903,914,926,938,949,962,974,986,997,1009,1021,1032,1044,1056,1068,1081,1092,1104,1115,1127,1139,1150,1162,1174,1187,1198,1210,1222,1233,1254,1266,65535,65535,65535,65535,65535,65535,65535,65535,65535,65535,65535,65535},
{1661,1664,1667,65535,65535,65535,65535,65535,65535,65535,65535,65535,65535,65535,65535,65535,65535,65535,65535,65535,65535,65535,65535,65535,65535,65535,65535,65535,65535,65535,65535,65535,65535,65535,65535,65535,65535,65535,65535,65535,65535,65535,65535,65535,65535,65535,65535,65535},
{5097,5100,5103,5106,5127,1326,1338,1350,1361,1373,1386,1398,1409,1421,1433,1444,1456,1468,1479,1492,1504,1516,1527,1539,1551,1562,1574,1586,1598,1610,1622,1634,1645,1657,1678,1689,65535,65535,65535,65535,65535,65535,65535,65535,65535,65535,65535,65535},
{2085,2088,2091,65535,65535,65535,65535,65535,65535,65535,65535,65535,65535,65535,65535,65535,65535,65535,65535,65535,65535,65535,65535,65535,65535,65535,65535,65535,65535,65535,65535,65535,65535,65535,65535,65535,65535,65535,65535,65535,65535,65535,65535,65535,65535,65535,65535,65535},
{5521,5524,5527,5530,5551,1751,1763,1774,1786,1798,1810,1822,1834,1846,1857,1869,1881,1892,1904,1917,1929,1940,1952,1964,1975,1987,1999,2010,2023,2035,2047,2058,2070,2082,2102,2114,65535,65535,65535,65535,65535,65535,65535,65535,65535,65535,65535,65535},
{2509,2512,2515,65535,65535,65535,65535,65535,65535,65535,65535,65535,65535,65535,65535,65535,65535,65535,65535,65535,65535,65535,65535,65535,65535,65535,65535,65535,65535,65535,65535,65535,65535,65535,65535,65535,65535,65535,65535,65535,65535,65535,65535,65535,65535,65535,65535,65535},
{5945,5948,5951,5954,5975,2175,2187,2198,2210,2222,2235,2246,2258,2270,2281,2293,2305,2316,2328,2341,2353,2364,2376,2388,2399,2411,2423,2434,2447,2459,2471,2482,2494,2506,2526,2538,65535,65535,65535,65535,65535,65535,65535,65535,65535,65535,65535,65535},
{2933,2936,2939,65535,65535,65535,65535,65535,65535,65535,65535,65535,65535,65535,65535,65535,65535,65535,65535,65535,65535,65535,65535,65535,65535,65535,65535,65535,65535,65535,65535,65535,65535,65535,65535,65535,65535,65535,65535,65535,65535,65535,65535,65535,65535,65535,65535,65535},
{6369,6372,6375,6378,2588,2600,2611,2623,2635,2647,3490,2671,2683,2694,2706,2718,2729,2741,2753,2766,2777,2789,2801,2812,2824,2836,2847,2859,2872,2884,2895,2907,2919,2930,2951,2963,65535,65535,65535,65535,65535,65535,65535,65535,65535,65535,65535,65535},
{3357,3360,3363,65535,65535,65535,65535,65535,65535,65535,65535,65535,65535,65535,65535,65535,65535,65535,65535,65535,65535,65535,65535,65535,65535,65535,65535,65535,65535,65535,65535,65535,65535,65535,65535,65535,65535,65535,65535,65535,65535,65535,65535,65535,65535,65535,65535,65535},
{6793,6796,6799,6802,3431,3023,3035,3047,3058,3070,3083,3095,3106,3118,3130,3141,3153,3165,3176,3189,3201,3213,3224,3236,3248,3259,3271,3283,3296,3307,3319,3331,3342,3354,3375,3386,65535,65535,65535,65535,65535,65535,65535,65535,65535,65535,65535,65535},
{390,393,396,65535,65535,65535,65535,65535,65535,65535,65535,65535,65535,65535,65535,65535,65535,65535,65535,65535,65535,65535,65535,65535,65535,65535,65535,65535,65535,65535,65535,65535,65535,65535,65535,65535,65535,65535,65535,65535,65535,65535,65535,65535,65535,65535,65535,65535},
{3826,3829,3832,3835,43,54,66,77,89,101,114,125,137,149,160,172,184,195,207,220,231,243,255,267,278,290,302,313,326,338,350,361,373,385,406,417,65535,65535,65535,65535,65535,65535,65535,65535,65535,65535,65535,65535},
{814,817,820,65535,65535,65535,65535,65535,65535,65535,65535,65535,65535,65535,65535,65535,65535,65535,65535,65535,65535,65535,65535,65535,65535,65535,65535,65535,65535,65535,65535,65535,65535,65535,65535,65535,65535,65535,65535,65535,65535,65535,65535,65535,65535,65535,65535,65535},
{4250,4253,4256,4259,4279,479,3454,3466,514,526,539,3502,562,3525,3537,597,3560,3572,632,3585,3596,3608,680,3631,3643,715,3666,3678,3680,763,3702,3714,798,3737,830,842,65535,65535,65535,65535,65535,65535,65535,65535,65535,65535,65535,65535},
{1238,1241,1244,65535,65535,65535,65535,65535,65535,65535,65535,65535,65535,65535,65535,65535,65535,65535,65535,65535,65535,65535,65535,65535,65535,65535,65535,65535,65535,65535,65535,65535,65535,65535,65535,65535,65535,65535,65535,65535,65535,65535,65535,65535,65535,65535,65535,65535},
{4674,4677,4680,4683,892,904,915,927,939,950,963,975,987,998,1010,1022,1033,1045,1057,1069,1082,1093,1105,1116,1128,1140,1151,1163,1175,1188,1199,1211,1223,1234,1255,1267,65535,65535,65535,65535,65535,65535,65535,65535,65535,65535,65535,65535},
{1662,1665,1668,65535,65535,65535,65535,65535,65535,65535,65535,65535,65535,65535,65535,65535,65535,65535,65535,65535,65535,65535,65535,65535,65535,65535,65535,65535,65535,65535,65535,65535,65535,65535,65535,65535,65535,65535,65535,65535,65535,65535,65535,65535,65535,65535,65535,65535},
{5098,5101,5104,5107,1316,1327,1339,1351,1362,1374,1387,1399,1410,1422,1434,1445,1457,1469,1480,1493,1505,1517,1528,1540,1552,1563,1575,1587,1599,1611,1623,1635,1646,1658,1679,1690,65535,65535,65535,65535,65535,65535,65535,65535,65535,65535,65535,65535},
{2086,2089,2092,65535,65535,65535,65535,65535,65535,65535,65535,65535,65535,65535,65535,65535,65535,65535,65535,65535,65535,65535,65535,65535,65535,65535,65535,65535,65535,65535,65535,65535,65535,65535,65535,65535,65535,65535,65535,65535,65535,65535,65535,65535,65535,65535,65535,65535},
{5522,5525,5528,5531,1740,1752,1764,1775,1787,1799,1811,1823,1835,1847,1858,1870,1882,1893,1905,1918,1930,1941,1953,1965,1976,1988,2000,2011,2024,2036,2048,2059,2071,2083,2103,2115,65535,65535,65535,65535,65535,65535,65535,65535,65535,65535,65535,65535},
{2510,2513,2516,65535,65535,65535,65535,65535,65535,65535,65535,65535,65535,65535,65535,65535,65535,65535,65535,65535,65535,65535,65535,65535,65535,65535,65535,65535,65535,65535,65535,65535,65535,65535,65535,65535,65535,65535,65535,65535,65535,65535,65535,65535,65535,65535,65535,65535},
{5946,5949,5952,5955,2164,2176,2188,2199,2211,2223,2236,2247,2259,2271,2282,2294,2306,2317,2329,2342,2354,2365,2377,2389,2400,2412,2424,2435,2448,2460,2472,2483,2495,2507,2527,2539,65535,65535,65535,65535,65535,65535,65535,65535,65535,65535,65535,65535},
{2934,2937,2940,65535,65535,65535,65535,65535,65535,65535,65535,65535,65535,65535,65535,65535,65535,65535,65535,65535,65535,65535,65535,65535,65535,65535,65535,65535,65535,65535,65535,65535,65535,65535,65535,65535,65535,65535,65535,65535,65535,65535,65535,65535,65535,65535,65535,65535},
{6370,6373,6376,6379,2589,3443,2612,2624,3478,2648,2660,2672,3514,2695,2707,3549,2730,2742,2754,2767,2778,2790,3620,2813,2825,3655,2848,2860,2873,3691,2896,2908,3726,2931,3758,3770,65535,65535,65535,65535,65535,65535,65535,65535,65535,65535,65535,65535},
{3358,3361,3364,65535,65535,65535,65535,65535,65535,65535,65535,65535,65535,65535,65535,65535,65535,65535,65535,65535,65535,65535,65535,65535,65535,65535,65535,65535,65535,65535,65535,65535,65535,65535,65535,65535,65535,65535,65535,65535,65535,65535,65535,65535,65535,65535,65535,65535},
{6794,6797,6800,6803,3013,3024,3036,3048,3059,3071,3084,3096,3107,3119,3131,3142,3154,3166,3177,3190,3202,3214,3225,3237,3249,3260,3272,3284,3297,3308,3320,3332,3343,3355,3376,3387,65535,65535,65535,65535,65535,65535,65535,65535,65535,65535,65535,65535},
{0,429,12,21,27,32,37,3428,51,3449,497,86,3484,110,545,134,3520,580,169,3555,615,204,216,651,240,252,3626,698,287,3661,733,322,335,3697,781,370,3732,403,414,65535,65535,65535,65535,65535,65535,65535,65535,65535},
{1,3393,435,444,3839,3844,3849,4276,474,63,3461,509,98,111,3497,557,146,3532,592,181,3567,627,217,3591,663,675,264,3638,710,299,3673,323,758,347,3709,793,382,826,837,65535,65535,65535,65535,65535,65535,65535,65535,65535},
{3740,3743,3746,65535,65535,65535,65535,65535,65535,65535,65535,65535,65535,65535,65535,65535,65535,65535,65535,65535,65535,65535,65535,65535,65535,65535,65535,65535,65535,65535,65535,65535,65535,65535,65535,65535,65535,65535,65535,65535,65535,65535,65535,65535,65535,65535,65535,65535},
{424,4241,3399,3408,450,455,460,465,3438,486,498,3473,521,534,546,3509,569,581,3544,604,616,3579,640,652,3603,3615,687,699,3650,722,734,746,3686,770,782,3721,805,3754,3765,65535,65535,65535,65535,65535,65535,65535,65535,65535},
{848,4666,859,867,4686,4690,4695,4700,897,908,920,932,943,956,968,980,991,1003,1015,1026,1038,1050,1062,1075,1086,1098,1109,1121,1133,1144,1156,1168,1181,1192,1204,1216,1227,1248,1260,65535,65535,65535,65535,65535,65535,65535,65535,65535},
{849,855,4671,868,875,879,884,889,898,909,921,933,944,957,969,981,992,1004,1016,1027,1039,1051,1063,1076,1087,1099,1110,1122,1134,1145,1157,1169,1182,1193,1205,1217,1228,1249,1261,65535,65535,65535,65535,65535,65535,65535,65535,65535},
{1272,1279,5095,1292,1299,5115,1308,1313,1322,1334,1345,1357,1369,1381,1393,1405,1417,1428,1440,1452,1463,1475,1487,1500,1511,1523,1535,1546,1558,1570,1581,1593,1606,1618,1629,1641,1653,1673,1685,65535,65535,65535,65535,65535,65535,65535,65535,65535},
{1273,5091,1284,1293,5111,1304,5120,5125,1323,1335,1346,1358,1370,1382,1394,1406,1418,1429,1441,1453,1464,1476,1488,1501,1512,1524,1536,1547,1559,1571,1582,1594,1607,1619,1630,1642,1654,1674,1686,65535,65535,65535,65535,65535,65535,65535,65535,65535},
{1696,1703,1708,1716,1723,1728,1732,1737,1746,1758,1769,1781,1793,1805,1817,1829,1841,1852,1864,1876,1887,1899,1912,1924,1936,1947,1959,1970,1982,1994,2005,2018,2030,2042,2053,2065,2077,2097,2109,65535,65535,65535,65535,65535,65535,65535,65535,65535},
{1697,5515,4247,1717,5535,5540,5544,5549,1747,1759,1770,1782,1794,1806,1818,1830,1842,1853,1865,1877,1888,1900,1913,1925,1937,1948,1960,1971,1983,1995,2006,2019,2031,2043,2054,2066,2078,2098,2110,65535,65535,65535,65535,65535,65535,65535,65535,65535},
{2120,2127,2132,2140,2147,2152,5968,2161,2170,2182,2194,2205,2217,2230,2242,2253,2265,2277,2288,2300,2312,2323,2336,2348,2360,2371,2383,2395,2406,2418,2430,2442,2454,2466,2478,2489,2501,2521,2533,65535,65535,65535,65535,65535,65535,65535,65535,65535},
{2121,5939,2133,2141,5959,5964,2157,5973,2171,2183,2195,2206,2218,2231,2243,2254,2266,2278,2289,2301,2313,2324,2337,2349,2361,2372,2384,2396,2407,2419,2431,2443,2455,2467,2479,2490,2502,2522,2534,65535,65535,65535,65535,65535,65535,65535,65535,65535},
{2544,6363,2556,2565,2571,2576,2581,6397,2595,2606,2618,2630,2641,2654,2666,2678,2689,2701,2713,2724,2736,2748,2760,2772,2784,2796,2807,2819,2831,2842,2854,2867,2879,2890,2902,2914,2925,2946,2958,65535,65535,65535,65535,65535,65535,65535,65535,65535},
{2545,430,2557,2566,6383,6388,6393,2586,2596,2607,2619,2631,2642,2655,2667,2679,2690,2702,2714,2725,2737,2749,2761,2773,2785,2797,2808,2820,2832,2843,2855,2868,2880,2891,2903,2915,2926,2947,2959,65535,65535,65535,65535,65535,65535,65535,65535,65535},
{2968,3394,2980,2990,6807,3000,3005,3010,3019,3031,3043,3054,3066,3079,3091,3102,3114,3126,3137,3149,3161,3172,3185,3197,3209,3220,3232,3244,3255,3267,3279,3291,3303,3315,3327,3338,3350,3370,3382,65535,65535,65535,65535,65535,65535,65535,65535,65535},
{2969,4242,2981,445,3414,6812,6817,6822,3020,3450,3462,3055,3485,3080,3498,3103,3521,3533,3138,3556,3568,3173,3186,3592,664,3221,3627,3639,3256,3662,3674,3292,3304,3698,3710,3339,3733,3371,3383,65535,65535,65535,65535,65535,65535,65535,65535,65535},
{3741,3744,3747,65535,65535,65535,65535,65535,65535,65535,65535,65535,65535,65535,65535,65535,65535,65535,65535,65535,65535,65535,65535,65535,65535,65535,65535,65535,65535,65535,65535,65535,65535,65535,65535,65535,65535,65535,65535,65535,65535,65535,65535,65535,65535,65535,65535,65535},
{425,431,436,3409,4262,3419,3424,3429,475,487,499,510,522,535,547,558,570,582,593,605,617,628,641,653,3604,676,688,700,711,723,735,747,759,771,783,794,806,827,838,65535,65535,65535,65535,65535,65535,65535,65535,65535},
{850,4667,860,869,4687,4691,4696,4701,899,910,922,934,945,958,970,982,993,1005,1017,1028,1040,1052,1064,1077,1088,1100,1111,1123,1135,1146,1158,1170,1183,1194,1206,1218,1229,1250,1262,65535,65535,65535,65535,65535,65535,65535,65535,65535},
{851,856,861,870,876,880,885,890,900,911,923,935,946,959,971,983,994,1006,1018,1029,1041,1053,1065,1078,1089,1101,1112,1124,1136,1147,1159,1171,1184,1195,1207,1219,1230,1251,1263,65535,65535,65535,65535,65535,65535,65535,65535,65535},
{1274,1280,1285,1294,1300,5116,1309,1314,1324,1336,1347,1359,1371,1383,1395,1407,1419,1430,1442,1454,1465,1477,1489,1502,1513,1525,1537,1548,1560,1572,1583,1595,1608,1620,1631,1643,1655,1675,1687,65535,65535,65535,65535,65535,65535,65535,65535,65535},
{1275,5092,3400,1295,5112,4267,5121,5126,3439,3451,1348,3474,3486,1384,1396,3510,3522,1431,3545,3557,1466,3580,1490,3593,1514,3616,3628,1549,3651,3663,1584,1596,3687,3699,1632,3722,3734,1676,3766,65535,65535,65535,65535,65535,65535,65535,65535,65535},
{1698,1704,1709,1718,1724,1729,1733,1738,1748,1760,1771,1783,1795,1807,1819,1831,1843,1854,1866,1878,1889,1901,1914,1926,1938,1949,1961,1972,1984,1996,2007,2020,2032,2044,2055,2067,2079,2099,2111,65535,65535,65535,65535,65535,65535,65535,65535,65535},
{1699,5516,1710,1719,5536,5541,5545,5550,1749,1761,1772,1784,1796,1808,1820,1832,1844,1855,1867,1879,1890,1902,1915,1927,665,1950,1962,1973,1985,1997,2008,2021,2033,2045,2056,2068,2080,2100,2112,65535,65535,65535,65535,65535,65535,65535,65535,65535},
{2122,2128,2134,2142,2148,2153,5969,2162,2172,2184,2196,2207,2219,2232,2244,2255,2267,2279,2290,2302,2314,2325,2338,2350,2362,2373,2385,2397,2408,2420,2432,2444,2456,2468,2480,2491,2503,2523,2535,65535,65535,65535,65535,65535,65535,65535,65535,65535},
{2123,5940,437,2143,5960,5965,4272,5974,2173,2185,3463,2208,2220,2233,3499,2256,2268,3534,2291,2303,3569,2326,2339,2351,3605,2374,2386,3640,2409,2421,3675,2445,2457,2469,3711,2492,2504,2524,2536,65535,65535,65535,65535,65535,65535,65535,65535,65535},
{2546,2552,2558,2567,2572,2577,2582,6398,2597,2608,2620,2632,2643,2656,2668,2680,2691,2703,2715,2726,2738,2750,2762,2774,2786,2798,2809,2821,2833,2844,2856,2869,2881,2892,2904,2916,2927,2948,2960,65535,65535,65535,65535,65535,65535,65535,65535,65535},
{2547,6364,3401,446,6384,6389,6394,4277,476,2609,2621,511,2644,2657,2669,559,2692,2704,594,2727,2739,629,2763,2775,2787,677,2810,2822,712,2845,2857,748,760,2893,2905,795,2928,3755,839,65535,65535,65535,65535,65535,65535,65535,65535,65535},
{2970,2976,2982,2991,2996,3001,3006,3011,3021,3032,3044,3056,3067,3081,3092,3104,3115,3127,3139,3150,3162,3174,3187,3198,3210,3222,3233,3245,3257,3268,3280,3293,3305,3316,3328,3340,3351,3372,3384,65535,65535,65535,65535,65535,65535,65535,65535,65535},
{2971,6788,2983,3410,6808,6813,6818,6823,3440,3033,3045,3475,3068,536,3093,3511,3116,3128,3546,3151,3163,3581,642,3199,3211,3617,3234,3246,3652,3269,3281,3294,3688,3317,3329,3723,3352,3373,3767,65535,65535,65535,65535,65535,65535,65535,65535,65535},
{3742,3745,3748,65535,65535,65535,65535,65535,65535,65535,65535,65535,65535,65535,65535,65535,65535,65535,65535,65535,65535,65535,65535,65535,65535,65535,65535,65535,65535,65535,65535,65535,65535,65535,65535,65535,65535,65535,65535,65535,65535,65535,65535,65535,65535,65535,65535,65535},
{426,3395,438,447,451,456,461,466,477,488,500,512,523,3488,548,560,571,583,595,606,618,630,643,654,666,678,689,701,713,724,736,749,761,772,784,796,807,828,840,65535,65535,65535,65535,65535,65535,65535,65535,65535},
{852,857,863,872,877,881,886,893,905,916,928,940,951,964,976,988,999,1011,1023,1034,1046,1058,1070,657,1094,1106,1117,1129,1141,1152,1164,1176,1189,1200,1212,1224,1235,1256,1268,65535,65535,65535,65535,65535,65535,65535,65535,65535},
{4664,4669,864,4684,4689,4693,4698,468,480,491,503,515,952,3491,551,563,574,586,598,609,621,633,1071,3597,669,681,692,704,716,727,739,1177,764,775,787,799,810,831,843,65535,65535,65535,65535,65535,65535,65535,65535,65535},
{1276,1281,1286,1296,1301,1305,1310,1317,1328,1340,1352,1363,1375,1388,1400,1411,1423,1435,1446,1458,1470,1481,1494,1506,1518,1529,1541,1553,1564,1576,1588,1600,1612,1624,1636,1647,1659,1680,1691,65535,65535,65535,65535,65535,65535,65535,65535,65535},
{5088,5093,1287,5108,5113,5117,5122,3432,1329,3455,3467,1364,1376,1389,3503,1412,3526,3538,1447,3561,3573,1482,1495,1507,3609,1530,3632,3644,1565,3667,3679,1601,1613,3703,3715,1648,3738,3759,1692,65535,65535,65535,65535,65535,65535,65535,65535,65535},
{1700,1705,1711,1720,1725,1730,1734,1741,1753,1765,1776,1788,1800,1812,1824,1836,1848,1859,1871,1883,1894,1906,1919,1931,1942,1954,1966,1977,1989,2001,2012,2025,2037,2049,2060,2072,811,2104,2116,65535,65535,65535,65535,65535,65535,65535,65535,65535},
{5512,5517,1712,5532,5537,5542,5546,1742,3444,492,1777,3479,527,1813,1825,3515,575,1860,3550,610,1895,1907,646,658,1943,3621,693,1978,3656,728,2013,2026,3692,776,2061,3727,3739,2105,3771,65535,65535,65535,65535,65535,65535,65535,65535,65535},
{2124,2129,2135,2144,2149,2154,2158,2165,2177,2189,2200,2212,2224,2237,2248,2260,2272,2283,2295,2307,2318,2330,2343,2355,2366,2378,2390,2401,2413,2425,2436,2449,2461,2473,2484,2496,2517,2528,2540,65535,65535,65535,65535,65535,65535,65535,65535,65535},
{5936,5941,2136,5956,5961,5966,5970,2166,2178,3456,2201,2213,2225,540,2249,2261,3527,2284,2296,3562,2319,2331,3586,3598,2367,2379,3633,2402,2414,3668,2437,2450,2462,3704,2485,2497,386,2529,2541,65535,65535,65535,65535,65535,65535,65535,65535,65535},
{2548,6365,2560,6380,2573,2578,2583,2590,2601,2613,2625,2636,2649,2661,2673,2684,2696,2708,2719,2731,2743,2755,2768,2779,2791,2802,2814,2826,2837,2849,2861,2874,2885,2897,2909,2920,2941,2952,2964,65535,65535,65535,65535,65535,65535,65535,65535,65535},
{6360,432,439,2569,6385,6390,6395,469,2602,2614,504,2637,528,3492,552,2685,2697,587,2720,2732,622,634,647,2780,670,2803,2815,705,2838,2850,740,753,2886,2898,788,2921,2942,2953,2965,65535,65535,65535,65535,65535,65535,65535,65535,65535},
{2972,2977,2984,2992,2997,3002,3007,3014,3025,3037,3049,3060,3072,3085,3097,3108,3120,3132,3143,3155,3167,3178,3191,3203,3215,3226,3238,3250,3261,3273,3285,3298,3309,3321,3333,3344,3365,3377,3388,65535,65535,65535,65535,65535,65535,65535,65535,65535},
{6784,6789,3403,6804,6809,6814,6819,3433,3026,3038,3468,3061,3073,3086,3504,3109,3121,3539,3144,3156,3574,3179,3192,3204,3610,3227,3239,3645,3262,3274,3286,3681,3310,3322,3716,3345,3366,832,3389,65535,65535,65535,65535,65535,65535,65535,65535,65535},
{427,4243,3402,3411,3415,3420,3425,3430,3441,3452,3464,3476,3487,537,3500,3512,3523,3535,3547,3558,3570,3582,644,3594,3606,3618,3629,3641,3653,3664,3676,750,3689,3700,3712,3724,3735,3756,3768,65535,65535,65535,65535,65535,65535,65535,65535,65535},
{428,3396,440,448,452,457,462,470,481,493,505,516,529,541,553,564,576,588,599,611,623,635,3587,659,671,682,694,706,717,729,741,754,765,777,789,800,821,3760,844,65535,65535,65535,65535,65535,65535,65535,65535,65535},
{853,4244,865,873,3416,882,887,894,906,917,929,941,953,965,977,989,1000,1012,1024,1035,1047,1059,1072,1083,1095,1107,1118,1130,1142,1153,1165,1178,1190,1201,1213,1225,1245,1257,1269,65535,65535,65535,65535,65535,65535,65535,65535,65535},
{4665,858,3404,4685,4264,4694,4699,895,3445,918,930,3480,954,966,978,3516,1001,1013,3551,1036,1048,1060,1073,1084,1096,3622,1119,1131,3657,1154,1166,1179,3693,1202,1214,3728,1246,1258,3772,65535,65535,65535,65535,65535,65535,65535,65535,65535},
{1277,1282,1288,1297,1302,1306,1311,1318,1330,1341,1353,1365,1377,1390,1401,1413,1424,1436,1448,1459,1471,1483,1496,1508,1519,1531,1542,1554,1566,1577,1589,1602,1614,1625,1637,1649,1669,1681,1693,65535,65535,65535,65535,65535,65535,65535,65535,65535},
{5089,5094,1289,5109,5114,5118,5123,1319,1331,1342,1354,1366,1378,3493,1402,1414,1425,1437,1449,1460,1472,1484,1497,3599,1520,1532,1543,1555,1567,1578,1590,1603,1615,1626,1638,1650,1670,1682,1694,65535,65535,65535,65535,65535,65535,65535,65535,65535},
{1701,1706,1713,1721,1726,3421,1735,1743,1754,1766,1778,1789,1801,1814,1826,1837,1849,1861,1872,1884,1896,1908,1920,1932,1944,1955,1967,1979,1990,2002,2014,2027,2038,2050,2062,2073,2093,2106,2117,65535,65535,65535,65535,65535,65535,65535,65535,65535},
{5513,5518,1714,5533,5538,4269,5547,3434,1755,3457,3469,1790,1802,1815,3505,1838,3528,3540,1873,3563,3575,1909,1921,1933,3611,1956,3634,3646,1991,3669,2015,3682,2039,3705,3717,2074,2094,833,2118,65535,65535,65535,65535,65535,65535,65535,65535,65535},
{2125,2130,2137,2145,2150,2155,2159,2167,2179,2190,2202,2214,2226,2238,2250,2262,2273,2285,2297,2308,2320,2332,2344,2356,2368,2380,2391,2403,2415,2426,2438,2451,2463,2474,2486,2498,2518,2530,2542,65535,65535,65535,65535,65535,65535,65535,65535,65535},
{5937,5942,2138,5957,5962,5967,5971,2168,482,2191,2203,517,2227,2239,2251,565,2274,2286,600,2309,2321,2333,2345,2357,2369,683,2392,2404,718,2427,2439,2452,766,2475,2487,801,3749,3761,845,65535,65535,65535,65535,65535,65535,65535,65535,65535},
{2549,2554,2561,6381,2574,2579,3426,2591,2603,2615,2626,2638,2650,2662,2674,2686,2698,2709,2721,2733,2744,2756,2769,2781,2792,2804,2816,2827,2839,2851,2862,2875,2887,2899,2910,2922,387,2954,2966,65535,65535,65535,65535,65535,65535,65535,65535,65535},
{6361,6366,2562,3412,6386,6391,4274,2592,3446,494,2627,3481,2651,2663,2675,3517,577,2710,3552,612,2745,2757,648,660,2793,3623,695,2828,3658,730,2863,2876,3694,778,2911,3729,2943,2955,3773,65535,65535,65535,65535,65535,65535,65535,65535,65535},
{2973,2978,2985,2993,2998,3003,3008,3015,3027,3039,3050,3062,3074,3087,3098,3110,3122,3133,3145,3157,3168,3180,3193,3205,3216,3228,3240,3251,3263,3275,3287,3299,3311,3323,3334,3346,3367,3378,3390,65535,65535,65535,65535,65535,65535,65535,65535,65535},
{6785,6790,2986,6805,6810,6815,6820,3016,3028,3458,3051,3063,3075,542,3099,3111,3529,3134,3146,3564,3169,3181,3588,3600,3217,3229,3635,3252,3264,3670,742,3300,3312,3706,3335,3347,822,3379,3391,65535,65535,65535,65535,65535,65535,65535,65535,65535},
{3392,433,441,4260,453,458,463,471,483,495,506,518,530,3494,554,566,578,589,601,613,624,636,649,661,672,684,696,707,719,731,743,755,767,779,790,802,3750,834,846,65535,65535,65535,65535,65535,65535,65535,65535,65535},
{4240,3397,3405,449,3417,3422,3427,3435,3447,3459,3470,3482,531,543,3506,3518,3530,3541,3553,3565,3576,637,3589,3601,3612,3624,3636,3647,3659,3671,744,3683,3695,3707,3718,3730,823,3762,3774,65535,65535,65535,65535,65535,65535,65535,65535,65535},
{2,4668,862,871,4688,4692,4697,4702,901,912,924,936,947,960,972,984,995,1007,1019,1030,1042,1054,1066,1079,1090,1102,1113,1125,1137,1148,1160,1172,1185,1196,1208,1220,1231,1252,1264,65535,65535,65535,65535,65535,65535,65535,65535,65535},
{854,4670,866,874,878,883,888,896,907,919,931,942,955,967,979,990,1002,1014,1025,1037,1049,1061,1074,1085,1097,1108,1120,1132,1143,1155,1167,1180,1191,1203,1215,1226,1247,1259,1270,65535,65535,65535,65535,65535,65535,65535,65535,65535},
{1278,4245,1290,1298,4265,1307,1312,1320,1332,1343,1355,1367,1379,1391,1403,1415,1426,1438,1450,1461,1473,1485,1498,1509,1521,1533,1544,1556,1568,1579,1591,1604,1616,1627,1639,1651,1671,1683,1695,65535,65535,65535,65535,65535,65535,65535,65535,65535},
{5090,1283,1291,5110,1303,5119,5124,1321,1333,1344,1356,1368,1380,1392,1404,1416,1427,1439,1451,1462,1474,1486,1499,1510,1522,1534,1545,1557,1569,1580,1592,1605,1617,1628,1640,1652,1672,1684,847,65535,65535,65535,65535,65535,65535,65535,65535,65535},
{1702,1707,1715,1722,1727,1731,1736,1744,1756,1767,1779,1791,1803,1816,1827,1839,1850,1862,1874,1885,1897,1910,1922,1934,1945,1957,1968,1980,1992,2003,2016,2028,2040,2051,2063,2075,2095,2107,2119,65535,65535,65535,65535,65535,65535,65535,65535,65535},
{5514,5519,442,5534,5539,5543,5548,1745,1757,1768,1780,1792,1804,3495,1828,1840,1851,1863,1875,1886,1898,1911,1923,1935,1946,1958,1969,1981,1993,2004,2017,2029,2041,2052,2064,2076,2096,2108,3775,65535,65535,65535,65535,65535,65535,65535,65535,65535},
{2126,2131,2139,2146,2151,4270,2160,2169,2180,2192,2204,2215,2228,2240,2252,2263,2275,2287,2298,2310,2322,2334,2346,2358,2370,2381,2393,2405,2416,2428,2440,2453,2464,2476,2488,2499,2519,2531,2543,65535,65535,65535,65535,65535,65535,65535,65535,65535},
{5938,5943,3406,5958,5963,2156,5972,472,2181,2193,507,2216,2229,2241,555,2264,2276,590,2299,2311,625,2335,2347,2359,673,2382,2394,708,2417,2429,2441,756,2465,2477,791,2500,2520,2532,418,65535,65535,65535,65535,65535,65535,65535,65535,65535},
{2550,2555,2563,2570,2575,2580,2584,2593,2604,2616,2628,2639,2652,2664,2676,2687,2699,2711,2722,2734,2746,2758,2770,2782,2794,2805,2817,2829,2840,2852,2864,2877,2888,2900,2912,2923,2944,2956,2967,65535,65535,65535,65535,65535,65535,65535,65535,65535},
{6362,6367,2564,6382,6387,6392,6396,3436,2605,2617,3471,2640,2653,2665,3507,2688,2700,3542,2723,2735,3577,2759,2771,2783,3613,2806,2818,3648,2841,2853,2865,3684,2889,2901,3719,2924,3751,835,419,65535,65535,65535,65535,65535,65535,65535,65535,65535},
{2974,2979,2987,2994,2999,3004,4275,3017,3029,3040,3052,3064,3076,3088,3100,3112,3123,3135,3147,3158,3170,3182,3194,3206,3218,3230,3241,3253,3265,3276,3288,3301,3313,3324,3336,3348,3368,3380,420,65535,65535,65535,65535,65535,65535,65535,65535,65535},
{6786,6791,2988,6806,6811,6816,3009,3018,484,3041,3053,519,3077,3089,3101,567,3124,3136,602,3159,3171,3183,3195,3207,3219,685,3242,3254,720,3277,3289,3302,768,3325,3337,803,3369,3763,421,65535,65535,65535,65535,65535,65535,65535,65535,65535},
{3,2553,2559,2568,4263,4268,4273,2587,2598,2610,2622,2633,2645,2658,2670,2681,2693,2705,2716,2728,2740,2751,2764,2776,2788,2799,2811,2823,2834,2846,2858,2870,2882,2894,2906,2917,2929,2949,2961,65535,65535,65535,65535,65535,65535,65535,65535,65535},
{2551,434,443,3413,454,459,2585,2594,3448,496,2629,3483,532,544,2677,3519,579,2712,3554,614,2747,638,650,662,2795,3625,697,2830,3660,732,2866,2878,3696,780,2913,3731,2945,2957,422,65535,65535,65535,65535,65535,65535,65535,65535,65535},
{2975,3398,3407,4261,3418,3423,6821,473,3030,3460,508,3065,3078,3496,556,3113,3531,591,3148,3566,626,3184,3590,3602,674,3231,3637,709,3266,3672,3290,757,3314,3708,792,3349,824,3381,423,65535,65535,65535,65535,65535,65535,65535,65535,65535},
{6787,4246,2989,2995,4266,4271,464,3437,485,3042,3472,520,533,3090,3508,568,3125,3543,603,3160,3578,639,3196,3208,3614,686,3243,3649,721,3278,745,3685,769,3326,3720,804,3752,836,1271,65535,65535,65535,65535,65535,65535,65535,65535,65535},
{4,8,13,22,28,33,38,3855,55,67,78,90,102,115,126,138,150,161,173,185,196,208,221,232,244,256,268,279,291,303,314,327,339,351,362,374,397,407,65535,65535,65535,65535,65535,65535,65535,65535,65535,65535},
{3816,3820,14,23,3840,3845,3850,44,56,68,79,91,103,116,127,139,151,162,174,186,197,209,222,233,245,257,269,280,292,304,315,328,340,352,363,375,398,408,65535,65535,65535,65535,65535,65535,65535,65535,65535,65535},
{5,9,15,24,29,34,39,45,57,69,80,92,104,117,128,140,152,163,175,187,198,210,223,234,246,258,270,281,293,305,316,329,341,353,364,376,399,409,65535,65535,65535,65535,65535,65535,65535,65535,65535,65535},
{3817,3821,16,3836,3841,3846,3851,46,58,70,81,93,105,118,129,141,153,164,176,188,199,211,224,235,247,259,271,282,294,306,317,330,342,354,365,377,400,410,65535,65535,65535,65535,65535,65535,65535,65535,65535,65535},
{6,10,17,25,30,35,40,47,59,71,82,94,106,119,130,142,154,165,177,189,200,212,225,236,248,260,272,283,295,307,318,331,343,355,366,378,401,411,65535,65535,65535,65535,65535,65535,65535,65535,65535,65535},
{3818,3822,18,3837,3842,3847,3852,48,60,72,83,95,107,120,131,143,155,166,178,190,201,213,226,237,249,261,273,284,296,308,319,332,344,356,367,379,402,412,65535,65535,65535,65535,65535,65535,65535,65535,65535,65535},
{7,11,19,26,31,36,41,49,61,73,84,96,108,121,132,144,156,167,179,191,202,214,227,238,250,262,274,285,297,309,320,333,345,357,368,380,825,413,65535,65535,65535,65535,65535,65535,65535,65535,65535,65535},
{3819,3823,20,3838,3843,3848,3853,50,62,74,85,97,109,122,133,145,157,168,180,192,203,215,228,239,251,263,275,286,298,310,321,334,346,358,369,381,3753,3764,65535,65535,65535,65535,65535,65535,65535,65535,65535,65535},
};

#define TABLED 1
#define TRIG 7
#define JB 22
#define PRE 2
#define CH 64
#define FIRST 5
constexpr int RING = SCHED_RING;
constexpr int NSLOT = 8;
constexpr int PLEN = SCHED_LE, LT = SCHED_LT, LM = 256 - 2 * PLEN - 2 * LT, NSEG = 4 / SCHED_NMID, LMID = NSEG * LM;
constexpr int NP = 8 + SCHED_NMID, NG = NP + (LT ? 8 : 0), NCONV = 3 * NG;
static_assert(LMID <= PLEN && LT <= RING && LT < LM && (LT == 0 || LT >= 6), "geometry");
__device__ __forceinline__ int group_len(int gm) { return gm < 8 ? PLEN : gm < NP ? LMID : LT; }
__device__ __forceinline__ int group_strip(int gm, int seg) { return gm < 8 ? gm >> 1 : gm < NP ? (gm - 8) * NSEG + seg : (gm - NP) >> 1; }
__device__ __forceinline__ int group_base(int gm) { return gm < NP ? PLEN + LT : PLEN + ((gm - NP) & 1) * (LT + LM); }
constexpr int TILEB = 12288;
constexpr int SLOTB = 280 * 64;
constexpr int W1S = 0, W2S = 73728, ABUF = 147456, XBUF = ABUF + 16 * 3072, MISC = XBUF + 8 * 3072;
constexpr int WBAR = MISC + 2560;
constexpr int RBUF = ABUF - 4 * SLOTB;
constexpr int CM = MISC + 2816, CTAB = CM + 256;
constexpr int SMEM_BYTES = CTAB + (PLEN + 16) * 16;
static_assert(RBUF % 512 == 0 && RBUF >= W2S && RBUF + NSLOT * SLOTB + 128 <= MISC && SMEM_BYTES <= 232448, "smem layout");

struct Globals {
  unsigned char scratch[RING * NG * 4 * TILEB];
  unsigned char wimg[147456];
  uint32_t wflag[32];
  uint32_t ready[NG * PLEN + 1];
  uint32_t cons[NG * PLEN];
  uint32_t epoch[1024];
};
__device__ __align__(1024) Globals g_state;

#define GELU_C3 0.32920349f
#define GELU_A2 0x40d940d9u
#define GELU_S2 0x3e133e13u
#define SCHED_FENCE() asm volatile("pmevent 0;" ::: "memory")
#define SPIN_LIMIT 0x1000000

__device__ __forceinline__ uint32_t smem_u32(const void* p) { return (uint32_t)__cvta_generic_to_shared(p); }
__device__ __forceinline__ void wg_fence() { asm volatile("wgmma.fence.sync.aligned;" ::: "memory"); }
__device__ __forceinline__ void wg_commit() { asm volatile("wgmma.commit_group.sync.aligned;" ::: "memory"); }
template <int N> __device__ __forceinline__ void wg_wait() { asm volatile("wgmma.wait_group.sync.aligned %0;" ::"n"(N) : "memory"); }
__device__ __forceinline__ void mbar_wait(uint32_t bar, uint32_t parity) {
  asm volatile("{\n.reg .pred p;\n.reg .u32 c;\nmbarrier.try_wait.parity.shared::cta.b64 p, [%0], %1;\n@p bra DONE_%=;\nmov.u32 c, 0;\nWAIT_%=:\nmbarrier.try_wait.parity.shared::cta.b64 p, [%0], %1;\n@p bra DONE_%=;\n"
               "add.u32 c, c, 1;\nsetp.lt.u32 p, c, 0x1000000;\n@p bra WAIT_%=;\ntrap;\nDONE_%=:\n}" ::"r"(bar), "r"(parity) : "memory");
}
__device__ __forceinline__ void mbar_arrive_elect(uint32_t bar) { asm volatile("{.reg .pred p; elect.sync _|p, 0xffffffff; @p mbarrier.arrive.shared::cta.b64 _, [%0];}" ::"r"(bar) : "memory"); }
__device__ __forceinline__ void mbar_init_elect(uint32_t bar, uint32_t cnt) { asm volatile("{.reg .pred p; elect.sync _|p, 0xffffffff; @p mbarrier.init.shared::cta.b64 [%0], %1;}" ::"r"(bar), "r"(cnt) : "memory"); }
__device__ __forceinline__ uint32_t ld_relaxed(const uint32_t* p) { uint32_t v; asm volatile("ld.relaxed.gpu.global.u32 %0, [%1];" : "=r"(v) : "l"(p) : "memory"); return v; }
__device__ __forceinline__ void red_add_elect(uint32_t* p) { asm volatile("{.reg .pred p; elect.sync _|p, 0xffffffff; @p red.relaxed.gpu.global.add.u32 [%0], 1;}" ::"l"(p) : "memory"); }
__device__ __forceinline__ void wait_value(const uint32_t* p, uint32_t target, int ns) {
  int spins = 0;
  while (ld_relaxed(p) != target) { __nanosleep(ns); if (++spins > SPIN_LIMIT) __trap(); }
}
template <int BYTES, bool INIT = false> __device__ __forceinline__ void bulk_load(uint32_t dst, const void* src, uint32_t bar, int go = 0) {
  if (INIT) asm volatile("{.reg .pred p; elect.sync _|p, 0xffffffff; @p mbarrier.init.shared::cta.b64 [%0], 1; @p fence.mbarrier_init.release.cluster;}" ::"r"(bar) : "memory");
  asm volatile("{\n.reg .pred p, q;\nsetp.ge.s32 q, %4, 0;\nelect.sync _|p, 0xffffffff;\nand.pred p, p, q;\n@p mbarrier.arrive.expect_tx.shared::cta.b64 _, [%1], %3;\n"
               "@p cp.async.bulk.shared::cluster.global.mbarrier::complete_tx::bytes [%0], [%2], %3, [%1];\n}"
               ::"r"(dst), "r"(bar), "l"(src), "n"(BYTES), "r"(go) : "memory");
}
__device__ __forceinline__ void lds128(uint32_t* r, uint32_t a) { asm volatile("ld.shared.v4.b32 {%0,%1,%2,%3}, [%4];" : "=r"(r[0]), "=r"(r[1]), "=r"(r[2]), "=r"(r[3]) : "r"(a) : "memory"); }
__device__ __forceinline__ uint2 lds64(uint32_t a) { uint2 v; asm volatile("ld.shared.v2.b32 {%0,%1}, [%2];" : "=r"(v.x), "=r"(v.y) : "r"(a) : "memory"); return v; }
__device__ __forceinline__ uint32_t lds32(uint32_t a) { uint32_t v; asm volatile("ld.shared.b32 %0, [%1];" : "=r"(v) : "r"(a) : "memory"); return v; }
__device__ __forceinline__ void sts32(uint32_t a, uint32_t v) { asm volatile("st.shared.b32 [%0], %1;" ::"r"(a), "r"(v) : "memory"); }
__device__ __forceinline__ void sts64(uint32_t a, uint2 v) { asm volatile("st.shared.v2.b32 [%0], {%1,%2};" ::"r"(a), "r"(v.x), "r"(v.y) : "memory"); }
__device__ __forceinline__ void sts128(uint32_t a, uint4 v) { asm volatile("st.shared.v4.b32 [%0], {%1,%2,%3,%4};" ::"r"(a), "r"(v.x), "r"(v.y), "r"(v.z), "r"(v.w) : "memory"); }
__device__ __forceinline__ uint64_t pol_evict_first() { uint64_t p; asm("createpolicy.fractional.L2::evict_first.b64 %0, 1.0;" : "=l"(p)); return p; }
__device__ __forceinline__ void stg128_stream(void* p, uint4 v, uint64_t pol) {
  asm volatile("st.global.L2::cache_hint.v4.b32 [%0], {%1,%2,%3,%4}, %5;" ::"l"(p), "r"(v.x), "r"(v.y), "r"(v.z), "r"(v.w), "l"(pol) : "memory");
}
__device__ __forceinline__ void stg128_if(uint32_t go, void* p, uint4 v) {
  asm volatile("{.reg .pred q; setp.ge.s32 q, %5, 0; @q st.global.v4.b32 [%0], {%1,%2,%3,%4};}" ::"l"(p), "r"(v.x), "r"(v.y), "r"(v.z), "r"(v.w), "r"(go) : "memory");
}
__device__ __forceinline__ uint32_t pack_f16(float lo, float hi) { uint32_t d; asm("cvt.rn.f16x2.f32 %0, %1, %2;" : "=r"(d) : "f"(hi), "f"(lo)); return d; }
__device__ __forceinline__ uint32_t pack_f16_sat(float lo, float hi) { uint32_t d; asm("cvt.rn.satfinite.f16x2.f32 %0, %1, %2;" : "=r"(d) : "f"(hi), "f"(lo)); return d; }
__device__ __forceinline__ uint32_t pack_bf16(float lo, float hi) { uint32_t d; asm("cvt.rn.bf16x2.f32 %0, %1, %2;" : "=r"(d) : "f"(hi), "f"(lo)); return d; }
__device__ __forceinline__ uint32_t bf2_to_h2(uint32_t w) { return pack_f16(__uint_as_float(w << 16), __uint_as_float(w & 0xffff0000u)); }
__device__ __forceinline__ uint32_t hadd2_bf16(uint32_t a, uint32_t b) { uint32_t d; asm("add.rn.bf16x2 %0, %1, %2;" : "=r"(d) : "r"(a), "r"(b)); return d; }
__device__ __forceinline__ uint32_t h2add(uint32_t a, uint32_t b) { uint32_t d; asm("add.rn.f16x2 %0, %1, %2;" : "=r"(d) : "r"(a), "r"(b)); return d; }
__device__ __forceinline__ uint32_t h2mul(uint32_t a, uint32_t b) { uint32_t d; asm("mul.rn.f16x2 %0, %1, %2;" : "=r"(d) : "r"(a), "r"(b)); return d; }
__device__ __forceinline__ uint32_t h2fma(uint32_t a, uint32_t b, uint32_t c) { uint32_t d; asm("fma.rn.f16x2 %0, %1, %2, %3;" : "=r"(d) : "r"(a), "r"(b), "r"(c)); return d; }
__device__ __forceinline__ uint32_t h2lo(uint32_t a) { uint32_t d; asm("{.reg .f16 l,h; mov.b32 {l,h}, %1; mov.b32 %0, {l,l};}" : "=r"(d) : "r"(a)); return d; }
__device__ __forceinline__ uint32_t h2hi(uint32_t a) { uint32_t d; asm("{.reg .f16 l,h; mov.b32 {l,h}, %1; mov.b32 %0, {h,h};}" : "=r"(d) : "r"(a)); return d; }
__device__ __forceinline__ float h_lo(uint32_t a) { float d; asm("{.reg .f16 l,h; mov.b32 {l,h}, %1; cvt.f32.f16 %0, l;}" : "=f"(d) : "r"(a)); return d; }
__device__ __forceinline__ float h_hi(uint32_t a) { float d; asm("{.reg .f16 l,h; mov.b32 {l,h}, %1; cvt.f32.f16 %0, h;}" : "=f"(d) : "r"(a)); return d; }
__device__ __forceinline__ float rsqrt_fast(float v) { float r; asm("rsqrt.approx.ftz.f32 %0, %1;" : "=f"(r) : "f"(v)); return r; }
__device__ __forceinline__ uint32_t prmt(uint32_t a, uint32_t b, uint32_t s) { uint32_t d; asm("prmt.b32 %0, %1, %2, %3;" : "=r"(d) : "r"(a), "r"(b), "r"(s)); return d; }
__device__ __forceinline__ void mma_sp(float* d, const uint32_t* a, const uint32_t* b, const float* c, uint32_t e) {
  asm("mma.sp::ordered_metadata.sync.aligned.m16n8k32.row.col.f32.bf16.bf16.f32 {%0,%1,%2,%3}, {%4,%5,%6,%7}, {%8,%9,%10,%11}, {%12,%13,%14,%15}, %16, 0;"
      : "=f"(d[0]), "=f"(d[1]), "=f"(d[2]), "=f"(d[3])
      : "r"(a[0]), "r"(a[1]), "r"(a[2]), "r"(a[3]), "r"(b[0]), "r"(b[1]), "r"(b[2]), "r"(b[3]), "f"(c[0]), "f"(c[1]), "f"(c[2]), "f"(c[3]), "r"(e));
}

__device__ __forceinline__ uint32_t gelu_tanh(uint32_t y) {
  uint32_t t, u, th;
  asm volatile("fma.rn.f16x2 %0, %1, %1, %2;" : "=r"(t) : "r"(y), "r"(GELU_A2));
  asm volatile("mul.rn.f16x2 %0, %1, %2;" : "=r"(u) : "r"(y), "r"(t));
  asm volatile("tanh.approx.f16x2 %0, %1;" : "=r"(th) : "r"(u));
  return th;
}
__device__ __forceinline__ uint32_t gelu_fin(uint32_t y, uint32_t th) {
  uint32_t g;
  asm volatile("fma.rn.f16x2 %0, %1, %2, %1;" : "=r"(g) : "r"(y), "r"(th));
  return g;
}

__device__ __forceinline__ void convert_weights(uint32_t sb, int rot, int warp, int lane) {
  if (warp < 12) {
    const int l8 = lane & 7, q4 = lane >> 3;
    int s = (warp >> 1) + rot; if (s >= 6) s -= 6;
    const uint32_t base = sb + W1S + s * 12288 + (warp & 1) * 384;
    mbar_wait(sb + WBAR + s * 8, 0);
    uint32_t v[3][4][4];
#pragma unroll
    for (int r = 0; r < 4; r++)
#pragma unroll
      for (int i = 0; i < 3; i++) lds128(v[i][r], base + i * 128 + (4 * (l8 >> 1) + 2 * (r & 1) + (l8 & 1)) * 768 + ((l8 + q4 + 4 * (r >> 1)) & 7) * 16);
    __syncwarp();
#pragma unroll
    for (int r = 0; r < 4; r++)
#pragma unroll
      for (int i = 0; i < 3; i++)
        sts128(base + i * 128 + (((l8 + q4 + 4 * (r >> 1)) & 7) + 8 * (r & 1)) * 768 + l8 * 16,
               make_uint4(bf2_to_h2(v[i][r][0]), bf2_to_h2(v[i][r][1]), bf2_to_h2(v[i][r][2]), bf2_to_h2(v[i][r][3])));
  }
  const int q = lane & 3, t = (lane >> 2) & 3, b = lane >> 4;
  int u = 3 * (warp ^ 15) + 8 * rot; if (u >= 48) u -= 48;
  uint32_t base[3], v[3][4][3];
#pragma unroll
  for (int i = 0; i < 3; i++) {
    const int ui = u + i >= 48 ? u + i - 48 : u + i;
    base[i] = sb + W2S + ui * 1536;
    if (i != 1) mbar_wait(sb + WBAR + 48 + (ui >> 3) * 8, 0);
  }
#pragma unroll
  for (int i = 0; i < 3; i++)
#pragma unroll
    for (int d = 0; d < 4; d++)
#pragma unroll
      for (int j = 0; j < 3; j++) v[i][d][j] = lds32(base[i] + (2 * ((q + d) & 3) + b) * 192 + j * 64 + t * 16 + q * 4);
  __syncwarp();
#pragma unroll
  for (int i = 0; i < 3; i++)
#pragma unroll
    for (int d = 0; d < 4; d++)
#pragma unroll
      for (int j = 0; j < 3; j++) sts32(base[i] + (4 * j + q) * 128 + (2 * ((q + d) & 3) + b) * 16 + t * 4, bf2_to_h2(v[i][d][j]));
}

__device__ __noinline__ void ln_wide(uint32_t ad) {
  float m[2], r[2];
#pragma unroll
  for (int hi = 0; hi < 2; hi++) {
    float sm = 0.f;
    for (int s = 0; s < 6; s++) { uint2 w = lds64(ad + s * 512 + hi * 8); sm += (h_lo(w.x) + h_hi(w.x)) + (h_lo(w.y) + h_hi(w.y)); }
    sm += __shfl_xor_sync(0xffffffffu, sm, 1); sm += __shfl_xor_sync(0xffffffffu, sm, 2);
    m[hi] = sm * (1.f / 96.f);
    float q = 0.f;
    for (int s = 0; s < 6; s++) {
      uint2 w = lds64(ad + s * 512 + hi * 8);
      float d0 = h_lo(w.x) - m[hi], d1 = h_hi(w.x) - m[hi], d2 = h_lo(w.y) - m[hi], d3 = h_hi(w.y) - m[hi];
      q += (d0 * d0 + d1 * d1) + (d2 * d2 + d3 * d3);
    }
    q += __shfl_xor_sync(0xffffffffu, q, 1); q += __shfl_xor_sync(0xffffffffu, q, 2);
    r[hi] = rsqrtf(fmaf(q, 1.f / 96.f, 1e-5f)) * GELU_C3;
  }
  for (int s = 0; s < 6; s++) {
    uint32_t w[4]; lds128(w, ad + s * 512);
    sts128(ad + s * 512, make_uint4(pack_f16((h_lo(w[0]) - m[0]) * r[0], (h_hi(w[0]) - m[0]) * r[0]), pack_f16((h_lo(w[2]) - m[1]) * r[1], (h_hi(w[2]) - m[1]) * r[1]),
                                    pack_f16((h_lo(w[1]) - m[0]) * r[0], (h_hi(w[1]) - m[0]) * r[0]), pack_f16((h_lo(w[3]) - m[1]) * r[1], (h_hi(w[3]) - m[1]) * r[1])));
  }
  asm volatile("fence.proxy.async.shared::cta;" ::: "memory");
}

__device__ __forceinline__ uint32_t layer_norm(const uint32_t (&raw)[6][4], uint32_t* a, uint32_t tag) {
  const uint32_t stale = ((raw[0][0] ^ tag) | (raw[1][0] ^ tag)) | ((raw[2][0] ^ tag) | (raw[3][0] ^ tag)) | ((raw[4][0] ^ tag) | (raw[5][0] ^ tag));
  uint32_t sm[2], qq[2];
#pragma unroll
  for (int hi = 0; hi < 2; hi++) {
    uint32_t s0 = h2add(raw[0][2 * hi], raw[1][2 * hi]), s1 = h2add(raw[0][2 * hi + 1], raw[1][2 * hi + 1]);
    uint32_t s2 = h2add(raw[2][2 * hi], raw[3][2 * hi]), s3 = h2add(raw[2][2 * hi + 1], raw[3][2 * hi + 1]);
    uint32_t s4 = h2add(raw[4][2 * hi], raw[5][2 * hi]), s5 = h2add(raw[4][2 * hi + 1], raw[5][2 * hi + 1]);
    sm[hi] = h2add(h2add(h2add(s0, s1), h2add(s2, s3)), h2add(s4, s5));
  }
#pragma unroll
  for (int hi = 0; hi < 2; hi++) {
    uint32_t q0 = h2mul(raw[0][2 * hi], raw[0][2 * hi]), q1 = h2mul(raw[0][2 * hi + 1], raw[0][2 * hi + 1]);
#pragma unroll
    for (int k = 1; k < 6; k++) { q0 = h2fma(raw[k][2 * hi], raw[k][2 * hi], q0); q1 = h2fma(raw[k][2 * hi + 1], raw[k][2 * hi + 1], q1); }
    qq[hi] = h2add(q0, q1);
  }
  uint32_t s = h2add(prmt(sm[0], sm[1], 0x5410), prmt(sm[0], sm[1], 0x7632));
  uint32_t q = h2add(prmt(qq[0], qq[1], 0x5410), prmt(qq[0], qq[1], 0x7632));
  s = h2add(s, __shfl_xor_sync(0xffffffffu, s, 1)); q = h2add(q, __shfl_xor_sync(0xffffffffu, q, 1));
  s = h2add(s, __shfl_xor_sync(0xffffffffu, s, 2)); q = h2add(q, __shfl_xor_sync(0xffffffffu, q, 2));
  constexpr float K1 = 1.f / (96.f * GELU_C3 * GELU_C3), K2 = 1e-5f / (GELU_C3 * GELU_C3), K3 = 1.f / (96.f * GELU_C3);
  const float e0 = fmaf(h_lo(q), K1, K2), e1 = fmaf(h_hi(q), K1, K2), m0 = h_lo(s) * K3, m1 = h_hi(s) * K3;
  const float v0 = fmaf(-m0, m0, e0), v1 = fmaf(-m1, m1, e1);
  const uint32_t r = pack_f16(rsqrt_fast(v0), rsqrt_fast(v1)), o = h2mul(h2mul(s, 0xA155A155u), r);
#pragma unroll
  for (int k = 0; k < 6; k++) {
    a[4 * k] = h2fma(raw[k][0], h2lo(r), h2lo(o)); a[4 * k + 2] = h2fma(raw[k][1], h2lo(r), h2lo(o));
    a[4 * k + 1] = h2fma(raw[k][2], h2hi(r), h2hi(o)); a[4 * k + 3] = h2fma(raw[k][3], h2hi(r), h2hi(o));
  }
  const bool fine = fmaf(v0, 4.f, -e0) > 0.f && fmaf(v1, 4.f, -e1) > 0.f;
  return (fine ? 0u : 2u) | (stale & 1);
}

constexpr int KS = CH / 16, NC = 384 / CH;
#define WG1_(n) wgmma_n##n##_f16
#define WG1(n) WG1_(n)
__device__ __forceinline__ void gemm1(uint32_t* p, const uint32_t* a, uint64_t d1, int c, int k0, int k1) {
#pragma unroll
  for (int s = 0; s < 6; s++)
    if (s >= k0 && s < k1) {
      if (s == 0) WG1(CH)<0>(p, a, d1 + c * CH); else WG1(CH)<1>(p, a + 4 * s, d1 + c * CH + s * (12288 >> 4));
    }
}
__device__ __forceinline__ void fetch_x(uint32_t xbuf, uint32_t bar, const CUtensorMap* tm, uint32_t c0, uint32_t c12, uint64_t pol, int go = 0) {
  asm volatile("{\n.reg .pred p, q;\nsetp.ge.s32 q, %7, 0;\nelect.sync _|p, 0xffffffff;\nand.pred p, p, q;\n"
               "@p mbarrier.arrive.expect_tx.shared::cta.b64 _, [%1], 3072;\n"
               "@p cp.async.bulk.tensor.3d.shared::cluster.global.mbarrier::complete_tx::bytes.L2::cache_hint [%0], [%2, {%3, %4, %5}], [%1], %6;\n}"
               ::"r"(xbuf), "r"(bar), "l"(tm), "r"(c0), "r"(c12 & 255), "r"(c12 >> 8), "l"(pol), "r"(go) : "memory");
}
__device__ __forceinline__ uint32_t slot_tag(int gm, int j, uint32_t epoch) {
  const int writes = (group_len(gm) - j % RING + RING - 1) / RING;
  return (epoch * writes + j / RING + 1) & 1;
}
__device__ __forceinline__ void build_tile_list(uint32_t sb, int k, int idx, bool tabled, bool is_conv, uint32_t epoch) {
  int n = -1;
  if (tabled) { if (k < 48) n = (int16_t)g_sched[idx][k]; }
  else if (!is_conv) {
    const int i = k * (gridDim.x - NCONV) + idx, r = i >> 2, r1 = r - LT * NG, r2 = r1 - (LMID - LT) * NP;
    const int j = r1 < 0 ? r / NG : r2 < 0 ? LT + r1 / NP : LMID + (r2 >> 3), gm = r1 < 0 ? r % NG : r2 < 0 ? r1 % NP : r2 & 7;
    if (i < 4096) n = (gm * PLEN + j) * 4 + (i & 3);
  }
  const int q = n >> 2, gm = q / PLEN, j = q - gm * PLEN, seg = j / LM;
  const int strip = group_strip(gm, seg), pair = gm < 8 ? ((gm & 1) ? 255 - j : j) : group_base(gm) + j - seg * LM;
  sts128(sb + MISC + 512 + k * 16, make_uint4(q, (((j % RING) * NG + gm) * 4 + (n & 3)) * TILEB + slot_tag(gm, j, epoch),
                                              (n & 2) * 384, (strip * 8 + (n & 1) * 4) | (pair << 9)));
  if (k == 0) sts64(sb + MISC + 256, make_uint2(epoch + 1, !is_conv));
}

__device__ __forceinline__ void mlp_setup(uint32_t sb, Globals* gs, int id, const __nv_bfloat16* __restrict__ w1, const __nv_bfloat16* __restrict__ w2,
                                          int idx, bool tabled, int warp, int lane) {
  const int rot = idx % 6;
  if (warp < 12) {
    const int m = warp >= 6; int s = warp - 6 * m + rot; if (s >= 6) s -= 6;
    bulk_load<12288, true>(sb + (6 * m + s) * 12288, (const char*)(m ? w2 : w1) + s * 12288, sb + WBAR + (6 * m + s) * 8);
  }
  __syncthreads();
  if (warp >= 12) build_tile_list(sb, threadIdx.x - 384, idx, tabled, false, ld_relaxed(&gs->epoch[id]));
  convert_weights(sb, rot, warp, lane);
  asm volatile("fence.proxy.async.shared::cta;" ::: "memory");
  __syncthreads();
  if (threadIdx.x == 480) {
    gs->epoch[id] = lds32(sb + MISC + 256);
    const uint32_t piece = tabled ? idx - 96 : idx;
    if (piece < 12) {
      asm volatile("cp.async.bulk.global.shared::cta.bulk_group [%0], [%1], 12288;\ncp.async.bulk.commit_group;\ncp.async.bulk.wait_group 0;\nfence.proxy.async.global;\n"
                   "red.release.gpu.global.add.u32 [%2], 1;" ::"l"(gs->wimg + piece * 12288), "r"(sb + piece * 12288), "l"(gs->wflag) : "memory");
    }
  }
  __syncwarp();
}

__device__ __forceinline__ void mlp_role(uint32_t sb, Globals* gs, const CUtensorMap* tmr, __nv_bfloat16* __restrict__ out) {
  uint32_t tid;
  asm volatile("mov.u32 %0, %%tid.x;" : "=r"(tid));
  const int warp = __shfl_sync(0xffffffffu, tid >> 5, 0), lane = tid & 31;
  const int wg = warp >> 2, w = warp & 3, g = lane >> 2, t = lane & 3;
  const uint32_t abuf = sb + ABUF + warp * 3072, xbuf = sb + XBUF + (warp & 7) * 3072;
  const uint32_t bar = sb + MISC + warp * 8, obar = sb + MISC + (warp ^ 8) * 8;
  const uint32_t tl = sb + MISC + 512;
  const uint32_t rtarget = 3 * lds32(sb + MISC + 256);
  const uint64_t d1 = ((uint64_t)(6144 >> 4) << 16) | ((uint64_t)(128 >> 4) << 32) | (uint64_t)(((sb + W1S) >> 4) & 0x3fff);
  const uint64_t d2 = ((uint64_t)(12288 >> 4) << 16) | ((uint64_t)(128 >> 4) << 32) | (uint64_t)(((sb + W2S) >> 4) & 0x3fff);
  const uint32_t ad = abuf + t * 128 + ((g ^ (2 * t)) << 4);
  const uint32_t xd = xbuf + g * 192 + t * 16;
  const uint32_t pofs = (g >> 1) * 3072 + (2 * w + (g & 1)) * 192 + t * 16;
  const int mybar = 1 + wg, nxtbar = 1 + ((wg + 1) & 3);
  const uint64_t pol = pol_evict_first();
  const unsigned char* const asrc = gs->scratch + w * 3072;
  uint32_t pha = 0, phx = 0, tp = tl + wg * 16;
  bool pending = lds32(sb + MISC + 260);
  uint32_t cur[4];
  lds128(cur, tp);
  if (wg < 2) fetch_x(xbuf, bar + 128, tmr, cur[2] + w * 192, cur[3], pol, cur[0]);
  while ((int)cur[0] >= 0) {
    uint32_t a[24], p[NC][CH / 4], gg[24][4], th[24][4], acc[24], raw[6][4], n2[4], n4[4];
    if (pending) {
      wait_value(&gs->ready[cur[0]], rtarget, 32);
      bulk_load<3072>(abuf, asrc + (cur[1] & ~1u), bar);
    }
    mbar_wait(bar, pha); pha ^= 1;
#pragma unroll
    for (int k = 0; k < 6; k++) lds128(raw[k], ad + k * 512);
    uint32_t st = layer_norm(raw, a, cur[1]);
    if (__any_sync(0xffffffffu, st != 0)) {
      for (int tries = 0; __any_sync(0xffffffffu, st & 1); tries++) {
        if (tries > SPIN_LIMIT) __trap();
        bulk_load<3072>(abuf, asrc + (cur[1] & ~1u), bar);
        mbar_wait(bar, pha); pha ^= 1;
        st = 0;
#pragma unroll
        for (int k = 0; k < 6; k++) st |= lds32(ad + k * 512) ^ cur[1];
      }
      ln_wide(ad);
#pragma unroll
      for (int k = 0; k < 6; k++) lds128(a + 4 * k, ad + k * 512);
    }
    if (tp != tl) asm volatile("bar.sync %0, 256;" ::"r"(mybar) : "memory");
    uint32_t rdy = 0;
    wg_fence();
    gemm1(p[0], a, d1, 0, 0, 6); wg_commit();
    gemm1(p[1], a, d1, 1, 0, 6 / KS); wg_commit();
    const int sig = lds32(tp + 16);
    lds128(n4, tp + 64);
    asm volatile("{.reg .pred p; setp.eq.u32 p, %1, 0; @p red.relaxed.gpu.global.add.u32 [%0], 1;}" ::"l"(&gs->cons[cur[0]] + lane), "r"(lane) : "memory");
#pragma unroll
    for (int j = 0; j < 24; j++) {
      const int c = j / KS, s = j % KS;
      if (j == JB) rdy = ld_relaxed(&gs->ready[max((int)n4[0], 0)]);
      if (s == 0) wg_wait<1>();
      if (j == TRIG) asm volatile("{.reg .pred p; setp.ge.s32 p, %1, 0; @p bar.arrive %0, 256;}" ::"r"(nxtbar), "r"(sig) : "memory");
#pragma unroll
      for (int i = 0; i < 4; i++) {
        if (!(s && i < PRE)) th[j][i] = gelu_tanh(p[c][4 * s + i]);
        gg[j][i] = gelu_fin(p[c][4 * s + i], th[j][i]);
      }
      wg_fence();
      if (j == 0) wgmma_n96_f16<0>(acc, gg[j], d2); else wgmma_n96_f16<1>(acc, gg[j], d2 + (16 * (j % 3) + j / 3) * (1536 >> 4));
      const int c1 = (j + 1) / KS + 1, u = (j + 1) % KS;
      if (c1 < NC) gemm1(p[c1], a, d1, c1, (6 * u) / KS, (6 * (u + 1)) / KS);
      wg_commit();
      if (s + 1 < KS) {
#pragma unroll
        for (int i = 0; i < PRE; i++) th[j + 1][i] = gelu_tanh(p[c][4 * s + 4 + i]);
      }
      if (j < 23) SCHED_FENCE();
    }
    pending = rdy != rtarget;
    bulk_load<3072>(abuf, asrc + (n4[1] & ~1u), bar, pending ? -1 : (int)n4[0]);
    wg_wait<0>();
    mbar_wait(bar + 128, phx); phx ^= 1;
#pragma unroll
    for (int k = 0; k < 24; k++) acc[k] = h2mul(acc[k], GELU_S2);
    char* const op = (char*)out + (cur[2] * 2 + (cur[3] & 255) * 3072 + (cur[3] >> 8) * (512 * 192) + pofs);
    lds128(n2, tp + 32);
#pragma unroll
    for (int k = 0; k < 6; k++) {
      const int hi = k / 3, j = k % 3;
      uint32_t xr[4];
      lds128(xr, xd + hi * 1536 + j * 64);
      uint4 o;
      o.x = hadd2_bf16(xr[0], pack_bf16(h_lo(acc[8 * j + hi]), h_hi(acc[8 * j + hi])));
      o.y = hadd2_bf16(xr[1], pack_bf16(h_lo(acc[8 * j + 2 + hi]), h_hi(acc[8 * j + 2 + hi])));
      o.z = hadd2_bf16(xr[2], pack_bf16(h_lo(acc[8 * j + 4 + hi]), h_hi(acc[8 * j + 4 + hi])));
      o.w = hadd2_bf16(xr[3], pack_bf16(h_lo(acc[8 * j + 6 + hi]), h_hi(acc[8 * j + 6 + hi])));
      stg128_stream(op + hi * (512 * 192) + j * 64, o, pol);
    }
    __syncwarp();
    if ((int)n2[0] >= 0) fetch_x(xbuf, obar + 128, tmr, n2[2] + w * 192, n2[3], pol);
    tp += 64;
#pragma unroll
    for (int k = 0; k < 4; k++) cur[k] = n4[k];
  }
}

__device__ __forceinline__ void conv_compute(uint32_t sb, Globals* gs, int third, int nit, int off, bool edge, bool up, int warp, int lane) {
  const int g = lane >> 2, t = lane & 3;
  const uint32_t full = sb + CM;
  const uint32_t wt = sb + 16384 + warp * 1024;
  sts128(wt + lane * 16, make_uint4(0, 0, 0, 0));
  if (lane < 4) sts128(wt + 512 + lane * 16, make_uint4(0, 0, 0, 0));
  asm volatile("setmaxnreg.inc.sync.aligned.u32 232;");
  uint32_t meta = 0;
#pragma unroll
  for (int a = 0; a < 4; a++) meta |= ((4 * (t & 1) + a + 1 >= g) ? 0x80008u : 0xD000Du) << (4 * a);
  meta = __shfl_sync(0xffffffffu, meta, lane);
  uint32_t aq[4];
#pragma unroll
  for (int q = 0; q < 4; q++) {
    const int pp = (g & 1) * 140 + (t & 1) * 70 + 16 * (g >> 1) + 2 * q + (t >> 1);
    aq[q] = __shfl_sync(0xffffffffu, sb + RBUF + pp * 64 + (((warp >> 1) ^ ((pp >> 1) & 3)) << 4) + (warp & 1) * 8, lane);
  }
  const int Q = third * 8 + warp;
  unsigned char* const obase = gs->scratch + (g >> 1) * 3072 + Q * 128 + (((2 * t + (g & 1)) ^ (2 * (Q & 3))) << 4);
  const float zero4[4] = {0.f, 0.f, 0.f, 0.f};
  float S[2][4][3][4];
  __syncwarp();
#pragma unroll
  for (int i = 0; i < 8; i++) {
    lds128((uint32_t*)S[i >> 2][i & 3][0], wt + i * 16);
#pragma unroll
    for (int k = 0; k < 8; k++) asm volatile("" : "=f"(S[i >> 2][i & 3][1 + (k >> 2)][k & 3]));
  }
  uint32_t A[4][4][4];
  asm volatile("bar.sync 5, 288;" ::: "memory");
  mbar_wait(sb + WBAR + 8, 0);
  {
#pragma unroll
    for (int k = 0; k < 2; k++) {
      const int tap = lane + 32 * k;
      if (tap < 49) sts64(wt + (tap + tap / 7 + 8) * 8, lds64(sb + tap * 192 + third * 64 + warp * 8));
    }
    __syncwarp();
    uint2 w[2][4][3];
#pragma unroll
    for (int h = 0; h < 2; h++) {
      uint32_t src = wt + ((4 * h + t - g) & 7) * 8 + (up ? 384 : 0);
#pragma unroll
      for (int u = 0; u < 4; u++) {
#pragma unroll
        for (int k = 0; k < 3; k++) w[h][u][k] = lds64(src + k * 64);
        src += up ? -128 : 128;
      }
    }
#pragma unroll
    for (int u = 0; u < 4; u++)
#pragma unroll
      for (int r = 0; r < 4; r++) {
        const uint2 w0 = w[r >> 1][u][1 - (r & 1)], w1 = w[r >> 1][u][2 - (r & 1)];
        A[0][u][r] = prmt(w0.x, w1.x, 0x5410); A[1][u][r] = prmt(w0.x, w1.x, 0x7632);
        A[2][u][r] = prmt(w0.y, w1.y, 0x5410); A[3][u][r] = prmt(w0.y, w1.y, 0x7632);
      }
  }
  uint32_t sofs = off * SLOTB, bar = full + off * 8, ph = 0, ot = sb + CTAB;
  const uint32_t oend = ot + nit * 16;
  asm volatile("bar.sync 0, 512;" ::: "memory");
  mbar_wait(bar, 0);
  uint2 X[3][4];
#pragma unroll 1
  for (int wu = edge; wu < 3; wu++) {
#pragma unroll
    for (int j = 0; j < 3; j++)
#pragma unroll
      for (int q = 0; q < 4; q++) X[j][q] = lds64(aq[q] + sofs + j * 512);
    mbar_arrive_elect(bar + 64);
    uint32_t B[8][4];
#pragma unroll
    for (int i = 0; i < 8; i++)
#pragma unroll
      for (int q = 0; q < 4; q++) B[i][q] = prmt((i & 2) ? X[i >> 2][q].y : X[i >> 2][q].x, (i & 2) ? X[(i >> 2) + 1][q].y : X[(i >> 2) + 1][q].x, (i & 1) ? 0x7632 : 0x5410);
    if (wu >= 1) {
      if (wu >= 2) {
        SCHED_FENCE();
#pragma unroll
        for (int i = 0; i < 8; i++) mma_sp(S[i >> 2][i & 3][2], A[i & 3][2], B[i], S[i >> 2][i & 3][1], meta);
      }
      SCHED_FENCE();
#pragma unroll
      for (int i = 0; i < 8; i++) mma_sp(S[i >> 2][i & 3][1], A[i & 3][1], B[i], S[i >> 2][i & 3][0], meta);
    }
#pragma unroll
    for (int i = 0; i < 8; i++) mma_sp(S[i >> 2][i & 3][0], A[i & 3][0], B[i], zero4, meta);
    sofs += SLOTB; bar += 8; ot += 16;
    if (sofs == NSLOT * SLOTB) { sofs = 0; bar = full; ph ^= 1; }
    mbar_wait(bar, ph);
  }
#pragma unroll
  for (int j = 0; j < 2; j++)
#pragma unroll
    for (int q = 0; q < 4; q++) X[j][q] = lds64(aq[q] + sofs + j * 512);
#pragma unroll 1
  do {
    const uint2 oe = lds64(ot);
    unsigned char* const o = obase + oe.x;
    const uint32_t dbar = bar + 64;
#pragma unroll
    for (int s = 0; s < 2; s++) {
      uint32_t B[4][4];
      if (s == 1) {
        sofs += SLOTB; bar += 8;
        if (sofs == NSLOT * SLOTB) { sofs = 0; bar = full; ph ^= 1; }
        mbar_wait(bar, ph);
      }
#pragma unroll
      for (int c = 0; c < 4; c++)
#pragma unroll
        for (int q = 0; q < 4; q++) B[c][q] = prmt(c < 2 ? X[s][q].x : X[s][q].y, c < 2 ? X[s + 1][q].x : X[s + 1][q].y, (c & 1) ? 0x7632 : 0x5410);
      if (s == 0) {
#pragma unroll
        for (int q = 0; q < 4; q++) X[2][q] = lds64(aq[q] + sofs + 2 * 512);
      } else {
#pragma unroll
        for (int j = 0; j < 2; j++)
#pragma unroll
          for (int q = 0; q < 4; q++) X[j][q] = lds64(aq[q] + sofs + j * 512);
      }
      float T[4][4];
      SCHED_FENCE();
#pragma unroll
      for (int c = 0; c < 4; c++) mma_sp(T[c], A[c][3], B[c], S[s][c][2], meta);
#pragma unroll
      for (int c = 0; c < 4; c++) mma_sp(S[s][c][2], A[c][2], B[c], S[s][c][1], meta);
      stg128_if(oe.x, o + (2 * s) * TILEB, make_uint4((pack_f16_sat(T[0][0], T[1][0]) & ~1u) | oe.y, pack_f16_sat(T[2][0], T[3][0]), pack_f16_sat(T[0][2], T[1][2]), pack_f16_sat(T[2][2], T[3][2])));
      stg128_if(oe.x, o + (2 * s + 1) * TILEB, make_uint4((pack_f16_sat(T[0][1], T[1][1]) & ~1u) | oe.y, pack_f16_sat(T[2][1], T[3][1]), pack_f16_sat(T[0][3], T[1][3]), pack_f16_sat(T[2][3], T[3][3])));
      if (s == 1) mbar_arrive_elect(dbar);
#pragma unroll
      for (int c = 0; c < 4; c++) mma_sp(S[s][c][1], A[c][1], B[c], S[s][c][0], meta);
#pragma unroll
      for (int c = 0; c < 4; c++) mma_sp(S[s][c][0], A[c][0], B[c], zero4, meta);
    }
    ot += 16;
  } while (ot != oend);
}

__device__ __forceinline__ void load_step(uint32_t sb, const CUtensorMap* tmx, int gm, int third, int it, int s, bool first = false) {
  const int seg = first ? 0 : it / (LM + 3);
  const int st = group_strip(gm, seg), J = gm < 8 ? ((gm & 1) ? 257 - it : it + 1) : group_base(gm) + it - seg * (LM + 3);
  asm volatile("{\n.reg .pred p;\n.reg .s32 c2;\n.reg .u32 d2;\nelect.sync _|p, 0xffffffff;\nadd.s32 c2, %4, 64;\nadd.u32 d2, %0, 8960;\n"
               "@p mbarrier.arrive.expect_tx.shared::cta.b64 _, [%2], 17920;\n"
               "@p cp.async.bulk.tensor.3d.shared::cluster.global.mbarrier::complete_tx::bytes [%0], [%1, {%3, %4, %5}], [%2];\n"
               "@p cp.async.bulk.tensor.3d.shared::cluster.global.mbarrier::complete_tx::bytes [d2], [%1, {%3, c2, %5}], [%2];\n}"
               ::"r"(sb + RBUF + s * SLOTB), "l"(tmx), "r"(sb + CM + s * 8), "r"(third * 32), "r"(st * 128 - 3), "r"(2 * J - 3) : "memory");
}
__device__ __forceinline__ void ring_bar_init(uint32_t bar, uint32_t cnt, bool ahead) {
  asm volatile("{\n.reg .pred p, q;\nelect.sync _|p, 0xffffffff;\n@p mbarrier.init.shared::cta.b64 [%0], %1;\n"
               "setp.ne.and.u32 q, %2, 0, p;\n@q mbarrier.arrive.shared::cta.b64 _, [%0], %1;\n@p fence.mbarrier_init.release.cluster;\n}" ::"r"(bar), "r"(cnt), "r"((uint32_t)ahead) : "memory");
}
__device__ __forceinline__ void conv_loader(uint32_t sb, Globals* gs, const CUtensorMap* tmx, int gm, int nit, int off, int cidx, int third, int k) {
  static_assert(FIRST >= 4 && NCONV >= 24, "loader");
  const uint32_t full = sb + CM;
  asm volatile("bar.sync 0, 512;" ::: "memory");
  if (FIRST + k < NSLOT) load_step(sb, tmx, gm, third, FIRST + k, (FIRST + k + off) & 7, true);
#pragma unroll 1
  for (int it = NSLOT + k; it < nit + NSLOT; it += 4) {
    const int u = it + off;
    const uint32_t ro = lds32(sb + CTAB + (it - NSLOT) * 16 + 8);
    mbar_wait(full + 64 + (u & 7) * 8, ((u >> 3) & 1) ^ 1);
    red_add_elect((uint32_t*)((char*)gs + ro));
    if (it < nit) load_step(sb, tmx, gm, third, it, u & 7);
    else if (it == nit) mbar_arrive_elect(full);
    if (it >= nit - 16) {
      const bool pre = it < nit - 12 && cidx < 24;
      if (pre || it == nit - 1) {
        wait_value(gs->wflag, 12 * lds32(sb + MISC + 256), 32);
        asm volatile("fence.acquire.gpu;\nfence.proxy.async.global;" ::: "memory");
      }
      if (pre) asm volatile("{.reg .pred p; elect.sync _|p, 0xffffffff; @p cp.async.bulk.prefetch.L2.global [%0], 1536;}" ::"l"(gs->wimg + (cidx * 4 + k) * 1536) : "memory");
      const int m = it == nit - 1 ? 0 : W2S;
      if (it == nit - 1 || it == nit + 3) bulk_load<73728>(sb + m, gs->wimg + m, sb + WBAR);
    }
  }
}

__device__ __forceinline__ void conv_credit(uint32_t sb, Globals* gs, int q0, int nit, int off, uint32_t ctarget, int k) {
  const uint32_t full = sb + CM;
#pragma unroll 1
  for (int it = k + NSLOT; it <= nit; it += 4) {
    const int u = it + off, q = (int)lds32(sb + CTAB + it * 16 + 12) - RING;
    mbar_wait(full + 64 + (u & 7) * 8, ((u >> 3) & 1) ^ 1);
    if (q >= q0) wait_value(&gs->cons[q], ctarget, 200);
    mbar_arrive_elect(full + (u & 7) * 8);
  }
}

__device__ __noinline__ int generic_role() {
  const int cidx = (blockIdx.x * NCONV) / gridDim.x;
  return cidx | ((((blockIdx.x + 1) * NCONV) / gridDim.x != cidx) << 16);
}

__global__ void __launch_bounds__(512, 1) convnext_kernel(const __nv_bfloat16* __restrict__ dw, const __nv_bfloat16* __restrict__ w1, const __nv_bfloat16* __restrict__ w2,
                                                          __nv_bfloat16* __restrict__ out, Globals* gs, int want_sms,
                                                          const __grid_constant__ CUtensorMap tmx, const __grid_constant__ CUtensorMap tmr) {
  extern __shared__ __align__(1024) unsigned char smem[];
  const uint32_t sb = smem_u32(smem);
  const int warp = __shfl_sync(0xffffffffu, threadIdx.x >> 5, 0), lane = threadIdx.x & 31;
  uint32_t smid, nsmid;
  asm volatile("mov.u32 %0, %%smid;" : "=r"(smid));
  asm volatile("mov.u32 %0, %%nsmid;" : "=r"(nsmid));
  const bool tabled = TABLED && (int)nsmid == want_sms;
  const int id = tabled ? smid : blockIdx.x;
  int cidx, idx, is_conv;
  if (tabled) {
    idx = smid;
    static_assert(SCHED_NMID == 1 && LT, "role table");
    is_conv = smid < 48 || smid == SCHED_MID0 || smid == SCHED_MID1 || smid == SCHED_MID2;
    cidx = smid < 48 ? (((smid >> 1) & 7) + (smid & 1) * NP) * 3 + (smid >> 4) : 24 + (smid == SCHED_MID1) + 2 * (smid == SCHED_MID2);
  } else {
    const int r = generic_role();
    cidx = r & 0xffff; is_conv = r >> 16;
    idx = blockIdx.x - cidx;
  }
  const int gm = cidx / 3, third = cidx - gm * 3;
  const int q0 = gm * PLEN, nit = gm < 8 ? PLEN + 2 : gm < NP ? NSEG * (LM + 3) : LT + 3, off = (8 - nit) & 7;
  if (is_conv && warp == 8) {
    bulk_load<9408, true>(sb, dw, sb + WBAR + 8);
    asm volatile("bar.arrive 5, 288;" ::: "memory");
#pragma unroll 1
    for (int it = 0; it < NSLOT; it++) {
      const int s = (it + off) & 7;
      ring_bar_init(sb + CM + s * 8, 2, s < off);
      if (it < FIRST) load_step(sb, &tmx, gm, third, it, s, true);
    }
  }
  if (warp == 15) asm volatile("prefetch.tensormap [%0];" ::"l"(&tmr) : "memory");
  mbar_init_elect(sb + MISC + warp * 8, 1); mbar_init_elect(sb + MISC + 128 + warp * 8, 1);
  asm volatile("fence.mbarrier_init.release.cluster;" ::: "memory");
  if (is_conv) {
    if (warp >= 8) ring_bar_init(sb + CM + warp * 8, 8, warp - 8 < off);
    if (warp == 9) mbar_init_elect(sb + WBAR, 2);
    const uint32_t lastph = (((nit + off) >> 3) & 1) ^ 1;
    if (warp < 8) {
      conv_compute(sb, gs, third, nit, off, gm < 8, gm < 8 && (gm & 1), warp, lane);
      asm volatile("setmaxnreg.dec.sync.aligned.u32 128;");
    } else if (warp >= 12) {
      asm volatile("setmaxnreg.dec.sync.aligned.u32 24;");
      const uint32_t epoch = ld_relaxed(&gs->epoch[id]);
#pragma unroll 1
      for (int it = threadIdx.x - 384; it <= nit; it += 128) {
        const int seg = it / (LM + 3), j = gm < 8 ? it - 2 : it - 3 * (seg + 1);
        const bool ok = it < nit && j >= (gm < 8 ? 0 : seg * LM);
        sts128(sb + CTAB + it * 16, make_uint4((ok ? (j % RING) * NG + gm : -1) * (4 * TILEB), slot_tag(gm, max(j, 0), epoch),
                                               offsetof(Globals, ready) + (ok ? q0 + j : NG * PLEN) * 4, ok ? q0 + j : -1));
      }
      if (threadIdx.x == 384) sts32(sb + MISC + 256, epoch + 1);
      asm volatile("bar.sync 0, 512;" ::: "memory");
      mbar_arrive_elect(sb + CM + ((((warp + 2) & 3) + off) & 7) * 8);
      mbar_arrive_elect(sb + CM + ((((warp + 2) & 3) + off + 4) & 7) * 8);
      build_tile_list(sb, threadIdx.x - 384, idx, tabled, true, epoch);
      if (threadIdx.x == 384) gs->epoch[id] = epoch + 1;
      asm volatile("bar.sync 6, 128;" ::: "memory");
      conv_credit(sb, gs, q0, nit, off, 16 * (epoch + 1), (warp + 2) & 3);
#pragma unroll 1
      for (int i = 0; i < 4; i++) {
        const uint2 e = lds64(sb + MISC + 512 + i * 16);
        mbar_wait(sb + CM + 64 + (4 + min(i, 2)) * 8, lastph);
        const int wi = 4 * i + (warp & 3);
        if ((int)e.x >= 0) bulk_load<3072>(sb + ABUF + wi * 3072, gs->scratch + (e.y & ~1u) + (warp & 3) * 3072, sb + MISC + wi * 8);
      }
      mbar_wait(sb + CM + 64 + 7 * 8, lastph);
      asm volatile("setmaxnreg.inc.sync.aligned.u32 128;");
    } else {
      asm volatile("setmaxnreg.dec.sync.aligned.u32 24;");
      conv_loader(sb, gs, &tmx, gm, nit, off, cidx, third, warp & 3);
      mbar_wait(sb + CM + 64 + 7 * 8, lastph);
      asm volatile("setmaxnreg.inc.sync.aligned.u32 128;");
    }
    mbar_wait(sb + WBAR, 0);
    asm volatile("bar.sync 0, 512;" ::: "memory");
  } else {
    mlp_setup(sb, gs, id, w1, w2, idx, tabled, warp, lane);
  }
  mlp_role(sb, gs, &tmr, out);
}

typedef CUresult (*PFN_encodeTiled)(CUtensorMap*, CUtensorMapDataType, cuuint32_t, void*, const cuuint64_t*, const cuuint64_t*, const cuuint32_t*, const cuuint32_t*,
                                    CUtensorMapInterleave, CUtensorMapSwizzle, CUtensorMapL2promotion, CUtensorMapFloatOOBfill);

extern "C" void kernel_launch(void* const* d_in, const int* in_sizes, int n_in, void* d_out, int out_size) {
  const __nv_bfloat16* x = (const __nv_bfloat16*)d_in[0];
  const __nv_bfloat16* dw = (const __nv_bfloat16*)d_in[1];
  const __nv_bfloat16* w1 = (const __nv_bfloat16*)d_in[2];
  const __nv_bfloat16* w2 = (const __nv_bfloat16*)d_in[3];
  static PFN_encodeTiled encode = nullptr;
  static int nsm = 0;
  static Globals* gs = nullptr;
  if (!encode) {
    void* fn = nullptr; cudaDriverEntryPointQueryResult qr;
    cudaGetDriverEntryPoint("cuTensorMapEncodeTiled", &fn, cudaEnableDefault, &qr);
    encode = (PFN_encodeTiled)fn;
    cudaGetSymbolAddress((void**)&gs, g_state);
    int dev = 0; cudaGetDevice(&dev);
    cudaDeviceGetAttribute(&nsm, cudaDevAttrMultiProcessorCount, dev);
    cudaFuncSetAttribute(convnext_kernel, cudaFuncAttributeMaxDynamicSharedMemorySize, SMEM_BYTES);
  }
  CUtensorMap tm, tr;
  cuuint64_t dims[3] = {96, 512, 512}, strides[2] = {192, 192 * 512};
  cuuint32_t box[3] = {32, 70, 2}, es[3] = {1, 1, 1};
  encode(&tm, CU_TENSOR_MAP_DATA_TYPE_BFLOAT16, 3, (void*)x, dims, strides, box, es, CU_TENSOR_MAP_INTERLEAVE_NONE, CU_TENSOR_MAP_SWIZZLE_64B,
         CU_TENSOR_MAP_L2_PROMOTION_L2_128B, CU_TENSOR_MAP_FLOAT_OOB_FILL_NONE);
  cuuint64_t dims2[3] = {1536, 32, 512}, strides2[2] = {3072, 192 * 512};
  cuuint32_t box2[3] = {192, 4, 2};
  encode(&tr, CU_TENSOR_MAP_DATA_TYPE_BFLOAT16, 3, (void*)x, dims2, strides2, box2, es, CU_TENSOR_MAP_INTERLEAVE_NONE, CU_TENSOR_MAP_SWIZZLE_NONE,
         CU_TENSOR_MAP_L2_PROMOTION_NONE, CU_TENSOR_MAP_FLOAT_OOB_FILL_NONE);
  convnext_kernel<<<nsm, 512, SMEM_BYTES>>>(dw, w1, w2, (__nv_bfloat16*)d_out, gs, nsm == 132 ? 132 : -1, tm, tr);
}
```

```cpp
#include <cuda_runtime.h>
#include <cuda_bf16.h>
#include <cuda.h>
#include <stdint.h>
#include <stddef.h>

template<int SCALE_D> __device__ __forceinline__ void wgmma_n64_f16(uint32_t* d, const uint32_t* a, uint64_t desc) {
  if (SCALE_D == 0) asm volatile("wgmma.mma_async.sync.aligned.m64n64k16.f16.f16.f16 {%0,%1,%2,%3,%4,%5,%6,%7,%8,%9,%10,%11,%12,%13,%14,%15}, {%16,%17,%18,%19}, %20, 0, 1, 1, 1;"
    : "=r"(d[0]),"=r"(d[1]),"=r"(d[2]),"=r"(d[3]),"=r"(d[4]),"=r"(d[5]),"=r"(d[6]),"=r"(d[7]),"=r"(d[8]),"=r"(d[9]),"=r"(d[10]),"=r"(d[11]),"=r"(d[12]),"=r"(d[13]),"=r"(d[14]),"=r"(d[15])
    : "r"(a[0]),"r"(a[1]),"r"(a[2]),"r"(a[3]),"l"(desc));
  if (SCALE_D == 1) asm volatile("wgmma.mma_async.sync.aligned.m64n64k16.f16.f16.f16 {%0,%1,%2,%3,%4,%5,%6,%7,%8,%9,%10,%11,%12,%13,%14,%15}, {%16,%17,%18,%19}, %20, 1, 1, 1, 1;"
    : "+r"(d[0]),"+r"(d[1]),"+r"(d[2]),"+r"(d[3]),"+r"(d[4]),"+r"(d[5]),"+r"(d[6]),"+r"(d[7]),"+r"(d[8]),"+r"(d[9]),"+r"(d[10]),"+r"(d[11]),"+r"(d[12]),"+r"(d[13]),"+r"(d[14]),"+r"(d[15])
    : "r"(a[0]),"r"(a[1]),"r"(a[2]),"r"(a[3]),"l"(desc));
}

template<int SCALE_D> __device__ __forceinline__ void wgmma_n96_f16(uint32_t* d, const uint32_t* a, uint64_t desc) {
  if (SCALE_D == 0) asm volatile("wgmma.mma_async.sync.aligned.m64n96k16.f16.f16.f16 {%0,%1,%2,%3,%4,%5,%6,%7,%8,%9,%10,%11,%12,%13,%14,%15,%16,%17,%18,%19,%20,%21,%22,%23}, {%24,%25,%26,%27}, %28, 0, 1, 1, 1;"
    : "=r"(d[0]),"=r"(d[1]),"=r"(d[2]),"=r"(d[3]),"=r"(d[4]),"=r"(d[5]),"=r"(d[6]),"=r"(d[7]),"=r"(d[8]),"=r"(d[9]),"=r"(d[10]),"=r"(d[11]),"=r"(d[12]),"=r"(d[13]),"=r"(d[14]),"=r"(d[15]),"=r"(d[16]),"=r"(d[17]),"=r"(d[18]),"=r"(d[19]),"=r"(d[20]),"=r"(d[21]),"=r"(d[22]),"=r"(d[23])
    : "r"(a[0]),"r"(a[1]),"r"(a[2]),"r"(a[3]),"l"(desc));
  if (SCALE_D == 1) asm volatile("wgmma.mma_async.sync.aligned.m64n96k16.f16.f16.f16 {%0,%1,%2,%3,%4,%5,%6,%7,%8,%9,%10,%11,%12,%13,%14,%15,%16,%17,%18,%19,%20,%21,%22,%23}, {%24,%25,%26,%27}, %28, 1, 1, 1, 1;"
    : "+r"(d[0]),"+r"(d[1]),"+r"(d[2]),"+r"(d[3]),"+r"(d[4]),"+r"(d[5]),"+r"(d[6]),"+r"(d[7]),"+r"(d[8]),"+r"(d[9]),"+r"(d[10]),"+r"(d[11]),"+r"(d[12]),"+r"(d[13]),"+r"(d[14]),"+r"(d[15]),"+r"(d[16]),"+r"(d[17]),"+r"(d[18]),"+r"(d[19]),"+r"(d[20]),"+r"(d[21]),"+r"(d[22]),"+r"(d[23])
    : "r"(a[0]),"r"(a[1]),"r"(a[2]),"r"(a[3]),"l"(desc));
}

#define SCHED_NMID 1
#define SCHED_LE 106
#define SCHED_LT 10
#define SCHED_RING 16
#define SCHED_MID0 50
#define SCHED_MID1 64
#define SCHED_MID2 78
__device__ const uint16_t g_sched[132][48] = {
{388,391,394,65535,65535,65535,65535,65535,65535,65535,65535,65535,65535,65535,65535,65535,65535,65535,65535,65535,65535,65535,65535,65535,65535,65535,65535,65535,65535,65535,65535,65535,65535,65535,65535,65535,65535,65535,65535,65535,65535,65535,65535,65535,65535,65535,65535,65535},
{3824,3827,3830,3833,42,52,64,75,87,99,112,123,135,147,158,170,182,193,205,218,229,241,253,265,276,288,300,311,324,336,348,359,371,383,404,415,65535,65535,65535,65535,65535,65535,65535,65535,65535,65535,65535,65535},
{812,815,818,65535,65535,65535,65535,65535,65535,65535,65535,65535,65535,65535,65535,65535,65535,65535,65535,65535,65535,65535,65535,65535,65535,65535,65535,65535,65535,65535,65535,65535,65535,65535,65535,65535,65535,65535,65535,65535,65535,65535,65535,65535,65535,65535,65535,65535},
{4248,4251,4254,4257,4278,478,489,501,513,524,3489,549,561,572,584,596,607,619,631,3584,655,667,679,690,702,714,725,737,751,762,773,785,797,808,829,841,65535,65535,65535,65535,65535,65535,65535,65535,65535,65535,65535,65535},
{1236,1239,1242,65535,65535,65535,65535,65535,65535,65535,65535,65535,65535,65535,65535,65535,65535,65535,65535,65535,65535,65535,65535,65535,65535,65535,65535,65535,65535,65535,65535,65535,65535,65535,65535,65535,65535,65535,65535,65535,65535,65535,65535,65535,65535,65535,65535,65535},
{4672,4675,4678,4681,891,902,913,925,937,948,961,973,985,996,1008,1020,1031,1043,1055,1067,1080,1091,1103,1114,1126,1138,1149,1161,1173,1186,1197,1209,1221,1232,1253,1265,65535,65535,65535,65535,65535,65535,65535,65535,65535,65535,65535,65535},
{1660,1663,1666,65535,65535,65535,65535,65535,65535,65535,65535,65535,65535,65535,65535,65535,65535,65535,65535,65535,65535,65535,65535,65535,65535,65535,65535,65535,65535,65535,65535,65535,65535,65535,65535,65535,65535,65535,65535,65535,65535,65535,65535,65535,65535,65535,65535,65535},
{5096,5099,5102,5105,1315,1325,1337,1349,1360,1372,1385,1397,1408,1420,1432,1443,1455,1467,1478,1491,1503,1515,1526,1538,1550,1561,1573,1585,1597,1609,1621,1633,1644,1656,1677,1688,65535,65535,65535,65535,65535,65535,65535,65535,65535,65535,65535,65535},
{2084,2087,2090,65535,65535,65535,65535,65535,65535,65535,65535,65535,65535,65535,65535,65535,65535,65535,65535,65535,65535,65535,65535,65535,65535,65535,65535,65535,65535,65535,65535,65535,65535,65535,65535,65535,65535,65535,65535,65535,65535,65535,65535,65535,65535,65535,65535,65535},
{5520,5523,5526,5529,1739,1750,1762,1773,1785,1797,1809,1821,1833,1845,1856,1868,1880,1891,1903,1916,1928,1939,1951,1963,1974,1986,1998,2009,2022,2034,2046,2057,2069,2081,2101,2113,65535,65535,65535,65535,65535,65535,65535,65535,65535,65535,65535,65535},
{2508,2511,2514,65535,65535,65535,65535,65535,65535,65535,65535,65535,65535,65535,65535,65535,65535,65535,65535,65535,65535,65535,65535,65535,65535,65535,65535,65535,65535,65535,65535,65535,65535,65535,65535,65535,65535,65535,65535,65535,65535,65535,65535,65535,65535,65535,65535,65535},
{5944,5947,5950,5953,2163,2174,2186,2197,2209,2221,2234,2245,2257,2269,2280,2292,2304,2315,2327,2340,2352,2363,2375,2387,2398,2410,2422,2433,2446,2458,2470,2481,2493,2505,2525,2537,65535,65535,65535,65535,65535,65535,65535,65535,65535,65535,65535,65535},
{2932,2935,2938,65535,65535,65535,65535,65535,65535,65535,65535,65535,65535,65535,65535,65535,65535,65535,65535,65535,65535,65535,65535,65535,65535,65535,65535,65535,65535,65535,65535,65535,65535,65535,65535,65535,65535,65535,65535,65535,65535,65535,65535,65535,65535,65535,65535,65535},
{6368,6371,6374,6377,6399,2599,3453,3465,2634,2646,2659,3501,2682,3524,3536,2717,3559,3571,2752,2765,3595,3607,2800,3630,3642,2835,3665,3677,2871,2883,3701,3713,2918,3736,2950,2962,65535,65535,65535,65535,65535,65535,65535,65535,65535,65535,65535,65535},
{3356,3359,3362,65535,65535,65535,65535,65535,65535,65535,65535,65535,65535,65535,65535,65535,65535,65535,65535,65535,65535,65535,65535,65535,65535,65535,65535,65535,65535,65535,65535,65535,65535,65535,65535,65535,65535,65535,65535,65535,65535,65535,65535,65535,65535,65535,65535,65535},
{6792,6795,6798,6801,3012,3022,3034,3046,3057,3069,3082,3094,3105,3117,3129,3140,3152,3164,3175,3188,3200,3212,3223,3235,3247,3258,3270,3282,3295,3306,3318,3330,3341,3353,3374,3385,65535,65535,65535,65535,65535,65535,65535,65535,65535,65535,65535,65535},
{389,392,395,65535,65535,65535,65535,65535,65535,65535,65535,65535,65535,65535,65535,65535,65535,65535,65535,65535,65535,65535,65535,65535,65535,65535,65535,65535,65535,65535,65535,65535,65535,65535,65535,65535,65535,65535,65535,65535,65535,65535,65535,65535,65535,65535,65535,65535},
{3825,3828,3831,3834,3854,53,65,76,88,100,113,124,136,148,159,171,183,194,206,219,230,242,254,266,277,289,301,312,325,337,349,360,372,384,405,416,65535,65535,65535,65535,65535,65535,65535,65535,65535,65535,65535,65535},
{813,816,819,65535,65535,65535,65535,65535,65535,65535,65535,65535,65535,65535,65535,65535,65535,65535,65535,65535,65535,65535,65535,65535,65535,65535,65535,65535,65535,65535,65535,65535,65535,65535,65535,65535,65535,65535,65535,65535,65535,65535,65535,65535,65535,65535,65535,65535},
{4249,4252,4255,4258,467,3442,490,502,3477,525,538,550,3513,573,585,3548,608,620,3583,645,656,668,3619,691,703,3654,726,738,752,3690,774,786,3725,809,3757,3769,65535,65535,65535,65535,65535,65535,65535,65535,65535,65535,65535,65535},
{1237,1240,1243,65535,65535,65535,65535,65535,65535,65535,65535,65535,65535,65535,65535,65535,65535,65535,65535,65535,65535,65535,65535,65535,65535,65535,65535,65535,65535,65535,65535,65535,65535,65535,65535,65535,65535,65535,65535,65535,65535,65535,65535,65535,65535,65535,65535,65535},
{4673,4676,4679,4682,4703,903,914,926,938,949,962,974,986,997,1009,1021,1032,1044,1056,1068,1081,1092,1104,1115,1127,1139,1150,1162,1174,1187,1198,1210,1222,1233,1254,1266,65535,65535,65535,65535,65535,65535,65535,65535,65535,65535,65535,65535},
{1661,1664,1667,65535,65535,65535,65535,65535,65535,65535,65535,65535,65535,65535,65535,65535,65535,65535,65535,65535,65535,65535,65535,65535,65535,65535,65535,65535,65535,65535,65535,65535,65535,65535,65535,65535,65535,65535,65535,65535,65535,65535,65535,65535,65535,65535,65535,65535},
{5097,5100,5103,5106,5127,1326,1338,1350,1361,1373,1386,1398,1409,1421,1433,1444,1456,1468,1479,1492,1504,1516,1527,1539,1551,1562,1574,1586,1598,1610,1622,1634,1645,1657,1678,1689,65535,65535,65535,65535,65535,65535,65535,65535,65535,65535,65535,65535},
{2085,2088,2091,65535,65535,65535,65535,65535,65535,65535,65535,65535,65535,65535,65535,65535,65535,65535,65535,65535,65535,65535,65535,65535,65535,65535,65535,65535,65535,65535,65535,65535,65535,65535,65535,65535,65535,65535,65535,65535,65535,65535,65535,65535,65535,65535,65535,65535},
{5521,5524,5527,5530,5551,1751,1763,1774,1786,1798,1810,1822,1834,1846,1857,1869,1881,1892,1904,1917,1929,1940,1952,1964,1975,1987,1999,2010,2023,2035,2047,2058,2070,2082,2102,2114,65535,65535,65535,65535,65535,65535,65535,65535,65535,65535,65535,65535},
{2509,2512,2515,65535,65535,65535,65535,65535,65535,65535,65535,65535,65535,65535,65535,65535,65535,65535,65535,65535,65535,65535,65535,65535,65535,65535,65535,65535,65535,65535,65535,65535,65535,65535,65535,65535,65535,65535,65535,65535,65535,65535,65535,65535,65535,65535,65535,65535},
{5945,5948,5951,5954,5975,2175,2187,2198,2210,2222,2235,2246,2258,2270,2281,2293,2305,2316,2328,2341,2353,2364,2376,2388,2399,2411,2423,2434,2447,2459,2471,2482,2494,2506,2526,2538,65535,65535,65535,65535,65535,65535,65535,65535,65535,65535,65535,65535},
{2933,2936,2939,65535,65535,65535,65535,65535,65535,65535,65535,65535,65535,65535,65535,65535,65535,65535,65535,65535,65535,65535,65535,65535,65535,65535,65535,65535,65535,65535,65535,65535,65535,65535,65535,65535,65535,65535,65535,65535,65535,65535,65535,65535,65535,65535,65535,65535},
{6369,6372,6375,6378,2588,2600,2611,2623,2635,2647,3490,2671,2683,2694,2706,2718,2729,2741,2753,2766,2777,2789,2801,2812,2824,2836,2847,2859,2872,2884,2895,2907,2919,2930,2951,2963,65535,65535,65535,65535,65535,65535,65535,65535,65535,65535,65535,65535},
{3357,3360,3363,65535,65535,65535,65535,65535,65535,65535,65535,65535,65535,65535,65535,65535,65535,65535,65535,65535,65535,65535,65535,65535,65535,65535,65535,65535,65535,65535,65535,65535,65535,65535,65535,65535,65535,65535,65535,65535,65535,65535,65535,65535,65535,65535,65535,65535},
{6793,6796,6799,6802,3431,3023,3035,3047,3058,3070,3083,3095,3106,3118,3130,3141,3153,3165,3176,3189,3201,3213,3224,3236,3248,3259,3271,3283,3296,3307,3319,3331,3342,3354,3375,3386,65535,65535,65535,65535,65535,65535,65535,65535,65535,65535,65535,65535},
{390,393,396,65535,65535,65535,65535,65535,65535,65535,65535,65535,65535,65535,65535,65535,65535,65535,65535,65535,65535,65535,65535,65535,65535,65535,65535,65535,65535,65535,65535,65535,65535,65535,65535,65535,65535,65535,65535,65535,65535,65535,65535,65535,65535,65535,65535,65535},
{3826,3829,3832,3835,43,54,66,77,89,101,114,125,137,149,160,172,184,195,207,220,231,243,255,267,278,290,302,313,326,338,350,361,373,385,406,417,65535,65535,65535,65535,65535,65535,65535,65535,65535,65535,65535,65535},
{814,817,820,65535,65535,65535,65535,65535,65535,65535,65535,65535,65535,65535,65535,65535,65535,65535,65535,65535,65535,65535,65535,65535,65535,65535,65535,65535,65535,65535,65535,65535,65535,65535,65535,65535,65535,65535,65535,65535,65535,65535,65535,65535,65535,65535,65535,65535},
{4250,4253,4256,4259,4279,479,3454,3466,514,526,539,3502,562,3525,3537,597,3560,3572,632,3585,3596,3608,680,3631,3643,715,3666,3678,3680,763,3702,3714,798,3737,830,842,65535,65535,65535,65535,65535,65535,65535,65535,65535,65535,65535,65535},
{1238,1241,1244,65535,65535,65535,65535,65535,65535,65535,65535,65535,65535,65535,65535,65535,65535,65535,65535,65535,65535,65535,65535,65535,65535,65535,65535,65535,65535,65535,65535,65535,65535,65535,65535,65535,65535,65535,65535,65535,65535,65535,65535,65535,65535,65535,65535,65535},
{4674,4677,4680,4683,892,904,915,927,939,950,963,975,987,998,1010,1022,1033,1045,1057,1069,1082,1093,1105,1116,1128,1140,1151,1163,1175,1188,1199,1211,1223,1234,1255,1267,65535,65535,65535,65535,65535,65535,65535,65535,65535,65535,65535,65535},
{1662,1665,1668,65535,65535,65535,65535,65535,65535,65535,65535,65535,65535,65535,65535,65535,65535,65535,65535,65535,65535,65535,65535,65535,65535,65535,65535,65535,65535,65535,65535,65535,65535,65535,65535,65535,65535,65535,65535,65535,65535,65535,65535,65535,65535,65535,65535,65535},
{5098,5101,5104,5107,1316,1327,1339,1351,1362,1374,1387,1399,1410,1422,1434,1445,1457,1469,1480,1493,1505,1517,1528,1540,1552,1563,1575,1587,1599,1611,1623,1635,1646,1658,1679,1690,65535,65535,65535,65535,65535,65535,65535,65535,65535,65535,65535,65535},
{2086,2089,2092,65535,65535,65535,65535,65535,65535,65535,65535,65535,65535,65535,65535,65535,65535,65535,65535,65535,65535,65535,65535,65535,65535,65535,65535,65535,65535,65535,65535,65535,65535,65535,65535,65535,65535,65535,65535,65535,65535,65535,65535,65535,65535,65535,65535,65535},
{5522,5525,5528,5531,1740,1752,1764,1775,1787,1799,1811,1823,1835,1847,1858,1870,1882,1893,1905,1918,1930,1941,1953,1965,1976,1988,2000,2011,2024,2036,2048,2059,2071,2083,2103,2115,65535,65535,65535,65535,65535,65535,65535,65535,65535,65535,65535,65535},
{2510,2513,2516,65535,65535,65535,65535,65535,65535,65535,65535,65535,65535,65535,65535,65535,65535,65535,65535,65535,65535,65535,65535,65535,65535,65535,65535,65535,65535,65535,65535,65535,65535,65535,65535,65535,65535,65535,65535,65535,65535,65535,65535,65535,65535,65535,65535,65535},
{5946,5949,5952,5955,2164,2176,2188,2199,2211,2223,2236,2247,2259,2271,2282,2294,2306,2317,2329,2342,2354,2365,2377,2389,2400,2412,2424,2435,2448,2460,2472,2483,2495,2507,2527,2539,65535,65535,65535,65535,65535,65535,65535,65535,65535,65535,65535,65535},
{2934,2937,2940,65535,65535,65535,65535,65535,65535,65535,65535,65535,65535,65535,65535,65535,65535,65535,65535,65535,65535,65535,65535,65535,65535,65535,65535,65535,65535,65535,65535,65535,65535,65535,65535,65535,65535,65535,65535,65535,65535,65535,65535,65535,65535,65535,65535,65535},
{6370,6373,6376,6379,2589,3443,2612,2624,3478,2648,2660,2672,3514,2695,2707,3549,2730,2742,2754,2767,2778,2790,3620,2813,2825,3655,2848,2860,2873,3691,2896,2908,3726,2931,3758,3770,65535,65535,65535,65535,65535,65535,65535,65535,65535,65535,65535,65535},
{3358,3361,3364,65535,65535,65535,65535,65535,65535,65535,65535,65535,65535,65535,65535,65535,65535,65535,65535,65535,65535,65535,65535,65535,65535,65535,65535,65535,65535,65535,65535,65535,65535,65535,65535,65535,65535,65535,65535,65535,65535,65535,65535,65535,65535,65535,65535,65535},
{6794,6797,6800,6803,3013,3024,3036,3048,3059,3071,3084,3096,3107,3119,3131,3142,3154,3166,3177,3190,3202,3214,3225,3237,3249,3260,3272,3284,3297,3308,3320,3332,3343,3355,3376,3387,65535,65535,65535,65535,65535,65535,65535,65535,65535,65535,65535,65535},
{0,429,12,21,27,32,37,3428,51,3449,497,86,3484,110,545,134,3520,580,169,3555,615,204,216,651,240,252,3626,698,287,3661,733,322,335,3697,781,370,3732,403,414,65535,65535,65535,65535,65535,65535,65535,65535,65535},
{1,3393,435,444,3839,3844,3849,4276,474,63,3461,509,98,111,3497,557,146,3532,592,181,3567,627,217,3591,663,675,264,3638,710,299,3673,323,758,347,3709,793,382,826,837,65535,65535,65535,65535,65535,65535,65535,65535,65535},
{3740,3743,3746,65535,65535,65535,65535,65535,65535,65535,65535,65535,65535,65535,65535,65535,65535,65535,65535,65535,65535,65535,65535,65535,65535,65535,65535,65535,65535,65535,65535,65535,65535,65535,65535,65535,65535,65535,65535,65535,65535,65535,65535,65535,65535,65535,65535,65535},
{424,4241,3399,3408,450,455,460,465,3438,486,498,3473,521,534,546,3509,569,581,3544,604,616,3579,640,652,3603,3615,687,699,3650,722,734,746,3686,770,782,3721,805,3754,3765,65535,65535,65535,65535,65535,65535,65535,65535,65535},
{848,4666,859,867,4686,4690,4695,4700,897,908,920,932,943,956,968,980,991,1003,1015,1026,1038,1050,1062,1075,1086,1098,1109,1121,1133,1144,1156,1168,1181,1192,1204,1216,1227,1248,1260,65535,65535,65535,65535,65535,65535,65535,65535,65535},
{849,855,4671,868,875,879,884,889,898,909,921,933,944,957,969,981,992,1004,1016,1027,1039,1051,1063,1076,1087,1099,1110,1122,1134,1145,1157,1169,1182,1193,1205,1217,1228,1249,1261,65535,65535,65535,65535,65535,65535,65535,65535,65535},
{1272,1279,5095,1292,1299,5115,1308,1313,1322,1334,1345,1357,1369,1381,1393,1405,1417,1428,1440,1452,1463,1475,1487,1500,1511,1523,1535,1546,1558,1570,1581,1593,1606,1618,1629,1641,1653,1673,1685,65535,65535,65535,65535,65535,65535,65535,65535,65535},
{1273,5091,1284,1293,5111,1304,5120,5125,1323,1335,1346,1358,1370,1382,1394,1406,1418,1429,1441,1453,1464,1476,1488,1501,1512,1524,1536,1547,1559,1571,1582,1594,1607,1619,1630,1642,1654,1674,1686,65535,65535,65535,65535,65535,65535,65535,65535,65535},
{1696,1703,1708,1716,1723,1728,1732,1737,1746,1758,1769,1781,1793,1805,1817,1829,1841,1852,1864,1876,1887,1899,1912,1924,1936,1947,1959,1970,1982,1994,2005,2018,2030,2042,2053,2065,2077,2097,2109,65535,65535,65535,65535,65535,65535,65535,65535,65535},
{1697,5515,4247,1717,5535,5540,5544,5549,1747,1759,1770,1782,1794,1806,1818,1830,1842,1853,1865,1877,1888,1900,1913,1925,1937,1948,1960,1971,1983,1995,2006,2019,2031,2043,2054,2066,2078,2098,2110,65535,65535,65535,65535,65535,65535,65535,65535,65535},
{2120,2127,2132,2140,2147,2152,5968,2161,2170,2182,2194,2205,2217,2230,2242,2253,2265,2277,2288,2300,2312,2323,2336,2348,2360,2371,2383,2395,2406,2418,2430,2442,2454,2466,2478,2489,2501,2521,2533,65535,65535,65535,65535,65535,65535,65535,65535,65535},
{2121,5939,2133,2141,5959,5964,2157,5973,2171,2183,2195,2206,2218,2231,2243,2254,2266,2278,2289,2301,2313,2324,2337,2349,2361,2372,2384,2396,2407,2419,2431,2443,2455,2467,2479,2490,2502,2522,2534,65535,65535,65535,65535,65535,65535,65535,65535,65535},
{2544,6363,2556,2565,2571,2576,2581,6397,2595,2606,2618,2630,2641,2654,2666,2678,2689,2701,2713,2724,2736,2748,2760,2772,2784,2796,2807,2819,2831,2842,2854,2867,2879,2890,2902,2914,2925,2946,2958,65535,65535,65535,65535,65535,65535,65535,65535,65535},
{2545,430,2557,2566,6383,6388,6393,2586,2596,2607,2619,2631,2642,2655,2667,2679,2690,2702,2714,2725,2737,2749,2761,2773,2785,2797,2808,2820,2832,2843,2855,2868,2880,2891,2903,2915,2926,2947,2959,65535,65535,65535,65535,65535,65535,65535,65535,65535},
{2968,3394,2980,2990,6807,3000,3005,3010,3019,3031,3043,3054,3066,3079,3091,3102,3114,3126,3137,3149,3161,3172,3185,3197,3209,3220,3232,3244,3255,3267,3279,3291,3303,3315,3327,3338,3350,3370,3382,65535,65535,65535,65535,65535,65535,65535,65535,65535},
{2969,4242,2981,445,3414,6812,6817,6822,3020,3450,3462,3055,3485,3080,3498,3103,3521,3533,3138,3556,3568,3173,3186,3592,664,3221,3627,3639,3256,3662,3674,3292,3304,3698,3710,3339,3733,3371,3383,65535,65535,65535,65535,65535,65535,65535,65535,65535},
{3741,3744,3747,65535,65535,65535,65535,65535,65535,65535,65535,65535,65535,65535,65535,65535,65535,65535,65535,65535,65535,65535,65535,65535,65535,65535,65535,65535,65535,65535,65535,65535,65535,65535,65535,65535,65535,65535,65535,65535,65535,65535,65535,65535,65535,65535,65535,65535},
{425,431,436,3409,4262,3419,3424,3429,475,487,499,510,522,535,547,558,570,582,593,605,617,628,641,653,3604,676,688,700,711,723,735,747,759,771,783,794,806,827,838,65535,65535,65535,65535,65535,65535,65535,65535,65535},
{850,4667,860,869,4687,4691,4696,4701,899,910,922,934,945,958,970,982,993,1005,1017,1028,1040,1052,1064,1077,1088,1100,1111,1123,1135,1146,1158,1170,1183,1194,1206,1218,1229,1250,1262,65535,65535,65535,65535,65535,65535,65535,65535,65535},
{851,856,861,870,876,880,885,890,900,911,923,935,946,959,971,983,994,1006,1018,1029,1041,1053,1065,1078,1089,1101,1112,1124,1136,1147,1159,1171,1184,1195,1207,1219,1230,1251,1263,65535,65535,65535,65535,65535,65535,65535,65535,65535},
{1274,1280,1285,1294,1300,5116,1309,1314,1324,1336,1347,1359,1371,1383,1395,1407,1419,1430,1442,1454,1465,1477,1489,1502,1513,1525,1537,1548,1560,1572,1583,1595,1608,1620,1631,1643,1655,1675,1687,65535,65535,65535,65535,65535,65535,65535,65535,65535},
{1275,5092,3400,1295,5112,4267,5121,5126,3439,3451,1348,3474,3486,1384,1396,3510,3522,1431,3545,3557,1466,3580,1490,3593,1514,3616,3628,1549,3651,3663,1584,1596,3687,3699,1632,3722,3734,1676,3766,65535,65535,65535,65535,65535,65535,65535,65535,65535},
{1698,1704,1709,1718,1724,1729,1733,1738,1748,1760,1771,1783,1795,1807,1819,1831,1843,1854,1866,1878,1889,1901,1914,1926,1938,1949,1961,1972,1984,1996,2007,2020,2032,2044,2055,2067,2079,2099,2111,65535,65535,65535,65535,65535,65535,65535,65535,65535},
{1699,5516,1710,1719,5536,5541,5545,5550,1749,1761,1772,1784,1796,1808,1820,1832,1844,1855,1867,1879,1890,1902,1915,1927,665,1950,1962,1973,1985,1997,2008,2021,2033,2045,2056,2068,2080,2100,2112,65535,65535,65535,65535,65535,65535,65535,65535,65535},
{2122,2128,2134,2142,2148,2153,5969,2162,2172,2184,2196,2207,2219,2232,2244,2255,2267,2279,2290,2302,2314,2325,2338,2350,2362,2373,2385,2397,2408,2420,2432,2444,2456,2468,2480,2491,2503,2523,2535,65535,65535,65535,65535,65535,65535,65535,65535,65535},
{2123,5940,437,2143,5960,5965,4272,5974,2173,2185,3463,2208,2220,2233,3499,2256,2268,3534,2291,2303,3569,2326,2339,2351,3605,2374,2386,3640,2409,2421,3675,2445,2457,2469,3711,2492,2504,2524,2536,65535,65535,65535,65535,65535,65535,65535,65535,65535},
{2546,2552,2558,2567,2572,2577,2582,6398,2597,2608,2620,2632,2643,2656,2668,2680,2691,2703,2715,2726,2738,2750,2762,2774,2786,2798,2809,2821,2833,2844,2856,2869,2881,2892,2904,2916,2927,2948,2960,65535,65535,65535,65535,65535,65535,65535,65535,65535},
{2547,6364,3401,446,6384,6389,6394,4277,476,2609,2621,511,2644,2657,2669,559,2692,2704,594,2727,2739,629,2763,2775,2787,677,2810,2822,712,2845,2857,748,760,2893,2905,795,2928,3755,839,65535,65535,65535,65535,65535,65535,65535,65535,65535},
{2970,2976,2982,2991,2996,3001,3006,3011,3021,3032,3044,3056,3067,3081,3092,3104,3115,3127,3139,3150,3162,3174,3187,3198,3210,3222,3233,3245,3257,3268,3280,3293,3305,3316,3328,3340,3351,3372,3384,65535,65535,65535,65535,65535,65535,65535,65535,65535},
{2971,6788,2983,3410,6808,6813,6818,6823,3440,3033,3045,3475,3068,536,3093,3511,3116,3128,3546,3151,3163,3581,642,3199,3211,3617,3234,3246,3652,3269,3281,3294,3688,3317,3329,3723,3352,3373,3767,65535,65535,65535,65535,65535,65535,65535,65535,65535},
{3742,3745,3748,65535,65535,65535,65535,65535,65535,65535,65535,65535,65535,65535,65535,65535,65535,65535,65535,65535,65535,65535,65535,65535,65535,65535,65535,65535,65535,65535,65535,65535,65535,65535,65535,65535,65535,65535,65535,65535,65535,65535,65535,65535,65535,65535,65535,65535},
{426,3395,438,447,451,456,461,466,477,488,500,512,523,3488,548,560,571,583,595,606,618,630,643,654,666,678,689,701,713,724,736,749,761,772,784,796,807,828,840,65535,65535,65535,65535,65535,65535,65535,65535,65535},
{852,857,863,872,877,881,886,893,905,916,928,940,951,964,976,988,999,1011,1023,1034,1046,1058,1070,657,1094,1106,1117,1129,1141,1152,1164,1176,1189,1200,1212,1224,1235,1256,1268,65535,65535,65535,65535,65535,65535,65535,65535,65535},
{4664,4669,864,4684,4689,4693,4698,468,480,491,503,515,952,3491,551,563,574,586,598,609,621,633,1071,3597,669,681,692,704,716,727,739,1177,764,775,787,799,810,831,843,65535,65535,65535,65535,65535,65535,65535,65535,65535},
{1276,1281,1286,1296,1301,1305,1310,1317,1328,1340,1352,1363,1375,1388,1400,1411,1423,1435,1446,1458,1470,1481,1494,1506,1518,1529,1541,1553,1564,1576,1588,1600,1612,1624,1636,1647,1659,1680,1691,65535,65535,65535,65535,65535,65535,65535,65535,65535},
{5088,5093,1287,5108,5113,5117,5122,3432,1329,3455,3467,1364,1376,1389,3503,1412,3526,3538,1447,3561,3573,1482,1495,1507,3609,1530,3632,3644,1565,3667,3679,1601,1613,3703,3715,1648,3738,3759,1692,65535,65535,65535,65535,65535,65535,65535,65535,65535},
{1700,1705,1711,1720,1725,1730,1734,1741,1753,1765,1776,1788,1800,1812,1824,1836,1848,1859,1871,1883,1894,1906,1919,1931,1942,1954,1966,1977,1989,2001,2012,2025,2037,2049,2060,2072,811,2104,2116,65535,65535,65535,65535,65535,65535,65535,65535,65535},
{5512,5517,1712,5532,5537,5542,5546,1742,3444,492,1777,3479,527,1813,1825,3515,575,1860,3550,610,1895,1907,646,658,1943,3621,693,1978,3656,728,2013,2026,3692,776,2061,3727,3739,2105,3771,65535,65535,65535,65535,65535,65535,65535,65535,65535},
{2124,2129,2135,2144,2149,2154,2158,2165,2177,2189,2200,2212,2224,2237,2248,2260,2272,2283,2295,2307,2318,2330,2343,2355,2366,2378,2390,2401,2413,2425,2436,2449,2461,2473,2484,2496,2517,2528,2540,65535,65535,65535,65535,65535,65535,65535,65535,65535},
{5936,5941,2136,5956,5961,5966,5970,2166,2178,3456,2201,2213,2225,540,2249,2261,3527,2284,2296,3562,2319,2331,3586,3598,2367,2379,3633,2402,2414,3668,2437,2450,2462,3704,2485,2497,386,2529,2541,65535,65535,65535,65535,65535,65535,65535,65535,65535},
{2548,6365,2560,6380,2573,2578,2583,2590,2601,2613,2625,2636,2649,2661,2673,2684,2696,2708,2719,2731,2743,2755,2768,2779,2791,2802,2814,2826,2837,2849,2861,2874,2885,2897,2909,2920,2941,2952,2964,65535,65535,65535,65535,65535,65535,65535,65535,65535},
{6360,432,439,2569,6385,6390,6395,469,2602,2614,504,2637,528,3492,552,2685,2697,587,2720,2732,622,634,647,2780,670,2803,2815,705,2838,2850,740,753,2886,2898,788,2921,2942,2953,2965,65535,65535,65535,65535,65535,65535,65535,65535,65535},
{2972,2977,2984,2992,2997,3002,3007,3014,3025,3037,3049,3060,3072,3085,3097,3108,3120,3132,3143,3155,3167,3178,3191,3203,3215,3226,3238,3250,3261,3273,3285,3298,3309,3321,3333,3344,3365,3377,3388,65535,65535,65535,65535,65535,65535,65535,65535,65535},
{6784,6789,3403,6804,6809,6814,6819,3433,3026,3038,3468,3061,3073,3086,3504,3109,3121,3539,3144,3156,3574,3179,3192,3204,3610,3227,3239,3645,3262,3274,3286,3681,3310,3322,3716,3345,3366,832,3389,65535,65535,65535,65535,65535,65535,65535,65535,65535},
{427,4243,3402,3411,3415,3420,3425,3430,3441,3452,3464,3476,3487,537,3500,3512,3523,3535,3547,3558,3570,3582,644,3594,3606,3618,3629,3641,3653,3664,3676,750,3689,3700,3712,3724,3735,3756,3768,65535,65535,65535,65535,65535,65535,65535,65535,65535},
{428,3396,440,448,452,457,462,470,481,493,505,516,529,541,553,564,576,588,599,611,623,635,3587,659,671,682,694,706,717,729,741,754,765,777,789,800,821,3760,844,65535,65535,65535,65535,65535,65535,65535,65535,65535},
{853,4244,865,873,3416,882,887,894,906,917,929,941,953,965,977,989,1000,1012,1024,1035,1047,1059,1072,1083,1095,1107,1118,1130,1142,1153,1165,1178,1190,1201,1213,1225,1245,1257,1269,65535,65535,65535,65535,65535,65535,65535,65535,65535},
{4665,858,3404,4685,4264,4694,4699,895,3445,918,930,3480,954,966,978,3516,1001,1013,3551,1036,1048,1060,1073,1084,1096,3622,1119,1131,3657,1154,1166,1179,3693,1202,1214,3728,1246,1258,3772,65535,65535,65535,65535,65535,65535,65535,65535,65535},
{1277,1282,1288,1297,1302,1306,1311,1318,1330,1341,1353,1365,1377,1390,1401,1413,1424,1436,1448,1459,1471,1483,1496,1508,1519,1531,1542,1554,1566,1577,1589,1602,1614,1625,1637,1649,1669,1681,1693,65535,65535,65535,65535,65535,65535,65535,65535,65535},
{5089,5094,1289,5109,5114,5118,5123,1319,1331,1342,1354,1366,1378,3493,1402,1414,1425,1437,1449,1460,1472,1484,1497,3599,1520,1532,1543,1555,1567,1578,1590,1603,1615,1626,1638,1650,1670,1682,1694,65535,65535,65535,65535,65535,65535,65535,65535,65535},
{1701,1706,1713,1721,1726,3421,1735,1743,1754,1766,1778,1789,1801,1814,1826,1837,1849,1861,1872,1884,1896,1908,1920,1932,1944,1955,1967,1979,1990,2002,2014,2027,2038,2050,2062,2073,2093,2106,2117,65535,65535,65535,65535,65535,65535,65535,65535,65535},
{5513,5518,1714,5533,5538,4269,5547,3434,1755,3457,3469,1790,1802,1815,3505,1838,3528,3540,1873,3563,3575,1909,1921,1933,3611,1956,3634,3646,1991,3669,2015,3682,2039,3705,3717,2074,2094,833,2118,65535,65535,65535,65535,65535,65535,65535,65535,65535},
{2125,2130,2137,2145,2150,2155,2159,2167,2179,2190,2202,2214,2226,2238,2250,2262,2273,2285,2297,2308,2320,2332,2344,2356,2368,2380,2391,2403,2415,2426,2438,2451,2463,2474,2486,2498,2518,2530,2542,65535,65535,65535,65535,65535,65535,65535,65535,65535},
{5937,5942,2138,5957,5962,5967,5971,2168,482,2191,2203,517,2227,2239,2251,565,2274,2286,600,2309,2321,2333,2345,2357,2369,683,2392,2404,718,2427,2439,2452,766,2475,2487,801,3749,3761,845,65535,65535,65535,65535,65535,65535,65535,65535,65535},
{2549,2554,2561,6381,2574,2579,3426,2591,2603,2615,2626,2638,2650,2662,2674,2686,2698,2709,2721,2733,2744,2756,2769,2781,2792,2804,2816,2827,2839,2851,2862,2875,2887,2899,2910,2922,387,2954,2966,65535,65535,65535,65535,65535,65535,65535,65535,65535},
{6361,6366,2562,3412,6386,6391,4274,2592,3446,494,2627,3481,2651,2663,2675,3517,577,2710,3552,612,2745,2757,648,660,2793,3623,695,2828,3658,730,2863,2876,3694,778,2911,3729,2943,2955,3773,65535,65535,65535,65535,65535,65535,65535,65535,65535},
{2973,2978,2985,2993,2998,3003,3008,3015,3027,3039,3050,3062,3074,3087,3098,3110,3122,3133,3145,3157,3168,3180,3193,3205,3216,3228,3240,3251,3263,3275,3287,3299,3311,3323,3334,3346,3367,3378,3390,65535,65535,65535,65535,65535,65535,65535,65535,65535},
{6785,6790,2986,6805,6810,6815,6820,3016,3028,3458,3051,3063,3075,542,3099,3111,3529,3134,3146,3564,3169,3181,3588,3600,3217,3229,3635,3252,3264,3670,742,3300,3312,3706,3335,3347,822,3379,3391,65535,65535,65535,65535,65535,65535,65535,65535,65535},
{3392,433,441,4260,453,458,463,471,483,495,506,518,530,3494,554,566,578,589,601,613,624,636,649,661,672,684,696,707,719,731,743,755,767,779,790,802,3750,834,846,65535,65535,65535,65535,65535,65535,65535,65535,65535},
{4240,3397,3405,449,3417,3422,3427,3435,3447,3459,3470,3482,531,543,3506,3518,3530,3541,3553,3565,3576,637,3589,3601,3612,3624,3636,3647,3659,3671,744,3683,3695,3707,3718,3730,823,3762,3774,65535,65535,65535,65535,65535,65535,65535,65535,65535},
{2,4668,862,871,4688,4692,4697,4702,901,912,924,936,947,960,972,984,995,1007,1019,1030,1042,1054,1066,1079,1090,1102,1113,1125,1137,1148,1160,1172,1185,1196,1208,1220,1231,1252,1264,65535,65535,65535,65535,65535,65535,65535,65535,65535},
{854,4670,866,874,878,883,888,896,907,919,931,942,955,967,979,990,1002,1014,1025,1037,1049,1061,1074,1085,1097,1108,1120,1132,1143,1155,1167,1180,1191,1203,1215,1226,1247,1259,1270,65535,65535,65535,65535,65535,65535,65535,65535,65535},
{1278,4245,1290,1298,4265,1307,1312,1320,1332,1343,1355,1367,1379,1391,1403,1415,1426,1438,1450,1461,1473,1485,1498,1509,1521,1533,1544,1556,1568,1579,1591,1604,1616,1627,1639,1651,1671,1683,1695,65535,65535,65535,65535,65535,65535,65535,65535,65535},
{5090,1283,1291,5110,1303,5119,5124,1321,1333,1344,1356,1368,1380,1392,1404,1416,1427,1439,1451,1462,1474,1486,1499,1510,1522,1534,1545,1557,1569,1580,1592,1605,1617,1628,1640,1652,1672,1684,847,65535,65535,65535,65535,65535,65535,65535,65535,65535},
{1702,1707,1715,1722,1727,1731,1736,1744,1756,1767,1779,1791,1803,1816,1827,1839,1850,1862,1874,1885,1897,1910,1922,1934,1945,1957,1968,1980,1992,2003,2016,2028,2040,2051,2063,2075,2095,2107,2119,65535,65535,65535,65535,65535,65535,65535,65535,65535},
{5514,5519,442,5534,5539,5543,5548,1745,1757,1768,1780,1792,1804,3495,1828,1840,1851,1863,1875,1886,1898,1911,1923,1935,1946,1958,1969,1981,1993,2004,2017,2029,2041,2052,2064,2076,2096,2108,3775,65535,65535,65535,65535,65535,65535,65535,65535,65535},
{2126,2131,2139,2146,2151,4270,2160,2169,2180,2192,2204,2215,2228,2240,2252,2263,2275,2287,2298,2310,2322,2334,2346,2358,2370,2381,2393,2405,2416,2428,2440,2453,2464,2476,2488,2499,2519,2531,2543,65535,65535,65535,65535,65535,65535,65535,65535,65535},
{5938,5943,3406,5958,5963,2156,5972,472,2181,2193,507,2216,2229,2241,555,2264,2276,590,2299,2311,625,2335,2347,2359,673,2382,2394,708,2417,2429,2441,756,2465,2477,791,2500,2520,2532,418,65535,65535,65535,65535,65535,65535,65535,65535,65535},
{2550,2555,2563,2570,2575,2580,2584,2593,2604,2616,2628,2639,2652,2664,2676,2687,2699,2711,2722,2734,2746,2758,2770,2782,2794,2805,2817,2829,2840,2852,2864,2877,2888,2900,2912,2923,2944,2956,2967,65535,65535,65535,65535,65535,65535,65535,65535,65535},
{6362,6367,2564,6382,6387,6392,6396,3436,2605,2617,3471,2640,2653,2665,3507,2688,2700,3542,2723,2735,3577,2759,2771,2783,3613,2806,2818,3648,2841,2853,2865,3684,2889,2901,3719,2924,3751,835,419,65535,65535,65535,65535,65535,65535,65535,65535,65535},
{2974,2979,2987,2994,2999,3004,4275,3017,3029,3040,3052,3064,3076,3088,3100,3112,3123,3135,3147,3158,3170,3182,3194,3206,3218,3230,3241,3253,3265,3276,3288,3301,3313,3324,3336,3348,3368,3380,420,65535,65535,65535,65535,65535,65535,65535,65535,65535},
{6786,6791,2988,6806,6811,6816,3009,3018,484,3041,3053,519,3077,3089,3101,567,3124,3136,602,3159,3171,3183,3195,3207,3219,685,3242,3254,720,3277,3289,3302,768,3325,3337,803,3369,3763,421,65535,65535,65535,65535,65535,65535,65535,65535,65535},
{3,2553,2559,2568,4263,4268,4273,2587,2598,2610,2622,2633,2645,2658,2670,2681,2693,2705,2716,2728,2740,2751,2764,2776,2788,2799,2811,2823,2834,2846,2858,2870,2882,2894,2906,2917,2929,2949,2961,65535,65535,65535,65535,65535,65535,65535,65535,65535},
{2551,434,443,3413,454,459,2585,2594,3448,496,2629,3483,532,544,2677,3519,579,2712,3554,614,2747,638,650,662,2795,3625,697,2830,3660,732,2866,2878,3696,780,2913,3731,2945,2957,422,65535,65535,65535,65535,65535,65535,65535,65535,65535},
{2975,3398,3407,4261,3418,3423,6821,473,3030,3460,508,3065,3078,3496,556,3113,3531,591,3148,3566,626,3184,3590,3602,674,3231,3637,709,3266,3672,3290,757,3314,3708,792,3349,824,3381,423,65535,65535,65535,65535,65535,65535,65535,65535,65535},
{6787,4246,2989,2995,4266,4271,464,3437,485,3042,3472,520,533,3090,3508,568,3125,3543,603,3160,3578,639,3196,3208,3614,686,3243,3649,721,3278,745,3685,769,3326,3720,804,3752,836,1271,65535,65535,65535,65535,65535,65535,65535,65535,65535},
{4,8,13,22,28,33,38,3855,55,67,78,90,102,115,126,138,150,161,173,185,196,208,221,232,244,256,268,279,291,303,314,327,339,351,362,374,397,407,65535,65535,65535,65535,65535,65535,65535,65535,65535,65535},
{3816,3820,14,23,3840,3845,3850,44,56,68,79,91,103,116,127,139,151,162,174,186,197,209,222,233,245,257,269,280,292,304,315,328,340,352,363,375,398,408,65535,65535,65535,65535,65535,65535,65535,65535,65535,65535},
{5,9,15,24,29,34,39,45,57,69,80,92,104,117,128,140,152,163,175,187,198,210,223,234,246,258,270,281,293,305,316,329,341,353,364,376,399,409,65535,65535,65535,65535,65535,65535,65535,65535,65535,65535},
{3817,3821,16,3836,3841,3846,3851,46,58,70,81,93,105,118,129,141,153,164,176,188,199,211,224,235,247,259,271,282,294,306,317,330,342,354,365,377,400,410,65535,65535,65535,65535,65535,65535,65535,65535,65535,65535},
{6,10,17,25,30,35,40,47,59,71,82,94,106,119,130,142,154,165,177,189,200,212,225,236,248,260,272,283,295,307,318,331,343,355,366,378,401,411,65535,65535,65535,65535,65535,65535,65535,65535,65535,65535},
{3818,3822,18,3837,3842,3847,3852,48,60,72,83,95,107,120,131,143,155,166,178,190,201,213,226,237,249,261,273,284,296,308,319,332,344,356,367,379,402,412,65535,65535,65535,65535,65535,65535,65535,65535,65535,65535},
{7,11,19,26,31,36,41,49,61,73,84,96,108,121,132,144,156,167,179,191,202,214,227,238,250,262,274,285,297,309,320,333,345,357,368,380,825,413,65535,65535,65535,65535,65535,65535,65535,65535,65535,65535},
{3819,3823,20,3838,3843,3848,3853,50,62,74,85,97,109,122,133,145,157,168,180,192,203,215,228,239,251,263,275,286,298,310,321,334,346,358,369,381,3753,3764,65535,65535,65535,65535,65535,65535,65535,65535,65535,65535},
};

#define TABLED 1
#define TRIG 7
#define JB 22
#define PRE 2
#define CH 64
#define FIRST 5
constexpr int RING = SCHED_RING;
constexpr int NSLOT = 8;
constexpr int PLEN = SCHED_LE, LT = SCHED_LT, LM = 256 - 2 * PLEN - 2 * LT, NSEG = 4 / SCHED_NMID, LMID = NSEG * LM;
constexpr int NP = 8 + SCHED_NMID, NG = NP + (LT ? 8 : 0), NCONV = 3 * NG;
static_assert(LMID <= PLEN && LT <= RING && LT < LM && (LT == 0 || LT >= 6), "geometry");
__device__ __forceinline__ int group_len(int gm) { return gm < 8 ? PLEN : gm < NP ? LMID : LT; }
__device__ __forceinline__ int group_strip(int gm, int seg) { return gm < 8 ? gm >> 1 : gm < NP ? (gm - 8) * NSEG + seg : (gm - NP) >> 1; }
__device__ __forceinline__ int group_base(int gm) { return gm < NP ? PLEN + LT : PLEN + ((gm - NP) & 1) * (LT + LM); }
constexpr int TILEB = 12288;
constexpr int SLOTB = 280 * 64;
constexpr int W1S = 0, W2S = 73728, ABUF = 147456, XBUF = ABUF + 16 * 3072, MISC = XBUF + 8 * 3072;
constexpr int WBAR = MISC + 2560;
constexpr int RBUF = ABUF - 4 * SLOTB;
constexpr int CM = MISC + 2816, CTAB = CM + 256;
constexpr int SMEM_BYTES = CTAB + (PLEN + 16) * 16;
static_assert(RBUF % 512 == 0 && RBUF >= W2S && RBUF + NSLOT * SLOTB + 128 <= MISC && SMEM_BYTES <= 232448, "smem layout");

struct Globals {
  unsigned char scratch[RING * NG * 4 * TILEB];
  unsigned char wimg[147456];
  uint32_t wflag[32];
  uint32_t ready[NG * PLEN + 1];
  uint32_t cons[NG * PLEN];
  uint32_t epoch[1024];
};
__device__ __align__(1024) Globals g_state;

#define GELU_C3 0.32920349f
#define GELU_A2 0x40d940d9u
#define GELU_S2 0x3e133e13u
#define SCHED_FENCE() asm volatile("pmevent 0;" ::: "memory")
#define SPIN_LIMIT 0x1000000

__device__ __forceinline__ uint32_t smem_u32(const void* p) { return (uint32_t)__cvta_generic_to_shared(p); }
__device__ __forceinline__ void wg_fence() { asm volatile("wgmma.fence.sync.aligned;" ::: "memory"); }
__device__ __forceinline__ void wg_commit() { asm volatile("wgmma.commit_group.sync.aligned;" ::: "memory"); }
template <int N> __device__ __forceinline__ void wg_wait() { asm volatile("wgmma.wait_group.sync.aligned %0;" ::"n"(N) : "memory"); }
__device__ __forceinline__ void mbar_wait(uint32_t bar, uint32_t parity) {
  asm volatile("{\n.reg .pred p;\n.reg .u32 c;\nmbarrier.try_wait.parity.shared::cta.b64 p, [%0], %1;\n@p bra DONE_%=;\nmov.u32 c, 0;\nWAIT_%=:\nmbarrier.try_wait.parity.shared::cta.b64 p, [%0], %1;\n@p bra DONE_%=;\n"
               "add.u32 c, c, 1;\nsetp.lt.u32 p, c, 0x1000000;\n@p bra WAIT_%=;\ntrap;\nDONE_%=:\n}" ::"r"(bar), "r"(parity) : "memory");
}
__device__ __forceinline__ void mbar_arrive_elect(uint32_t bar) { asm volatile("{.reg .pred p; elect.sync _|p, 0xffffffff; @p mbarrier.arrive.shared::cta.b64 _, [%0];}" ::"r"(bar) : "memory"); }
__device__ __forceinline__ void mbar_init_elect(uint32_t bar, uint32_t cnt) { asm volatile("{.reg .pred p; elect.sync _|p, 0xffffffff; @p mbarrier.init.shared::cta.b64 [%0], %1;}" ::"r"(bar), "r"(cnt) : "memory"); }
__device__ __forceinline__ uint32_t ld_relaxed(const uint32_t* p) { uint32_t v; asm volatile("ld.relaxed.gpu.global.u32 %0, [%1];" : "=r"(v) : "l"(p) : "memory"); return v; }
__device__ __forceinline__ void red_add_elect(uint32_t* p) { asm volatile("{.reg .pred p; elect.sync _|p, 0xffffffff; @p red.relaxed.gpu.global.add.u32 [%0], 1;}" ::"l"(p) : "memory"); }
__device__ __forceinline__ void wait_value(const uint32_t* p, uint32_t target, int ns) {
  int spins = 0;
  while (ld_relaxed(p) != target) { __nanosleep(ns); if (++spins > SPIN_LIMIT) __trap(); }
}
template <int BYTES, bool INIT = false> __device__ __forceinline__ void bulk_load(uint32_t dst, const void* src, uint32_t bar, int go = 0) {
  if (INIT) asm volatile("{.reg .pred p; elect.sync _|p, 0xffffffff; @p mbarrier.init.shared::cta.b64 [%0], 1; @p fence.mbarrier_init.release.cluster;}" ::"r"(bar) : "memory");
  asm volatile("{\n.reg .pred p, q;\nsetp.ge.s32 q, %4, 0;\nelect.sync _|p, 0xffffffff;\nand.pred p, p, q;\n@p mbarrier.arrive.expect_tx.shared::cta.b64 _, [%1], %3;\n"
               "@p cp.async.bulk.shared::cluster.global.mbarrier::complete_tx::bytes [%0], [%2], %3, [%1];\n}"
               ::"r"(dst), "r"(bar), "l"(src), "n"(BYTES), "r"(go) : "memory");
}
__device__ __forceinline__ void lds128(uint32_t* r, uint32_t a) { asm volatile("ld.shared.v4.b32 {%0,%1,%2,%3}, [%4];" : "=r"(r[0]), "=r"(r[1]), "=r"(r[2]), "=r"(r[3]) : "r"(a) : "memory"); }
__device__ __forceinline__ uint2 lds64(uint32_t a) { uint2 v; asm volatile("ld.shared.v2.b32 {%0,%1}, [%2];" : "=r"(v.x), "=r"(v.y) : "r"(a) : "memory"); return v; }
__device__ __forceinline__ uint32_t lds32(uint32_t a) { uint32_t v; asm volatile("ld.shared.b32 %0, [%1];" : "=r"(v) : "r"(a) : "memory"); return v; }
__device__ __forceinline__ void sts32(uint32_t a, uint32_t v) { asm volatile("st.shared.b32 [%0], %1;" ::"r"(a), "r"(v) : "memory"); }
__device__ __forceinline__ void sts64(uint32_t a, uint2 v) { asm volatile("st.shared.v2.b32 [%0], {%1,%2};" ::"r"(a), "r"(v.x), "r"(v.y) : "memory"); }
__device__ __forceinline__ void sts128(uint32_t a, uint4 v) { asm volatile("st.shared.v4.b32 [%0], {%1,%2,%3,%4};" ::"r"(a), "r"(v.x), "r"(v.y), "r"(v.z), "r"(v.w) : "memory"); }
__device__ __forceinline__ uint64_t pol_evict_first() { uint64_t p; asm("createpolicy.fractional.L2::evict_first.b64 %0, 1.0;" : "=l"(p)); return p; }
__device__ __forceinline__ void stg128_stream(void* p, uint4 v, uint64_t pol) {
  asm volatile("st.global.L2::cache_hint.v4.b32 [%0], {%1,%2,%3,%4}, %5;" ::"l"(p), "r"(v.x), "r"(v.y), "r"(v.z), "r"(v.w), "l"(pol) : "memory");
}
__device__ __forceinline__ void stg128_if(uint32_t go, void* p, uint4 v) {
  asm volatile("{.reg .pred q; setp.ge.s32 q, %5, 0; @q st.global.v4.b32 [%0], {%1,%2,%3,%4};}" ::"l"(p), "r"(v.x), "r"(v.y), "r"(v.z), "r"(v.w), "r"(go) : "memory");
}
__device__ __forceinline__ uint32_t pack_f16(float lo, float hi) { uint32_t d; asm("cvt.rn.f16x2.f32 %0, %1, %2;" : "=r"(d) : "f"(hi), "f"(lo)); return d; }
__device__ __forceinline__ uint32_t pack_f16_sat(float lo, float hi) { uint32_t d; asm("cvt.rn.satfinite.f16x2.f32 %0, %1, %2;" : "=r"(d) : "f"(hi), "f"(lo)); return d; }
__device__ __forceinline__ uint32_t pack_bf16(float lo, float hi) { uint32_t d; asm("cvt.rn.bf16x2.f32 %0, %1, %2;" : "=r"(d) : "f"(hi), "f"(lo)); return d; }
__device__ __forceinline__ uint32_t bf2_to_h2(uint32_t w) { return pack_f16(__uint_as_float(w << 16), __uint_as_float(w & 0xffff0000u)); }
__device__ __forceinline__ uint32_t hadd2_bf16(uint32_t a, uint32_t b) { uint32_t d; asm("add.rn.bf16x2 %0, %1, %2;" : "=r"(d) : "r"(a), "r"(b)); return d; }
__device__ __forceinline__ uint32_t h2add(uint32_t a, uint32_t b) { uint32_t d; asm("add.rn.f16x2 %0, %1, %2;" : "=r"(d) : "r"(a), "r"(b)); return d; }
__device__ __forceinline__ uint32_t h2mul(uint32_t a, uint32_t b) { uint32_t d; asm("mul.rn.f16x2 %0, %1, %2;" : "=r"(d) : "r"(a), "r"(b)); return d; }
__device__ __forceinline__ uint32_t h2fma(uint32_t a, uint32_t b, uint32_t c) { uint32_t d; asm("fma.rn.f16x2 %0, %1, %2, %3;" : "=r"(d) : "r"(a), "r"(b), "r"(c)); return d; }
__device__ __forceinline__ uint32_t h2lo(uint32_t a) { uint32_t d; asm("{.reg .f16 l,h; mov.b32 {l,h}, %1; mov.b32 %0, {l,l};}" : "=r"(d) : "r"(a)); return d; }
__device__ __forceinline__ uint32_t h2hi(uint32_t a) { uint32_t d; asm("{.reg .f16 l,h; mov.b32 {l,h}, %1; mov.b32 %0, {h,h};}" : "=r"(d) : "r"(a)); return d; }
__device__ __forceinline__ float h_lo(uint32_t a) { float d; asm("{.reg .f16 l,h; mov.b32 {l,h}, %1; cvt.f32.f16 %0, l;}" : "=f"(d) : "r"(a)); return d; }
__device__ __forceinline__ float h_hi(uint32_t a) { float d; asm("{.reg .f16 l,h; mov.b32 {l,h}, %1; cvt.f32.f16 %0, h;}" : "=f"(d) : "r"(a)); return d; }
__device__ __forceinline__ float rsqrt_fast(float v) { float r; asm("rsqrt.approx.ftz.f32 %0, %1;" : "=f"(r) : "f"(v)); return r; }
__device__ __forceinline__ uint32_t prmt(uint32_t a, uint32_t b, uint32_t s) { uint32_t d; asm("prmt.b32 %0, %1, %2, %3;" : "=r"(d) : "r"(a), "r"(b), "r"(s)); return d; }
__device__ __forceinline__ void mma_sp(float* d, const uint32_t* a, const uint32_t* b, const float* c, uint32_t e) {
  asm("mma.sp::ordered_metadata.sync.aligned.m16n8k32.row.col.f32.bf16.bf16.f32 {%0,%1,%2,%3}, {%4,%5,%6,%7}, {%8,%9,%10,%11}, {%12,%13,%14,%15}, %16, 0;"
      : "=f"(d[0]), "=f"(d[1]), "=f"(d[2]), "=f"(d[3])
      : "r"(a[0]), "r"(a[1]), "r"(a[2]), "r"(a[3]), "r"(b[0]), "r"(b[1]), "r"(b[2]), "r"(b[3]), "f"(c[0]), "f"(c[1]), "f"(c[2]), "f"(c[3]), "r"(e));
}

__device__ __forceinline__ uint32_t gelu_tanh(uint32_t y) {
  uint32_t t, u, th;
  asm volatile("fma.rn.f16x2 %0, %1, %1, %2;" : "=r"(t) : "r"(y), "r"(GELU_A2));
  asm volatile("mul.rn.f16x2 %0, %1, %2;" : "=r"(u) : "r"(y), "r"(t));
  asm volatile("tanh.approx.f16x2 %0, %1;" : "=r"(th) : "r"(u));
  return th;
}
__device__ __forceinline__ uint32_t gelu_fin(uint32_t y, uint32_t th) {
  uint32_t g;
  asm volatile("fma.rn.f16x2 %0, %1, %2, %1;" : "=r"(g) : "r"(y), "r"(th));
  return g;
}

__device__ __forceinline__ void convert_weights(uint32_t sb, int rot, int warp, int lane) {
  if (warp < 12) {
    const int l8 = lane & 7, q4 = lane >> 3;
    int s = (warp >> 1) + rot; if (s >= 6) s -= 6;
    const uint32_t base = sb + W1S + s * 12288 + (warp & 1) * 384;
    mbar_wait(sb + WBAR + s * 8, 0);
    uint32_t v[3][4][4];
#pragma unroll
    for (int r = 0; r < 4; r++)
#pragma unroll
      for (int i = 0; i < 3; i++) lds128(v[i][r], base + i * 128 + (4 * (l8 >> 1) + 2 * (r & 1) + (l8 & 1)) * 768 + ((l8 + q4 + 4 * (r >> 1)) & 7) * 16);
    __syncwarp();
#pragma unroll
    for (int r = 0; r < 4; r++)
#pragma unroll
      for (int i = 0; i < 3; i++)
        sts128(base + i * 128 + (((l8 + q4 + 4 * (r >> 1)) & 7) + 8 * (r & 1)) * 768 + l8 * 16,
               make_uint4(bf2_to_h2(v[i][r][0]), bf2_to_h2(v[i][r][1]), bf2_to_h2(v[i][r][2]), bf2_to_h2(v[i][r][3])));
  }
  const int q = lane & 3, t = (lane >> 2) & 3, b = lane >> 4;
  int u = 3 * (warp ^ 15) + 8 * rot; if (u >= 48) u -= 48;
  uint32_t base[3], v[3][4][3];
#pragma unroll
  for (int i = 0; i < 3; i++) {
    const int ui = u + i >= 48 ? u + i - 48 : u + i;
    base[i] = sb + W2S + ui * 1536;
    if (i != 1) mbar_wait(sb + WBAR + 48 + (ui >> 3) * 8, 0);
  }
#pragma unroll
  for (int i = 0; i < 3; i++)
#pragma unroll
    for (int d = 0; d < 4; d++)
#pragma unroll
      for (int j = 0; j < 3; j++) v[i][d][j] = lds32(base[i] + (2 * ((q + d) & 3) + b) * 192 + j * 64 + t * 16 + q * 4);
  __syncwarp();
#pragma unroll
  for (int i = 0; i < 3; i++)
#pragma unroll
    for (int d = 0; d < 4; d++)
#pragma unroll
      for (int j = 0; j < 3; j++) sts32(base[i] + (4 * j + q) * 128 + (2 * ((q + d) & 3) + b) * 16 + t * 4, bf2_to_h2(v[i][d][j]));
}

__device__ __noinline__ void ln_wide(uint32_t ad) {
  float m[2], r[2];
  for (int s = 0; s < 6; s++) sts32(ad + s * 512, lds32(ad + s * 512) & ~1u);
#pragma unroll
  for (int hi = 0; hi < 2; hi++) {
    float sm = 0.f;
    for (int s = 0; s < 6; s++) { uint2 w = lds64(ad + s * 512 + hi * 8); sm += (h_lo(w.x) + h_hi(w.x)) + (h_lo(w.y) + h_hi(w.y)); }
    sm += __shfl_xor_sync(0xffffffffu, sm, 1); sm += __shfl_xor_sync(0xffffffffu, sm, 2);
    m[hi] = sm * (1.f / 96.f);
    float q = 0.f;
    for (int s = 0; s < 6; s++) {
      uint2 w = lds64(ad + s * 512 + hi * 8);
      float d0 = h_lo(w.x) - m[hi], d1 = h_hi(w.x) - m[hi], d2 = h_lo(w.y) - m[hi], d3 = h_hi(w.y) - m[hi];
      q += (d0 * d0 + d1 * d1) + (d2 * d2 + d3 * d3);
    }
    q += __shfl_xor_sync(0xffffffffu, q, 1); q += __shfl_xor_sync(0xffffffffu, q, 2);
    r[hi] = rsqrtf(fmaf(q, 1.f / 96.f, 1e-5f)) * GELU_C3;
  }
  for (int s = 0; s < 6; s++) {
    uint32_t w[4]; lds128(w, ad + s * 512);
    sts128(ad + s * 512, make_uint4(pack_f16((h_lo(w[0]) - m[0]) * r[0], (h_hi(w[0]) - m[0]) * r[0]), pack_f16((h_lo(w[2]) - m[1]) * r[1], (h_hi(w[2]) - m[1]) * r[1]),
                                    pack_f16((h_lo(w[1]) - m[0]) * r[0], (h_hi(w[1]) - m[0]) * r[0]), pack_f16((h_lo(w[3]) - m[1]) * r[1], (h_hi(w[3]) - m[1]) * r[1])));
  }
  asm volatile("fence.proxy.async.shared::cta;" ::: "memory");
}

__device__ __forceinline__ uint32_t layer_norm(uint32_t (&raw)[6][4], uint32_t* a, uint32_t tag) {
#pragma unroll
  for (int k = 0; k < 6; k++) raw[k][0] ^= tag;
  const uint32_t stale = (raw[0][0] | raw[1][0] | raw[2][0]) | (raw[3][0] | raw[4][0] | raw[5][0]);
  uint32_t sm[2], qq[2];
#pragma unroll
  for (int hi = 0; hi < 2; hi++) {
    uint32_t s0 = h2add(raw[0][2 * hi], raw[1][2 * hi]), s1 = h2add(raw[0][2 * hi + 1], raw[1][2 * hi + 1]);
    uint32_t s2 = h2add(raw[2][2 * hi], raw[3][2 * hi]), s3 = h2add(raw[2][2 * hi + 1], raw[3][2 * hi + 1]);
    uint32_t s4 = h2add(raw[4][2 * hi], raw[5][2 * hi]), s5 = h2add(raw[4][2 * hi + 1], raw[5][2 * hi + 1]);
    sm[hi] = h2add(h2add(h2add(s0, s1), h2add(s2, s3)), h2add(s4, s5));
  }
#pragma unroll
  for (int hi = 0; hi < 2; hi++) {
    uint32_t q0 = h2mul(raw[0][2 * hi], raw[0][2 * hi]), q1 = h2mul(raw[0][2 * hi + 1], raw[0][2 * hi + 1]);
#pragma unroll
    for (int k = 1; k < 6; k++) { q0 = h2fma(raw[k][2 * hi], raw[k][2 * hi], q0); q1 = h2fma(raw[k][2 * hi + 1], raw[k][2 * hi + 1], q1); }
    qq[hi] = h2add(q0, q1);
  }
  uint32_t s = h2add(prmt(sm[0], sm[1], 0x5410), prmt(sm[0], sm[1], 0x7632));
  uint32_t q = h2add(prmt(qq[0], qq[1], 0x5410), prmt(qq[0], qq[1], 0x7632));
  s = h2add(s, __shfl_xor_sync(0xffffffffu, s, 1)); q = h2add(q, __shfl_xor_sync(0xffffffffu, q, 1));
  s = h2add(s, __shfl_xor_sync(0xffffffffu, s, 2)); q = h2add(q, __shfl_xor_sync(0xffffffffu, q, 2));
  constexpr float K1 = 1.f / (96.f * GELU_C3 * GELU_C3), K2 = 1e-5f / (GELU_C3 * GELU_C3), K3 = 1.f / (96.f * GELU_C3);
  const float e0 = fmaf(h_lo(q), K1, K2), e1 = fmaf(h_hi(q), K1, K2), m0 = h_lo(s) * K3, m1 = h_hi(s) * K3;
  const float v0 = fmaf(-m0, m0, e0), v1 = fmaf(-m1, m1, e1);
  const uint32_t r = pack_f16(rsqrt_fast(v0), rsqrt_fast(v1)), o = h2mul(h2mul(s, 0xA155A155u), r);
#pragma unroll
  for (int k = 0; k < 6; k++) {
    a[4 * k] = h2fma(raw[k][0], h2lo(r), h2lo(o)); a[4 * k + 2] = h2fma(raw[k][1], h2lo(r), h2lo(o));
    a[4 * k + 1] = h2fma(raw[k][2], h2hi(r), h2hi(o)); a[4 * k + 3] = h2fma(raw[k][3], h2hi(r), h2hi(o));
  }
  const bool fine = fmaf(v0, 4.f, -e0) > 0.f && fmaf(v1, 4.f, -e1) > 0.f;
  return (fine ? 0u : 2u) | (stale & 1);
}

constexpr int KS = CH / 16, NC = 384 / CH;
#define WG1_(n) wgmma_n##n##_f16
#define WG1(n) WG1_(n)
__device__ __forceinline__ void gemm1(uint32_t* p, const uint32_t* a, uint64_t d1, int c, int k0, int k1) {
#pragma unroll
  for (int s = 0; s < 6; s++)
    if (s >= k0 && s < k1) {
      if (s == 0) WG1(CH)<0>(p, a, d1 + c * CH); else WG1(CH)<1>(p, a + 4 * s, d1 + c * CH + s * (12288 >> 4));
    }
}
__device__ __forceinline__ void fetch_x(uint32_t xbuf, uint32_t bar, const CUtensorMap* tm, uint32_t c0, uint32_t c12, uint64_t pol, int go = 0) {
  asm volatile("{\n.reg .pred p, q;\nsetp.ge.s32 q, %7, 0;\nelect.sync _|p, 0xffffffff;\nand.pred p, p, q;\n"
               "@p mbarrier.arrive.expect_tx.shared::cta.b64 _, [%1], 3072;\n"
               "@p cp.async.bulk.tensor.3d.shared::cluster.global.mbarrier::complete_tx::bytes.L2::cache_hint [%0], [%2, {%3, %4, %5}], [%1], %6;\n}"
               ::"r"(xbuf), "r"(bar), "l"(tm), "r"(c0), "r"(c12 & 255), "r"(c12 >> 8), "l"(pol), "r"(go) : "memory");
}
__device__ __forceinline__ uint32_t slot_tag(int gm, int j, uint32_t epoch) {
  const int writes = (group_len(gm) - j % RING + RING - 1) / RING;
  return (epoch * writes + j / RING + 1) & 1;
}
__device__ __forceinline__ void build_tile_list(uint32_t sb, int k, int idx, bool tabled, bool is_conv, uint32_t epoch) {
  int n = -1;
  if (tabled) { if (k < 48) n = (int16_t)g_sched[idx][k]; }
  else if (!is_conv) {
    const int i = k * (gridDim.x - NCONV) + idx, r = i >> 2, r1 = r - LT * NG, r2 = r1 - (LMID - LT) * NP;
    const int j = r1 < 0 ? r / NG : r2 < 0 ? LT + r1 / NP : LMID + (r2 >> 3), gm = r1 < 0 ? r % NG : r2 < 0 ? r1 % NP : r2 & 7;
    if (i < 4096) n = (gm * PLEN + j) * 4 + (i & 3);
  }
  const int q = n >> 2, gm = q / PLEN, j = q - gm * PLEN, seg = j / LM;
  const int strip = group_strip(gm, seg), pair = gm < 8 ? ((gm & 1) ? 255 - j : j) : group_base(gm) + j - seg * LM;
  sts128(sb + MISC + 512 + k * 16, make_uint4(q, (((j % RING) * NG + gm) * 4 + (n & 3)) * TILEB + slot_tag(gm, j, epoch),
                                              (n & 2) * 384, (strip * 8 + (n & 1) * 4) | (pair << 9)));
  if (k == 0) sts64(sb + MISC + 256, make_uint2(epoch + 1, !is_conv));
}

__device__ __forceinline__ void mlp_setup(uint32_t sb, Globals* gs, int id, const __nv_bfloat16* __restrict__ w1, const __nv_bfloat16* __restrict__ w2,
                                          int idx, bool tabled, int warp, int lane) {
  const int rot = idx % 6;
  if (warp < 12) {
    const int m = warp >= 6; int s = warp - 6 * m + rot; if (s >= 6) s -= 6;
    bulk_load<12288, true>(sb + (6 * m + s) * 12288, (const char*)(m ? w2 : w1) + s * 12288, sb + WBAR + (6 * m + s) * 8);
  }
  __syncthreads();
  if (warp >= 12) build_tile_list(sb, threadIdx.x - 384, idx, tabled, false, ld_relaxed(&gs->epoch[id]));
  convert_weights(sb, rot, warp, lane);
  asm volatile("fence.proxy.async.shared::cta;" ::: "memory");
  __syncthreads();
  if (threadIdx.x == 480) {
    gs->epoch[id] = lds32(sb + MISC + 256);
    const uint32_t piece = tabled ? idx - 96 : idx;
    if (piece < 12) {
      asm volatile("cp.async.bulk.global.shared::cta.bulk_group [%0], [%1], 12288;\ncp.async.bulk.commit_group;\ncp.async.bulk.wait_group 0;\nfence.proxy.async.global;\n"
                   "red.release.gpu.global.add.u32 [%2], 1;" ::"l"(gs->wimg + piece * 12288), "r"(sb + piece * 12288), "l"(gs->wflag) : "memory");
    }
  }
  __syncwarp();
}

__device__ __forceinline__ void mlp_role(uint32_t sb, Globals* gs, const CUtensorMap* tmr, __nv_bfloat16* __restrict__ out) {
  uint32_t tid;
  asm volatile("mov.u32 %0, %%tid.x;" : "=r"(tid));
  const int warp = __shfl_sync(0xffffffffu, tid >> 5, 0), lane = tid & 31;
  const int wg = warp >> 2, w = warp & 3, g = lane >> 2, t = lane & 3;
  const uint32_t abuf = sb + ABUF + warp * 3072, xbuf = sb + XBUF + (warp & 7) * 3072;
  const uint32_t bar = sb + MISC + warp * 8, obar = sb + MISC + (warp ^ 8) * 8;
  const uint32_t tl = sb + MISC + 512;
  const uint32_t rtarget = 3 * lds32(sb + MISC + 256);
  const uint64_t d1 = ((uint64_t)(6144 >> 4) << 16) | ((uint64_t)(128 >> 4) << 32) | (uint64_t)(((sb + W1S) >> 4) & 0x3fff);
  const uint64_t d2 = ((uint64_t)(12288 >> 4) << 16) | ((uint64_t)(128 >> 4) << 32) | (uint64_t)(((sb + W2S) >> 4) & 0x3fff);
  const uint32_t ad = abuf + t * 128 + ((g ^ (2 * t)) << 4);
  const uint32_t xd = xbuf + g * 192 + t * 16;
  const uint32_t pofs = (g >> 1) * 3072 + (2 * w + (g & 1)) * 192 + t * 16;
  const int mybar = 1 + wg, nxtbar = 1 + ((wg + 1) & 3);
  const uint64_t pol = pol_evict_first();
  const unsigned char* const asrc = gs->scratch + w * 3072;
  uint32_t pha = 0, phx = 0, tp = tl + wg * 16;
  bool pending = lds32(sb + MISC + 260);
  uint32_t cur[4];
  lds128(cur, tp);
  if (wg < 2) fetch_x(xbuf, bar + 128, tmr, cur[2] + w * 192, cur[3], pol, cur[0]);
  while ((int)cur[0] >= 0) {
    uint32_t a[24], p[NC][CH / 4], gg[24][4], th[24][4], acc[24], raw[6][4], n2[4], n4[4];
    if (pending) {
      wait_value(&gs->ready[cur[0]], rtarget, 32);
      bulk_load<3072>(abuf, asrc + (cur[1] & ~1u), bar);
    }
    for (int tries = 0;; tries++) {
      mbar_wait(bar, pha); pha ^= 1;
#pragma unroll
      for (int k = 0; k < 6; k++) lds128(raw[k], ad + k * 512);
      const uint32_t st = layer_norm(raw, a, cur[1] & 1);
      if (!__any_sync(0xffffffffu, st != 0)) break;
      if (!__any_sync(0xffffffffu, st & 1)) {
        ln_wide(ad);
#pragma unroll
        for (int k = 0; k < 6; k++) lds128(a + 4 * k, ad + k * 512);
        break;
      }
      if (tries > SPIN_LIMIT) __trap();
      bulk_load<3072>(abuf, asrc + (cur[1] & ~1u), bar);
    }
    if (tp != tl) asm volatile("bar.sync %0, 256;" ::"r"(mybar) : "memory");
    uint32_t rdy = 0;
    wg_fence();
    gemm1(p[0], a, d1, 0, 0, 6); wg_commit();
    gemm1(p[1], a, d1, 1, 0, 6 / KS); wg_commit();
    const int sig = lds32(tp + 16);
    lds128(n4, tp + 64);
    asm volatile("{.reg .pred p; setp.eq.u32 p, %1, 0; @p red.relaxed.gpu.global.add.u32 [%0], 1;}" ::"l"(&gs->cons[cur[0]] + lane), "r"(lane) : "memory");
#pragma unroll
    for (int j = 0; j < 24; j++) {
      const int c = j / KS, s = j % KS;
      if (j == JB) rdy = ld_relaxed(&gs->ready[max((int)n4[0], 0)]);
      if (s == 0) wg_wait<1>();
      if (j == TRIG) asm volatile("{.reg .pred p; setp.ge.s32 p, %1, 0; @p bar.arrive %0, 256;}" ::"r"(nxtbar), "r"(sig) : "memory");
#pragma unroll
      for (int i = 0; i < 4; i++) {
        if (!(s && i < PRE)) th[j][i] = gelu_tanh(p[c][4 * s + i]);
        gg[j][i] = gelu_fin(p[c][4 * s + i], th[j][i]);
      }
      wg_fence();
      if (j == 0) wgmma_n96_f16<0>(acc, gg[j], d2); else wgmma_n96_f16<1>(acc, gg[j], d2 + (16 * (j % 3) + j / 3) * (1536 >> 4));
      const int c1 = (j + 1) / KS + 1, u = (j + 1) % KS;
      if (c1 < NC) gemm1(p[c1], a, d1, c1, (6 * u) / KS, (6 * (u + 1)) / KS);
      wg_commit();
      if (s + 1 < KS) {
#pragma unroll
        for (int i = 0; i < PRE; i++) th[j + 1][i] = gelu_tanh(p[c][4 * s + 4 + i]);
      }
      if (j < 23) SCHED_FENCE();
    }
    pending = rdy != rtarget;
    bulk_load<3072>(abuf, asrc + (n4[1] & ~1u), bar, pending ? -1 : (int)n4[0]);
    wg_wait<0>();
    mbar_wait(bar + 128, phx); phx ^= 1;
#pragma unroll
    for (int k = 0; k < 24; k++) acc[k] = h2mul(acc[k], GELU_S2);
    char* const op = (char*)out + (cur[2] * 2 + (cur[3] & 255) * 3072 + (cur[3] >> 8) * (512 * 192) + pofs);
    lds128(n2, tp + 32);
#pragma unroll
    for (int k = 0; k < 6; k++) {
      const int hi = k / 3, j = k % 3;
      uint32_t xr[4];
      lds128(xr, xd + hi * 1536 + j * 64);
      uint4 o;
      o.x = hadd2_bf16(xr[0], pack_bf16(h_lo(acc[8 * j + hi]), h_hi(acc[8 * j + hi])));
      o.y = hadd2_bf16(xr[1], pack_bf16(h_lo(acc[8 * j + 2 + hi]), h_hi(acc[8 * j + 2 + hi])));
      o.z = hadd2_bf16(xr[2], pack_bf16(h_lo(acc[8 * j + 4 + hi]), h_hi(acc[8 * j + 4 + hi])));
      o.w = hadd2_bf16(xr[3], pack_bf16(h_lo(acc[8 * j + 6 + hi]), h_hi(acc[8 * j + 6 + hi])));
      stg128_stream(op + hi * (512 * 192) + j * 64, o, pol);
    }
    __syncwarp();
    if ((int)n2[0] >= 0) fetch_x(xbuf, obar + 128, tmr, n2[2] + w * 192, n2[3], pol);
    tp += 64;
#pragma unroll
    for (int k = 0; k < 4; k++) cur[k] = n4[k];
  }
}

__device__ __forceinline__ void conv_compute(uint32_t sb, Globals* gs, int third, int nit, int off, bool edge, bool up, int warp, int lane) {
  const int g = lane >> 2, t = lane & 3;
  const uint32_t full = sb + CM;
  const uint32_t wt = sb + 16384 + warp * 1024;
  sts128(wt + lane * 16, make_uint4(0, 0, 0, 0));
  if (lane < 4) sts128(wt + 512 + lane * 16, make_uint4(0, 0, 0, 0));
  asm volatile("setmaxnreg.inc.sync.aligned.u32 232;");
  uint32_t meta = 0;
#pragma unroll
  for (int a = 0; a < 4; a++) meta |= ((4 * (t & 1) + a + 1 >= g) ? 0x80008u : 0xD000Du) << (4 * a);
  meta = __shfl_sync(0xffffffffu, meta, lane);
  uint32_t aq[4];
#pragma unroll
  for (int q = 0; q < 4; q++) {
    const int pp = (g & 1) * 140 + (t & 1) * 70 + 16 * (g >> 1) + 2 * q + (t >> 1);
    aq[q] = __shfl_sync(0xffffffffu, sb + RBUF + pp * 64 + (((warp >> 1) ^ ((pp >> 1) & 3)) << 4) + (warp & 1) * 8, lane);
  }
  const int Q = third * 8 + warp;
  unsigned char* const obase = gs->scratch + (g >> 1) * 3072 + Q * 128 + (((2 * t + (g & 1)) ^ (2 * (Q & 3))) << 4);
  const float zero4[4] = {0.f, 0.f, 0.f, 0.f};
  float S[2][4][3][4];
  __syncwarp();
#pragma unroll
  for (int i = 0; i < 8; i++) {
    lds128((uint32_t*)S[i >> 2][i & 3][0], wt + i * 16);
#pragma unroll
    for (int k = 0; k < 8; k++) asm volatile("" : "=f"(S[i >> 2][i & 3][1 + (k >> 2)][k & 3]));
  }
  uint32_t A[4][4][4];
  asm volatile("bar.sync 5, 288;" ::: "memory");
  mbar_wait(sb + WBAR + 8, 0);
  {
#pragma unroll
    for (int k = 0; k < 2; k++) {
      const int tap = lane + 32 * k;
      if (tap < 49) sts64(wt + (tap + tap / 7 + 8) * 8, lds64(sb + tap * 192 + third * 64 + warp * 8));
    }
    __syncwarp();
    uint2 w[2][4][3];
#pragma unroll
    for (int h = 0; h < 2; h++) {
      uint32_t src = wt + ((4 * h + t - g) & 7) * 8 + (up ? 384 : 0);
#pragma unroll
      for (int u = 0; u < 4; u++) {
#pragma unroll
        for (int k = 0; k < 3; k++) w[h][u][k] = lds64(src + k * 64);
        src += up ? -128 : 128;
      }
    }
#pragma unroll
    for (int u = 0; u < 4; u++)
#pragma unroll
      for (int r = 0; r < 4; r++) {
        const uint2 w0 = w[r >> 1][u][1 - (r & 1)], w1 = w[r >> 1][u][2 - (r & 1)];
        A[0][u][r] = prmt(w0.x, w1.x, 0x5410); A[1][u][r] = prmt(w0.x, w1.x, 0x7632);
        A[2][u][r] = prmt(w0.y, w1.y, 0x5410); A[3][u][r] = prmt(w0.y, w1.y, 0x7632);
      }
  }
  uint32_t sofs = off * SLOTB, bar = full + off * 8, ph = 0, ot = sb + CTAB;
  const uint32_t oend = ot + nit * 16;
  asm volatile("bar.sync 0, 512;" ::: "memory");
  mbar_wait(bar, 0);
  uint2 X[3][4];
#pragma unroll 1
  for (int wu = edge; wu < 3; wu++) {
#pragma unroll
    for (int j = 0; j < 3; j++)
#pragma unroll
      for (int q = 0; q < 4; q++) X[j][q] = lds64(aq[q] + sofs + j * 512);
    mbar_arrive_elect(bar + 64);
    uint32_t B[8][4];
#pragma unroll
    for (int i = 0; i < 8; i++)
#pragma unroll
      for (int q = 0; q < 4; q++) B[i][q] = prmt((i & 2) ? X[i >> 2][q].y : X[i >> 2][q].x, (i & 2) ? X[(i >> 2) + 1][q].y : X[(i >> 2) + 1][q].x, (i & 1) ? 0x7632 : 0x5410);
    if (wu >= 1) {
      if (wu >= 2) {
        SCHED_FENCE();
#pragma unroll
        for (int i = 0; i < 8; i++) mma_sp(S[i >> 2][i & 3][2], A[i & 3][2], B[i], S[i >> 2][i & 3][1], meta);
      }
      SCHED_FENCE();
#pragma unroll
      for (int i = 0; i < 8; i++) mma_sp(S[i >> 2][i & 3][1], A[i & 3][1], B[i], S[i >> 2][i & 3][0], meta);
    }
#pragma unroll
    for (int i = 0; i < 8; i++) mma_sp(S[i >> 2][i & 3][0], A[i & 3][0], B[i], zero4, meta);
    sofs += SLOTB; bar += 8; ot += 16;
    if (sofs == NSLOT * SLOTB) { sofs = 0; bar = full; ph ^= 1; }
    mbar_wait(bar, ph);
  }
#pragma unroll
  for (int j = 0; j < 2; j++)
#pragma unroll
    for (int q = 0; q < 4; q++) X[j][q] = lds64(aq[q] + sofs + j * 512);
#pragma unroll 1
  do {
    const uint2 oe = lds64(ot);
    unsigned char* const o = obase + oe.x;
    const uint32_t dbar = bar + 64;
#pragma unroll
    for (int s = 0; s < 2; s++) {
      uint32_t B[4][4];
      if (s == 1) {
        sofs += SLOTB; bar += 8;
        if (sofs == NSLOT * SLOTB) { sofs = 0; bar = full; ph ^= 1; }
        mbar_wait(bar, ph);
      }
#pragma unroll
      for (int c = 0; c < 4; c++)
#pragma unroll
        for (int q = 0; q < 4; q++) B[c][q] = prmt(c < 2 ? X[s][q].x : X[s][q].y, c < 2 ? X[s + 1][q].x : X[s + 1][q].y, (c & 1) ? 0x7632 : 0x5410);
      if (s == 0) {
#pragma unroll
        for (int q = 0; q < 4; q++) X[2][q] = lds64(aq[q] + sofs + 2 * 512);
      } else {
#pragma unroll
        for (int j = 0; j < 2; j++)
#pragma unroll
          for (int q = 0; q < 4; q++) X[j][q] = lds64(aq[q] + sofs + j * 512);
      }
      float T[4][4];
      SCHED_FENCE();
#pragma unroll
      for (int c = 0; c < 4; c++) mma_sp(T[c], A[c][3], B[c], S[s][c][2], meta);
#pragma unroll
      for (int c = 0; c < 4; c++) mma_sp(S[s][c][2], A[c][2], B[c], S[s][c][1], meta);
      stg128_if(oe.x, o + (2 * s) * TILEB, make_uint4((pack_f16_sat(T[0][0], T[1][0]) & ~1u) | oe.y, pack_f16_sat(T[2][0], T[3][0]), pack_f16_sat(T[0][2], T[1][2]), pack_f16_sat(T[2][2], T[3][2])));
      stg128_if(oe.x, o + (2 * s + 1) * TILEB, make_uint4((pack_f16_sat(T[0][1], T[1][1]) & ~1u) | oe.y, pack_f16_sat(T[2][1], T[3][1]), pack_f16_sat(T[0][3], T[1][3]), pack_f16_sat(T[2][3], T[3][3])));
      if (s == 1) mbar_arrive_elect(dbar);
#pragma unroll
      for (int c = 0; c < 4; c++) mma_sp(S[s][c][1], A[c][1], B[c], S[s][c][0], meta);
#pragma unroll
      for (int c = 0; c < 4; c++) mma_sp(S[s][c][0], A[c][0], B[c], zero4, meta);
    }
    ot += 16;
  } while (ot != oend);
}

__device__ __forceinline__ void load_step(uint32_t sb, const CUtensorMap* tmx, int gm, int third, int it, int s, bool first = false) {
  const int seg = first ? 0 : it / (LM + 3);
  const int st = group_strip(gm, seg), J = gm < 8 ? ((gm & 1) ? 257 - it : it + 1) : group_base(gm) + it - seg * (LM + 3);
  asm volatile("{\n.reg .pred p;\n.reg .s32 c2;\n.reg .u32 d2;\nelect.sync _|p, 0xffffffff;\nadd.s32 c2, %4, 64;\nadd.u32 d2, %0, 8960;\n"
               "@p mbarrier.arrive.expect_tx.shared::cta.b64 _, [%2], 17920;\n"
               "@p cp.async.bulk.tensor.3d.shared::cluster.global.mbarrier::complete_tx::bytes [%0], [%1, {%3, %4, %5}], [%2];\n"
               "@p cp.async.bulk.tensor.3d.shared::cluster.global.mbarrier::complete_tx::bytes [d2], [%1, {%3, c2, %5}], [%2];\n}"
               ::"r"(sb + RBUF + s * SLOTB), "l"(tmx), "r"(sb + CM + s * 8), "r"(third * 32), "r"(st * 128 - 3), "r"(2 * J - 3) : "memory");
}
__device__ __forceinline__ void ring_bar_init(uint32_t bar, uint32_t cnt, bool ahead) {
  asm volatile("{\n.reg .pred p, q;\nelect.sync _|p, 0xffffffff;\n@p mbarrier.init.shared::cta.b64 [%0], %1;\n"
               "setp.ne.and.u32 q, %2, 0, p;\n@q mbarrier.arrive.shared::cta.b64 _, [%0], %1;\n@p fence.mbarrier_init.release.cluster;\n}" ::"r"(bar), "r"(cnt), "r"((uint32_t)ahead) : "memory");
}
__device__ __forceinline__ void conv_loader(uint32_t sb, Globals* gs, const CUtensorMap* tmx, int gm, int nit, int off, int cidx, int third, int k) {
  static_assert(FIRST >= 4 && NCONV >= 24, "loader");
  const uint32_t full = sb + CM;
  asm volatile("bar.sync 0, 512;" ::: "memory");
  if (FIRST + k < NSLOT) load_step(sb, tmx, gm, third, FIRST + k, (FIRST + k + off) & 7, true);
#pragma unroll 1
  for (int it = NSLOT + k; it < nit + NSLOT; it += 4) {
    const int u = it + off;
    const uint32_t ro = lds32(sb + CTAB + (it - NSLOT) * 16 + 8);
    mbar_wait(full + 64 + (u & 7) * 8, ((u >> 3) & 1) ^ 1);
    red_add_elect((uint32_t*)((char*)gs + ro));
    if (it < nit) load_step(sb, tmx, gm, third, it, u & 7);
    else if (it == nit) mbar_arrive_elect(full);
    if (it >= nit - 16) {
      const bool pre = it < nit - 12 && cidx < 24;
      if (pre || it == nit - 1) {
        wait_value(gs->wflag, 12 * lds32(sb + MISC + 256), 32);
        asm volatile("fence.acquire.gpu;\nfence.proxy.async.global;" ::: "memory");
      }
      if (pre) asm volatile("{.reg .pred p; elect.sync _|p, 0xffffffff; @p cp.async.bulk.prefetch.L2.global [%0], 1536;}" ::"l"(gs->wimg + (cidx * 4 + k) * 1536) : "memory");
      const int m = it == nit - 1 ? 0 : W2S;
      if (it == nit - 1 || it == nit + 3) bulk_load<73728>(sb + m, gs->wimg + m, sb + WBAR);
    }
  }
}

__device__ __forceinline__ void conv_credit(uint32_t sb, Globals* gs, int q0, int nit, int off, uint32_t ctarget, int k) {
  const uint32_t full = sb + CM;
#pragma unroll 1
  for (int it = k + NSLOT; it <= nit; it += 4) {
    const int u = it + off, q = (int)lds32(sb + CTAB + it * 16 + 12) - RING;
    mbar_wait(full + 64 + (u & 7) * 8, ((u >> 3) & 1) ^ 1);
    if (q >= q0) wait_value(&gs->cons[q], ctarget, 200);
    mbar_arrive_elect(full + (u & 7) * 8);
  }
}

__device__ __noinline__ int generic_role() {
  const int cidx = (blockIdx.x * NCONV) / gridDim.x;
  return cidx | ((((blockIdx.x + 1) * NCONV) / gridDim.x != cidx) << 16);
}

__global__ void __launch_bounds__(512, 1) convnext_kernel(const __nv_bfloat16* __restrict__ dw, const __nv_bfloat16* __restrict__ w1, const __nv_bfloat16* __restrict__ w2,
                                                          __nv_bfloat16* __restrict__ out, Globals* gs, int want_sms,
                                                          const __grid_constant__ CUtensorMap tmx, const __grid_constant__ CUtensorMap tmr) {
  extern __shared__ __align__(1024) unsigned char smem[];
  const uint32_t sb = smem_u32(smem);
  const int warp = __shfl_sync(0xffffffffu, threadIdx.x >> 5, 0), lane = threadIdx.x & 31;
  uint32_t smid, nsmid;
  asm volatile("mov.u32 %0, %%smid;" : "=r"(smid));
  asm volatile("mov.u32 %0, %%nsmid;" : "=r"(nsmid));
  const bool tabled = TABLED && (int)nsmid == want_sms;
  const int id = tabled ? smid : blockIdx.x;
  int cidx, idx, is_conv;
  if (tabled) {
    idx = smid;
    static_assert(SCHED_NMID == 1 && LT, "role table");
    is_conv = smid < 48 || smid == SCHED_MID0 || smid == SCHED_MID1 || smid == SCHED_MID2;
    cidx = smid < 48 ? (((smid >> 1) & 7) + (smid & 1) * NP) * 3 + (smid >> 4) : 24 + (smid == SCHED_MID1) + 2 * (smid == SCHED_MID2);
  } else {
    const int r = generic_role();
    cidx = r & 0xffff; is_conv = r >> 16;
    idx = blockIdx.x - cidx;
  }
  const int gm = cidx / 3, third = cidx - gm * 3;
  const int q0 = gm * PLEN, nit = gm < 8 ? PLEN + 2 : gm < NP ? NSEG * (LM + 3) : LT + 3, off = (8 - nit) & 7;
  if (is_conv && warp == 8) {
    bulk_load<9408, true>(sb, dw, sb + WBAR + 8);
    asm volatile("bar.arrive 5, 288;" ::: "memory");
#pragma unroll 1
    for (int it = 0; it < NSLOT; it++) {
      const int s = (it + off) & 7;
      ring_bar_init(sb + CM + s * 8, 2, s < off);
      if (it < FIRST) load_step(sb, &tmx, gm, third, it, s, true);
    }
  }
  if (warp == 15) asm volatile("prefetch.tensormap [%0];" ::"l"(&tmr) : "memory");
  mbar_init_elect(sb + MISC + warp * 8, 1); mbar_init_elect(sb + MISC + 128 + warp * 8, 1);
  asm volatile("fence.mbarrier_init.release.cluster;" ::: "memory");
  if (is_conv) {
    if (warp >= 8) ring_bar_init(sb + CM + warp * 8, 8, warp - 8 < off);
    if (warp == 9) mbar_init_elect(sb + WBAR, 2);
    const uint32_t lastph = (((nit + off) >> 3) & 1) ^ 1;
    if (warp < 8) {
      conv_compute(sb, gs, third, nit, off, gm < 8, gm < 8 && (gm & 1), warp, lane);
      asm volatile("setmaxnreg.dec.sync.aligned.u32 128;");
    } else if (warp >= 12) {
      asm volatile("setmaxnreg.dec.sync.aligned.u32 24;");
      const uint32_t epoch = ld_relaxed(&gs->epoch[id]);
#pragma unroll 1
      for (int it = threadIdx.x - 384; it <= nit; it += 128) {
        const int seg = it / (LM + 3), j = gm < 8 ? it - 2 : it - 3 * (seg + 1);
        const bool ok = it < nit && j >= (gm < 8 ? 0 : seg * LM);
        sts128(sb + CTAB + it * 16, make_uint4((ok ? (j % RING) * NG + gm : -1) * (4 * TILEB), slot_tag(gm, max(j, 0), epoch),
                                               offsetof(Globals, ready) + (ok ? q0 + j : NG * PLEN) * 4, ok ? q0 + j : -1));
      }
      if (threadIdx.x == 384) sts32(sb + MISC + 256, epoch + 1);
      asm volatile("bar.sync 0, 512;" ::: "memory");
      mbar_arrive_elect(sb + CM + ((((warp + 2) & 3) + off) & 7) * 8);
      mbar_arrive_elect(sb + CM + ((((warp + 2) & 3) + off + 4) & 7) * 8);
      build_tile_list(sb, threadIdx.x - 384, idx, tabled, true, epoch);
      if (threadIdx.x == 384) gs->epoch[id] = epoch + 1;
      asm volatile("bar.sync 6, 128;" ::: "memory");
      conv_credit(sb, gs, q0, nit, off, 16 * (epoch + 1), (warp + 2) & 3);
#pragma unroll 1
      for (int i = 0; i < 4; i++) {
        const uint2 e = lds64(sb + MISC + 512 + i * 16);
        mbar_wait(sb + CM + 64 + (4 + min(i, 2)) * 8, lastph);
        const int wi = 4 * i + (warp & 3);
        if ((int)e.x >= 0) bulk_load<3072>(sb + ABUF + wi * 3072, gs->scratch + (e.y & ~1u) + (warp & 3) * 3072, sb + MISC + wi * 8);
      }
      mbar_wait(sb + CM + 64 + 7 * 8, lastph);
      asm volatile("setmaxnreg.inc.sync.aligned.u32 128;");
    } else {
      asm volatile("setmaxnreg.dec.sync.aligned.u32 24;");
      conv_loader(sb, gs, &tmx, gm, nit, off, cidx, third, warp & 3);
      mbar_wait(sb + CM + 64 + 7 * 8, lastph);
      asm volatile("setmaxnreg.inc.sync.aligned.u32 128;");
    }
    mbar_wait(sb + WBAR, 0);
    asm volatile("bar.sync 0, 512;" ::: "memory");
  } else {
    mlp_setup(sb, gs, id, w1, w2, idx, tabled, warp, lane);
  }
  mlp_role(sb, gs, &tmr, out);
}

typedef CUresult (*PFN_encodeTiled)(CUtensorMap*, CUtensorMapDataType, cuuint32_t, void*, const cuuint64_t*, const cuuint64_t*, const cuuint32_t*, const cuuint32_t*,
                                    CUtensorMapInterleave, CUtensorMapSwizzle, CUtensorMapL2promotion, CUtensorMapFloatOOBfill);

extern "C" void kernel_launch(void* const* d_in, const int* in_sizes, int n_in, void* d_out, int out_size) {
  const __nv_bfloat16* x = (const __nv_bfloat16*)d_in[0];
  const __nv_bfloat16* dw = (const __nv_bfloat16*)d_in[1];
  const __nv_bfloat16* w1 = (const __nv_bfloat16*)d_in[2];
  const __nv_bfloat16* w2 = (const __nv_bfloat16*)d_in[3];
  static PFN_encodeTiled encode = nullptr;
  static int nsm = 0;
  static Globals* gs = nullptr;
  if (!encode) {
    void* fn = nullptr; cudaDriverEntryPointQueryResult qr;
    cudaGetDriverEntryPoint("cuTensorMapEncodeTiled", &fn, cudaEnableDefault, &qr);
    encode = (PFN_encodeTiled)fn;
    cudaGetSymbolAddress((void**)&gs, g_state);
    int dev = 0; cudaGetDevice(&dev);
    cudaDeviceGetAttribute(&nsm, cudaDevAttrMultiProcessorCount, dev);
    cudaFuncSetAttribute(convnext_kernel, cudaFuncAttributeMaxDynamicSharedMemorySize, SMEM_BYTES);
  }
  CUtensorMap tm, tr;
  cuuint64_t dims[3] = {96, 512, 512}, strides[2] = {192, 192 * 512};
  cuuint32_t box[3] = {32, 70, 2}, es[3] = {1, 1, 1};
  encode(&tm, CU_TENSOR_MAP_DATA_TYPE_BFLOAT16, 3, (void*)x, dims, strides, box, es, CU_TENSOR_MAP_INTERLEAVE_NONE, CU_TENSOR_MAP_SWIZZLE_64B,
         CU_TENSOR_MAP_L2_PROMOTION_L2_128B, CU_TENSOR_MAP_FLOAT_OOB_FILL_NONE);
  cuuint64_t dims2[3] = {1536, 32, 512}, strides2[2] = {3072, 192 * 512};
  cuuint32_t box2[3] = {192, 4, 2};
  encode(&tr, CU_TENSOR_MAP_DATA_TYPE_BFLOAT16, 3, (void*)x, dims2, strides2, box2, es, CU_TENSOR_MAP_INTERLEAVE_NONE, CU_TENSOR_MAP_SWIZZLE_NONE,
         CU_TENSOR_MAP_L2_PROMOTION_NONE, CU_TENSOR_MAP_FLOAT_OOB_FILL_NONE);
  convnext_kernel<<<nsm, 512, SMEM_BYTES>>>(dw, w1, w2, (__nv_bfloat16*)d_out, gs, nsm == 132 ? 132 : -1, tm, tr);
}
```
